```python
import torch

def _softmax(x, axis=-1):
    return torch.softmax(x, dim=axis)

def _gelu(x):
    return torch.nn.functional.gelu(x, approximate='tanh')

def _silu(x):
    return torch.nn.functional.silu(x)

def _sigmoid(x):
    return torch.sigmoid(x)

def _layernorm(x, axis=-1, eps=1e-05):
    m = x.mean(dim=axis, keepdim=True)
    v = x.var(dim=axis, keepdim=True, unbiased=False)
    return (x - m) / torch.sqrt(v + eps)

def _scatter_add(tgt, idx, src, axis=0):
    return tgt.clone().index_add_(axis, idx, src)

def _segment_sum(src, seg, n):
    out = torch.zeros((n,) + src.shape[1:], dtype=src.dtype)
    return out.index_add_(0, seg, src)

def _pad(x, pw):
    flat = tuple((v for pair in reversed(pw) for v in pair))
    return torch.nn.functional.pad(x, flat)
kernel_name = 'interleave_layers__memory_aug_recurrent_mem_tr__moe_arch_mod__prompt'

def setup_inputs():

    _w = lambda a: (lambda t: t.to(torch.bfloat16) if t.is_floating_point() else t)(torch.as_tensor(a))

    def _A_setup():
        B, S, Dm = (1, 2048, 512)
        H, Dh = (32, 128)
        M, seg = (8, 32)
        seg = min(seg, S)
        S = S // seg * seg
        return {'x': _w((lambda *s: torch.randn(*s, dtype=torch.bfloat16) * 0.05)(B, S, Dm)), 'mem0': _w((lambda *s: torch.randn(*s, dtype=torch.bfloat16) * 0.8)(B, M, Dm)), 'Wq': _w((lambda *s: torch.randn(*s, dtype=torch.bfloat16) * 0.8)(Dm, H, Dh) * Dm ** (-0.5)), 'Wk': _w((lambda *s: torch.randn(*s, dtype=torch.bfloat16) * 0.8)(Dm, H, Dh) * Dm ** (-0.5)), 'Wv': _w((lambda *s: torch.randn(*s, dtype=torch.bfloat16) * 0.8)(Dm, H, Dh) * Dm ** (-0.5)), 'Wo': _w((lambda *s: torch.randn(*s, dtype=torch.bfloat16) * 0.8)(H, Dh, Dm) * (H * Dh) ** (-0.5)), 'seg_len': seg}
    _A_in = _A_setup()

    def _B_setup():
        B, S, D, F, C = (1, 2048, 512, 1792, 1)
        return {'x': _w((lambda *s: torch.randn(*s, dtype=torch.bfloat16) * 0.05)(B, S, D)), 'w_r': _w((lambda *s: torch.randn(*s, dtype=torch.bfloat16) * 0.05)(D)), 'w_gate': _w((lambda *s: torch.randn(*s, dtype=torch.bfloat16) * 0.05)(D, F)), 'w_up': _w((lambda *s: torch.randn(*s, dtype=torch.bfloat16) * 0.05)(D, F)), 'w_down': _w((lambda *s: torch.randn(*s, dtype=torch.bfloat16) * 0.05)(F, D))}
    _B_in = _B_setup()
    return {'A_x': _A_in['x'], 'A_mem0': _A_in['mem0'], 'A_Wq': _A_in['Wq'], 'A_Wk': _A_in['Wk'], 'A_Wv': _A_in['Wv'], 'A_Wo': _A_in['Wo'], 'A_seg_len': _A_in['seg_len'], 'B_x': _B_in['x'], 'B_w_r': _B_in['w_r'], 'B_w_gate': _B_in['w_gate'], 'B_w_up': _B_in['w_up'], 'B_w_down': _B_in['w_down']}

def reference(A_x, A_mem0, A_Wq, A_Wk, A_Wv, A_Wo, A_seg_len, B_x, B_w_r, B_w_gate, B_w_up, B_w_down):

    def _A_ref(x, mem0, Wq, Wk, Wv, Wo, seg_len):
        B, S, Dm = x.shape
        H, Dh = (Wq.shape[1], Wq.shape[2])
        M = mem0.shape[1]
        scale = Dh ** (-0.5)
        n_seg = S // seg_len
        L = M + seg_len
        idx = torch.arange(L)
        mask = (idx[:, None] < M) | (idx[:, None] >= idx[None, :])
        mem = mem0
        outs = []
        for s in range(n_seg):
            xs = x[:, s * seg_len:(s + 1) * seg_len, :].clone()
            h = torch.concatenate([mem, xs], axis=1)
            q = torch.einsum('btd,dhe->bhte', h, Wq)
            k = torch.einsum('btd,dhe->bhte', h, Wk)
            v = torch.einsum('btd,dhe->bhte', h, Wv)
            scores = torch.einsum('bhqe,bhke->bhqk', q, k) * scale
            scores = torch.where(mask[None, None], scores, -1000000000.0)
            p = _softmax(scores, axis=-1)
            o = torch.einsum('bhqk,bhke->bhqe', p, v)
            o = torch.einsum('bhte,hed->btd', o, Wo)
            mem = o[:, :M, :].clone()
            outs.append(o[:, M:, :])
        return torch.concatenate(outs, axis=1)

    def _B_ref(x, w_r, w_gate, w_up, w_down):
        B, S, D = x.shape
        C = 1
        r = x @ w_r
        idx = torch.argsort(-r, axis=-1)[:, :C]
        idx_e = (lambda x, n, axis: torch.repeat_interleave(x, n, dim=axis))(idx.reshape(B, C, 1), D, axis=2)
        x_sel = (lambda x, i, axis: torch.take_along_dim(x, i, dim=axis))(x, idx_e, axis=1)
        g = _silu(x_sel @ w_gate)
        u = x_sel @ w_up
        y = g * u @ w_down
        r_sel = _sigmoid((lambda x, i, axis: torch.take_along_dim(x, i, dim=axis))(r, idx, axis=1))
        y = y * r_sel.reshape(B, C, 1)
        b_off = (torch.arange(B) * S).reshape(B, 1)
        flat_idx = (idx + b_off).reshape(B * C)
        zero = (x * 0.0).reshape(B * S, D)
        upd = _scatter_add(zero, flat_idx, y.reshape(B * C, D), axis=0)
        return x + upd.reshape(B, S, D)
    x = A_x
    x = x + _A_ref(_layernorm(x, axis=-1), A_mem0, A_Wq, A_Wk, A_Wv, A_Wo, A_seg_len)
    x = x + _B_ref(_layernorm(x, axis=-1), B_w_r, B_w_gate, B_w_up, B_w_down)
    x = x + _A_ref(_layernorm(x, axis=-1), A_mem0, A_Wq, A_Wk, A_Wv, A_Wo, A_seg_len)
    x = x + _B_ref(_layernorm(x, axis=-1), B_w_r, B_w_gate, B_w_up, B_w_down)
    return x
```

```cpp
#include <cuda_runtime.h>
#include <cuda_bf16.h>
#include <stdint.h>

namespace {

typedef __nv_bfloat16 bf16;

constexpr int NSEG = 64;
#define LAG_ 5
constexpr int LAG = LAG_;
constexpr int NSTEP = NSEG + LAG;
constexpr int ORING = 8, PRING = 4;
#define E1_ 10
#define E2_ 0
#define E3_ 10
constexpr int E1 = E1_, E2 = E2_, E3 = E3_, EA = E1 + E2 + E3;
static_assert(EA % 4 == 0 && EA > 0 && EA < 32 && E1 > 0, "early part: whole 64-column chunks");
#define RW_ 176
#define RA_ 136
#define RC_ 24
#define STR2(x) #x
#define STR(x) STR2(x)
#define RED_ 30
#define ARR_ 7
#define HADD_ 1
#define PAUSE_ 21
#define PD1_ 3
#define PD2_ 7
#define DPOLL_ 0
#define SALT_ 0
#define KP1_ 1
#define EARLY_ 0
#define PRIV_ 1
#define OLOAD_ 8192
#define PST_ 8192
#define PCHK_ 1
#define HAND_ 4
#define GO3_ 2
#define NPROBE_ 6
#define TP(i, v) (v)
#define XDLY_ TP(0, 1700)
#define YDLY_ TP(1, 2900)
#define X1_ TP(2, 200)
#define X2_ TP(3, 350)
#define Y1_ TP(4, 200)
#define Y2_ TP(5, 350)
#define HGAP_ TP(6, 100)
#define TGAP_ TP(7, 100)
#define ADLY_ TP(8, 0)
#define ODLY_ TP(9, 2700)
#define LDLY_ TP(10, 3600)
#define LGAP_ 200
#define HDLY_ TP(11, 0)
#define TDLY_ TP(15, 0)
#define SDLY_ TP(12, 800)
#define AGAP_ TP(13, 100)
#define KDLY_ TP(14, 300)
__device__ uint32_t g_epoch;
__device__ __align__(1024) uint8_t g_h[2][NSEG][32768];
__device__ __align__(128) uint2 g_hc[NSEG][256];
__device__ __align__(128) bf16 g_x2[2048 * 512];
__device__ __align__(128) bf16 g_x2c[NSEG][512];
__device__ __align__(128) uint8_t g_o[3][ORING][32][8192];
__device__ __align__(128) uint8_t g_pp[3][PRING][8 * 32768];
__device__ __align__(128) bf16 g_n[2048 * 512];
__device__ __align__(128) uint8_t g_xch[96 * 16384 + 65536 + 8192];
__device__ __align__(128) bf16 g_req1[2048][2][512];
__device__ __align__(128) bf16 g_req2[2][2048][2][512];
__device__ __align__(128) float g_y[NSEG + 1][512 + 32];
__device__ __align__(128) uint8_t g_tok[96][2][16384];
__device__ uint32_t f_choice[96][2];
__device__ uint32_t f_h1[NSEG], f_hc[NSEG];
__device__ __align__(128) unsigned long long f_h2[NSEG][16];
__device__ __align__(128) unsigned long long f_b2[2][NSEG];
__device__ uint32_t f_c2[NSEG * 8];
__device__ __align__(128) uint32_t f_o[NSTEP][8][16];
__device__ uint32_t f_acc[3][NSEG * 8];
__device__ uint32_t f_zero;
__device__ __align__(128) unsigned long long g_sync[2][96];

__device__ __forceinline__ uint32_t smem_u32(const void* p) { return (uint32_t)__cvta_generic_to_shared(p); }
__device__ __forceinline__ int fresh_tid() { const int t = threadIdx.x; return __shfl_sync(~0u, t, t & 31); }
__device__ __forceinline__ unsigned long long gtime64() { unsigned long long t; asm volatile("mov.u64 %0, %%globaltimer;" : "=l"(t) :: "memory"); return t; }
__device__ __forceinline__ uint32_t clk() { unsigned long long c; asm volatile("mov.u64 %0, %%clock64;" : "=l"(c) :: "memory"); return (uint32_t)c; }
__device__ __forceinline__ void wait_until(uint32_t t) {
  while ((int)(t - clk()) > 450) __nanosleep(32);
  uint32_t c;
  do { asm volatile("mov.u32 %0, %%clock;" : "=r"(c) :: "memory"); } while ((int)(c - t) < 0);
}
__device__ __forceinline__ void mbar_init(uint32_t bar, uint32_t cnt) { asm volatile("mbarrier.init.shared::cta.b64 [%0], %1;" :: "r"(bar), "r"(cnt) : "memory"); }
__device__ __forceinline__ void mbar_arrive(uint32_t bar) { asm volatile("mbarrier.arrive.shared::cta.b64 _, [%0];" :: "r"(bar) : "memory"); }
__device__ __forceinline__ void mbar_arrive_remote(uint32_t bar) { asm volatile("mbarrier.arrive.relaxed.cluster.shared::cluster.b64 _, [%0];" :: "r"(bar) : "memory"); }
__device__ __forceinline__ void mbar_expect(uint32_t bar, uint32_t bytes) { asm volatile("mbarrier.arrive.expect_tx.shared::cta.b64 _, [%0], %1;" :: "r"(bar), "r"(bytes) : "memory"); }
__device__ __forceinline__ bool mbar_try(uint32_t bar, uint32_t parity) {
  uint32_t ok;
  asm volatile("{.reg .pred p; mbarrier.try_wait.parity.shared::cta.b64 p, [%1], %2; selp.u32 %0, 1, 0, p;}" : "=r"(ok) : "r"(bar), "r"(parity) : "memory");
  return ok;
}
__device__ __forceinline__ bool mbar_test(uint32_t bar, uint32_t parity) {
  uint32_t ok;
  asm volatile("{.reg .pred p; mbarrier.test_wait.parity.shared::cta.b64 p, [%1], %2; selp.u32 %0, 1, 0, p;}" : "=r"(ok) : "r"(bar), "r"(parity) : "memory");
  return ok;
}
__device__ __forceinline__ void mbar_wait(uint32_t bar, uint32_t parity) {
  asm volatile("{\n.reg .pred p;\nWAIT:\nmbarrier.try_wait.parity.shared::cta.b64 p, [%0], %1;\n@!p bra WAIT;\n}" :: "r"(bar), "r"(parity) : "memory");
}
__device__ __forceinline__ uint32_t ld_acq(const uint32_t* p) { uint32_t v; asm volatile("ld.acquire.gpu.global.u32 %0, [%1];" : "=r"(v) : "l"(p) : "memory"); return v; }
__device__ __forceinline__ unsigned long long ld_acq64(const unsigned long long* p) { unsigned long long v; asm volatile("ld.acquire.gpu.global.u64 %0, [%1];" : "=l"(v) : "l"(p) : "memory"); return v; }
__device__ __forceinline__ void st_rel(uint32_t* p, uint32_t v) { asm volatile("st.release.gpu.global.u32 [%0], %1;" :: "l"(p), "r"(v) : "memory"); }
__device__ __forceinline__ void st_rel64(unsigned long long* p, unsigned long long v) { asm volatile("st.release.gpu.global.u64 [%0], %1;" :: "l"(p), "l"(v) : "memory"); }
__device__ __forceinline__ void red_rel(uint32_t* p, uint32_t v) { asm volatile("red.release.gpu.global.add.u32 [%0], %1;" :: "l"(p), "r"(v) : "memory"); }
__device__ __forceinline__ uint32_t ld_rlx(const uint32_t* p) { uint32_t v; asm volatile("ld.relaxed.gpu.global.u32 %0, [%1];" : "=r"(v) : "l"(p) : "memory"); return v; }
__device__ __forceinline__ unsigned long long ld_rlxu64(const unsigned long long* p) { unsigned long long v; asm volatile("ld.relaxed.gpu.global.u64 %0, [%1];" : "=l"(v) : "l"(p) : "memory"); return v; }
__device__ __forceinline__ void st_rlx(uint32_t* p, uint32_t v) { asm volatile("st.relaxed.gpu.global.u32 [%0], %1;" :: "l"(p), "r"(v) : "memory"); }
__device__ __forceinline__ void bulk_wait() { asm volatile("cp.async.bulk.commit_group;\n cp.async.bulk.wait_group 0;" ::: "memory"); }
__device__ __forceinline__ void fence_acq() { asm volatile("fence.acquire.gpu;" ::: "memory"); }
__device__ __forceinline__ void wait_eq(const uint32_t* p, uint32_t v) {
  int guard = 0;
  while (ld_rlx(p) != v) { __nanosleep(64); if (++guard > (1 << 22)) __trap(); }
  fence_acq();
}
__device__ __forceinline__ unsigned long long rword(uint32_t E, int tok, float r) {
  uint32_t u = __float_as_uint(r + 0.f);
  u = r != r ? 0u : (u >> 31) ? ~u : u | 0x80000000u;
  return (unsigned long long)E << 43 | (unsigned long long)u << 11 | (uint32_t)(2047 - tok);
}
__device__ __forceinline__ int rtok(unsigned long long v) { return 2047 - (int)(v & 2047u); }
__device__ __forceinline__ float rscore(unsigned long long v) { const uint32_t u = (uint32_t)(v >> 11); return __uint_as_float((u >> 31) ? u & 0x7fffffffu : ~u); }
__device__ __forceinline__ bool rfresh(unsigned long long v, uint32_t E) { return (uint32_t)(v >> 43) == (E & 0x1FFFFFu); }
template <int TOP> __device__ __forceinline__ unsigned long long warp_max(unsigned long long v) {
#pragma unroll
  for (int o = TOP; o > 0; o >>= 1) { const unsigned long long ov = __shfl_xor_sync(~0u, v, o); v = ov > v ? ov : v; }
  return v;
}
template <int off> __device__ __forceinline__ uint2 ld_rlx64(const void* p) { unsigned long long v; asm volatile("ld.relaxed.gpu.global.b64 %0, [%1+%2];" : "=l"(v) : "l"(p), "n"(off) : "memory"); return make_uint2((uint32_t)v, (uint32_t)(v >> 32)); }
template <int off> __device__ __forceinline__ uint4 ld_rlx128(const void* p) {
  unsigned long long a, b; asm volatile("ld.relaxed.gpu.global.v2.b64 {%0,%1}, [%2+%3];" : "=l"(a), "=l"(b) : "l"(p), "n"(off) : "memory");
  return make_uint4((uint32_t)a, (uint32_t)(a >> 32), (uint32_t)b, (uint32_t)(b >> 32));
}
__device__ __forceinline__ void st_rlx64(void* p, uint32_t lo, uint32_t hi) { asm volatile("{.reg .b64 t; mov.b64 t, {%1,%2}; st.relaxed.gpu.global.b64 [%0], t;}" :: "l"(p), "r"(lo), "r"(hi) : "memory"); }
__device__ __forceinline__ void cp_async16(uint32_t dst, const void* src) { asm volatile("cp.async.cg.shared.global [%0], [%1], 16;" :: "r"(dst), "l"(src) : "memory"); }
__device__ __forceinline__ void cp_async_wait() { asm volatile("cp.async.wait_all;" ::: "memory"); }
__device__ __forceinline__ void fence_async_smem() { asm volatile("fence.proxy.async.shared::cta;" ::: "memory"); }
__device__ __forceinline__ void fence_async_glob() { asm volatile("fence.proxy.async.global;" ::: "memory"); }
__device__ __forceinline__ void fence_async_acq() { asm volatile("fence.proxy.async::generic.acquire.sync_restrict::shared::cluster.cluster;" ::: "memory"); }
__device__ __forceinline__ float ex2(float x) { float y; asm("ex2.approx.ftz.f32 %0, %1;" : "=f"(y) : "f"(x)); return y; }
__device__ __forceinline__ float sqrt_fast(float x) { float y; asm("sqrt.approx.ftz.f32 %0, %1;" : "=f"(y) : "f"(x)); return y; }
__device__ __forceinline__ float rcp(float x) { float y; asm("rcp.approx.ftz.f32 %0, %1;" : "=f"(y) : "f"(x)); return y; }
__device__ __forceinline__ void bar_sync(int id, int n) { asm volatile("bar.sync %0, %1;" :: "r"(id), "r"(n) : "memory"); }
__device__ __forceinline__ bool bar_or(int id, int n, bool v) {
  uint32_t r;
  asm volatile("{.reg .pred p, q; setp.ne.u32 p, %3, 0; barrier.cta.red.or.aligned.pred q, %1, %2, p; selp.u32 %0, 1, 0, q;}" : "=r"(r) : "r"(id), "r"(n), "r"((uint32_t)v) : "memory");
  return r;
}
__device__ __forceinline__ uint32_t mapa(uint32_t a, uint32_t rank) { uint32_t r; asm volatile("mapa.shared::cluster.u32 %0, %1, %2;" : "=r"(r) : "r"(a), "r"(rank)); return r; }
__device__ __forceinline__ void cluster_sync() { asm volatile("barrier.cluster.arrive.release.aligned; barrier.cluster.wait.acquire.aligned;" ::: "memory"); }
__device__ __forceinline__ void st_async32(uint32_t dst, uint32_t v, uint32_t bar) { asm volatile("st.async.shared::cluster.mbarrier::complete_tx::bytes.b32 [%0], %1, [%2];" :: "r"(dst), "r"(v), "r"(bar) : "memory"); }
__device__ __forceinline__ void bulk_g2s(uint32_t dst, const void* src, uint32_t bytes, uint32_t bar) {
  asm volatile("cp.async.bulk.shared::cluster.global.mbarrier::complete_tx::bytes [%0], [%1], %2, [%3];" :: "r"(dst), "l"(src), "r"(bytes), "r"(bar) : "memory");
}
__device__ __forceinline__ void bulk_g2s_mc(uint32_t dst, const void* src, uint32_t bytes, uint32_t bar, uint16_t mask) {
  asm volatile("cp.async.bulk.shared::cluster.global.mbarrier::complete_tx::bytes.multicast::cluster [%0], [%1], %2, [%3], %4;"
               :: "r"(dst), "l"(src), "r"(bytes), "r"(bar), "h"(mask) : "memory");
}
__device__ __forceinline__ void bulk_s2c(uint32_t dst, uint32_t src, uint32_t bytes, uint32_t bar) {
  asm volatile("cp.async.bulk.shared::cluster.shared::cta.mbarrier::complete_tx::bytes [%0], [%1], %2, [%3];" :: "r"(dst), "r"(src), "r"(bytes), "r"(bar) : "memory");
}
__device__ __forceinline__ void bulk_s2g(void* dst, uint32_t src, uint32_t bytes) {
  asm volatile("cp.async.bulk.global.shared::cta.bulk_group [%0], [%1], %2;" :: "l"(dst), "r"(src), "r"(bytes) : "memory");
}
#define ELECT(op) "{.reg .pred p; elect.sync _|p, 0xffffffff; @p " op "}"
__device__ __forceinline__ void e_arrive(uint32_t bar) { asm volatile(ELECT("mbarrier.arrive.shared::cta.b64 _, [%0];") :: "r"(bar) : "memory"); }
__device__ __forceinline__ void e_expect(uint32_t bar, uint32_t bytes) { asm volatile(ELECT("mbarrier.arrive.expect_tx.shared::cta.b64 _, [%0], %1;") :: "r"(bar), "r"(bytes) : "memory"); }
__device__ __forceinline__ void e_g2s(uint32_t dst, const void* src, uint32_t bytes, uint32_t bar) {
  asm volatile(ELECT("cp.async.bulk.shared::cluster.global.mbarrier::complete_tx::bytes [%0], [%1], %2, [%3];") :: "r"(dst), "l"(src), "r"(bytes), "r"(bar) : "memory");
}
__device__ __forceinline__ void e_mc(uint32_t dst, const void* src, uint32_t bytes, uint32_t bar, uint16_t mask) {
  asm volatile(ELECT("cp.async.bulk.shared::cluster.global.mbarrier::complete_tx::bytes.multicast::cluster [%0], [%1], %2, [%3], %4;")
               :: "r"(dst), "l"(src), "r"(bytes), "r"(bar), "h"(mask) : "memory");
}
__device__ __forceinline__ void e_s2g(void* dst, uint32_t src, uint32_t bytes) {
  asm volatile(ELECT("cp.async.bulk.global.shared::cta.bulk_group [%0], [%1], %2;") :: "l"(dst), "r"(src), "r"(bytes) : "memory");
}
__device__ __forceinline__ void e_st_rel(uint32_t* p, uint32_t v) { asm volatile(ELECT("st.release.gpu.global.u32 [%0], %1;") :: "l"(p), "r"(v) : "memory"); }
__device__ __forceinline__ uint32_t clk32() { uint32_t c; asm volatile("mov.u32 %0, %%clock;" : "=r"(c) :: "memory"); return c; }
__device__ __forceinline__ void spin_until(uint32_t t) { while ((int)(clk32() - t) < 0) {} }
__device__ __forceinline__ uint32_t uni(uint32_t v) { return __shfl_sync(~0u, v, 0); }
__device__ __forceinline__ uint32_t pack2(float lo, float hi) { uint32_t r; asm("cvt.rn.bf16x2.f32 %0, %1, %2;" : "=r"(r) : "f"(hi), "f"(lo)); return r; }
__device__ __forceinline__ uint32_t add2(uint32_t a, uint32_t b) { uint32_t r; asm("add.rn.bf16x2 %0, %1, %2;" : "=r"(r) : "r"(a), "r"(b)); return r; }
__device__ __forceinline__ float rbf(float x) { return __bfloat162float(__float2bfloat16_rn(x)); }
__device__ __forceinline__ float blo(uint32_t u) { return __uint_as_float(u << 16); }
__device__ __forceinline__ float bhi(uint32_t u) { return __uint_as_float(u & 0xffff0000u); }
__device__ __forceinline__ uint32_t pack2_tag(float lo, float hi, uint32_t tag) {
  uint32_t u = __float_as_uint(lo) >> 16;
  u += (u ^ tag) & 1u;
  return (pack2(0.f, hi) & 0xffff0000u) | (u & 0xffffu);
}
__device__ __forceinline__ uint32_t xo2(uint32_t a, uint32_t b, uint32_t t) { uint32_t r; asm("lop3.b32 %0, %1, %2, %3, 0x7e;" : "=r"(r) : "r"(a), "r"(b), "r"(t)); return r; }
__device__ __forceinline__ uint32_t or3(uint32_t a, uint32_t b, uint32_t c) { uint32_t r; asm("lop3.b32 %0, %1, %2, %3, 0xfe;" : "=r"(r) : "r"(a), "r"(b), "r"(c)); return r; }
__device__ __forceinline__ void stmatrix4(uint32_t a, uint32_t r0, uint32_t r1, uint32_t r2, uint32_t r3) {
  asm volatile("stmatrix.sync.aligned.m8n8.x4.shared.b16 [%0], {%1,%2,%3,%4};" :: "r"(a), "r"(r0), "r"(r1), "r"(r2), "r"(r3) : "memory");
}
__device__ __forceinline__ void stmatrix4_t(uint32_t a, uint32_t r0, uint32_t r1, uint32_t r2, uint32_t r3) {
  asm volatile("stmatrix.sync.aligned.m8n8.x4.trans.shared.b16 [%0], {%1,%2,%3,%4};" :: "r"(a), "r"(r0), "r"(r1), "r"(r2), "r"(r3) : "memory");
}
__device__ __forceinline__ void ldmatrix4_t(uint32_t* r, uint32_t a) {
  asm volatile("ldmatrix.sync.aligned.m8n8.x4.trans.shared.b16 {%0,%1,%2,%3}, [%4];" : "=r"(r[0]), "=r"(r[1]), "=r"(r[2]), "=r"(r[3]) : "r"(a) : "memory");
}
__device__ __forceinline__ void ldmatrix4(uint32_t* r, uint32_t a) {
  asm volatile("ldmatrix.sync.aligned.m8n8.x4.shared.b16 {%0,%1,%2,%3}, [%4];" : "=r"(r[0]), "=r"(r[1]), "=r"(r[2]), "=r"(r[3]) : "r"(a) : "memory");
}
__device__ __forceinline__ void hmma16(float* c, const uint32_t* a, uint32_t b0, uint32_t b1) {
  asm volatile("mma.sync.aligned.m16n8k16.row.col.f32.bf16.bf16.f32 {%0,%1,%2,%3}, {%4,%5,%6,%7}, {%8,%9}, {%0,%1,%2,%3};"
               : "+f"(c[0]), "+f"(c[1]), "+f"(c[2]), "+f"(c[3]) : "r"(a[0]), "r"(a[1]), "r"(a[2]), "r"(a[3]), "r"(b0), "r"(b1));
}
__device__ __forceinline__ void hmma8(float* c, uint32_t a0, uint32_t a1, uint32_t b0) {
  asm volatile("mma.sync.aligned.m16n8k8.row.col.f32.bf16.bf16.f32 {%0,%1,%2,%3}, {%4,%5}, {%6}, {%0,%1,%2,%3};"
               : "+f"(c[0]), "+f"(c[1]), "+f"(c[2]), "+f"(c[3]) : "r"(a0), "r"(a1), "r"(b0));
}
__device__ __forceinline__ uint4 lds128(uint32_t a) { uint4 v; asm volatile("ld.shared.v4.u32 {%0,%1,%2,%3}, [%4];" : "=r"(v.x), "=r"(v.y), "=r"(v.z), "=r"(v.w) : "r"(a) : "memory"); return v; }
__device__ __forceinline__ void sts128(uint32_t a, uint4 v) { asm volatile("st.shared.v4.u32 [%0], {%1,%2,%3,%4};" :: "r"(a), "r"(v.x), "r"(v.y), "r"(v.z), "r"(v.w) : "memory"); }
__device__ __forceinline__ void sts128f(uint32_t a, float x, float y, float z, float w) { asm volatile("st.shared.v4.f32 [%0], {%1,%2,%3,%4};" :: "r"(a), "f"(x), "f"(y), "f"(z), "f"(w) : "memory"); }
__device__ __forceinline__ void sts64f(uint32_t a, float x, float y) { asm volatile("st.shared.v2.f32 [%0], {%1,%2};" :: "r"(a), "f"(x), "f"(y) : "memory"); }
__device__ __forceinline__ uint32_t lds32(uint32_t a) { uint32_t v; asm volatile("ld.shared.u32 %0, [%1];" : "=r"(v) : "r"(a) : "memory"); return v; }
__device__ __forceinline__ void sts32(uint32_t a, uint32_t v) { asm volatile("st.shared.u32 [%0], %1;" :: "r"(a), "r"(v) : "memory"); }

constexpr uint32_t SBASE = 1024;
__host__ __device__ constexpr uint64_t mkdesc(uint32_t off, uint32_t lbo, uint32_t sbo, uint32_t swz) {
  return (uint64_t)(((SBASE + off) & 0x3FFFF) >> 4) | ((uint64_t)(lbo >> 4) << 16) | ((uint64_t)(sbo >> 4) << 32) | ((uint64_t)swz << 62);
}
__device__ __forceinline__ void wg_fence() { asm volatile("wgmma.fence.sync.aligned;" ::: "memory"); }
__device__ __forceinline__ void wg_commit() { asm volatile("wgmma.commit_group.sync.aligned;" ::: "memory"); }
template <int N> __device__ __forceinline__ void wg_wait() { asm volatile("wgmma.wait_group.sync.aligned %0;" :: "n"(N) : "memory"); }

template <int N> __device__ __forceinline__ void reg_fence(float (&d)[N], int n = N) {
#pragma unroll
  for (int i = 0; i < N; i++) if (i < n) asm volatile("" : "+f"(d[i]) :: "memory");
}
#define F4(b) "+f"(d[b]), "+f"(d[b + 1]), "+f"(d[b + 2]), "+f"(d[b + 3])
#define F8(b) F4(b), F4(b + 4)
#define F16(b) F8(b), F8(b + 8)
#define G4(b) "=f"(d[b]), "=f"(d[b + 1]), "=f"(d[b + 2]), "=f"(d[b + 3])
#define G8(b) G4(b), G4(b + 4)
#define G16(b) G8(b), G8(b + 8)
#define RS_IN "r"(a[0]), "r"(a[1]), "r"(a[2]), "r"(a[3]), "l"(db), "n"(SD), "n"(TB)
#define SS_IN "l"(da), "l"(db), "n"(SD), "n"(TA), "n"(TB)
#define WG_OP(str, out0, out1, in) do { if (SD || KEEP) asm volatile(str : out1 : in); else asm volatile(str : out0 : in); } while (0)
#define O12(X) X##8(0), X##4(8)
#define O20(X) X##16(0), X##4(16)
#define O32(X) X##16(0), X##16(16)
template <int SD, int TB, int KEEP = 0> __device__ __forceinline__ void wgmma_rs24(float* d, const uint32_t* a, uint64_t db) {
  WG_OP("wgmma.mma_async.sync.aligned.m64n24k16.f32.bf16.bf16 {%0,%1,%2,%3,%4,%5,%6,%7,%8,%9,%10,%11}, {%12,%13,%14,%15}, %16, %17, 1, 1, %18;", O12(G), O12(F), RS_IN);
}
template <int SD, int TB, int KEEP = 0> __device__ __forceinline__ void wgmma_rs32(float* d, const uint32_t* a, uint64_t db) {
  WG_OP("wgmma.mma_async.sync.aligned.m64n32k16.f32.bf16.bf16 {%0,%1,%2,%3,%4,%5,%6,%7,%8,%9,%10,%11,%12,%13,%14,%15}, {%16,%17,%18,%19}, %20, %21, 1, 1, %22;", G16(0), F16(0), RS_IN);
}
template <int SD, int TB, int KEEP = 0> __device__ __forceinline__ void wgmma_rs40(float* d, const uint32_t* a, uint64_t db) {
  WG_OP("wgmma.mma_async.sync.aligned.m64n40k16.f32.bf16.bf16 {%0,%1,%2,%3,%4,%5,%6,%7,%8,%9,%10,%11,%12,%13,%14,%15,"
        "%16,%17,%18,%19}, {%20,%21,%22,%23}, %24, %25, 1, 1, %26;", O20(G), O20(F), RS_IN);
}
template <int SD, int TB, int KEEP = 0> __device__ __forceinline__ void wgmma_rs64(float* d, const uint32_t* a, uint64_t db) {
  WG_OP("wgmma.mma_async.sync.aligned.m64n64k16.f32.bf16.bf16 {%0,%1,%2,%3,%4,%5,%6,%7,%8,%9,%10,%11,%12,%13,%14,%15,"
        "%16,%17,%18,%19,%20,%21,%22,%23,%24,%25,%26,%27,%28,%29,%30,%31}, {%32,%33,%34,%35}, %36, %37, 1, 1, %38;", O32(G), O32(F), RS_IN);
}
template <int SD, int TA, int TB, int KEEP = 0> __device__ __forceinline__ void wgmma_ss24(float* d, uint64_t da, uint64_t db) {
  WG_OP("wgmma.mma_async.sync.aligned.m64n24k16.f32.bf16.bf16 {%0,%1,%2,%3,%4,%5,%6,%7,%8,%9,%10,%11}, %12, %13, %14, 1, 1, %15, %16;", O12(G), O12(F), SS_IN);
}
template <int SD, int TA, int TB, int KEEP = 0> __device__ __forceinline__ void wgmma_ss8(float* d, uint64_t da, uint64_t db) {
  WG_OP("wgmma.mma_async.sync.aligned.m64n8k16.f32.bf16.bf16 {%0,%1,%2,%3}, %4, %5, %6, 1, 1, %7, %8;", G4(0), F4(0), SS_IN);
}
__device__ __forceinline__ void bar_arrive(int id, int n) { asm volatile("bar.arrive %0, %1;" :: "r"(id), "r"(n) : "memory"); }
__device__ __forceinline__ uint32_t vis_bits(int pos, int t) {
  uint32_t m = 0;
#pragma unroll
  for (int i = 0; i < 8; i++) m |= (8 * (i / 2 + 1) + 2 * t + (i & 1) <= pos) ? 1u << i : 0u;
  return m;
}

__device__ __forceinline__ int route_step(int s, uint32_t E, unsigned long long& run) {
  int guard = 0; unsigned long long m, n;
  for (;;) {
    asm volatile("ld.relaxed.gpu.global.v2.b64 {%0,%1}, [%2];" : "=l"(m), "=l"(n) : "l"(f_h2[s]) : "memory");
    if ((uint32_t)n == E * 4u) break;
    __nanosleep(40);
    if (++guard > (1 << 22)) __trap();
  }
  fence_acq();
  m = ld_rlxu64(f_h2[s]);
  if (s == 0 || m > run) { run = m; return rtok(m) & 31; }
  return -1;
}

struct Params {
  const bf16 *x, *mem0, *wq, *wk, *wv, *wo, *wr, *wg, *wu, *wd;
  bf16* out;
  unsigned long long zero;
};

constexpr uint32_t WSTG_STRIDE = 272;
__device__ __forceinline__ void stage_weights(uint32_t stg, const bf16* src, int ld, int tid, int nthr) {
  for (int i = tid; i < 512 * 16; i += nthr) {
    int k = i >> 4, c = i & 15;
    cp_async16(stg + k * WSTG_STRIDE + c * 16, src + (size_t)k * ld + c * 8);
  }
}
__device__ __forceinline__ void load_frags(uint32_t (*W)[4], uint32_t stg, int wg, int w, int lane) {
  uint32_t a = stg + ((lane >> 4) * 8 + (lane & 7)) * WSTG_STRIDE + (64 * wg + 16 * w + ((lane >> 3) & 1) * 8) * 2;
#pragma unroll
  for (int ks = 0; ks < 32; ks++) ldmatrix4_t(W[ks], a + ks * 16 * WSTG_STRIDE);
}

constexpr uint32_t M_H = 0;
constexpr uint32_t M_MEM = 65536;
constexpr uint32_t M_Q = M_MEM + 24576;
constexpr uint32_t M_K = M_Q + 12288;
constexpr uint32_t M_V = M_K + 12288;
constexpr uint32_t M_OM = M_V + 12288;
constexpr uint32_t M_OST = M_OM + 6144;
constexpr uint32_t M_TST = M_OST + 8192;
constexpr uint32_t M_WO = M_TST + 16384;
constexpr uint32_t M_M0 = M_WO + 49152;
constexpr uint32_t M_PT = M_M0 + 2048;
constexpr uint32_t M_BAR = M_PT + 12288;
constexpr uint32_t M_TOTAL = M_BAR + 384;
static_assert(M_TOTAL <= 232448, "main smem");
static_assert(M_WO >= 512 * WSTG_STRIDE, "staging overlaps Wo");
enum { B_LAND = 0  , B_QK = 3, B_V, B_TOK, B_OM, B_HA, B_HB, B_HAE, B_HBE, B_OST, B_OFREE, B_SYNC,
       B_STG, B_SS, B_TFREE, B_KFREE, B_VFREE, B_FIX  , B_NUM = B_FIX + 8 };
static_assert(B_NUM * 8 <= 256, "barriers");
constexpr uint32_t M_CAND = M_BAR + 256;
constexpr uint32_t M_BASE = M_BAR + 272;
constexpr uint32_t M_ZERO = M_BAR + 280;
constexpr uint32_t M_NEAR = M_BAR + 288;
enum { N_GO1 = 2, N_GO2, N_GO3, N_GO4, N_AG, N_W };

#define GSTAMP(slot, i)
#define TSTAMP(slot, i, k)
#define STAMP(i)
#define ASTAMP(i)
#define WSTAMP(i)
#define CSTAMP(i, v)
#define PIN(x) asm volatile("" : "+r"(x))
#define SCHED(k) asm volatile("{\n.reg .pred p;\nsetp.ne.u32 p, %0, 0;\n@p trap;\n}" :: "r"(zz & (1u << (k))) : "memory")
#define HOLD(k, v) asm volatile("{\n.reg .pred p;\nsetp.ne.u32 p, %0, 0;\n@p st.shared.u32 [%0], %1;\n}" :: "r"(zz & (1u << (k))), "r"(v) : "memory")
#define DRAIN(a) (lds32((a) + zz) & zz)
#define BAR(i) (sb + M_BAR + 8 * (i))

__device__ __forceinline__ int probe_near(const uint8_t* p) {
  int best0 = 1 << 30, best1 = 1 << 30; uint32_t v = 0;
#pragma unroll 1
  for (int r = 0; r < NPROBE_; r++) {
    uint32_t t0 = clk();
    asm volatile("atom.relaxed.gpu.global.or.b32 %0, [%1], %2;" : "=r"(v) : "l"(p + (r & 1) * 4096 + 3968), "r"(v & 0u) : "memory");
    if (v == 0x7fffffffu) t0++;
    int d = (int)(clk() - t0);
    if (r & 1) best1 = min(best1, d); else best0 = min(best0, d);
  }
  return best1 < best0;
}
__device__ __forceinline__ void fill_mem0(uint32_t img, int w, int lane, int slot, const bf16* mem0) {
  PIN(w); PIN(lane);
  const int k0 = w + lane;
  uint4 u[2];
#pragma unroll
  for (int i = 0; i < 2; i++) {
    const unsigned short* m = (const unsigned short*)mem0 + k0 + 32 * i;
    u[i] = make_uint4(m[0] | (uint32_t)m[512] << 16, m[1024] | (uint32_t)m[1536] << 16, m[2048] | (uint32_t)m[2560] << 16, m[3072] | (uint32_t)m[3584] << 16);
  }
  __syncwarp();
#pragma unroll
  for (int i = 0; i < 2; i++) sts128(img + ((k0 >> 4) + 2 * i) * 768 + slot * 256 + (lane & 15) * 16, u[i]);
}

__device__ __forceinline__ void paced_h(uint32_t dst, const uint8_t* src, uint32_t o0, uint32_t o1, uint32_t piece, uint32_t bar, int gap) {
  uint32_t t = clk32();
#pragma unroll 1
  for (uint32_t o = o0; o < o1; o += piece) {
    e_mc(dst + o, src + o, piece, bar, 7);
    spin_until(t += gap);
  }
}

__device__ __forceinline__ void weight_role(const Params& p, const uint32_t sb, const int warp, const int cta, const int C, const uint32_t E,
                                            const uint8_t* const memg) {
  const int tid = fresh_tid(), lane = tid & 31;
  const int wg = warp >> 2, w = warp & 3;
  uint32_t W[32][4];
  cp_async_wait();
  bar_sync(1, 256);
  load_frags(W, sb, wg, w, lane);
  bar_sync(1, 256);
  if (tid < 128) sts128(sb + M_V + 5 * 2048 + tid * 16, make_uint4(0, 0, 0, 0));
  fence_async_smem();
  cluster_sync();
  if (tid == 0 && cta == 0) GSTAMP(0, 1);
  if (tid == 0) TSTAMP(13, cta, 0);

  const uint32_t rba = mapa(sb, C == 2 ? 0 : 2), rbc = mapa(sb, C == 1 ? 0 : 1);
  const uint32_t MYBAR = M_BAR + 8 * (C < 2 ? B_QK : B_V);
  uint32_t qoff = M_Q + C * 12288 + warp * 256 + lane * 4;
  uint32_t toff = sb + warp * 256 + (lane >> 4) * 2048 + (lane & 15) * 16;
  uint32_t rbar = mapa(sb + M_BAR, min(lane, 2));
  uint32_t sv = sb + M_MEM + lane * 32 + ((lane >> 2) & 3) * 8;
  PIN(qoff); PIN(toff); PIN(rbar); PIN(sv);
  uint32_t tag = (((E - 1) * (uint32_t)(NSTEP - 1)) & 1) ^ 1, fix = 0;
  const bool sig = w == 0 && lane < 3;
  const int pk = PAUSE_ + (cta < 36 ? 0 : cta < 72 ? PD1_ : PD2_);
  int cand = -1;
  float d[16];
#pragma unroll
  for (int i = 0; i < 16; i++) d[i] = 0.f;
  uint32_t tp[8];
#pragma unroll 1
  for (int T = -1; T < NSTEP; T++) {
    const uint32_t ph = T & 1;
    const uint64_t Z = p.zero << ph;
    const uint32_t zz = (uint32_t)Z;
    if (T >= 0) {
      WSTAMP(0);
      const uint64_t db = mkdesc(M_MEM, 128, 256, 0) + Z;
      stmatrix4(toff + M_TST + 8192, tp[0], tp[1], tp[2], tp[3]); stmatrix4(toff + M_TST + 12288, tp[4], tp[5], tp[6], tp[7]);
      if (sig) mbar_arrive_remote(rbar + 8 * B_HBE);
      mbar_wait(BAR(B_LAND), ph);
      WSTAMP(1);
      tag ^= 1;
      uint32_t bad = 0;
      bool redo = false, ready = false;
      wg_fence();
      wgmma_rs24<0, 1, KP1_>(d, W[0], db);
#pragma unroll
      for (int ks = 1; ks < 32; ks++) {
        if (ks == 2 || ks == 14) bad |= xo2(lds32(sv + (ks == 2 ? 0 : 9) * 1024 + warp * 1024), lds32(sv + (ks == 2 ? 8 : 17) * 1024), tag);
        if (ks == 25) bad |= lds32(sv + (18 + min(warp, 5)) * 1024) ^ tag;
        if (ks == 6) {
          const uint32_t z5 = DRAIN(toff + M_TST);
          __syncwarp();
          if (lane == 0) mbar_arrive(BAR(B_STG) + z5);
        }
        if (ks == 27) ready = mbar_test(BAR(C < 2 ? B_KFREE : B_VFREE), ph ^ 1) & mbar_test(BAR(B_HA), ph);
        if ((EARLY_ && (ks == 9 || ks == 21)) || ks == RED_) redo = bar_or(N_W, 256, T > 0 && (bad & 1u));
        if (ks == 12 || ks == 24) {
          if (EARLY_ && __builtin_expect(redo, 0)) break;
          mbar_wait(BAR(B_LAND + ks / 12), ph); WSTAMP(6 + ks / 12); wg_fence();
        }
        wgmma_rs24<1, 1>(d, W[ks], db + ks * 48);
      }
      wg_commit();
      uint32_t a0 = rba + qoff, a1 = a0 + 128, a2 = rbc + qoff, a3 = a2 + 128, ba = rba + MYBAR, bc = rbc + MYBAR;
      PIN(a0); PIN(a1); PIN(a2); PIN(a3); PIN(ba); PIN(bc);
      if (!ready) {
        mbar_wait(BAR(C < 2 ? B_KFREE : B_VFREE), ph ^ 1);
        if (T < NSTEP - 1) mbar_wait(BAR(B_HA), ph);
      }
      wg_wait<0>(); reg_fence(d);
      if (__builtin_expect(redo, 0)) {
        auto stale = [&]() { return __any_sync(~0u, or3(lds32(sv + warp * 3072) ^ tag, lds32(sv + warp * 3072 + 1024) ^ tag, lds32(sv + warp * 3072 + 2048) ^ tag) & 1u); };
        auto fetch = [&]() {
          e_expect(BAR(B_FIX + warp), 3072);
          e_g2s(sb + M_MEM + warp * 3072, memg + warp * 8192 + uni(lds32(sb + M_NEAR + warp * 4)) * 4096, 3072, BAR(B_FIX + warp));
        };
        mbar_wait(BAR(B_LAND + warp / 3), ph);
        bool late = stale();
        if (late) fetch();
        constexpr uint64_t dc = mkdesc(M_MEM, 128, 256, 0);
#pragma unroll
        for (int ks = 0; ks < 32; ks++) {
          if (ks % 12 == 0) {
            if (ks) { wg_commit(); wg_wait<0>(); reg_fence(d); }
            if (warp / 3 == ks / 12) {
              for (int guard = 0; late; guard++) {
                mbar_wait(BAR(B_FIX + warp), fix); fix ^= 1;
                late = stale();
                if (late) fetch();
                if (guard > (1 << 20)) __trap();
              }
            }
            bar_sync(N_W, 256);
            wg_fence();
          }
          if (ks == 0) wgmma_rs24<0, 1, 1>(d, W[0], dc); else wgmma_rs24<1, 1>(d, W[ks], dc + ks * 48);
        }
        wg_commit();
        wg_wait<0>(); reg_fence(d);
      }
      WSTAMP(2);
      uint32_t lo[3], hi[3];
#pragma unroll
      for (int j = 0; j < 3; j++) { lo[j] = pack2(d[4 * j], d[4 * j + 1]); hi[j] = pack2(d[4 * j + 2], d[4 * j + 3]); }
      if (__builtin_expect(T == 0, 0)) { sts32(sb + M_M0 + tid * 8, lo[0]); sts32(sb + M_M0 + tid * 8 + 4, hi[0]); }
      if (__builtin_expect(cand >= 0, 0)) {
        if (T == LAG) { lo[1] = lds32(sb + M_M0 + tid * 8); hi[1] = lds32(sb + M_M0 + tid * 8 + 4); }
        if (C < 2) { st_async32(a0 + 5 * 2048, lo[2], ba); st_async32(a1 + 5 * 2048, hi[2], ba); }
        else { sts32(sb + qoff + 5 * 2048, lo[2]); sts32(sb + qoff + 5 * 2048 + 128, hi[2]); }
        lo[2] = lo[1]; hi[2] = hi[1];
      }
      uint32_t z5;
      if (C == 0) {
        sts32(sb + qoff, lo[0]); sts32(sb + qoff + 128, hi[0]); z5 = DRAIN(sb + qoff);
        st_async32(a0, lo[2], ba); st_async32(a1, hi[2], ba); st_async32(a2, lo[1], bc); st_async32(a3, hi[1], bc);
      } else if (C == 1) {
        sts32(sb + qoff, lo[1]); sts32(sb + qoff + 128, hi[1]); z5 = DRAIN(sb + qoff);
        st_async32(a0, lo[2], ba); st_async32(a1, hi[2], ba); st_async32(a2, lo[0], bc); st_async32(a3, hi[0], bc);
      } else {
        sts32(sb + qoff, lo[2]); sts32(sb + qoff + 128, hi[2]); z5 = DRAIN(sb + qoff);
        st_async32(a0, lo[0], ba); st_async32(a1, hi[0], ba); st_async32(a2, lo[1], bc); st_async32(a3, hi[1], bc);
      }
      __syncwarp();
      if (lane == 0) { mbar_arrive(sb + MYBAR + z5); if (w == 3) mbar_arrive(BAR(B_SS)); }
      if (T == NSTEP - 1) break;
    }
    {
      const uint64_t dh = mkdesc(M_H, 16, 1024, 1) + Z;
      if (T < 0) mbar_wait(BAR(B_HA), ph);
      WSTAMP(3);
      wg_fence();
      wgmma_rs32<0, 0, 1>(d, W[0], dh);
#pragma unroll
      for (int ks = 1; ks < EA; ks++) {
        if (ks == E1 || ks == E1 + E2) {
          wg_commit();
          if (T >= 0) { if (ks == E1 && E2 > 0) bar_sync(N_GO1, 384); if (ks == E1 + E2) bar_sync(N_GO2, 384); }
          wg_fence();
        }
        wgmma_rs32<1, 0>(d, W[ks], dh + (ks >> 2) * 256 + (ks & 3) * 2);
      }
      wg_commit();
      mbar_wait(BAR(B_HB), ph);
      wg_wait<0>();
      if (sig) mbar_arrive_remote(rbar + 8 * B_HAE);
      WSTAMP(4);
      if (T >= 0) bar_sync(N_GO3, 384);
      if (wg == 1) bar_sync(N_W, 256);
      wg_fence();
#pragma unroll
      for (int ks = EA; ks < 32; ks++) wgmma_rs32<1, 0>(d, W[ks], dh + (ks >> 2) * 256 + (ks & 3) * 2);
      wg_commit();
      if (wg == 0) bar_arrive(N_W, 256);
      mbar_wait(BAR(B_TFREE), ph ^ 1);
      wg_wait<0>(); reg_fence(d);
#pragma unroll
      for (int i = 0; i < 8; i++) { tp[i] = pack2(d[2 * i], d[2 * i + 1]); PIN(tp[i]); }
      wg_fence();
      wgmma_rs32<0, 0, 1>(d, W[0], dh + 2048);
      stmatrix4(toff + M_TST, tp[0], tp[1], tp[2], tp[3]); stmatrix4(toff + M_TST + 4096, tp[4], tp[5], tp[6], tp[7]);
#pragma unroll
      for (int ks = 1; ks < 32; ks++) {
        if (PAUSE_ && (ks == PAUSE_ || ks == PAUSE_ + PD1_ || ks == PAUSE_ + PD2_)) {
          wg_commit();
          if (T >= 0 && ks == pk) bar_sync(N_GO4, 384);
          wg_fence();
        }
        wgmma_rs32<1, 0>(d, W[ks], dh + 2048 + (ks >> 2) * 256 + (ks & 3) * 2);
      }
      wg_commit();
      if (T >= 0) cand = __shfl_sync(~0u, (int)lds32(sb + M_CAND + ((T + 1) & 3) * 4), 0);
      wg_wait<0>(); reg_fence(d);
      if (T >= 0) WSTAMP(6);
#pragma unroll
      for (int i = 0; i < 8; i++) tp[i] = pack2(d[2 * i], d[2 * i + 1]);
    }
  }
  cluster_sync();
  if (tid == 0 && cta == 0) GSTAMP(0, 5);
}

__device__ __forceinline__ void attn_role(const Params& p, const uint32_t sb, const int w, const int cta, const int head, const int C, const uint32_t E,
                                          uint8_t* const part, uint8_t* const memg) {
  const int tid = fresh_tid(), lane = tid & 31;
  const int g = lane >> 2, t = lane & 3;
  uint32_t tag = ((E - 1) * (uint32_t)(NSTEP - 1)) & 1;
#pragma unroll 1
  for (int k = 0; k < 2; k++) {
#pragma unroll 1
    for (int i = 0; i < 6; i++) sts128(sb + M_MEM + (w + 4 * k) * 3072 + lane * 16 + i * 512, make_uint4(0, 0, 0, 0));
    fill_mem0(sb + M_MEM, (w + 4 * k) * 64, lane, 0, p.mem0);
  }
  fence_async_smem();
  bar_sync(N_AG, 128);
  if (w == 3 && lane < 3) mbar_arrive(BAR(B_LAND + lane));
  if (w < 2 && lane == 0) {
    const int n = probe_near(part + cta * 16384 + w * 8192);
    sts32(sb + M_NEAR + 32 + w * 4, n);
    st_rel(&f_choice[cta][w], (E << 1) | (uint32_t)n);
  }
  __syncwarp();
  uint32_t nb;
  {
    const int i = min(lane >> 1, C < 2 ? 8 : 5);
    const int r = ((i / 3 * 3 + C) * 4 + w) * 3 + i % 3;
    int guard = 0; uint32_t cw;
    while (__any_sync(~0u, ((cw = ld_acq(&f_choice[r][lane & 1])) >> 1) != (E & 0x7FFFFFFFu))) { if (++guard > (1 << 22)) __trap(); }
    nb = __ballot_sync(~0u, cw & 1) >> (lane >> 4);
  }
  bar_sync(N_AG, 128);
  const uint32_t pt0 = sb + M_PT + (tid & 127) * 16;
  {
    const uint32_t po = (C * 4 + w) * 49152 + (lane >> 4) * 8192 + ((lane >> 3) & 1) * 2048 + head * 64 + (lane & 7) * 8;
    const uint8_t* in = part + (cta * 16384 + (w >> 1) * 8192 + lds32(sb + M_NEAR + 32 + (w >> 1) * 4) * 4096 + (w & 1) * 2048 + lane * 8);
    const uint8_t* outp = memg + ((cta / 12) * 8192 + (cta % 12) * 256 + w * 64 + (lane >> 4) * 4096 + (lane & 4) * 8 + (lane & 8) * 2 + (lane & 3) * 4);
#pragma unroll 1
    for (int i = 0; i < 12; i++) {
      const int j = i / 4 * 3 + (i & 3);
      const uint8_t* a = (i & 3) < 3 ? part + (po + i / 4 * 589824 + (i & 3) * 16384 + ((nb >> (2 * j)) & 1) * 4096) : i == 11 ? in : outp;
      asm volatile("st.shared.u64 [%0], %1;" :: "r"(pt0 + (i >> 1) * 2048 + (i & 1) * 8), "l"(a) : "memory");
    }
  }
  const int xd = __shfl_sync(~0u, XDLY_ + (cta < 36 ? 0 : cta < 72 ? X1_ : X2_), 0);
  const uint32_t rba = mapa(sb, C == 2 ? 0 : 2), rbc = mapa(sb, C == 1 ? 0 : 1);
  uint32_t vis = vis_bits(8 + 8 * w + g, t);
  uint32_t ln = lane;
#pragma unroll
  for (int i = 0; i < SALT_; i++) ln += lds32(sb + M_ZERO);
  PIN(vis); PIN(ln);
  uint32_t fa[8][4];
#pragma unroll
  for (int ks = 0; ks < 8; ks++) ldmatrix4_t(fa[ks], sb + M_WO + 32768 + w * 256 + (lane >> 4) * 1024 + (lane & 15) * 16 + ks * 2048);
#pragma unroll 1
  for (int T = 0; T < NSTEP; T++) {
    const uint32_t ph = T & 1;
    const uint32_t zz = uni(lds32(sb + M_ZERO));
    const bool more = T < NSTEP - 1;
    const float sc = 0.08838834764831845f * 1.4426950408889634f;
    tag ^= 1;
    float s[20];
    const uint8_t* in; int cnext = -1; uint32_t tx; bool synced;
    float x[10], tm, ts;
    uint32_t pt[5];
    auto tok_max = [&]() {
      PIN(vis);
      x[0] = s[2]; x[1] = s[3];
#pragma unroll
      for (int i = 0; i < 8; i++) x[2 + i] = (vis >> i & 1) ? s[4 * (i / 2 + 1) + 2 + (i & 1)] : -INFINITY;
      tm = fmaxf(fmaxf(fmaxf(fmaxf(x[0], x[1]), fmaxf(x[2], x[3])), fmaxf(fmaxf(x[4], x[5]), fmaxf(x[6], x[7]))), fmaxf(x[8], x[9]));
      HOLD(7, __float_as_uint(tm));
    };
    auto tok_exp1 = [&]() {
      tm = fmaxf(tm, __shfl_xor_sync(~0u, tm, 1));
      tm = fmaxf(tm, __shfl_xor_sync(~0u, tm, 2));
      const float b = -tm * sc;
#pragma unroll
      for (int i = 0; i < 10; i++) x[i] = fmaf(x[i], sc, b);
      HOLD(10, __float_as_uint(x[9]));
    };
    auto tok_exp2 = [&]() {
#pragma unroll
      for (int i = 0; i < 10; i++) x[i] = ex2(x[i]);
      ts = (((x[0] + x[1]) + (x[2] + x[3])) + ((x[4] + x[5]) + (x[6] + x[7]))) + (x[8] + x[9]);
#pragma unroll
      for (int k = 0; k < 5; k++) pt[k] = pack2(x[2 * k], x[2 * k + 1]);
      HOLD(8, __float_as_uint(ts));
    };
    {
      uint32_t q[8][4];
      auto load_q = [&](uint32_t a, int h) {
#pragma unroll
        for (int k2 = 0; k2 < 4; k2++) {
          uint32_t r[4];
          ldmatrix4_t(r, a + k2 * 512);
          q[2 * k2][h] = r[0]; q[2 * k2][h + 2] = r[1]; q[2 * k2 + 1][h] = r[2]; q[2 * k2 + 1][h + 2] = r[3];
        }
      };
      PIN(ln);
      const uint32_t qa = sb + M_Q + ln * 16;
      const int cand = C == 2 ? (int)uni(lds32(sb + M_CAND + (T & 3) * 4)) : -1;
      mbar_wait(BAR(B_TOK), ph);
      load_q(qa + (1 + w) * 2048, 1);
      mbar_wait(BAR(B_QK), ph);
      ASTAMP(0);
      if (__builtin_expect(cand >= 0, 0)) {
        mbar_wait(BAR(B_V), ph);
        PIN(ln);
        const int e = w * 32 + ln;
#pragma unroll
        for (int i = 0; i < 3; i++) {
          const uint32_t v = lds32(sb + M_Q + i * 12288 + 5 * 2048 + e * 16 + 4);
          asm volatile("st.shared.u16 [%0], %1;" :: "r"(sb + M_Q + i * 12288 + (1 + (cand >> 3)) * 2048 + e * 16 + (cand & 7) * 2), "h"((unsigned short)v) : "memory");
        }
        fence_async_smem();
        bar_sync(N_AG, 128);
        load_q(qa + (1 + w) * 2048, 1);
      }
      load_q(qa, 0);
      fence_async_smem();
      constexpr uint64_t dk = mkdesc(M_K, 128, 2048, 0);
      wg_fence();
      wgmma_rs40<0, 1>(s, q[0], dk);
#pragma unroll
      for (int ks = 1; ks < 8; ks++) wgmma_rs40<1, 1>(s, q[ks], dk + ks * 16);
      wg_commit();
    }
    if (more) {
      uint32_t v[5][4];
      PIN(ln);
      const uint32_t va = sb + M_V + w * 512 + ((ln >> 3) & 1) * 128 + (ln >> 4) * 2048 + (ln & 7) * 16;
      const uint32_t ooff = M_OM + w * 1536 + C * 256 + ln * 4;
      mbar_wait(BAR(B_V), ph);
      wg_wait<0>(); reg_fence(s);
      if (E2 > 0) bar_arrive(N_GO1, 384);
      if (ln < 3) mbar_arrive_remote(mapa(BAR(B_KFREE), ln));
      ldmatrix4(v[0], va); ldmatrix4(v[1], va + 256); ldmatrix4(v[2], va + 4096); ldmatrix4(v[3], va + 4096 + 256);
      ldmatrix4(v[4], sb + M_V + 8192 + w * 512 + ln * 16);
      ASTAMP(1);
      float m = fmaxf(fmaxf(fmaxf(fmaxf(s[0], s[1]), fmaxf(s[4], s[5])), fmaxf(fmaxf(s[8], s[9]), fmaxf(s[12], s[13]))), fmaxf(s[16], s[17]));
      m = fmaxf(m, __shfl_xor_sync(~0u, m, 1));
      m = fmaxf(m, __shfl_xor_sync(~0u, m, 2));
      const float b = -m * sc;
      uint32_t pm[5];
#pragma unroll
      for (int j = 0; j < 5; j++) pm[j] = pack2(ex2(fmaf(s[4 * j], sc, b)), ex2(fmaf(s[4 * j + 1], sc, b)));
      float o0[4] = {0.f, 0.f, 0.f, 0.f}, o1[4] = {0.f, 0.f, 0.f, 0.f}, l[4] = {0.f, 0.f, 0.f, 0.f};
      const uint32_t one[4] = {0x3f803f80u, 0x3f803f80u, 0x3f803f80u, 0x3f803f80u};
      hmma16(l, one, pm[0], pm[1]); hmma16(o0, v[0], pm[0], pm[1]); hmma16(o1, v[1], pm[0], pm[1]);
      hmma16(l, one, pm[2], pm[3]); hmma16(o0, v[2], pm[2], pm[3]); hmma16(o1, v[3], pm[2], pm[3]);
      hmma8(l, one[0], one[1], pm[4]); hmma8(o0, v[4][0], v[4][1], pm[4]); hmma8(o1, v[4][2], v[4][3], pm[4]);
      const float r0 = rcp(l[0]), r1 = rcp(l[1]);
      const uint32_t u0 = pack2(o0[0] * r0, o0[1] * r1), u1 = pack2(o0[2] * r0, o0[3] * r1), u2 = pack2(o1[0] * r0, o1[1] * r1), u3 = pack2(o1[2] * r0, o1[3] * r1);
      constexpr uint32_t OB = M_BAR + 8 * B_OM;
      const uint32_t a0 = rba + ooff, a1 = rbc + ooff;
      st_async32(a0, u0, rba + OB); st_async32(a1, u0, rbc + OB);
      st_async32(a0 + 128, u1, rba + OB); st_async32(a1 + 128, u1, rbc + OB);
      st_async32(a0 + 768, u2, rba + OB); st_async32(a1 + 768, u2, rbc + OB);
      st_async32(a0 + 896, u3, rba + OB); st_async32(a1 + 896, u3, rbc + OB);
      if (E3 > 0) bar_arrive(N_GO2, 384);
      sts32(sb + ooff, u0); sts32(sb + ooff + 128, u1); sts32(sb + ooff + 768, u2); sts32(sb + ooff + 896, u3);
      ASTAMP(2);
      uint32_t fb[8][4];
      const uint32_t wa = sb + M_WO + 16384 + w * 256 + (ln >> 4) * 1024 + (ln & 15) * 16 + zz;
      ldmatrix4_t(fb[0], wa);
      SCHED(3);
#pragma unroll
      for (int ks = 1; ks < 8; ks++) {
        ldmatrix4_t(fb[ks], wa + ks * 2048);
        if (ks == ARR_) { __syncwarp(); if (ln == 0) mbar_arrive(BAR(B_OM) + (fb[0][0] & zz)); }
      }
      if (C == 2) cnext = (int)uni(lds32(sb + M_CAND + ((T + 1) & 3) * 4));
      {
        float d[12], e[12];
        constexpr uint64_t ob = mkdesc(M_OM, 128, 256, 0);
        uint8_t* q[3][3];
        auto addr = [&](int i) {
          asm volatile("ld.shared.v2.u64 {%0,%1}, [%2];" : "=l"(q[i][0]), "=l"(q[i][1]) : "r"(pt0 + i * 4096) : "memory");
          if (i < 2) asm volatile("ld.shared.u64 %0, [%1];" : "=l"(q[i][2]) : "r"(pt0 + i * 4096 + 2048) : "memory");
          else asm volatile("ld.shared.v2.u64 {%0,%1}, [%2];" : "=l"(q[i][2]), "=l"(in) : "r"(pt0 + i * 4096 + 2048) : "memory");
        };
        auto put = [&](const float* d, int i) {
          st_rlx64(q[i][0], (pack2(d[0], d[1]) & ~1u) | tag, pack2(d[2], d[3]));
          st_rlx64(q[i][1], (pack2(d[4], d[5]) & ~1u) | tag, pack2(d[6], d[7]));
          st_rlx64(q[i][2], (pack2(d[8], d[9]) & ~1u) | tag, pack2(d[10], d[11]));
        };
        addr(0); addr(1);
        SCHED(6);
        tok_max();
        ASTAMP(3);
        mbar_wait(BAR(B_OM), ph);
        fence_async_smem();
        ASTAMP(4);
        constexpr uint64_t w0 = mkdesc(M_WO, 1024, 128, 0);
        float (&f)[12] = d;
        wg_fence();
        wgmma_ss24<0, 1, 1>(d, w0, ob);
#pragma unroll
        for (int ks = 1; ks < 8; ks++) wgmma_ss24<1, 1, 1>(d, w0 + ks * 128, ob + ks * 48);
        wg_commit();
        wgmma_rs24<0, 1>(e, fb[0], ob);
#pragma unroll
        for (int ks = 1; ks < HAND_; ks++) wgmma_rs24<1, 1>(e, fb[ks], ob + ks * 48);
        wg_commit();
        wg_wait<1>(); reg_fence(d);
        put(d, 0);
        addr(2);
        SCHED(4);
        ASTAMP(5);
        wg_fence();
#pragma unroll
        for (int ks = HAND_; ks < 8; ks++) wgmma_rs24<1, 1>(e, fb[ks], ob + ks * 48);
        wg_commit();
        wgmma_rs24<0, 1, 1>(f, fa[0], ob);
#pragma unroll
        for (int ks = 1; ks < HAND_; ks++) wgmma_rs24<1, 1>(f, fa[ks], ob + ks * 48);
        wg_commit();
        wg_wait<1>(); reg_fence(e);
        put(e, 1);
        SCHED(5);
        wg_fence();
#pragma unroll
        for (int ks = HAND_; ks < 8; ks++) wgmma_rs24<1, 1>(f, fa[ks], ob + ks * 48);
        wg_commit();
        if (GO3_ == 0) bar_arrive(N_GO3, 384);
        synced = __all_sync(~0u, mbar_test(BAR(B_SYNC), ph));
        tx = uni(lds32(sb + M_BASE + ph * 4)) + xd;
        wg_wait<0>(); reg_fence(f);
        if (GO3_ == 1) bar_arrive(N_GO3, 384);
        if (C < 2) put(f, 2);
        if (GO3_ == 2) bar_arrive(N_GO3, 384);
        ASTAMP(6);
      }
    } else {
      mbar_wait(BAR(B_V), ph);
      wg_wait<0>(); reg_fence(s);
      tok_max();
    }
    uint2 v[8];
#pragma unroll
    for (int i = 0; i < 8; i++) v[i] = make_uint2(zz, zz);
    auto poll = [&](uint2* v) {
      v[0] = ld_rlx64<0>(in); v[1] = ld_rlx64<256>(in); v[2] = ld_rlx64<512>(in); v[3] = ld_rlx64<768>(in);
      v[4] = ld_rlx64<1024>(in); v[5] = ld_rlx64<1280>(in); v[6] = ld_rlx64<1536>(in); v[7] = ld_rlx64<1792>(in);
    };
    uint8_t* outp;
    asm volatile("ld.shared.u64 %0, [%1];" : "=l"(outp) : "r"(pt0 + 2048 + 8) : "memory");
    const bool sum = more && cnext < 0;
    if (more) {
      if (!synced) { mbar_wait(BAR(B_SYNC), ph); tx = uni(lds32(sb + M_BASE + ph * 4)) + xd; }
      ASTAMP(7);
      if (__builtin_expect(cnext >= 0, 0)) {
        const unsigned long long* hp = (const unsigned long long*)&g_hc[T + 1 - LAG][0] + ((cta / 3) * 8 + 2 * w + ((ln >> 2) & 1));
        unsigned long long v0; int guard = 0;
        while (v0 = ld_rlxu64(hp), !__all_sync(~0u, (uint32_t)(v0 >> 32) == E)) { if (++guard > (1 << 22)) __trap(); }
        st_rlx((uint32_t*)outp, (ln & 3) == 1 ? ((uint32_t)v0 >> ((ln & 8) * 2)) & 0xffffu : (ln & 1) ? 0u : tag);
      } else {
        spin_until(tx);
        ASTAMP(8);
        poll(v);
      }
    }
    auto late = [&](const uint2* v) {
      return __any_sync(~0u, (or3(xo2(v[0].x, v[1].x, tag), xo2(v[2].x, v[3].x, tag), xo2(v[4].x, v[5].x, tag)) | xo2(v[6].x, v[7].x, tag)) & 1u);
    };
    tok_exp1(); tok_exp2();
    if (sum) {
      ASTAMP(9);
      int guard = 0;
      while (late(v)) {
        if (++guard > (1 << 22)) __trap();
        poll(v);
      }
#pragma unroll
      for (int i = 0; i < 4; i++) { v[i].x = add2(v[i].x, v[i + 4].x); v[i].y = add2(v[i].y, v[i + 4].y); }
#define SUM8(f, m) ((f(v[0].m) + f(v[1].m)) + (f(v[2].m) + f(v[3].m)))
      const float a0 = SUM8(blo, x), a1 = SUM8(bhi, x), b0 = SUM8(blo, y), b1 = SUM8(bhi, y);
      const bool hi = ln & 8;
      float k0 = (hi ? b0 : a0) + __shfl_xor_sync(~0u, hi ? a0 : b0, 8), k1 = (hi ? b1 : a1) + __shfl_xor_sync(~0u, hi ? a1 : b1, 8);
      k0 += __shfl_xor_sync(~0u, k0, 16); k1 += __shfl_xor_sync(~0u, k1, 16);
      st_rlx((uint32_t*)outp, (ln & 1) ? pack2(k0, k1) : pack2_tag(k0, k1, tag));
      ASTAMP(10);
      CSTAMP(12 + w, (clk() & ~15u) | min(guard + 1, 15));
    }
    if (PAUSE_ && more) bar_arrive(N_GO4, 384);
    {
      PIN(ln);
      const uint32_t oa = sb + M_OST + w * 128 + (ln >> 3) * 512 + (ln & 7) * 16;
      const uint32_t a[3][4] = {{0, pt[0], 0, pt[1]}, {0, pt[2], 0, pt[3]}, {0, pt[4], 0, 0}};
      constexpr uint64_t dv = mkdesc(M_V, 2048, 128, 0);
#pragma unroll 1
      for (int h = 0; h < 2; h++) {
        float o[32];
        const uint64_t dh = dv + (uint64_t)(h * 64);
        wg_fence();
        wgmma_rs64<0, 0>(o, a[0], dh); wgmma_rs64<1, 0>(o, a[1], dh + 256); wgmma_rs64<1, 0>(o, a[2], dh + 512);
        wg_commit();
        if (h == 0) {
          ts += __shfl_xor_sync(~0u, ts, 1);
          ts += __shfl_xor_sync(~0u, ts, 2);
          ts = rcp(ts);
          mbar_wait(BAR(B_OFREE), ph ^ 1);
        }
        wg_wait<0>(); reg_fence(o);
        if (h == 1 && ln < 3) mbar_arrive_remote(mapa(BAR(B_VFREE), ln));
#define OT(i) pack2(o[4 * (i) + 2] * ts, o[4 * (i) + 3] * ts)
        stmatrix4(oa + h * 4096, OT(0), OT(1), OT(2), OT(3));
        stmatrix4(oa + h * 4096 + 2048, OT(4), OT(5), OT(6), OT(7));
      }
      const uint32_t z5 = DRAIN(oa);
      __syncwarp();
      if (ln == 0) mbar_arrive(BAR(B_OST) + z5);
      ASTAMP(11);
    }
  }
}

__global__ void __cluster_dims__(3, 1, 1) __launch_bounds__(512, 1) main_kernel(Params p) {
  extern __shared__ __align__(1024) uint8_t sm[];
  const uint32_t sb = smem_u32(sm);
  if ((sb & 0xFFFFFFu) != SBASE) __trap();
  asm volatile("griddepcontrol.launch_dependents;");
  const int warp = __shfl_sync(~0u, threadIdx.x >> 5, 0);
  const int cta = blockIdx.x, head = cta / 3, c = cta % 3;
  const uint32_t E = __shfl_sync(~0u, *(volatile uint32_t*)&g_epoch + 1, 0);
  uint8_t* const part = (uint8_t*)(((uintptr_t)g_xch + 8191) & ~(uintptr_t)8191);
  uint8_t* const memg = part + 96 * 16384;

  if (threadIdx.x == 0 && cta == 0) GSTAMP(0, 0);
  if (threadIdx.x < B_NUM) {
    const int i = threadIdx.x;
    const uint32_t cnt = i == B_STG ? 8 : i == B_OST ? 4 : i == B_HAE || i == B_HBE ? 6 : i == B_KFREE || i == B_VFREE ? 12 : i == B_SS ? 2 : i == B_OM ? 5 :
                         i == B_QK ? (c < 2 ? 9 : 1) : i == B_V ? (c < 2 ? 1 : 9) : 1;
    mbar_init(BAR(i), cnt);
    if (i == B_HA || i == B_HB || i == B_STG || i == B_HAE || i == B_HBE || i == B_TFREE)
      asm volatile("mbarrier.arrive.shared::cta.b64 _, [%0], %1;" :: "r"(BAR(i)), "r"(cnt) : "memory");
    asm volatile("fence.mbarrier_init.release.cluster;" ::: "memory");
  }
  if (warp < 8) {
    const int tid = threadIdx.x;
    uint4 wa[6], wb[6];
#pragma unroll
    for (int i = 0; i < 6; i++) {
      const int mi = i >> 1, e = (tid >> 2) + (i & 1) * 64;
      const uint4* src = (const uint4*)(p.wo + (size_t)(head * 128 + e) * 512 + min(3 * mi + c, 7) * 64 + (tid & 3) * 16);
      wa[i] = __ldg(src); wb[i] = __ldg(src + 1);
    }
    stage_weights(sb, (c == 0 ? p.wq : c == 1 ? p.wk : p.wv) + head * 128, 4096, tid, 256);
#pragma unroll
    for (int i = 0; i < 6; i++) {
      const int mi = i >> 1, e = (tid >> 2) + (i & 1) * 64;
      const uint4 a = wa[i], b = wb[i];
      const uint32_t dst = sb + M_WO + mi * 16384 + (e >> 3) * 1024 + (tid & 3) * 256 + (e & 7) * 16;
      sts128(dst, make_uint4(__byte_perm(a.x, a.y, 0x5410), __byte_perm(a.z, a.w, 0x5410), __byte_perm(b.x, b.y, 0x5410), __byte_perm(b.z, b.w, 0x5410)));
      sts128(dst + 128, make_uint4(__byte_perm(a.x, a.y, 0x7632), __byte_perm(a.z, a.w, 0x7632), __byte_perm(b.x, b.y, 0x7632), __byte_perm(b.z, b.w, 0x7632)));
    }
  } else {
    const int i0 = threadIdx.x - 256;
    const uint32_t tag0 = ((E - 1) * (uint32_t)(NSTEP - 1)) & 1;
    for (int i = i0; i < 1024; i += 256) *(uint4*)(part + cta * 16384 + i * 16) = make_uint4(tag0, 0, tag0, 0);
    if (i0 < 16) *(uint32_t*)(memg + i0 * 4096 + 3968) = 0;
    if (i0 < 12) sts32(sb + M_ZERO + i0 * 4, 0);
  }

  if (warp < 8) {
    asm volatile("setmaxnreg.inc.sync.aligned.u32 " STR(RW_) ";");
    weight_role(p, sb, warp, cta, c, E, memg);
  } else if (warp < 12) {
    if (RA_ < 128) asm volatile("setmaxnreg.dec.sync.aligned.u32 " STR(RA_) ";");
    if (RA_ > 128) asm volatile("setmaxnreg.inc.sync.aligned.u32 " STR(RA_) ";");
    cluster_sync();
    attn_role(p, sb, warp - 8, cta, head, c, E, part, memg);
    cluster_sync();
  } else {
    asm volatile("setmaxnreg.dec.sync.aligned.u32 " STR(RC_) ";");
    const int tid = fresh_tid(), lane = tid & 31;
    const int w = warp - 12;
    cluster_sync();
    if (w < 3 && lane == 0) {
      const int tl = min(3 * w + c, 7);
      const int n = probe_near(memg + tl * 8192);
      for (int r = 0; r < 3; r++) asm volatile("st.shared::cluster.u32 [%0], %1;" :: "r"(mapa(sb + M_NEAR + tl * 4, r)), "r"(n) : "memory");
    }
    __syncwarp();
    if (w == 0) {
      uint32_t s0 = c * 8192, s1 = (3 + c) * 8192, s2 = min(6 + c, 7) * 8192;
#pragma unroll 1
      for (int T = 0; T < NSTEP - 1; T++) {
        const uint32_t ph = T & 1;
        mbar_wait(BAR(B_SS), ph);
        const uint32_t cq = clk();
        const uint32_t g0 = (uint32_t)gtime64(); uint32_t g1, ce;
        do { g1 = (uint32_t)gtime64(); ce = clk(); } while (g1 == g0);
        const uint32_t tn = g1 * 8 - (((ce - cq) * 37u) >> 3), id = E * 128u + T;
        if (lane == 0) st_rlx64(&g_sync[ph][cta], tn, id);
        if (lane < 3) mbar_expect(BAR(B_LAND + lane), lane < 2 ? 9216 : 6144);
        if (T == 0) { s0 += uni(lds32(sb + M_NEAR + c * 4)) * 4096; s1 += uni(lds32(sb + M_NEAR + (3 + c) * 4)) * 4096; s2 += uni(lds32(sb + M_NEAR + min(6 + c, 7) * 4)) * 4096; }
        wait_until(cq + SDLY_);
        int guard = 0; unsigned long long v0, v1, v2;
        for (;;) {
          v0 = ld_rlxu64(&g_sync[ph][lane]); v1 = ld_rlxu64(&g_sync[ph][lane + 32]); v2 = ld_rlxu64(&g_sync[ph][lane + 64]);
          if (__all_sync(~0u, (uint32_t)(v0 >> 32) == id && (uint32_t)(v1 >> 32) == id && (uint32_t)(v2 >> 32) == id)) break;
          if (++guard > (1 << 22)) __trap();
        }
        const int dl = __reduce_max_sync(~0u, max(max((int)((uint32_t)v0 - tn), (int)((uint32_t)v1 - tn)), (int)((uint32_t)v2 - tn)));
        const uint32_t base = uni(cq + ((min(dl, 8 * 4096) * 7) >> 5));
        if (lane == 0) { sts32(sb + M_BASE + ph * 4, base); mbar_arrive(BAR(B_SYNC)); }
        CSTAMP(0, base); CSTAMP(1, clk());
        const uint32_t ts = base + YDLY_;
        uint32_t nr = 0;
        if (PRIV_) nr = __ballot_sync(~0u, lds32(sb + M_NEAR + (lane & 7) * 4) != 0);
        wait_until(ts);
        if (PRIV_ & 1) { for (int k = 0; k < 3; k++) e_g2s(sb + M_MEM + k * 3072, memg + k * 8192 + ((nr >> k) & 1) * 4096, 3072, BAR(B_LAND)); }
        else e_mc(sb + M_MEM + c * 3072, memg + s0, 3072, BAR(B_LAND), 7);
        CSTAMP(2, clk());
        spin_until(ts + Y1_);
        if (PRIV_ & 2) { for (int k = 3; k < 6; k++) e_g2s(sb + M_MEM + k * 3072, memg + k * 8192 + ((nr >> k) & 1) * 4096, 3072, BAR(B_LAND + 1)); }
        else e_mc(sb + M_MEM + (3 + c) * 3072, memg + s1, 3072, BAR(B_LAND + 1), 7);
        CSTAMP(3, clk());
        spin_until(ts + Y2_);
        if (PRIV_ & 4) { for (int k = 6; k < 8; k++) e_g2s(sb + M_MEM + k * 3072, memg + k * 8192 + ((nr >> k) & 1) * 4096, 3072, BAR(B_LAND + 2)); }
        else if (c < 2) e_mc(sb + M_MEM + (6 + c) * 3072, memg + s2, 3072, BAR(B_LAND + 2), 7);
        CSTAMP(4, clk());
      }
    } else if (w == 1) {
#pragma unroll 1
      for (int T = 0; T < NSTEP; T++) {
        const uint32_t ph = T & 1;
        const int s = c == 0 ? T : T - LAG;
        const bool act = s >= 0 && s < NSEG;
        mbar_wait(BAR(B_OST), ph);
        if (cta == 0) TSTAMP(2, T, 0);
        fence_async_smem();
        if (T < NSTEP - 1) wait_until(uni(lds32(sb + M_BASE + ph * 4)) + ODLY_);
        STAMP(22);
        if (act) { e_s2g(g_o[c][s % ORING][head], sb + M_OST, 8192); bulk_wait(); __syncwarp(); }
        e_arrive(BAR(B_OFREE));
        if (cta == 0) TSTAMP(2, T, 1);
        if (act) e_st_rel(&f_o[T][head >> 2][c * 4 + (head & 3)], E);
        if (cta == 0) TSTAMP(2, T, 2);
      }
    } else if (w == 2) {
      unsigned long long run = 0;
      static_assert(LAG >= 2, "config");
      constexpr uint32_t NA = EA / 4 * 4096;
      e_expect(BAR(B_QK), c < 2 ? 2048 : 4096); e_expect(BAR(B_V), c == 0 ? 10240 : c == 1 ? 2048 : 0);
      e_expect(BAR(B_TOK), c == 0 ? 16384 : 0); e_expect(BAR(B_OM), 4096);
      if (lane < 2) sts32(sb + M_CAND + lane * 4, (uint32_t)-1);
      e_expect(BAR(B_HA), NA); e_expect(BAR(B_HB), 65536 - NA);
      wait_eq(&f_h1[c == 1 ? 0 : 1], E); fence_async_glob();
      {
        const uint32_t o0 = c == 0 ? NA : 0, o1 = c == 2 ? NA : 32768;
        e_mc(sb + M_H + (c == 1 ? 32768 : 0) + o0, g_h[0][c == 1 ? 0 : 1] + o0, o1 - o0, BAR(c == 2 ? B_HA : B_HB), 7);
      }
      if (c == 2) wait_eq(&f_h1[2], E);
      mbar_wait(BAR(B_HAE), 1);
      e_expect(BAR(B_HA), NA);
      if (c == 2) { fence_async_glob(); e_mc(sb + M_H, g_h[0][2], NA, BAR(B_HA), 7); }
      int cprev = -1;
#pragma unroll 1
      for (int T = 0; T < NSTEP - 1; T++) {
        const int s1 = T + 2, s2 = T + 2 - LAG;
        const uint32_t ph = T & 1;
        const bool l1 = s1 < NSEG, l2 = s2 >= 0 && s2 < NSEG, la = s1 + 1 < NSEG;
        const bool mine = c == 0 ? l1 : c == 1 ? l2 : la;
        const uint32_t* fl = c != 1 ? &f_h1[min(s1 + (c >> 1), NSEG - 1)] : (const uint32_t*)&f_h2[max(s2, 0)][1];
        const uint32_t want = c != 1 ? E : E * 4u;
        mbar_wait(BAR(B_HBE), ph ^ 1);
        const bool early = uni(ld_acq(fl)) == want;
        mbar_wait(BAR(B_LAND + 2), ph);
        STAMP(16);
        e_expect(BAR(B_HB), (l1 ? 32768 - NA : 0) + (l2 ? 32768 : 0));
        if (mine) {
          if (!early) wait_eq(fl, want);
          fence_async_glob();
          if (c == 1) { mbar_wait(BAR(B_QK), ph); spin_until(clk32() + HDLY_); }
          if (c < 2) paced_h(sb + M_H + c * 32768, g_h[c][c ? s2 : s1], c ? 0 : NA, 32768, 4096, BAR(B_HB), HGAP_);
        }
        int cd = -1;
        if (l2) { cd = route_step(s2, E, run); if (cta == 0) TSTAMP(5, s2, 0); }
        if (lane == 0) sts32(sb + M_CAND + ((T + 2) & 3) * 4, (uint32_t)cd);
        __syncwarp();
        STAMP(17);
        mbar_wait(BAR(B_HAE), ph);
        e_expect(BAR(B_HA), la ? NA : 0);
        if (c == 2 && la) {
          spin_until(clk32() + ADLY_);
          STAMP(18);
          paced_h(sb + M_H, g_h[0][s1 + 1], 0, NA, 4096, BAR(B_HA), AGAP_);
        }
        mbar_wait(BAR(B_OST), ph);
        e_expect(BAR(B_QK), c < 2 ? 2048 : cprev >= 0 ? 8192 : 4096);
        e_expect(BAR(B_V), c < 2 ? 10240 : 8192);
        e_expect(BAR(B_TOK), 16384);
        e_expect(BAR(B_OM), 4096);
        cprev = cd;
      }
    } else {
      const uint32_t mytok = sb + M_Q + c * 12288 + 2048, tb = BAR(c < 2 ? B_TOK : B_V);
#pragma unroll 1
      for (int T = 0; T < NSTEP - 1; T++) {
        const uint32_t ph = T & 1;
        uint8_t* const tok = g_tok[cta][ph ^ 1];
        mbar_wait(BAR(B_STG), ph ^ 1);
        fence_async_smem();
        if (cta == 0 && (T == 0 || T == NSEG || T == NSTEP - 2)) GSTAMP(0, T == 0 ? 2 : T == NSEG ? 3 : 4);
        if (T > 0) { mbar_wait(BAR(B_QK), ph); spin_until(clk32() + TDLY_); }
        STAMP(20);
        uint32_t t = clk32();
#pragma unroll 1
        for (uint32_t o = 0; o < 16384; o += 4096) { e_s2g(tok + o, sb + M_TST + o, 4096); spin_until(t += TGAP_); }
        bulk_wait();
        __syncwarp();
        e_arrive(BAR(B_TFREE));
        if (T == 0) e_mc(mytok, tok + 8192, 8192, tb, 1);
        STAMP(21);
        mbar_wait(BAR(c < 2 ? B_KFREE : B_VFREE), ph);
        if (c < 2) t += KDLY_; else t = uni(lds32(sb + M_BASE + ph * 4)) + LDLY_;
        wait_until(t);
        STAMP(23);
        e_mc(mytok, tok, 8192, tb, 1);
        spin_until(t + LGAP_);
        e_mc(mytok, tok + 8192, 8192, tb, 6);
        STAMP(24);
      }
    }
    __syncwarp();
    cluster_sync();
  }
}

constexpr uint32_t A_RING = 0;
constexpr int A_NST = 6;
constexpr uint32_t A_STG = A_RING + A_NST * 8192;
constexpr uint32_t A_WD = A_STG + 8192;
constexpr uint32_t A_WG = A_WD + 57344;
constexpr uint32_t A_WU = A_WG + 57344;
constexpr uint32_t A_XN = A_WU + 57344;
constexpr uint32_t A_BAR = A_XN + 2048;
constexpr uint32_t A_TOTAL = A_BAR + 256;
static_assert(A_TOTAL <= 232448, "aux smem");

__device__ __forceinline__ void load_row(uint32_t* v, const void* row, int lane) {
  const uint4 a = __ldcg((const uint4*)row + lane), b = __ldcg((const uint4*)row + 32 + lane);
  v[0] = a.x; v[1] = a.y; v[2] = a.z; v[3] = a.w; v[4] = b.x; v[5] = b.y; v[6] = b.z; v[7] = b.w;
}
__device__ __forceinline__ void store_row(void* row, const uint32_t* v, int lane) {
  ((uint4*)row)[lane] = make_uint4(v[0], v[1], v[2], v[3]); ((uint4*)row)[32 + lane] = make_uint4(v[4], v[5], v[6], v[7]);
}
__device__ __forceinline__ void store_img(uint8_t* img, int r, const uint32_t* v, int lane) {
  uint8_t* b = img + (lane >> 3) * 4096 + (r >> 3) * 1024 + (r & 7) * 128 + (((lane ^ r) & 7) << 4);
  *(uint4*)b = make_uint4(v[0], v[1], v[2], v[3]);
  *(uint4*)(b + 16384) = make_uint4(v[4], v[5], v[6], v[7]);
}
template <int NT> __device__ __forceinline__ void ln_rows(const uint32_t (*v)[8], uint32_t (*y)[8]) {
  float c[NT], sm[NT], sq[NT];
#pragma unroll
  for (int k = 0; k < NT; k++) {
    c[k] = blo(__shfl_sync(~0u, v[k][0], 0));
    float s0 = 0.f, s1 = 0.f, q0 = 0.f, q1 = 0.f;
#pragma unroll
    for (int i = 0; i < 8; i++) { const float a = blo(v[k][i]) - c[k], b = bhi(v[k][i]) - c[k]; s0 += a; s1 += b; q0 = fmaf(a, a, q0); q1 = fmaf(b, b, q1); }
    sm[k] = s0 + s1; sq[k] = q0 + q1;
  }
#pragma unroll
  for (int o = 16; o > 0; o >>= 1)
#pragma unroll
    for (int k = 0; k < NT; k++) {
      sm[k] += __shfl_xor_sync(~0u, sm[k], o); sq[k] += __shfl_xor_sync(~0u, sq[k], o);
    }
#pragma unroll
  for (int k = 0; k < NT; k++) {
    const float dm = sm[k] * (1.f / 512.f), var = fmaxf(fmaf(-dm, dm, sq[k] * (1.f / 512.f)), 0.f);
    const float mb = rbf(c[k] + dm), inv = rcp(rbf(sqrt_fast(rbf(rbf(var) + 1e-5f))));
#pragma unroll
    for (int i = 0; i < 8; i++) { const uint32_t a = pack2(blo(v[k][i]) - mb, bhi(v[k][i]) - mb); y[k][i] = pack2(blo(a) * inv, bhi(a) * inv); }
  }
}
__device__ __forceinline__ void input_ln_pair(const bf16* x, int s, int pr, int lane) {
  uint32_t v[2][8], y[2][8];
  load_row(v[0], x + (size_t)(s * 32 + 2 * pr) * 512, lane); load_row(v[1], x + (size_t)(s * 32 + 2 * pr + 1) * 512, lane);
  ln_rows<2>(v, y);
  store_img(g_h[0][s], 2 * pr, y[0], lane); store_img(g_h[0][s], 2 * pr + 1, y[1], lane);
}
__device__ __forceinline__ float load_wr(uint32_t* wv, const bf16* wr, int lane) {
  load_row(wv, wr, lane);
  float wsum = 0.f;
#pragma unroll
  for (int i = 0; i < 8; i++) wsum += blo(wv[i]) + bhi(wv[i]);
#pragma unroll
  for (int o = 16; o > 0; o >>= 1) wsum += __shfl_xor_sync(~0u, wsum, o);
  return wsum;
}

__device__ __forceinline__ unsigned long long token_post(int st, int tk, const bf16* res, bf16* dst, bf16* req, unsigned long long best,
                                                         const uint32_t* wv, float wsum, uint32_t E, int lane) {
  const int s = tk >> 5;
  uint32_t x[8];
  load_row(x, res, lane);
  wait_eq(&f_acc[st][s * 8], E * 32u);
  if (tk == s * 32 && st == 0 && lane == 0) TSTAMP(4, s, 0);
  {
    const uint4* pp = (const uint4*)(g_pp[st][s % PRING] + (lane >> 4) * 8192 + (tk & 31) * 256 + (((lane & 15) ^ (tk & 7)) << 4));
    uint4 q[8][2];
#pragma unroll
    for (int k = 0; k < 8; k++) { q[k][0] = __ldcg(pp + k * 2048); q[k][1] = __ldcg(pp + k * 2048 + 1024); }
#define PSUM(f, h, m) (((f(q[0][h].m) + f(q[1][h].m)) + (f(q[2][h].m) + f(q[3][h].m))) + ((f(q[4][h].m) + f(q[5][h].m)) + (f(q[6][h].m) + f(q[7][h].m))))
#define PADD(i, h, m) x[i] = add2(x[i], pack2(PSUM(blo, h, m), PSUM(bhi, h, m)))
    PADD(0, 0, x); PADD(1, 0, y); PADD(2, 0, z); PADD(3, 0, w); PADD(4, 1, x); PADD(5, 1, y); PADD(6, 1, z); PADD(7, 1, w);
  }
  const float c = blo(__shfl_sync(~0u, x[0], 0));
  float s0 = 0.f, s1 = 0.f, q0 = 0.f, q1 = 0.f, r0 = 0.f, r1 = 0.f;
#pragma unroll
  for (int i = 0; i < 8; i++) {
    const float a = blo(x[i]) - c, b = bhi(x[i]) - c;
    s0 += a; s1 += b; q0 = fmaf(a, a, q0); q1 = fmaf(b, b, q1); r0 = fmaf(a, blo(wv[i]), r0); r1 = fmaf(b, bhi(wv[i]), r1);
  }
  s0 += s1; q0 += q1; r0 += r1;
#pragma unroll
  for (int o = 16; o > 0; o >>= 1) { s0 += __shfl_xor_sync(~0u, s0, o); q0 += __shfl_xor_sync(~0u, q0, o); r0 += __shfl_xor_sync(~0u, r0, o); }
  const float dm = s0 * (1.f / 512.f), m = c + dm, var = fmaxf(fmaf(-dm, dm, q0 * (1.f / 512.f)), 0.f);
  const float mb = rbf(m), inv = rcp(rbf(sqrt_fast(rbf(rbf(var) + 1e-5f))));
  const uint32_t nmb = pack2(-mb, -mb);
  const unsigned long long wd = rword(E, tk, fmaf(c - mb, wsum, r0) * inv);
  uint32_t xn[8], x2[8];
#pragma unroll
  for (int i = 0; i < 8; i++) { const uint32_t d = add2(x[i], nmb); xn[i] = pack2(blo(d) * inv, bhi(d) * inv); x2[i] = add2(x[i], xn[i]); }
  if (st == 0) {
    const float mb2 = rbf(fmaf(m - mb, inv, m)), inv2 = rcp(rbf(sqrt_fast(rbf(rbf(var * (1.f + inv) * (1.f + inv)) + 1e-5f))));
    const uint32_t nmb2 = pack2(-mb2, -mb2);
    uint32_t h[8];
#pragma unroll
    for (int i = 0; i < 8; i++) { const uint32_t d2 = add2(x2[i], nmb2); h[i] = pack2(blo(d2) * inv2, bhi(d2) * inv2); }
    store_img(g_h[1][s], tk & 31, h, lane);
  }
  store_row(dst, x2, lane);
  if (wd > best) { store_row(req, xn, lane); store_row(req + 512, x, lane); }
  return wd;
}

__device__ __forceinline__ void ffn_slice(uint32_t sb, const bf16* xn, float* yacc, int t) {
  const int w = t >> 5, g = (t >> 2) & 7;
  { const uint2 u = __ldcg((const uint2*)xn + t); asm volatile("st.shared.v2.u32 [%0], {%1,%2};" :: "r"(sb + A_XN + t * 8), "r"(u.x), "r"(u.y) : "memory"); }
  fence_async_smem();
  bar_sync(4, 128);
  float ga[4], ua[4];
  constexpr uint64_t da = mkdesc(A_WG, 896, 128, 0), db = mkdesc(A_XN, 16, 128, 0);
  wg_fence();
  wgmma_ss8<0, 1, 0>(ga, da, db); wgmma_ss8<0, 1, 0>(ua, da + (A_WU - A_WG) / 16, db);
#pragma unroll
  for (int ks = 1; ks < 32; ks++) { wgmma_ss8<1, 1, 0>(ga, da + ks * 112, db + ks * 2); wgmma_ss8<1, 1, 0>(ua, da + (A_WU - A_WG) / 16 + ks * 112, db + ks * 2); }
  wg_commit(); wg_wait<0>(); reg_fence(ga); reg_fence(ua);
  if ((t & 3) == 0) {
#pragma unroll
    for (int h = 0; h < 2; h++) {
      const float gs = rbf(ga[2 * h]), us = rbf(ua[2 * h]);
      const float v = 16 * w + 8 * h < 56 ? rbf(gs * rcp(1.f + __expf(-gs))) * us : 0.f;
      asm volatile("st.shared.u16 [%0], %1;" :: "r"(sb + A_XN + 1280 + (16 * w + 8 * h + g) * 2), "h"((unsigned short)pack2(v, 0.f)) : "memory");
    }
  }
  fence_async_smem();
  bar_sync(4, 128);
#pragma unroll 1
  for (int j = 0; j < 2; j++) {
    float y[4][4];
    const uint64_t dd = mkdesc(A_WD, 8192, 128, 0) + (uint64_t)(j * 256);
    wg_fence();
#pragma unroll
    for (int m = 0; m < 4; m++) {
      wgmma_ss8<0, 1, 0>(y[m], dd + m * 64, mkdesc(A_XN + 1280, 16, 128, 0));
#pragma unroll
      for (int ks = 1; ks < 4; ks++) wgmma_ss8<1, 1, 0>(y[m], dd + m * 64 + ks * 1024, mkdesc(A_XN + 1280 + ks * 32, 16, 128, 0));
    }
    wg_commit(); wg_wait<0>();
#pragma unroll
    for (int m = 0; m < 4; m++) {
      reg_fence(y[m]);
      if ((t & 3) == 0) { float* o = yacc + j * 256 + m * 64 + 16 * w + g; atomicAdd(o, y[m][0]); atomicAdd(o + 8, y[m][2]); }
    }
  }
  bar_sync(4, 128);
  if (t == 0) red_rel((uint32_t*)(yacc + 512), 1);
  __syncwarp();
}

__device__ __forceinline__ void ffn_finish(int q, const bf16* req, float r, int lane, uint32_t* v) {
  uint32_t xn[8];
  load_row(xn, req, lane); load_row(v, req + 512, lane);
  const float rs = rbf(1.f / (1.f + __expf(-rbf(r))));
  wait_eq((const uint32_t*)&g_y[q][512], 32u);
  float4 y[4];
#pragma unroll
  for (int i = 0; i < 4; i++) y[i] = __ldcg((const float4*)g_y[q] + (i >> 1) * 64 + 2 * lane + (i & 1));
#pragma unroll
  for (int i = 0; i < 4; i++) {
    v[2 * i] = add2(v[2 * i], add2(xn[2 * i], pack2(rbf(y[i].x) * rs, rbf(y[i].y) * rs)));
    v[2 * i + 1] = add2(v[2 * i + 1], add2(xn[2 * i + 1], pack2(rbf(y[i].z) * rs, rbf(y[i].w) * rs)));
  }
}
__device__ __forceinline__ unsigned long long final_route(int ts, uint32_t E, int lane) {
  if (lane < 2) wait_eq(&f_c2[(NSEG - 2 + lane) * 8], E * 64u);
  __syncwarp();
  const unsigned long long a = ld_rlxu64(&f_b2[lane < ts ? 0 : 1][lane]), b = ld_rlxu64(&f_b2[lane + 32 < ts ? 0 : 1][lane + 32]);
  return warp_max<16>(a > b ? a : b);
}

__global__ void __launch_bounds__(512, 1) aux_kernel(Params p) {
  extern __shared__ __align__(1024) uint8_t sm[];
  const uint32_t sb = smem_u32(sm);
  if ((sb & 0xFFFFFFu) != SBASE) __trap();
  const int warp = __shfl_sync(~0u, threadIdx.x >> 5, 0);
  const int cta = blockIdx.x;
  const uint32_t E = __shfl_sync(~0u, *(volatile uint32_t*)&g_epoch + 1, 0);
  const uint32_t bars = sb + A_BAR;

  if (cta < 32) {
    const int cg = cta & 3, kg = cta >> 2;
    if (threadIdx.x == 0) {
      for (int i = 0; i < A_NST; i++) { mbar_init(bars + 8 * i, 1); mbar_init(bars + 64 + 8 * i, 2); }
      mbar_init(bars + 128, 8); mbar_init(bars + 136, 8); mbar_init(bars + 144, 1);
      asm volatile("fence.mbarrier_init.release.cluster;" ::: "memory");
    }
    if (warp < 8) {
      asm volatile("setmaxnreg.inc.sync.aligned.u32 176;");
      const int tid = fresh_tid(), lane = tid & 31;
      uint32_t W[32][4];
      stage_weights(sb + A_WD, p.wo + (size_t)kg * 512 * 512 + cg * 128, 512, tid, 256);
      cp_async_wait();
      bar_sync(1, 256);
      load_frags(W, sb + A_WD, warp >> 2, warp & 3, lane);
      bar_sync(2, 512);
      const uint32_t so = sb + A_STG + ((lane >> 4) * 8 + (lane & 7)) * 256 + (((warp * 2 + ((lane >> 3) & 1)) ^ (lane & 7)) << 4);
      int stage = 0; uint32_t ph = 0, job = 0;
#pragma unroll 1
      for (int T = 0; T < NSTEP; T++) {
#pragma unroll 1
        for (int k = 0; k < 3; k++) {
          const int st = k == 0 ? 0 : 3 - k, s = st == 0 ? T : T - LAG;
          if (s < 0 || s >= NSEG) continue;
          float d[16];
#pragma unroll
          for (int hh = 0; hh < 4; hh++) {
            mbar_wait(bars + 8 * stage, ph);
            const uint64_t db = mkdesc(A_RING, 512, 128, 0) + (uint64_t)(stage * 512);
            wg_fence();
            if (hh == 0) wgmma_rs32<0, 0>(d, W[0], db); else wgmma_rs32<1, 0>(d, W[hh * 8], db);
#pragma unroll
            for (int ks = 1; ks < 8; ks++) wgmma_rs32<1, 0>(d, W[hh * 8 + ks], db + ks * 64);
            wg_commit();
            if (hh > 0) { wg_wait<1>(); if ((tid & 127) == 0) mbar_arrive(bars + 64 + 8 * (stage == 0 ? A_NST - 1 : stage - 1)); }
            if (++stage == A_NST) { stage = 0; ph ^= 1; }
          }
          mbar_wait(bars + 144, (job & 1) ^ 1);
          wg_wait<0>(); reg_fence(d);
          if ((tid & 127) == 0) mbar_arrive(bars + 64 + 8 * (stage == 0 ? A_NST - 1 : stage - 1));
          if (cta == 0 && tid == 0) TSTAMP(6, T, k);
          const uint32_t a = so;
          stmatrix4_t(a, pack2(d[0], d[1]), pack2(d[2], d[3]), pack2(d[4], d[5]), pack2(d[6], d[7]));
          stmatrix4_t(a + 4096, pack2(d[8], d[9]), pack2(d[10], d[11]), pack2(d[12], d[13]), pack2(d[14], d[15]));
          fence_async_smem();
          __syncwarp();
          if (lane == 0) mbar_arrive(bars + 128 + 8 * (job & 1));
          job++;
        }
      }
    } else if (warp < 12) {
      asm volatile("setmaxnreg.dec.sync.aligned.u32 120;");
      const int tid = fresh_tid(), lane = tid & 31;
      const int w = warp - 8, t = tid - 256;
#pragma unroll 1
      for (int s = cta + 4; s < NSEG; s += 32) {
#pragma unroll 1
        for (int pr = w; pr < 16; pr += 4) input_ln_pair(p.x, s, pr, lane);
        bar_sync(4, 128);
        if (t == 0) st_rel(&f_h1[s], E);
      }
      bar_sync(2, 512);
      { int guard = 0; while ((ld_rlx(&f_choice[cta * 3][0]) >> 1) != (E & 0x7FFFFFFFu)) { __nanosleep(200); if (++guard > (1 << 22)) __trap(); } }
#pragma unroll 1
      for (int i = t; i < 512 * 7; i += 128) {
        const int k = i / 7, pc = i % 7;
        cp_async16(sb + A_WG + (k >> 3) * 896 + pc * 128 + (k & 7) * 16, p.wg + (size_t)k * 1792 + cta * 56 + pc * 8);
        cp_async16(sb + A_WU + (k >> 3) * 896 + pc * 128 + (k & 7) * 16, p.wu + (size_t)k * 1792 + cta * 56 + pc * 8);
        cp_async16(sb + A_WD + (i >> 9) * 8192 + (i & 63) * 128 + ((i >> 6) & 7) * 16, p.wd + (size_t)cta * 56 * 512 + i * 8);
      }
      uint32_t wv[8];
      const float wsum = load_wr(wv, p.wr, lane);
      cp_async_wait();
      fence_async_smem();
      wait_eq(&f_zero, E * 32u);
      bar_sync(4, 128);
      const int tj = (cta * 4 + w) & 31, st = 1 + ((cta >> 3) & 1), sq = cta >> 4;
      unsigned long long run = 0, best = 0, hist = 0;
#pragma unroll 1
      for (int i = 0; i <= NSTEP; i++) {
        int tok = -1; const bf16* req = nullptr;
        if (i < NSEG) {
          const int cd = (int)uni(route_step(i, E, run));
          run = __shfl_sync(~0u, run, 0);
          hist = hist << 8 | (uint32_t)(cd + 1);
          if (cd >= 0) { tok = rtok(run); req = g_req1[tok][0]; }
        } else {
          hist <<= 8;
          if (i == NSTEP) {
            if (t == 0 && cta == 0) GSTAMP(1, 3);
            tok = rtok(final_route(rtok(run) >> 5, E, lane));
            req = g_req2[(tok >> 5) < (rtok(run) >> 5) ? 0 : 1][tok][0];
          }
        }
        tok = __shfl_sync(~0u, tok, 0);
        if (tok >= 0) {
          if (cta == 0 && t == 0) TSTAMP(8, i, 0);
          ffn_slice(sb, req, g_y[min(i, NSEG)], t);
          if (cta == 0 && t == 0) TSTAMP(8, i, 1);
        }
        if (i == NSEG - 1 && st == 1) {
          if (t == 0 && cta == 0) GSTAMP(1, 0);
          wait_eq(&f_c2[(NSEG - 3 - LAG) * 8], E * 64u); wait_eq(&f_c2[(NSEG - 2 - LAG) * 8], E * 64u);
#pragma unroll 2
          for (int s = sq; s < min(rtok(run) >> 5, NSEG - 1 - LAG); s += 2) {
            uint32_t v[8];
            load_row(v, g_n + (size_t)(s * 32 + tj) * 512, lane);
            store_row(p.out + (size_t)(s * 32 + tj) * 512, v, lane);
          }
        }
        const int s = i - LAG;
        if (s < 0 || s >= NSEG) continue;
        const int cd = (int)((hist >> (8 * LAG)) & 255) - 1;
        if (cd >= 0 && st == 2) best = 0;
        if ((s & 1) != sq) continue;
        const int tk = s * 32 + tj;
        const bool known = i >= NSEG - 1;
        if (!known || (s < (rtok(run) >> 5)) == (st == 1)) {
          if (st == 2 && cd == tj) wait_eq(&f_hc[s], E);
          const unsigned long long wd = token_post(st, tk, st == 2 && cd == tj ? g_x2c[s] : g_x2 + (size_t)tk * 512,
                                                   (st == 2 || known ? p.out : g_n) + (size_t)tk * 512, g_req2[st - 1][tk][0], best, wv, wsum, E, lane);
          best = max(best, wd);
          if (lane == 0) asm volatile("red.relaxed.gpu.global.max.u64 [%0], %1;" :: "l"(&f_b2[st - 1][s]), "l"(wd) : "memory");
        }
        __syncwarp();
        if (lane == 0) red_rel(&f_c2[s * 8], 1);
        __syncwarp();
      }
    } else {
      asm volatile("setmaxnreg.dec.sync.aligned.u32 40;");
      const int tid = fresh_tid(), lane = tid & 31;
      const int t = tid - 384, w = warp - 12;
      for (int i = cta * 128 + t; i < (NSEG + 1) * 544 / 4; i += 4096) ((float4*)&g_y[0][0])[i] = make_float4(0.f, 0.f, 0.f, 0.f);
      bar_sync(3, 128);
      if (t == 0) red_rel(&f_zero, 1);
      bar_sync(2, 512);
      if (w == 0) {
        const int k = lane >> 2, st = k == 0 ? 0 : 3 - k;
        int cnt = 0;
#pragma unroll 1
        for (int T = 0; T < NSTEP; T++) {
          const int s = st == 0 ? T : T - LAG;
          bool todo = lane < 12 && s >= 0 && s < NSEG;
          const int idx = cnt + lane - (T >= NSEG ? 4 : 0);
          const int stage = idx % A_NST; const uint32_t ph = ((idx / A_NST) & 1) ^ 1;
          const uint32_t* fl = &f_o[T][kg][st * 4 + (lane & 3)];
          const uint8_t* src = g_o[st][s % ORING][kg * 4 + (lane & 3)];
          bool ready = false; int guard = 0;
          uint32_t pend = __ballot_sync(~0u, todo);
          cnt += __popc(pend);
          while (pend) {
            if (todo && !ready) ready = ld_rlx(fl) == E;
            const bool go = todo && ready && (lane < A_NST || !((pend >> (lane - A_NST)) & 1)) && mbar_test(bars + 64 + 8 * stage, ph);
            if (go) { mbar_expect(bars + 8 * stage, OLOAD_); bulk_g2s(sb + A_RING + stage * 8192, src, OLOAD_, bars + 8 * stage); todo = false; }
            const uint32_t np = __ballot_sync(~0u, todo);
            if (np == pend) __nanosleep(40);
            pend = np;
            if (++guard > (1 << 22)) __trap();
          }
          if (cta == 0 && lane == 0) TSTAMP(3, T, 0);
        }
      } else if (w < 3) {
        uint32_t job = 0;
#pragma unroll 1
        for (int T = 0; T < NSTEP; T++) {
#pragma unroll 1
          for (int k = 0; k < 3; k++) {
            const int st = k == 0 ? 0 : 3 - k, s = st == 0 ? T : T - LAG;
            if (s < 0 || s >= NSEG) continue;
            if ((job++ & 1) != w - 1) continue;
            if (s >= PRING && PCHK_) wait_eq(st == 0 ? (const uint32_t*)&f_h2[s - PRING][1] : &f_c2[(s - PRING) * 8], st == 0 ? E * 4u : E * 64u);
            mbar_wait(bars + 128 + 8 * (w - 1), ((job - 1) >> 1) & 1);
            if (cta == 0 && st == 0) TSTAMP(7, s, 0);
            e_s2g(g_pp[st][s % PRING] + cta * 8192, sb + A_STG, PST_);
            asm volatile("cp.async.bulk.commit_group;\n cp.async.bulk.wait_group.read 0;" ::: "memory");
            __syncwarp();
            e_arrive(bars + 144);
            bulk_wait();
            __syncwarp();
            if (lane == 0) red_rel(&f_acc[st][s * 8], 1);
            __syncwarp();
            if (cta == 0 && st == 0) TSTAMP(7, s, 1);
          }
        }
      }
    }
  } else {
    const int tid = fresh_tid(), lane = tid & 31;
    const int qd = cta - 32;
    input_ln_pair(p.x, qd, warp, lane);
    bar_sync(6, 512);
    if (tid == 0) st_rel(&f_h1[qd], E);
    if (warp == 15) {
      unsigned long long run = 0;
      wait_eq(&f_zero, E * 32u);
#pragma unroll 1
      for (int s = 0; s < NSEG; s++) {
        const int cd = route_step(s, E, run);
        if (cd >= 0 && qd == (s & 1)) {
          uint32_t v[1][8], h[1][8];
          ffn_finish(s, g_req1[s * 32 + cd][0], rscore(run), lane, v[0]);
          if (lane == 0) TSTAMP(8, s, 2);
          ln_rows<1>(v, h);
#pragma unroll
          for (int i = 0; i < 8; i++) st_rlx64(&g_hc[s][(i >> 2) * 128 + 4 * lane + (i & 3)], h[0][i], E);
          if (lane == 0) TSTAMP(8, s, 3);
          store_row(g_x2c[s], v[0], lane);
          __syncwarp();
          if (lane == 0) st_rel(&f_hc[s], E);
        }
      }
      if (qd == 1) {
        uint32_t v[8];
        const int ts = rtok(run) >> 5;
        run = final_route(ts, E, lane);
        if (lane == 0) GSTAMP(1, 1);
        ffn_finish(NSEG, g_req2[(rtok(run) >> 5) < ts ? 0 : 1][rtok(run)][0], rscore(run), lane, v);
        store_row(p.out + (size_t)rtok(run) * 512, v, lane);
        if (lane == 0) GSTAMP(1, 2);
        asm volatile("griddepcontrol.wait;" ::: "memory");
        if (lane == 0) *(volatile uint32_t*)&g_epoch = E;
      }
    } else if (warp < 8) {
      uint32_t wv[8];
      const float wsum = load_wr(wv, p.wr, lane);
      unsigned long long best = 0;
#pragma unroll 1
      for (int s = 0; s < NSEG; s++) {
        const int tk = s * 32 + qd * 8 + warp;
        const unsigned long long wd = token_post(0, tk, p.x + (size_t)tk * 512, g_x2 + (size_t)tk * 512, g_req1[tk][0], best, wv, wsum, E, lane);
        best = max(best, wd);
        if (lane == 0) asm volatile("red.relaxed.gpu.global.max.u64 [%0], %1;" :: "l"(f_h2[s]), "l"(wd) : "memory");
        bar_sync(5, 256);
        if (tid == 0) { if (qd == 0) TSTAMP(4, s, 1); red_rel((uint32_t*)(f_h2[s] + 1), 1); if (qd == 0) TSTAMP(4, s, 2); }
        __syncwarp();
      }
    }
  }
}

}

extern "C" void kernel_launch(void* const* d_in, const int* in_sizes, int n_in, void* d_out, int out_size) {
  (void)in_sizes; (void)n_in; (void)out_size;
  static bool init = false;
  if (!init) {
    cudaFuncSetAttribute(main_kernel, cudaFuncAttributeMaxDynamicSharedMemorySize, M_TOTAL);
    cudaFuncSetAttribute(aux_kernel, cudaFuncAttributeMaxDynamicSharedMemorySize, A_TOTAL);
    init = true;
  }
  Params p;
  p.x = (const bf16*)d_in[0]; p.mem0 = (const bf16*)d_in[1]; p.wq = (const bf16*)d_in[2]; p.wk = (const bf16*)d_in[3];
  p.wv = (const bf16*)d_in[4]; p.wo = (const bf16*)d_in[5]; p.wr = (const bf16*)d_in[8]; p.wg = (const bf16*)d_in[9];
  p.wu = (const bf16*)d_in[10]; p.wd = (const bf16*)d_in[11]; p.out = (bf16*)d_out; p.zero = 0;
  cudaStream_t st = cudaStreamPerThread;
  main_kernel<<<96, 512, M_TOTAL, st>>>(p);
  cudaLaunchConfig_t cfg = {};
  cfg.gridDim = dim3(36); cfg.blockDim = dim3(512); cfg.dynamicSmemBytes = A_TOTAL; cfg.stream = st;
  cudaLaunchAttribute at[1];
  at[0].id = cudaLaunchAttributeProgrammaticStreamSerialization; at[0].val.programmaticStreamSerializationAllowed = 1;
  cfg.attrs = at; cfg.numAttrs = 1;
  cudaLaunchKernelEx(&cfg, aux_kernel, p);
}
```

```cpp
#include <cuda_runtime.h>
#include <cuda_bf16.h>
#include <stdint.h>

namespace {

typedef __nv_bfloat16 bf16;

constexpr int NSEG = 64;
#define LAG_ 5
constexpr int LAG = LAG_;
constexpr int NSTEP = NSEG + LAG;
constexpr int ORING = 8, PRING = 4;
#define E1_ 10
#define E2_ 0
#define E3_ 10
constexpr int E1 = E1_, E2 = E2_, E3 = E3_, EA = E1 + E2 + E3;
static_assert(EA % 4 == 0 && EA > 0 && EA < 32 && E1 > 0, "early part: whole 64-column chunks");
#define RW_ 176
#define RA_ 136
#define RC_ 24
#define STR2(x) #x
#define STR(x) STR2(x)
#define RED_ 30
#define ARR_ 7
#define HADD_ 1
#define PAUSE_ 21
#define PD1_ 3
#define PD2_ 7
#define DPOLL_ 0
#define SALT_ 0
#define KP1_ 1
#define EARLY_ 0
#define PRIV_ 1
#define OLOAD_ 8192
#define PST_ 8192
#define PCHK_ 1
#define ALT_ 1
#define PH_ 0
#define HAND_ 4
#define GO3_ 2
#define NPROBE_ 6
#define TP(i, v) (v)
#define XDLY_ TP(0, 1700)
#define YDLY_ TP(1, 2900)
#define X1_ TP(2, 200)
#define X2_ TP(3, 350)
#define Y1_ TP(4, 200)
#define Y2_ TP(5, 350)
#define HGAP_ TP(6, 100)
#define TGAP_ TP(7, 100)
#define ADLY_ TP(8, 0)
#define ODLY_ TP(9, 2700)
#define LDLY_ TP(10, 3600)
#define LGAP_ 200
#define HDLY_ TP(11, 0)
#define TDLY_ TP(15, 0)
#define SDLY_ TP(12, 800)
#define AGAP_ TP(13, 100)
#define KDLY_ TP(14, 300)
__device__ uint32_t g_epoch;
__device__ __align__(1024) uint8_t g_h[2][NSEG][32768];
__device__ __align__(128) uint2 g_hc[NSEG][256];
__device__ __align__(128) bf16 g_x2[2048 * 512];
__device__ __align__(128) bf16 g_x2c[NSEG][512];
__device__ __align__(128) uint8_t g_o[3][ORING][32][8192];
__device__ __align__(128) uint8_t g_pp[3][PRING][8 * 32768];
__device__ __align__(128) bf16 g_n[2048 * 512];
__device__ __align__(128) uint8_t g_xch[96 * 16384 + 65536 + 8192];
__device__ __align__(128) bf16 g_req1[2048][2][512];
__device__ __align__(128) bf16 g_req2[2][2048][2][512];
__device__ __align__(128) float g_y[NSTEP + 1][512 + 32];
__device__ __align__(128) uint8_t g_tok[96][2][16384];
__device__ uint32_t f_choice[96][2];
__device__ uint32_t f_h1[NSEG], f_hc[NSEG];
__device__ __align__(128) unsigned long long f_h2[NSEG][16];
__device__ __align__(128) unsigned long long f_b2[2][NSEG];
__device__ uint32_t f_c2[NSEG * 8];
__device__ __align__(128) uint32_t f_o[NSTEP][8][16];
__device__ uint32_t f_acc[3][NSEG * 8];
__device__ uint32_t f_zero, f_cp;
__device__ __align__(128) unsigned long long g_sync[2][96];

#define TRAP() __trap()
__device__ __forceinline__ uint32_t smem_u32(const void* p) { return (uint32_t)__cvta_generic_to_shared(p); }
__device__ __forceinline__ int fresh_tid() { const int t = threadIdx.x; return __shfl_sync(~0u, t, t & 31); }
__device__ __forceinline__ unsigned long long gtime64() { unsigned long long t; asm volatile("mov.u64 %0, %%globaltimer;" : "=l"(t) :: "memory"); return t; }
__device__ __forceinline__ uint32_t clk() { unsigned long long c; asm volatile("mov.u64 %0, %%clock64;" : "=l"(c) :: "memory"); return (uint32_t)c; }
__device__ __forceinline__ void wait_until(uint32_t t) {
  while ((int)(t - clk()) > 450) __nanosleep(32);
  uint32_t c;
  do { asm volatile("mov.u32 %0, %%clock;" : "=r"(c) :: "memory"); } while ((int)(c - t) < 0);
}
__device__ __forceinline__ void mbar_init(uint32_t bar, uint32_t cnt) { asm volatile("mbarrier.init.shared::cta.b64 [%0], %1;" :: "r"(bar), "r"(cnt) : "memory"); }
__device__ __forceinline__ void mbar_arrive(uint32_t bar) { asm volatile("mbarrier.arrive.shared::cta.b64 _, [%0];" :: "r"(bar) : "memory"); }
__device__ __forceinline__ void mbar_arrive_remote(uint32_t bar) { asm volatile("mbarrier.arrive.relaxed.cluster.shared::cluster.b64 _, [%0];" :: "r"(bar) : "memory"); }
__device__ __forceinline__ void mbar_expect(uint32_t bar, uint32_t bytes) { asm volatile("mbarrier.arrive.expect_tx.shared::cta.b64 _, [%0], %1;" :: "r"(bar), "r"(bytes) : "memory"); }
__device__ __forceinline__ bool mbar_try(uint32_t bar, uint32_t parity) {
  uint32_t ok;
  asm volatile("{.reg .pred p; mbarrier.try_wait.parity.shared::cta.b64 p, [%1], %2; selp.u32 %0, 1, 0, p;}" : "=r"(ok) : "r"(bar), "r"(parity) : "memory");
  return ok;
}
__device__ __forceinline__ bool mbar_test(uint32_t bar, uint32_t parity) {
  uint32_t ok;
  asm volatile("{.reg .pred p; mbarrier.test_wait.parity.shared::cta.b64 p, [%1], %2; selp.u32 %0, 1, 0, p;}" : "=r"(ok) : "r"(bar), "r"(parity) : "memory");
  return ok;
}
__device__ __forceinline__ void mbar_wait(uint32_t bar, uint32_t parity) {
  asm volatile("{\n.reg .pred p;\nWAIT:\nmbarrier.try_wait.parity.shared::cta.b64 p, [%0], %1;\n@!p bra WAIT;\n}" :: "r"(bar), "r"(parity) : "memory");
}
__device__ __forceinline__ uint32_t ld_acq(const uint32_t* p) { uint32_t v; asm volatile("ld.acquire.gpu.global.u32 %0, [%1];" : "=r"(v) : "l"(p) : "memory"); return v; }
__device__ __forceinline__ unsigned long long ld_acq64(const unsigned long long* p) { unsigned long long v; asm volatile("ld.acquire.gpu.global.u64 %0, [%1];" : "=l"(v) : "l"(p) : "memory"); return v; }
__device__ __forceinline__ void st_rel(uint32_t* p, uint32_t v) { asm volatile("st.release.gpu.global.u32 [%0], %1;" :: "l"(p), "r"(v) : "memory"); }
__device__ __forceinline__ void st_rel64(unsigned long long* p, unsigned long long v) { asm volatile("st.release.gpu.global.u64 [%0], %1;" :: "l"(p), "l"(v) : "memory"); }
__device__ __forceinline__ void red_rel(uint32_t* p, uint32_t v) { asm volatile("red.release.gpu.global.add.u32 [%0], %1;" :: "l"(p), "r"(v) : "memory"); }
__device__ __forceinline__ uint32_t ld_rlx(const uint32_t* p) { uint32_t v; asm volatile("ld.relaxed.gpu.global.u32 %0, [%1];" : "=r"(v) : "l"(p) : "memory"); return v; }
__device__ __forceinline__ unsigned long long ld_rlxu64(const unsigned long long* p) { unsigned long long v; asm volatile("ld.relaxed.gpu.global.u64 %0, [%1];" : "=l"(v) : "l"(p) : "memory"); return v; }
__device__ __forceinline__ void st_rlx(uint32_t* p, uint32_t v) { asm volatile("st.relaxed.gpu.global.u32 [%0], %1;" :: "l"(p), "r"(v) : "memory"); }
__device__ __forceinline__ void bulk_wait() { asm volatile("cp.async.bulk.commit_group;\n cp.async.bulk.wait_group 0;" ::: "memory"); }
__device__ __forceinline__ void fence_acq() { asm volatile("fence.acquire.gpu;" ::: "memory"); }
__device__ __forceinline__ void wait_hint(const uint32_t* p, uint32_t v) {
  int guard = 0;
  while (ld_rlx(p) != v) { __nanosleep(32); if (++guard > (1 << 22)) TRAP(); }
}
__device__ __forceinline__ void wait_eq(const uint32_t* p, uint32_t v) {
  int guard = 0;
  while (ld_rlx(p) != v) { __nanosleep(64); if (++guard > (1 << 22)) TRAP(); }
  fence_acq();
}
__device__ __forceinline__ unsigned long long rword(uint32_t E, int tok, float r) {
  uint32_t u = __float_as_uint(r + 0.f);
  u = r != r ? 0u : (u >> 31) ? ~u : u | 0x80000000u;
  return (unsigned long long)E << 43 | (unsigned long long)u << 11 | (uint32_t)(2047 - tok);
}
__device__ __forceinline__ int rtok(unsigned long long v) { return 2047 - (int)(v & 2047u); }
__device__ __forceinline__ float rscore(unsigned long long v) { const uint32_t u = (uint32_t)(v >> 11); return __uint_as_float((u >> 31) ? u & 0x7fffffffu : ~u); }
__device__ __forceinline__ bool rfresh(unsigned long long v, uint32_t E) { return (uint32_t)(v >> 43) == (E & 0x1FFFFFu); }
template <int TOP> __device__ __forceinline__ unsigned long long warp_max(unsigned long long v) {
#pragma unroll
  for (int o = TOP; o > 0; o >>= 1) { const unsigned long long ov = __shfl_xor_sync(~0u, v, o); v = ov > v ? ov : v; }
  return v;
}
template <int off> __device__ __forceinline__ uint2 ld_rlx64(const void* p) { unsigned long long v; asm volatile("ld.relaxed.gpu.global.b64 %0, [%1+%2];" : "=l"(v) : "l"(p), "n"(off) : "memory"); return make_uint2((uint32_t)v, (uint32_t)(v >> 32)); }
template <int off> __device__ __forceinline__ uint4 ld_rlx128(const void* p) {
  unsigned long long a, b; asm volatile("ld.relaxed.gpu.global.v2.b64 {%0,%1}, [%2+%3];" : "=l"(a), "=l"(b) : "l"(p), "n"(off) : "memory");
  return make_uint4((uint32_t)a, (uint32_t)(a >> 32), (uint32_t)b, (uint32_t)(b >> 32));
}
__device__ __forceinline__ void st_rlx64(void* p, uint32_t lo, uint32_t hi) { asm volatile("{.reg .b64 t; mov.b64 t, {%1,%2}; st.relaxed.gpu.global.b64 [%0], t;}" :: "l"(p), "r"(lo), "r"(hi) : "memory"); }
__device__ __forceinline__ void cp_async16(uint32_t dst, const void* src) { asm volatile("cp.async.cg.shared.global [%0], [%1], 16;" :: "r"(dst), "l"(src) : "memory"); }
__device__ __forceinline__ void cp_async_wait() { asm volatile("cp.async.wait_all;" ::: "memory"); }
__device__ __forceinline__ void fence_async_smem() { asm volatile("fence.proxy.async.shared::cta;" ::: "memory"); }
__device__ __forceinline__ void fence_async_glob() { asm volatile("fence.proxy.async.global;" ::: "memory"); }
__device__ __forceinline__ void fence_async_acq() { asm volatile("fence.proxy.async::generic.acquire.sync_restrict::shared::cluster.cluster;" ::: "memory"); }
__device__ __forceinline__ float ex2(float x) { float y; asm("ex2.approx.ftz.f32 %0, %1;" : "=f"(y) : "f"(x)); return y; }
__device__ __forceinline__ float sqrt_fast(float x) { float y; asm("sqrt.approx.ftz.f32 %0, %1;" : "=f"(y) : "f"(x)); return y; }
__device__ __forceinline__ float rcp(float x) { float y; asm("rcp.approx.ftz.f32 %0, %1;" : "=f"(y) : "f"(x)); return y; }
__device__ __forceinline__ void bar_sync(int id, int n) { asm volatile("bar.sync %0, %1;" :: "r"(id), "r"(n) : "memory"); }
__device__ __forceinline__ bool bar_or(int id, int n, bool v) {
  uint32_t r;
  asm volatile("{.reg .pred p, q; setp.ne.u32 p, %3, 0; barrier.cta.red.or.aligned.pred q, %1, %2, p; selp.u32 %0, 1, 0, q;}" : "=r"(r) : "r"(id), "r"(n), "r"((uint32_t)v) : "memory");
  return r;
}
__device__ __forceinline__ uint32_t mapa(uint32_t a, uint32_t rank) { uint32_t r; asm volatile("mapa.shared::cluster.u32 %0, %1, %2;" : "=r"(r) : "r"(a), "r"(rank)); return r; }
__device__ __forceinline__ void cluster_sync() { asm volatile("barrier.cluster.arrive.release.aligned; barrier.cluster.wait.acquire.aligned;" ::: "memory"); }
__device__ __forceinline__ void st_async32(uint32_t dst, uint32_t v, uint32_t bar) { asm volatile("st.async.shared::cluster.mbarrier::complete_tx::bytes.b32 [%0], %1, [%2];" :: "r"(dst), "r"(v), "r"(bar) : "memory"); }
__device__ __forceinline__ void bulk_g2s(uint32_t dst, const void* src, uint32_t bytes, uint32_t bar) {
  asm volatile("cp.async.bulk.shared::cluster.global.mbarrier::complete_tx::bytes [%0], [%1], %2, [%3];" :: "r"(dst), "l"(src), "r"(bytes), "r"(bar) : "memory");
}
__device__ __forceinline__ void bulk_g2s_mc(uint32_t dst, const void* src, uint32_t bytes, uint32_t bar, uint16_t mask) {
  asm volatile("cp.async.bulk.shared::cluster.global.mbarrier::complete_tx::bytes.multicast::cluster [%0], [%1], %2, [%3], %4;"
               :: "r"(dst), "l"(src), "r"(bytes), "r"(bar), "h"(mask) : "memory");
}
__device__ __forceinline__ void bulk_s2c(uint32_t dst, uint32_t src, uint32_t bytes, uint32_t bar) {
  asm volatile("cp.async.bulk.shared::cluster.shared::cta.mbarrier::complete_tx::bytes [%0], [%1], %2, [%3];" :: "r"(dst), "r"(src), "r"(bytes), "r"(bar) : "memory");
}
__device__ __forceinline__ void bulk_s2g(void* dst, uint32_t src, uint32_t bytes) {
  asm volatile("cp.async.bulk.global.shared::cta.bulk_group [%0], [%1], %2;" :: "l"(dst), "r"(src), "r"(bytes) : "memory");
}
#define ELECT(op) "{.reg .pred p; elect.sync _|p, 0xffffffff; @p " op "}"
__device__ __forceinline__ void e_arrive(uint32_t bar) { asm volatile(ELECT("mbarrier.arrive.shared::cta.b64 _, [%0];") :: "r"(bar) : "memory"); }
__device__ __forceinline__ void e_expect(uint32_t bar, uint32_t bytes) { asm volatile(ELECT("mbarrier.arrive.expect_tx.shared::cta.b64 _, [%0], %1;") :: "r"(bar), "r"(bytes) : "memory"); }
__device__ __forceinline__ void e_g2s(uint32_t dst, const void* src, uint32_t bytes, uint32_t bar) {
  asm volatile(ELECT("cp.async.bulk.shared::cluster.global.mbarrier::complete_tx::bytes [%0], [%1], %2, [%3];") :: "r"(dst), "l"(src), "r"(bytes), "r"(bar) : "memory");
}
__device__ __forceinline__ void e_mc(uint32_t dst, const void* src, uint32_t bytes, uint32_t bar, uint16_t mask) {
  asm volatile(ELECT("cp.async.bulk.shared::cluster.global.mbarrier::complete_tx::bytes.multicast::cluster [%0], [%1], %2, [%3], %4;")
               :: "r"(dst), "l"(src), "r"(bytes), "r"(bar), "h"(mask) : "memory");
}
__device__ __forceinline__ void e_s2g(void* dst, uint32_t src, uint32_t bytes) {
  asm volatile(ELECT("cp.async.bulk.global.shared::cta.bulk_group [%0], [%1], %2;") :: "l"(dst), "r"(src), "r"(bytes) : "memory");
}
__device__ __forceinline__ void e_st_rel(uint32_t* p, uint32_t v) { asm volatile(ELECT("st.release.gpu.global.u32 [%0], %1;") :: "l"(p), "r"(v) : "memory"); }
__device__ __forceinline__ uint32_t clk32() { uint32_t c; asm volatile("mov.u32 %0, %%clock;" : "=r"(c) :: "memory"); return c; }
__device__ __forceinline__ void spin_until(uint32_t t) { while ((int)(clk32() - t) < 0) {} }
__device__ __forceinline__ uint32_t uni(uint32_t v) { return __shfl_sync(~0u, v, 0); }
__device__ __forceinline__ uint32_t pack2(float lo, float hi) { uint32_t r; asm("cvt.rn.bf16x2.f32 %0, %1, %2;" : "=r"(r) : "f"(hi), "f"(lo)); return r; }
__device__ __forceinline__ uint32_t add2(uint32_t a, uint32_t b) { uint32_t r; asm("add.rn.bf16x2 %0, %1, %2;" : "=r"(r) : "r"(a), "r"(b)); return r; }
__device__ __forceinline__ float rbf(float x) { return __bfloat162float(__float2bfloat16_rn(x)); }
__device__ __forceinline__ float blo(uint32_t u) { return __uint_as_float(u << 16); }
__device__ __forceinline__ float bhi(uint32_t u) { return __uint_as_float(u & 0xffff0000u); }
__device__ __forceinline__ uint32_t gentag(uint32_t g) { return (g & 1u) | (g & 2u) << 15; }
__device__ __forceinline__ uint32_t pack2_tag(float lo, float hi, uint32_t tag) {
  const uint32_t u = __byte_perm(__float_as_uint(lo), __float_as_uint(hi), 0x7632);
  return u + ((u ^ tag) & 0x10001u);
}
__device__ __forceinline__ uint32_t xo2(uint32_t a, uint32_t b, uint32_t t) { uint32_t r; asm("lop3.b32 %0, %1, %2, %3, 0x7e;" : "=r"(r) : "r"(a), "r"(b), "r"(t)); return r; }
__device__ __forceinline__ uint32_t or3(uint32_t a, uint32_t b, uint32_t c) { uint32_t r; asm("lop3.b32 %0, %1, %2, %3, 0xfe;" : "=r"(r) : "r"(a), "r"(b), "r"(c)); return r; }
__device__ __forceinline__ void stmatrix4(uint32_t a, uint32_t r0, uint32_t r1, uint32_t r2, uint32_t r3) {
  asm volatile("stmatrix.sync.aligned.m8n8.x4.shared.b16 [%0], {%1,%2,%3,%4};" :: "r"(a), "r"(r0), "r"(r1), "r"(r2), "r"(r3) : "memory");
}
__device__ __forceinline__ void stmatrix4_t(uint32_t a, uint32_t r0, uint32_t r1, uint32_t r2, uint32_t r3) {
  asm volatile("stmatrix.sync.aligned.m8n8.x4.trans.shared.b16 [%0], {%1,%2,%3,%4};" :: "r"(a), "r"(r0), "r"(r1), "r"(r2), "r"(r3) : "memory");
}
__device__ __forceinline__ void ldmatrix4_t(uint32_t* r, uint32_t a) {
  asm volatile("ldmatrix.sync.aligned.m8n8.x4.trans.shared.b16 {%0,%1,%2,%3}, [%4];" : "=r"(r[0]), "=r"(r[1]), "=r"(r[2]), "=r"(r[3]) : "r"(a) : "memory");
}
__device__ __forceinline__ void ldmatrix4(uint32_t* r, uint32_t a) {
  asm volatile("ldmatrix.sync.aligned.m8n8.x4.shared.b16 {%0,%1,%2,%3}, [%4];" : "=r"(r[0]), "=r"(r[1]), "=r"(r[2]), "=r"(r[3]) : "r"(a) : "memory");
}
__device__ __forceinline__ void hmma16(float* c, const uint32_t* a, uint32_t b0, uint32_t b1) {
  asm volatile("mma.sync.aligned.m16n8k16.row.col.f32.bf16.bf16.f32 {%0,%1,%2,%3}, {%4,%5,%6,%7}, {%8,%9}, {%0,%1,%2,%3};"
               : "+f"(c[0]), "+f"(c[1]), "+f"(c[2]), "+f"(c[3]) : "r"(a[0]), "r"(a[1]), "r"(a[2]), "r"(a[3]), "r"(b0), "r"(b1));
}
__device__ __forceinline__ void hmma8(float* c, uint32_t a0, uint32_t a1, uint32_t b0) {
  asm volatile("mma.sync.aligned.m16n8k8.row.col.f32.bf16.bf16.f32 {%0,%1,%2,%3}, {%4,%5}, {%6}, {%0,%1,%2,%3};"
               : "+f"(c[0]), "+f"(c[1]), "+f"(c[2]), "+f"(c[3]) : "r"(a0), "r"(a1), "r"(b0));
}
__device__ __forceinline__ uint4 lds128(uint32_t a) { uint4 v; asm volatile("ld.shared.v4.u32 {%0,%1,%2,%3}, [%4];" : "=r"(v.x), "=r"(v.y), "=r"(v.z), "=r"(v.w) : "r"(a) : "memory"); return v; }
__device__ __forceinline__ void sts128(uint32_t a, uint4 v) { asm volatile("st.shared.v4.u32 [%0], {%1,%2,%3,%4};" :: "r"(a), "r"(v.x), "r"(v.y), "r"(v.z), "r"(v.w) : "memory"); }
__device__ __forceinline__ void sts128f(uint32_t a, float x, float y, float z, float w) { asm volatile("st.shared.v4.f32 [%0], {%1,%2,%3,%4};" :: "r"(a), "f"(x), "f"(y), "f"(z), "f"(w) : "memory"); }
__device__ __forceinline__ void sts64f(uint32_t a, float x, float y) { asm volatile("st.shared.v2.f32 [%0], {%1,%2};" :: "r"(a), "f"(x), "f"(y) : "memory"); }
__device__ __forceinline__ uint32_t lds32(uint32_t a) { uint32_t v; asm volatile("ld.shared.u32 %0, [%1];" : "=r"(v) : "r"(a) : "memory"); return v; }
__device__ __forceinline__ void sts32(uint32_t a, uint32_t v) { asm volatile("st.shared.u32 [%0], %1;" :: "r"(a), "r"(v) : "memory"); }

constexpr uint32_t SBASE = 1024;
__host__ __device__ constexpr uint64_t mkdesc(uint32_t off, uint32_t lbo, uint32_t sbo, uint32_t swz) {
  return (uint64_t)(((SBASE + off) & 0x3FFFF) >> 4) | ((uint64_t)(lbo >> 4) << 16) | ((uint64_t)(sbo >> 4) << 32) | ((uint64_t)swz << 62);
}
__device__ __forceinline__ void wg_fence() { asm volatile("wgmma.fence.sync.aligned;" ::: "memory"); }
__device__ __forceinline__ void wg_commit() { asm volatile("wgmma.commit_group.sync.aligned;" ::: "memory"); }
template <int N> __device__ __forceinline__ void wg_wait() { asm volatile("wgmma.wait_group.sync.aligned %0;" :: "n"(N) : "memory"); }

template <int N> __device__ __forceinline__ void reg_fence(float (&d)[N], int n = N) {
#pragma unroll
  for (int i = 0; i < N; i++) if (i < n) asm volatile("" : "+f"(d[i]) :: "memory");
}
#define F4(b) "+f"(d[b]), "+f"(d[b + 1]), "+f"(d[b + 2]), "+f"(d[b + 3])
#define F8(b) F4(b), F4(b + 4)
#define F16(b) F8(b), F8(b + 8)
#define G4(b) "=f"(d[b]), "=f"(d[b + 1]), "=f"(d[b + 2]), "=f"(d[b + 3])
#define G8(b) G4(b), G4(b + 4)
#define G16(b) G8(b), G8(b + 8)
#define RS_IN "r"(a[0]), "r"(a[1]), "r"(a[2]), "r"(a[3]), "l"(db), "n"(SD), "n"(TB)
#define SS_IN "l"(da), "l"(db), "n"(SD), "n"(TA), "n"(TB)
#define WG_OP(str, out0, out1, in) do { if (SD || KEEP) asm volatile(str : out1 : in); else asm volatile(str : out0 : in); } while (0)
#define O12(X) X##8(0), X##4(8)
#define O20(X) X##16(0), X##4(16)
#define O32(X) X##16(0), X##16(16)
template <int SD, int TB, int KEEP = 0> __device__ __forceinline__ void wgmma_rs24(float* d, const uint32_t* a, uint64_t db) {
  WG_OP("wgmma.mma_async.sync.aligned.m64n24k16.f32.bf16.bf16 {%0,%1,%2,%3,%4,%5,%6,%7,%8,%9,%10,%11}, {%12,%13,%14,%15}, %16, %17, 1, 1, %18;", O12(G), O12(F), RS_IN);
}
template <int SD, int TB, int KEEP = 0> __device__ __forceinline__ void wgmma_rs32(float* d, const uint32_t* a, uint64_t db) {
  WG_OP("wgmma.mma_async.sync.aligned.m64n32k16.f32.bf16.bf16 {%0,%1,%2,%3,%4,%5,%6,%7,%8,%9,%10,%11,%12,%13,%14,%15}, {%16,%17,%18,%19}, %20, %21, 1, 1, %22;", G16(0), F16(0), RS_IN);
}
template <int SD, int TB, int KEEP = 0> __device__ __forceinline__ void wgmma_rs40(float* d, const uint32_t* a, uint64_t db) {
  WG_OP("wgmma.mma_async.sync.aligned.m64n40k16.f32.bf16.bf16 {%0,%1,%2,%3,%4,%5,%6,%7,%8,%9,%10,%11,%12,%13,%14,%15,"
        "%16,%17,%18,%19}, {%20,%21,%22,%23}, %24, %25, 1, 1, %26;", O20(G), O20(F), RS_IN);
}
template <int SD, int TB, int KEEP = 0> __device__ __forceinline__ void wgmma_rs64(float* d, const uint32_t* a, uint64_t db) {
  WG_OP("wgmma.mma_async.sync.aligned.m64n64k16.f32.bf16.bf16 {%0,%1,%2,%3,%4,%5,%6,%7,%8,%9,%10,%11,%12,%13,%14,%15,"
        "%16,%17,%18,%19,%20,%21,%22,%23,%24,%25,%26,%27,%28,%29,%30,%31}, {%32,%33,%34,%35}, %36, %37, 1, 1, %38;", O32(G), O32(F), RS_IN);
}
template <int SD, int TA, int TB, int KEEP = 0> __device__ __forceinline__ void wgmma_ss24(float* d, uint64_t da, uint64_t db) {
  WG_OP("wgmma.mma_async.sync.aligned.m64n24k16.f32.bf16.bf16 {%0,%1,%2,%3,%4,%5,%6,%7,%8,%9,%10,%11}, %12, %13, %14, 1, 1, %15, %16;", O12(G), O12(F), SS_IN);
}
template <int SD, int TA, int TB, int KEEP = 0> __device__ __forceinline__ void wgmma_ss8(float* d, uint64_t da, uint64_t db) {
  WG_OP("wgmma.mma_async.sync.aligned.m64n8k16.f32.bf16.bf16 {%0,%1,%2,%3}, %4, %5, %6, 1, 1, %7, %8;", G4(0), F4(0), SS_IN);
}
__device__ __forceinline__ void bar_arrive(int id, int n) { asm volatile("bar.arrive %0, %1;" :: "r"(id), "r"(n) : "memory"); }
__device__ __forceinline__ uint32_t vis_bits(int pos, int t) {
  uint32_t m = 0;
#pragma unroll
  for (int i = 0; i < 8; i++) m |= (8 * (i / 2 + 1) + 2 * t + (i & 1) <= pos) ? 1u << i : 0u;
  return m;
}

__device__ __forceinline__ int route_step(int s, uint32_t E, unsigned long long& run) {
  int guard = 0; unsigned long long m, n;
  for (;;) {
    asm volatile("ld.relaxed.gpu.global.v2.b64 {%0,%1}, [%2];" : "=l"(m), "=l"(n) : "l"(f_h2[s]) : "memory");
    if ((uint32_t)n == E * 4u) break;
    __nanosleep(40);
    if (++guard > (1 << 22)) TRAP();
  }
  fence_acq();
  if (s == 0 || m > run) { run = m; return rtok(m) & 31; }
  return -1;
}

struct Params {
  const bf16 *x, *mem0, *wq, *wk, *wv, *wo, *wr, *wg, *wu, *wd;
  bf16* out;
  unsigned long long zero;
};

constexpr uint32_t WSTG_STRIDE = 272;
__device__ __forceinline__ void stage_weights(uint32_t stg, const bf16* src, int ld, int tid, int nthr) {
  for (int i = tid; i < 512 * 16; i += nthr) {
    int k = i >> 4, c = i & 15;
    cp_async16(stg + k * WSTG_STRIDE + c * 16, src + (size_t)k * ld + c * 8);
  }
}
__device__ __forceinline__ void load_frags(uint32_t (*W)[4], uint32_t stg, int wg, int w, int lane) {
  uint32_t a = stg + ((lane >> 4) * 8 + (lane & 7)) * WSTG_STRIDE + (64 * wg + 16 * w + ((lane >> 3) & 1) * 8) * 2;
#pragma unroll
  for (int ks = 0; ks < 32; ks++) ldmatrix4_t(W[ks], a + ks * 16 * WSTG_STRIDE);
}

constexpr uint32_t M_H = 0;
constexpr uint32_t M_MEM = 65536;
constexpr uint32_t M_Q = M_MEM + 24576;
constexpr uint32_t M_K = M_Q + 12288;
constexpr uint32_t M_V = M_K + 12288;
constexpr uint32_t M_OM = M_V + 12288;
constexpr uint32_t M_OST = M_OM + 6144;
constexpr uint32_t M_TST = M_OST + 8192;
constexpr uint32_t M_WO = M_TST + 16384;
constexpr uint32_t M_M0 = M_WO + 49152;
constexpr uint32_t M_PT = M_M0 + 2048;
constexpr uint32_t M_BAR = M_PT + 12288;
constexpr uint32_t M_TOTAL = M_BAR + 384;
static_assert(M_TOTAL <= 232448, "main smem");
static_assert(M_WO >= 512 * WSTG_STRIDE, "staging overlaps Wo");
enum { B_LAND = 0  , B_QK = 3, B_V, B_TOK, B_OM, B_HA, B_HB, B_HAE, B_HBE, B_OST, B_OFREE, B_SYNC,
       B_STG, B_SS, B_TFREE, B_KFREE, B_VFREE, B_FIX  , B_NUM = B_FIX + 8 };
static_assert(B_NUM * 8 <= 256, "barriers");
constexpr uint32_t M_CAND = M_BAR + 256;
constexpr uint32_t M_BASE = M_BAR + 272;
constexpr uint32_t M_ZERO = M_BAR + 280;
constexpr uint32_t M_NEAR = M_BAR + 288;
enum { N_GO1 = 2, N_GO2, N_GO3, N_GO4, N_AG, N_W };

#define GSTAMP(slot, i)
#define TSTAMP(slot, i, k)
#define STAMP(i)
#define ASTAMP(i)
#define WSTAMP(i)
#define CSTAMP(i, v)
#define PIN(x) asm volatile("" : "+r"(x))
#define SCHED(k) asm volatile("{\n.reg .pred p;\nsetp.ne.u32 p, %0, 0;\n@p trap;\n}" :: "r"(zz & (1u << (k))) : "memory")
#define HOLD(k, v) asm volatile("{\n.reg .pred p;\nsetp.ne.u32 p, %0, 0;\n@p st.shared.u32 [%0], %1;\n}" :: "r"(zz & (1u << (k))), "r"(v) : "memory")
#define DRAIN(a) (lds32((a) + zz) & zz)
#define BAR(i) (sb + M_BAR + 8 * (i))

__device__ __forceinline__ int probe_near(const uint8_t* p) {
  int best0 = 1 << 30, best1 = 1 << 30; uint32_t v = 0;
#pragma unroll 1
  for (int r = 0; r < NPROBE_; r++) {
    uint32_t t0 = clk();
    asm volatile("atom.relaxed.gpu.global.or.b32 %0, [%1], %2;" : "=r"(v) : "l"(p + (r & 1) * 4096 + 3968), "r"(v & 0u) : "memory");
    if (v == 0x7fffffffu) t0++;
    int d = (int)(clk() - t0);
    if (r & 1) best1 = min(best1, d); else best0 = min(best0, d);
  }
  return best1 < best0;
}
__device__ __forceinline__ void fill_mem0(uint32_t img, int w, int lane, int slot, const bf16* mem0) {
  PIN(w); PIN(lane);
  const int k0 = w + lane;
  uint4 u[2];
#pragma unroll
  for (int i = 0; i < 2; i++) {
    const unsigned short* m = (const unsigned short*)mem0 + k0 + 32 * i;
    u[i] = make_uint4(m[0] | (uint32_t)m[512] << 16, m[1024] | (uint32_t)m[1536] << 16, m[2048] | (uint32_t)m[2560] << 16, m[3072] | (uint32_t)m[3584] << 16);
  }
  __syncwarp();
#pragma unroll
  for (int i = 0; i < 2; i++) sts128(img + ((k0 >> 4) + 2 * i) * 768 + slot * 256 + (lane & 15) * 16, u[i]);
}

__device__ __forceinline__ void paced_h(uint32_t dst, const uint8_t* src, uint32_t o0, uint32_t o1, uint32_t piece, uint32_t bar, int gap) {
  uint32_t t = clk32();
#pragma unroll 1
  for (uint32_t o = o0; o < o1; o += piece) {
    e_mc(dst + o, src + o, piece, bar, 7);
    spin_until(t += gap);
  }
}

__device__ __forceinline__ void weight_role(const Params& p, const uint32_t sb, const int warp, const int cta, const int C, const uint32_t E,
                                            const uint8_t* const memg) {
  const int tid = fresh_tid(), lane = tid & 31;
  const int wg = warp >> 2, w = warp & 3;
  uint32_t W[32][4];
  cp_async_wait();
  bar_sync(1, 256);
  load_frags(W, sb, wg, w, lane);
  bar_sync(1, 256);
  if (tid < 128) sts128(sb + M_V + 5 * 2048 + tid * 16, make_uint4(0, 0, 0, 0));
  fence_async_smem();
  cluster_sync();
  if (tid == 0 && cta == 0) GSTAMP(0, 1);
  if (tid == 0) TSTAMP(13, cta, 0);

  const uint32_t rba = mapa(sb, C == 2 ? 0 : 2), rbc = mapa(sb, C == 1 ? 0 : 1);
  const uint32_t MYBAR = M_BAR + 8 * (C < 2 ? B_QK : B_V);
  uint32_t qoff = M_Q + C * 12288 + warp * 256 + lane * 4;
  uint32_t toff = sb + warp * 256 + (lane >> 4) * 2048 + (lane & 15) * 16;
  uint32_t rbar = mapa(sb + M_BAR, min(lane, 2));
  uint32_t sv = sb + M_MEM + lane * 32 + ((lane >> 2) & 3) * 8;
  PIN(qoff); PIN(toff); PIN(rbar); PIN(sv);
  const uint32_t gen0 = (E - 1) * (uint32_t)(NSTEP - 1);
  uint32_t fix = 0;
  const bool sig = w == 0 && lane < 3;
  const int pk = PAUSE_ + (cta < 36 ? 0 : cta < 72 ? PD1_ : PD2_);
  int cand = -1;
  float d[16];
#pragma unroll
  for (int i = 0; i < 16; i++) d[i] = 0.f;
  uint32_t tp[8];
#pragma unroll 1
  for (int T = -1; T < NSTEP; T++) {
    const uint32_t ph = T & 1;
    const uint64_t Z = p.zero << ph;
    const uint32_t zz = (uint32_t)Z;
    if (T >= 0) {
      WSTAMP(0);
      const uint64_t db = mkdesc(M_MEM, 128, 256, 0) + Z;
      stmatrix4(toff + M_TST + 8192, tp[0], tp[1], tp[2], tp[3]); stmatrix4(toff + M_TST + 12288, tp[4], tp[5], tp[6], tp[7]);
      if (sig) mbar_arrive_remote(rbar + 8 * B_HBE);
      mbar_wait(BAR(B_LAND), ph);
      WSTAMP(1);
      const uint32_t gt = gentag(gen0 + T);
      auto old = [&](uint32_t a) { return lds32(a) ^ gt; };
      uint32_t bad = 0;
      bool redo = false, ready = false;
      wg_fence();
      wgmma_rs24<0, 1, KP1_>(d, W[0], db);
#pragma unroll
      for (int ks = 1; ks < 32; ks++) {
        if (ks == 2 || ks == 14) bad |= xo2(lds32(sv + (ks == 2 ? 0 : 9) * 1024 + warp * 1024), lds32(sv + (ks == 2 ? 8 : 17) * 1024), gt);
        if (ks == 25) bad |= old(sv + (18 + min(warp, 5)) * 1024);
        if (ks == 6) {
          const uint32_t z5 = DRAIN(toff + M_TST);
          __syncwarp();
          if (lane == 0) mbar_arrive(BAR(B_STG) + z5);
        }
        if (ks == 27) ready = mbar_test(BAR(C < 2 ? B_KFREE : B_VFREE), ph ^ 1) & mbar_test(BAR(B_HA), ph);
        if ((EARLY_ && (ks == 9 || ks == 21)) || ks == RED_) redo = bar_or(N_W, 256, T > 0 && (bad & 0x10001u));
        if (ks == 12 || ks == 24) {
          if (EARLY_ && __builtin_expect(redo, 0)) break;
          mbar_wait(BAR(B_LAND + ks / 12), ph); WSTAMP(6 + ks / 12); wg_fence();
        }
        wgmma_rs24<1, 1>(d, W[ks], db + ks * 48);
      }
      wg_commit();
      uint32_t a0 = rba + qoff, a1 = a0 + 128, a2 = rbc + qoff, a3 = a2 + 128, ba = rba + MYBAR, bc = rbc + MYBAR;
      PIN(a0); PIN(a1); PIN(a2); PIN(a3); PIN(ba); PIN(bc);
      if (!ready) {
        mbar_wait(BAR(C < 2 ? B_KFREE : B_VFREE), ph ^ 1);
        if (T < NSTEP - 1) mbar_wait(BAR(B_HA), ph);
      }
      wg_wait<0>(); reg_fence(d);
      if (__builtin_expect(redo, 0)) {
        auto stale = [&]() { return __any_sync(~0u, (old(sv + warp * 3072) | old(sv + warp * 3072 + 1024) | old(sv + warp * 3072 + 2048)) & 0x10001u); };
        auto fetch = [&](int r) {
          e_expect(BAR(B_FIX + warp), 3072);
          e_g2s(sb + M_MEM + warp * 3072, memg + warp * 8192 + ((uni(lds32(sb + M_NEAR + warp * 4)) ^ r) & 1) * 4096, 3072, BAR(B_FIX + warp));
        };
        mbar_wait(BAR(B_LAND + warp / 3), ph);
        bool late = stale();
        if (late) fetch(0);
        constexpr uint64_t dc = mkdesc(M_MEM, 128, 256, 0);
#pragma unroll
        for (int ks = 0; ks < 32; ks++) {
          if (ks % 12 == 0) {
            if (ks) { wg_commit(); wg_wait<0>(); reg_fence(d); }
            if (warp / 3 == ks / 12) {
              for (int guard = 0; late; guard++) {
                mbar_wait(BAR(B_FIX + warp), fix); fix ^= 1;
                late = stale();
                if (late) fetch(ALT_ ? guard + 1 : 0);
                if (guard > (1 << 20)) TRAP();
              }
            }
            bar_sync(N_W, 256);
            wg_fence();
          }
          if (ks == 0) wgmma_rs24<0, 1, 1>(d, W[0], dc); else wgmma_rs24<1, 1>(d, W[ks], dc + ks * 48);
        }
        wg_commit();
        wg_wait<0>(); reg_fence(d);
      }
      WSTAMP(2);
      uint32_t lo[3], hi[3];
#pragma unroll
      for (int j = 0; j < 3; j++) { lo[j] = pack2(d[4 * j], d[4 * j + 1]); hi[j] = pack2(d[4 * j + 2], d[4 * j + 3]); }
      if (__builtin_expect(T == 0, 0)) { sts32(sb + M_M0 + tid * 8, lo[0]); sts32(sb + M_M0 + tid * 8 + 4, hi[0]); }
      if (__builtin_expect(cand >= 0, 0)) {
        if (T == LAG) { lo[1] = lds32(sb + M_M0 + tid * 8); hi[1] = lds32(sb + M_M0 + tid * 8 + 4); }
        if (C < 2) { st_async32(a0 + 5 * 2048, lo[2], ba); st_async32(a1 + 5 * 2048, hi[2], ba); }
        else { sts32(sb + qoff + 5 * 2048, lo[2]); sts32(sb + qoff + 5 * 2048 + 128, hi[2]); }
        lo[2] = lo[1]; hi[2] = hi[1];
      }
      uint32_t z5;
      if (C == 0) {
        sts32(sb + qoff, lo[0]); sts32(sb + qoff + 128, hi[0]); z5 = DRAIN(sb + qoff);
        st_async32(a0, lo[2], ba); st_async32(a1, hi[2], ba); st_async32(a2, lo[1], bc); st_async32(a3, hi[1], bc);
      } else if (C == 1) {
        sts32(sb + qoff, lo[1]); sts32(sb + qoff + 128, hi[1]); z5 = DRAIN(sb + qoff);
        st_async32(a0, lo[2], ba); st_async32(a1, hi[2], ba); st_async32(a2, lo[0], bc); st_async32(a3, hi[0], bc);
      } else {
        sts32(sb + qoff, lo[2]); sts32(sb + qoff + 128, hi[2]); z5 = DRAIN(sb + qoff);
        st_async32(a0, lo[0], ba); st_async32(a1, hi[0], ba); st_async32(a2, lo[1], bc); st_async32(a3, hi[1], bc);
      }
      __syncwarp();
      if (lane == 0) { mbar_arrive(sb + MYBAR + z5); if (w == 3) mbar_arrive(BAR(B_SS)); }
      if (T == NSTEP - 1) break;
    }
    {
      const uint64_t dh = mkdesc(M_H, 16, 1024, 1) + Z;
      if (T < 0) mbar_wait(BAR(B_HA), ph);
      WSTAMP(3);
      wg_fence();
      wgmma_rs32<0, 0, 1>(d, W[0], dh);
#pragma unroll
      for (int ks = 1; ks < EA; ks++) {
        if (ks == E1 || ks == E1 + E2) {
          wg_commit();
          if (T >= 0) { if (ks == E1 && E2 > 0) bar_sync(N_GO1, 384); if (ks == E1 + E2) bar_sync(N_GO2, 384); }
          wg_fence();
        }
        wgmma_rs32<1, 0>(d, W[ks], dh + (ks >> 2) * 256 + (ks & 3) * 2);
      }
      wg_commit();
      mbar_wait(BAR(B_HB), ph);
      wg_wait<0>();
      if (sig) mbar_arrive_remote(rbar + 8 * B_HAE);
      WSTAMP(4);
      if (T >= 0) bar_sync(N_GO3, 384);
      if (wg == 1) bar_sync(N_W, 256);
      wg_fence();
#pragma unroll
      for (int ks = EA; ks < 32; ks++) wgmma_rs32<1, 0>(d, W[ks], dh + (ks >> 2) * 256 + (ks & 3) * 2);
      wg_commit();
      if (wg == 0) bar_arrive(N_W, 256);
      mbar_wait(BAR(B_TFREE), ph ^ 1);
      wg_wait<0>(); reg_fence(d);
#pragma unroll
      for (int i = 0; i < 8; i++) { tp[i] = pack2(d[2 * i], d[2 * i + 1]); PIN(tp[i]); }
      wg_fence();
      wgmma_rs32<0, 0, 1>(d, W[0], dh + 2048);
      stmatrix4(toff + M_TST, tp[0], tp[1], tp[2], tp[3]); stmatrix4(toff + M_TST + 4096, tp[4], tp[5], tp[6], tp[7]);
#pragma unroll
      for (int ks = 1; ks < 32; ks++) {
        if (PAUSE_ && (ks == PAUSE_ || ks == PAUSE_ + PD1_ || ks == PAUSE_ + PD2_)) {
          wg_commit();
          if (T >= 0 && ks == pk) bar_sync(N_GO4, 384);
          wg_fence();
        }
        wgmma_rs32<1, 0>(d, W[ks], dh + 2048 + (ks >> 2) * 256 + (ks & 3) * 2);
      }
      wg_commit();
      if (T >= 0) cand = __shfl_sync(~0u, (int)lds32(sb + M_CAND + ((T + 1) & 3) * 4), 0);
      wg_wait<0>(); reg_fence(d);
      if (T >= 0) WSTAMP(6);
#pragma unroll
      for (int i = 0; i < 8; i++) tp[i] = pack2(d[2 * i], d[2 * i + 1]);
    }
  }
  cluster_sync();
  if (tid == 0 && cta == 0) GSTAMP(0, 5);
}

__device__ __forceinline__ void attn_role(const Params& p, const uint32_t sb, const int w, const int cta, const int head, const int C, const uint32_t E,
                                          uint8_t* const part, uint8_t* const memg) {
  const int tid = fresh_tid(), lane = tid & 31;
  const int g = lane >> 2, t = lane & 3;
  uint32_t tag = ((E - 1) * (uint32_t)(NSTEP - 1)) & 1;
#pragma unroll 1
  for (int k = 0; k < 2; k++) {
#pragma unroll 1
    for (int i = 0; i < 6; i++) sts128(sb + M_MEM + (w + 4 * k) * 3072 + lane * 16 + i * 512, make_uint4(0, 0, 0, 0));
    fill_mem0(sb + M_MEM, (w + 4 * k) * 64, lane, 0, p.mem0);
  }
  fence_async_smem();
  bar_sync(N_AG, 128);
  if (w == 3 && lane < 3) mbar_arrive(BAR(B_LAND + lane));
  if (w < 2 && lane == 0) {
    const int n = probe_near(part + cta * 16384 + w * 8192);
    sts32(sb + M_NEAR + 32 + w * 4, n);
    st_rel(&f_choice[cta][w], (E << 1) | (uint32_t)n);
  }
  __syncwarp();
  uint32_t nb;
  {
    const int i = min(lane >> 1, C < 2 ? 8 : 5);
    const int r = ((i / 3 * 3 + C) * 4 + w) * 3 + i % 3;
    int guard = 0; uint32_t cw;
    while (__any_sync(~0u, ((cw = ld_acq(&f_choice[r][lane & 1])) >> 1) != (E & 0x7FFFFFFFu))) { if (++guard > (1 << 22)) TRAP(); }
    nb = __ballot_sync(~0u, cw & 1) >> (lane >> 4);
  }
  bar_sync(N_AG, 128);
  const uint32_t pt0 = sb + M_PT + (tid & 127) * 16;
  {
    const uint32_t po = (C * 4 + w) * 49152 + (lane >> 4) * 8192 + ((lane >> 3) & 1) * 2048 + head * 64 + (lane & 7) * 8;
    const uint8_t* in = part + (cta * 16384 + (w >> 1) * 8192 + lds32(sb + M_NEAR + 32 + (w >> 1) * 4) * 4096 + (w & 1) * 2048 + lane * 8);
    const uint8_t* outp = memg + ((cta / 12) * 8192 + (cta % 12) * 256 + w * 64 + (lane >> 4) * 4096 + (lane & 4) * 8 + (lane & 8) * 2 + (lane & 3) * 4);
#pragma unroll 1
    for (int i = 0; i < 12; i++) {
      const int j = i / 4 * 3 + (i & 3);
      const uint8_t* a = (i & 3) < 3 ? part + (po + i / 4 * 589824 + (i & 3) * 16384 + ((nb >> (2 * j)) & 1) * 4096) : i == 11 ? in : outp;
      asm volatile("st.shared.u64 [%0], %1;" :: "r"(pt0 + (i >> 1) * 2048 + (i & 1) * 8), "l"(a) : "memory");
    }
  }
  const int xd = __shfl_sync(~0u, XDLY_ + (cta < 36 ? 0 : cta < 72 ? X1_ : X2_), 0);
  const uint32_t rba = mapa(sb, C == 2 ? 0 : 2), rbc = mapa(sb, C == 1 ? 0 : 1);
  uint32_t vis = vis_bits(8 + 8 * w + g, t);
  uint32_t ln = lane;
#pragma unroll
  for (int i = 0; i < SALT_; i++) ln += lds32(sb + M_ZERO);
  PIN(vis); PIN(ln);
  uint32_t fa[8][4];
#pragma unroll
  for (int ks = 0; ks < 8; ks++) ldmatrix4_t(fa[ks], sb + M_WO + 32768 + w * 256 + (lane >> 4) * 1024 + (lane & 15) * 16 + ks * 2048);
#pragma unroll 1
  for (int T = 0; T < NSTEP; T++) {
    const uint32_t ph = T & 1;
    const uint32_t zz = uni(lds32(sb + M_ZERO));
    const bool more = T < NSTEP - 1;
    const float sc = 0.08838834764831845f * 1.4426950408889634f;
    tag ^= 1;
    float s[20];
    const uint8_t* in; int cnext = -1; uint32_t tx; bool synced;
    float x[10], tm, ts;
    uint32_t pt[5];
    auto tok_max = [&]() {
      PIN(vis);
      x[0] = s[2]; x[1] = s[3];
#pragma unroll
      for (int i = 0; i < 8; i++) x[2 + i] = (vis >> i & 1) ? s[4 * (i / 2 + 1) + 2 + (i & 1)] : -INFINITY;
      tm = fmaxf(fmaxf(fmaxf(fmaxf(x[0], x[1]), fmaxf(x[2], x[3])), fmaxf(fmaxf(x[4], x[5]), fmaxf(x[6], x[7]))), fmaxf(x[8], x[9]));
      HOLD(7, __float_as_uint(tm));
    };
    auto tok_exp1 = [&]() {
      tm = fmaxf(tm, __shfl_xor_sync(~0u, tm, 1));
      tm = fmaxf(tm, __shfl_xor_sync(~0u, tm, 2));
      const float b = -tm * sc;
#pragma unroll
      for (int i = 0; i < 10; i++) x[i] = fmaf(x[i], sc, b);
      HOLD(10, __float_as_uint(x[9]));
    };
    auto tok_exp2 = [&]() {
#pragma unroll
      for (int i = 0; i < 10; i++) x[i] = ex2(x[i]);
      ts = (((x[0] + x[1]) + (x[2] + x[3])) + ((x[4] + x[5]) + (x[6] + x[7]))) + (x[8] + x[9]);
#pragma unroll
      for (int k = 0; k < 5; k++) pt[k] = pack2(x[2 * k], x[2 * k + 1]);
      HOLD(8, __float_as_uint(ts));
    };
    {
      uint32_t q[8][4];
      auto load_q = [&](uint32_t a, int h) {
#pragma unroll
        for (int k2 = 0; k2 < 4; k2++) {
          uint32_t r[4];
          ldmatrix4_t(r, a + k2 * 512);
          q[2 * k2][h] = r[0]; q[2 * k2][h + 2] = r[1]; q[2 * k2 + 1][h] = r[2]; q[2 * k2 + 1][h + 2] = r[3];
        }
      };
      PIN(ln);
      const uint32_t qa = sb + M_Q + ln * 16;
      const int cand = C == 2 ? (int)uni(lds32(sb + M_CAND + (T & 3) * 4)) : -1;
      mbar_wait(BAR(B_TOK), ph);
      load_q(qa + (1 + w) * 2048, 1);
      mbar_wait(BAR(B_QK), ph);
      ASTAMP(0);
      if (__builtin_expect(cand >= 0, 0)) {
        mbar_wait(BAR(B_V), ph);
        PIN(ln);
        const int e = w * 32 + ln;
#pragma unroll
        for (int i = 0; i < 3; i++) {
          const uint32_t v = lds32(sb + M_Q + i * 12288 + 5 * 2048 + e * 16 + 4);
          asm volatile("st.shared.u16 [%0], %1;" :: "r"(sb + M_Q + i * 12288 + (1 + (cand >> 3)) * 2048 + e * 16 + (cand & 7) * 2), "h"((unsigned short)v) : "memory");
        }
        fence_async_smem();
        bar_sync(N_AG, 128);
        load_q(qa + (1 + w) * 2048, 1);
      }
      load_q(qa, 0);
      fence_async_smem();
      constexpr uint64_t dk = mkdesc(M_K, 128, 2048, 0);
      wg_fence();
      wgmma_rs40<0, 1>(s, q[0], dk);
#pragma unroll
      for (int ks = 1; ks < 8; ks++) wgmma_rs40<1, 1>(s, q[ks], dk + ks * 16);
      wg_commit();
    }
    if (more) {
      uint32_t v[5][4];
      PIN(ln);
      const uint32_t va = sb + M_V + w * 512 + ((ln >> 3) & 1) * 128 + (ln >> 4) * 2048 + (ln & 7) * 16;
      const uint32_t ooff = M_OM + w * 1536 + C * 256 + ln * 4;
      mbar_wait(BAR(B_V), ph);
      wg_wait<0>(); reg_fence(s);
      if (E2 > 0) bar_arrive(N_GO1, 384);
      if (ln < 3) mbar_arrive_remote(mapa(BAR(B_KFREE), ln));
      ldmatrix4(v[0], va); ldmatrix4(v[1], va + 256); ldmatrix4(v[2], va + 4096); ldmatrix4(v[3], va + 4096 + 256);
      ldmatrix4(v[4], sb + M_V + 8192 + w * 512 + ln * 16);
      ASTAMP(1);
      float m = fmaxf(fmaxf(fmaxf(fmaxf(s[0], s[1]), fmaxf(s[4], s[5])), fmaxf(fmaxf(s[8], s[9]), fmaxf(s[12], s[13]))), fmaxf(s[16], s[17]));
      m = fmaxf(m, __shfl_xor_sync(~0u, m, 1));
      m = fmaxf(m, __shfl_xor_sync(~0u, m, 2));
      const float b = -m * sc;
      uint32_t pm[5];
#pragma unroll
      for (int j = 0; j < 5; j++) pm[j] = pack2(ex2(fmaf(s[4 * j], sc, b)), ex2(fmaf(s[4 * j + 1], sc, b)));
      float o0[4] = {0.f, 0.f, 0.f, 0.f}, o1[4] = {0.f, 0.f, 0.f, 0.f}, l[4] = {0.f, 0.f, 0.f, 0.f};
      const uint32_t one[4] = {0x3f803f80u, 0x3f803f80u, 0x3f803f80u, 0x3f803f80u};
      hmma16(l, one, pm[0], pm[1]); hmma16(o0, v[0], pm[0], pm[1]); hmma16(o1, v[1], pm[0], pm[1]);
      hmma16(l, one, pm[2], pm[3]); hmma16(o0, v[2], pm[2], pm[3]); hmma16(o1, v[3], pm[2], pm[3]);
      hmma8(l, one[0], one[1], pm[4]); hmma8(o0, v[4][0], v[4][1], pm[4]); hmma8(o1, v[4][2], v[4][3], pm[4]);
      const float r0 = rcp(l[0]), r1 = rcp(l[1]);
      const uint32_t u0 = pack2(o0[0] * r0, o0[1] * r1), u1 = pack2(o0[2] * r0, o0[3] * r1), u2 = pack2(o1[0] * r0, o1[1] * r1), u3 = pack2(o1[2] * r0, o1[3] * r1);
      constexpr uint32_t OB = M_BAR + 8 * B_OM;
      const uint32_t a0 = rba + ooff, a1 = rbc + ooff;
      st_async32(a0, u0, rba + OB); st_async32(a1, u0, rbc + OB);
      st_async32(a0 + 128, u1, rba + OB); st_async32(a1 + 128, u1, rbc + OB);
      st_async32(a0 + 768, u2, rba + OB); st_async32(a1 + 768, u2, rbc + OB);
      st_async32(a0 + 896, u3, rba + OB); st_async32(a1 + 896, u3, rbc + OB);
      if (E3 > 0) bar_arrive(N_GO2, 384);
      sts32(sb + ooff, u0); sts32(sb + ooff + 128, u1); sts32(sb + ooff + 768, u2); sts32(sb + ooff + 896, u3);
      ASTAMP(2);
      uint32_t fb[8][4];
      const uint32_t wa = sb + M_WO + 16384 + w * 256 + (ln >> 4) * 1024 + (ln & 15) * 16 + zz;
      ldmatrix4_t(fb[0], wa);
      SCHED(3);
#pragma unroll
      for (int ks = 1; ks < 8; ks++) {
        ldmatrix4_t(fb[ks], wa + ks * 2048);
        if (ks == ARR_) { __syncwarp(); if (ln == 0) mbar_arrive(BAR(B_OM) + (fb[0][0] & zz)); }
      }
      if (C == 2) cnext = (int)uni(lds32(sb + M_CAND + ((T + 1) & 3) * 4));
      {
        float d[12], e[12];
        constexpr uint64_t ob = mkdesc(M_OM, 128, 256, 0);
        uint8_t* q[3][3];
        auto addr = [&](int i) {
          asm volatile("ld.shared.v2.u64 {%0,%1}, [%2];" : "=l"(q[i][0]), "=l"(q[i][1]) : "r"(pt0 + i * 4096) : "memory");
          if (i < 2) asm volatile("ld.shared.u64 %0, [%1];" : "=l"(q[i][2]) : "r"(pt0 + i * 4096 + 2048) : "memory");
          else asm volatile("ld.shared.v2.u64 {%0,%1}, [%2];" : "=l"(q[i][2]), "=l"(in) : "r"(pt0 + i * 4096 + 2048) : "memory");
        };
        auto put = [&](const float* d, int i) {
          st_rlx64(q[i][0], (pack2(d[0], d[1]) & ~1u) | tag, pack2(d[2], d[3]));
          st_rlx64(q[i][1], (pack2(d[4], d[5]) & ~1u) | tag, pack2(d[6], d[7]));
          st_rlx64(q[i][2], (pack2(d[8], d[9]) & ~1u) | tag, pack2(d[10], d[11]));
        };
        addr(0); addr(1);
        SCHED(6);
        tok_max();
        ASTAMP(3);
        mbar_wait(BAR(B_OM), ph);
        fence_async_smem();
        ASTAMP(4);
        constexpr uint64_t w0 = mkdesc(M_WO, 1024, 128, 0);
        float (&f)[12] = d;
        wg_fence();
        wgmma_ss24<0, 1, 1>(d, w0, ob);
#pragma unroll
        for (int ks = 1; ks < 8; ks++) wgmma_ss24<1, 1, 1>(d, w0 + ks * 128, ob + ks * 48);
        wg_commit();
        wgmma_rs24<0, 1>(e, fb[0], ob);
#pragma unroll
        for (int ks = 1; ks < HAND_; ks++) wgmma_rs24<1, 1>(e, fb[ks], ob + ks * 48);
        wg_commit();
        wg_wait<1>(); reg_fence(d);
        put(d, 0);
        addr(2);
        SCHED(4);
        ASTAMP(5);
        wg_fence();
#pragma unroll
        for (int ks = HAND_; ks < 8; ks++) wgmma_rs24<1, 1>(e, fb[ks], ob + ks * 48);
        wg_commit();
        wgmma_rs24<0, 1, 1>(f, fa[0], ob);
#pragma unroll
        for (int ks = 1; ks < HAND_; ks++) wgmma_rs24<1, 1>(f, fa[ks], ob + ks * 48);
        wg_commit();
        wg_wait<1>(); reg_fence(e);
        put(e, 1);
        SCHED(5);
        wg_fence();
#pragma unroll
        for (int ks = HAND_; ks < 8; ks++) wgmma_rs24<1, 1>(f, fa[ks], ob + ks * 48);
        wg_commit();
        if (GO3_ == 0) bar_arrive(N_GO3, 384);
        synced = __all_sync(~0u, mbar_test(BAR(B_SYNC), ph));
        tx = uni(lds32(sb + M_BASE + ph * 4)) + xd;
        wg_wait<0>(); reg_fence(f);
        if (GO3_ == 1) bar_arrive(N_GO3, 384);
        if (C < 2) put(f, 2);
        if (GO3_ == 2) bar_arrive(N_GO3, 384);
        ASTAMP(6);
      }
    } else {
      mbar_wait(BAR(B_V), ph);
      wg_wait<0>(); reg_fence(s);
      tok_max();
    }
    uint2 v[8];
#pragma unroll
    for (int i = 0; i < 8; i++) v[i] = make_uint2(zz, zz);
    auto poll = [&](uint2* v) {
      v[0] = ld_rlx64<0>(in); v[1] = ld_rlx64<256>(in); v[2] = ld_rlx64<512>(in); v[3] = ld_rlx64<768>(in);
      v[4] = ld_rlx64<1024>(in); v[5] = ld_rlx64<1280>(in); v[6] = ld_rlx64<1536>(in); v[7] = ld_rlx64<1792>(in);
    };
    uint8_t* outp;
    asm volatile("ld.shared.u64 %0, [%1];" : "=l"(outp) : "r"(pt0 + 2048 + 8) : "memory");
    const uint32_t itag = gentag((E - 1) * (uint32_t)(NSTEP - 1) + T + 1);
    const bool sum = more && cnext < 0;
    if (more) {
      if (!synced) { mbar_wait(BAR(B_SYNC), ph); tx = uni(lds32(sb + M_BASE + ph * 4)) + xd; }
      ASTAMP(7);
      if (__builtin_expect(cnext >= 0, 0)) {
        const unsigned long long* hp = (const unsigned long long*)&g_hc[T + 1 - LAG][0] + ((cta / 3) * 8 + 2 * w + ((ln >> 2) & 1));
        unsigned long long v0; int guard = 0;
        while (v0 = ld_rlxu64(hp), !__all_sync(~0u, (uint32_t)(v0 >> 32) == E)) { if (++guard > (1 << 22)) TRAP(); }
        st_rlx((uint32_t*)outp, (ln & 3) == 1 ? ((uint32_t)v0 >> ((ln & 8) * 2)) & 0xffffu : (ln & 1) ? 0u : itag);
      } else {
        spin_until(tx);
        ASTAMP(8);
        poll(v);
      }
    }
    auto late = [&](const uint2* v) {
      return __any_sync(~0u, (or3(xo2(v[0].x, v[1].x, tag), xo2(v[2].x, v[3].x, tag), xo2(v[4].x, v[5].x, tag)) | xo2(v[6].x, v[7].x, tag)) & 1u);
    };
    tok_exp1(); tok_exp2();
    if (sum) {
      ASTAMP(9);
      int guard = 0;
      while (late(v)) {
        if (++guard > (1 << 22)) TRAP();
        poll(v);
      }
#pragma unroll
      for (int i = 0; i < 4; i++) { v[i].x = add2(v[i].x, v[i + 4].x); v[i].y = add2(v[i].y, v[i + 4].y); }
#define SUM8(f, m) ((f(v[0].m) + f(v[1].m)) + (f(v[2].m) + f(v[3].m)))
      const float a0 = SUM8(blo, x), a1 = SUM8(bhi, x), b0 = SUM8(blo, y), b1 = SUM8(bhi, y);
      const bool hi = ln & 8;
      float k0 = (hi ? b0 : a0) + __shfl_xor_sync(~0u, hi ? a0 : b0, 8), k1 = (hi ? b1 : a1) + __shfl_xor_sync(~0u, hi ? a1 : b1, 8);
      k0 += __shfl_xor_sync(~0u, k0, 16); k1 += __shfl_xor_sync(~0u, k1, 16);
      st_rlx((uint32_t*)outp, (ln & 1) ? pack2(k0, k1) : pack2_tag(k0, k1, itag));
      ASTAMP(10);
      CSTAMP(12 + w, (clk() & ~15u) | min(guard + 1, 15));
    }
    if (PAUSE_ && more) bar_arrive(N_GO4, 384);
    {
      PIN(ln);
      const uint32_t oa = sb + M_OST + w * 128 + (ln >> 3) * 512 + (ln & 7) * 16;
      const uint32_t a[3][4] = {{0, pt[0], 0, pt[1]}, {0, pt[2], 0, pt[3]}, {0, pt[4], 0, 0}};
      constexpr uint64_t dv = mkdesc(M_V, 2048, 128, 0);
#pragma unroll 1
      for (int h = 0; h < 2; h++) {
        float o[32];
        const uint64_t dh = dv + (uint64_t)(h * 64);
        wg_fence();
        wgmma_rs64<0, 0>(o, a[0], dh); wgmma_rs64<1, 0>(o, a[1], dh + 256); wgmma_rs64<1, 0>(o, a[2], dh + 512);
        wg_commit();
        if (h == 0) {
          ts += __shfl_xor_sync(~0u, ts, 1);
          ts += __shfl_xor_sync(~0u, ts, 2);
          ts = rcp(ts);
          mbar_wait(BAR(B_OFREE), ph ^ 1);
        }
        wg_wait<0>(); reg_fence(o);
        if (h == 1 && ln < 3) mbar_arrive_remote(mapa(BAR(B_VFREE), ln));
#define OT(i) pack2(o[4 * (i) + 2] * ts, o[4 * (i) + 3] * ts)
        stmatrix4(oa + h * 4096, OT(0), OT(1), OT(2), OT(3));
        stmatrix4(oa + h * 4096 + 2048, OT(4), OT(5), OT(6), OT(7));
      }
      const uint32_t z5 = DRAIN(oa);
      __syncwarp();
      if (ln == 0) mbar_arrive(BAR(B_OST) + z5);
      ASTAMP(11);
    }
  }
}

__global__ void __cluster_dims__(3, 1, 1) __launch_bounds__(512, 1) main_kernel(Params p) {
  extern __shared__ __align__(1024) uint8_t sm[];
  const uint32_t sb = smem_u32(sm);
  if ((sb & 0xFFFFFFu) != SBASE) TRAP();
  asm volatile("griddepcontrol.launch_dependents;");
  const int warp = __shfl_sync(~0u, threadIdx.x >> 5, 0);
  const int cta = blockIdx.x, head = cta / 3, c = cta % 3;
  const uint32_t E = __shfl_sync(~0u, *(volatile uint32_t*)&g_epoch + 1, 0);
  uint8_t* const part = (uint8_t*)(((uintptr_t)g_xch + 8191) & ~(uintptr_t)8191);
  uint8_t* const memg = part + 96 * 16384;

  if (threadIdx.x == 0 && cta == 0) GSTAMP(0, 0);
  if (threadIdx.x < B_NUM) {
    const int i = threadIdx.x;
    const uint32_t cnt = i == B_STG ? 8 : i == B_OST ? 4 : i == B_HAE || i == B_HBE ? 6 : i == B_KFREE || i == B_VFREE ? 12 : i == B_SS ? 2 : i == B_OM ? 5 :
                         i == B_QK ? (c < 2 ? 9 : 1) : i == B_V ? (c < 2 ? 1 : 9) : 1;
    mbar_init(BAR(i), cnt);
    if (i == B_HA || i == B_HB || i == B_STG || i == B_HAE || i == B_HBE || i == B_TFREE)
      asm volatile("mbarrier.arrive.shared::cta.b64 _, [%0], %1;" :: "r"(BAR(i)), "r"(cnt) : "memory");
    asm volatile("fence.mbarrier_init.release.cluster;" ::: "memory");
  }
  if (warp < 8) {
    const int tid = threadIdx.x;
    uint4 wa[6], wb[6];
#pragma unroll
    for (int i = 0; i < 6; i++) {
      const int mi = i >> 1, e = (tid >> 2) + (i & 1) * 64;
      const uint4* src = (const uint4*)(p.wo + (size_t)(head * 128 + e) * 512 + min(3 * mi + c, 7) * 64 + (tid & 3) * 16);
      wa[i] = __ldg(src); wb[i] = __ldg(src + 1);
    }
    stage_weights(sb, (c == 0 ? p.wq : c == 1 ? p.wk : p.wv) + head * 128, 4096, tid, 256);
#pragma unroll
    for (int i = 0; i < 6; i++) {
      const int mi = i >> 1, e = (tid >> 2) + (i & 1) * 64;
      const uint4 a = wa[i], b = wb[i];
      const uint32_t dst = sb + M_WO + mi * 16384 + (e >> 3) * 1024 + (tid & 3) * 256 + (e & 7) * 16;
      sts128(dst, make_uint4(__byte_perm(a.x, a.y, 0x5410), __byte_perm(a.z, a.w, 0x5410), __byte_perm(b.x, b.y, 0x5410), __byte_perm(b.z, b.w, 0x5410)));
      sts128(dst + 128, make_uint4(__byte_perm(a.x, a.y, 0x7632), __byte_perm(a.z, a.w, 0x7632), __byte_perm(b.x, b.y, 0x7632), __byte_perm(b.z, b.w, 0x7632)));
    }
  } else {
    const int i0 = threadIdx.x - 256;
    const uint32_t tag0 = ((E - 1) * (uint32_t)(NSTEP - 1)) & 1;
    for (int i = i0; i < 1024; i += 256) *(uint4*)(part + cta * 16384 + i * 16) = make_uint4(tag0, 0, tag0, 0);
    if (i0 < 16) *(uint32_t*)(memg + i0 * 4096 + 3968) = 0;
    if (i0 < 12) sts32(sb + M_ZERO + i0 * 4, 0);
  }

  if (warp < 8) {
    asm volatile("setmaxnreg.inc.sync.aligned.u32 " STR(RW_) ";");
    weight_role(p, sb, warp, cta, c, E, memg);
  } else if (warp < 12) {
    if (RA_ < 128) asm volatile("setmaxnreg.dec.sync.aligned.u32 " STR(RA_) ";");
    if (RA_ > 128) asm volatile("setmaxnreg.inc.sync.aligned.u32 " STR(RA_) ";");
    cluster_sync();
    attn_role(p, sb, warp - 8, cta, head, c, E, part, memg);
    cluster_sync();
  } else {
    asm volatile("setmaxnreg.dec.sync.aligned.u32 " STR(RC_) ";");
    const int tid = fresh_tid(), lane = tid & 31;
    const int w = warp - 12;
    cluster_sync();
    if (w < 3 && lane == 0) {
      const int tl = min(3 * w + c, 7);
      const int n = probe_near(memg + tl * 8192);
      for (int r = 0; r < 3; r++) asm volatile("st.shared::cluster.u32 [%0], %1;" :: "r"(mapa(sb + M_NEAR + tl * 4, r)), "r"(n) : "memory");
    }
    __syncwarp();
    if (w == 0) {
      uint32_t s0 = c * 8192, s1 = (3 + c) * 8192, s2 = min(6 + c, 7) * 8192;
#pragma unroll 1
      for (int T = 0; T < NSTEP - 1; T++) {
        const uint32_t ph = T & 1;
        mbar_wait(BAR(B_SS), ph);
        const uint32_t cq = clk();
        const uint32_t g0 = (uint32_t)gtime64(); uint32_t g1, ce;
        do { g1 = (uint32_t)gtime64(); ce = clk(); } while (g1 == g0);
        const uint32_t tn = g1 * 8 - (((ce - cq) * 37u) >> 3), id = E * 128u + T;
        if (lane == 0) st_rlx64(&g_sync[ph][cta], tn, id);
        if (lane < 3) mbar_expect(BAR(B_LAND + lane), lane < 2 ? 9216 : 6144);
        if (T == 0) { s0 += uni(lds32(sb + M_NEAR + c * 4)) * 4096; s1 += uni(lds32(sb + M_NEAR + (3 + c) * 4)) * 4096; s2 += uni(lds32(sb + M_NEAR + min(6 + c, 7) * 4)) * 4096; }
        wait_until(cq + SDLY_);
        int guard = 0; unsigned long long v0, v1, v2;
        for (;;) {
          v0 = ld_rlxu64(&g_sync[ph][lane]); v1 = ld_rlxu64(&g_sync[ph][lane + 32]); v2 = ld_rlxu64(&g_sync[ph][lane + 64]);
          if (__all_sync(~0u, (uint32_t)(v0 >> 32) == id && (uint32_t)(v1 >> 32) == id && (uint32_t)(v2 >> 32) == id)) break;
          if (++guard > (1 << 22)) TRAP();
        }
        const int dl = __reduce_max_sync(~0u, max(max((int)((uint32_t)v0 - tn), (int)((uint32_t)v1 - tn)), (int)((uint32_t)v2 - tn)));
        const uint32_t base = uni(cq + ((min(dl, 8 * 4096) * 7) >> 5));
        if (lane == 0) { sts32(sb + M_BASE + ph * 4, base); mbar_arrive(BAR(B_SYNC)); }
        CSTAMP(0, base); CSTAMP(1, clk());
        const uint32_t ts = base + YDLY_;
        uint32_t nr = 0;
        if (PRIV_) nr = __ballot_sync(~0u, lds32(sb + M_NEAR + (lane & 7) * 4) != 0);
        wait_until(ts);
        if (PRIV_ & 1) { for (int k = 0; k < 3; k++) e_g2s(sb + M_MEM + k * 3072, memg + k * 8192 + ((nr >> k) & 1) * 4096, 3072, BAR(B_LAND)); }
        else e_mc(sb + M_MEM + c * 3072, memg + s0, 3072, BAR(B_LAND), 7);
        CSTAMP(2, clk());
        spin_until(ts + Y1_);
        if (PRIV_ & 2) { for (int k = 3; k < 6; k++) e_g2s(sb + M_MEM + k * 3072, memg + k * 8192 + ((nr >> k) & 1) * 4096, 3072, BAR(B_LAND + 1)); }
        else e_mc(sb + M_MEM + (3 + c) * 3072, memg + s1, 3072, BAR(B_LAND + 1), 7);
        CSTAMP(3, clk());
        spin_until(ts + Y2_);
        if (PRIV_ & 4) { for (int k = 6; k < 8; k++) e_g2s(sb + M_MEM + k * 3072, memg + k * 8192 + ((nr >> k) & 1) * 4096, 3072, BAR(B_LAND + 2)); }
        else if (c < 2) e_mc(sb + M_MEM + (6 + c) * 3072, memg + s2, 3072, BAR(B_LAND + 2), 7);
        CSTAMP(4, clk());
      }
    } else if (w == 1) {
#pragma unroll 1
      for (int T = 0; T < NSTEP; T++) {
        const uint32_t ph = T & 1;
        const int s = c == 0 ? T : T - LAG;
        const bool act = s >= 0 && s < NSEG;
        mbar_wait(BAR(B_OST), ph);
        if (cta == 0) TSTAMP(2, T, 0);
        fence_async_smem();
        if (T < NSTEP - 1) wait_until(uni(lds32(sb + M_BASE + ph * 4)) + ODLY_);
        STAMP(22);
        if (act) { e_s2g(g_o[c][s % ORING][head], sb + M_OST, 8192); bulk_wait(); __syncwarp(); }
        e_arrive(BAR(B_OFREE));
        if (cta == 0) TSTAMP(2, T, 1);
        if (act) e_st_rel(&f_o[T][head >> 2][c * 4 + (head & 3)], E);
        if (cta == 0) TSTAMP(2, T, 2);
      }
    } else if (w == 2) {
      unsigned long long run = 0;
      static_assert(LAG >= 2, "config");
      constexpr uint32_t NA = EA / 4 * 4096;
      e_expect(BAR(B_QK), c < 2 ? 2048 : 4096); e_expect(BAR(B_V), c == 0 ? 10240 : c == 1 ? 2048 : 0);
      e_expect(BAR(B_TOK), c == 0 ? 16384 : 0); e_expect(BAR(B_OM), 4096);
      if (lane < 2) sts32(sb + M_CAND + lane * 4, (uint32_t)-1);
      e_expect(BAR(B_HA), NA); e_expect(BAR(B_HB), 65536 - NA);
      wait_eq(&f_h1[c == 1 ? 0 : 1], E); fence_async_glob();
      {
        const uint32_t o0 = c == 0 ? NA : 0, o1 = c == 2 ? NA : 32768;
        e_mc(sb + M_H + (c == 1 ? 32768 : 0) + o0, g_h[0][c == 1 ? 0 : 1] + o0, o1 - o0, BAR(c == 2 ? B_HA : B_HB), 7);
      }
      if (c == 2) wait_eq(&f_h1[2], E);
      mbar_wait(BAR(B_HAE), 1);
      e_expect(BAR(B_HA), NA);
      if (c == 2) { fence_async_glob(); e_mc(sb + M_H, g_h[0][2], NA, BAR(B_HA), 7); }
      int cprev = -1;
#pragma unroll 1
      for (int T = 0; T < NSTEP - 1; T++) {
        const int s1 = T + 2, s2 = T + 2 - LAG;
        const uint32_t ph = T & 1;
        const bool l1 = s1 < NSEG, l2 = s2 >= 0 && s2 < NSEG, la = s1 + 1 < NSEG;
        const bool mine = c == 0 ? l1 : c == 1 ? l2 : la;
        const uint32_t* fl = c != 1 ? &f_h1[min(s1 + (c >> 1), NSEG - 1)] : (const uint32_t*)&f_h2[max(s2, 0)][1];
        const uint32_t want = c != 1 ? E : E * 4u;
        mbar_wait(BAR(B_HBE), ph ^ 1);
        const bool early = uni(ld_acq(fl)) == want;
        mbar_wait(BAR(B_LAND + 2), ph);
        STAMP(16);
        e_expect(BAR(B_HB), (l1 ? 32768 - NA : 0) + (l2 ? 32768 : 0));
        if (mine) {
          if (!early) wait_eq(fl, want);
          fence_async_glob();
          if (c == 1) { mbar_wait(BAR(B_QK), ph); spin_until(clk32() + HDLY_); }
          if (c < 2) paced_h(sb + M_H + c * 32768, g_h[c][c ? s2 : s1], c ? 0 : NA, 32768, 4096, BAR(B_HB), HGAP_);
        }
        int cd = -1;
        if (l2) { cd = route_step(s2, E, run); if (cta == 0) TSTAMP(5, s2, 0); }
        if (lane == 0) sts32(sb + M_CAND + ((T + 2) & 3) * 4, (uint32_t)cd);
        __syncwarp();
        STAMP(17);
        mbar_wait(BAR(B_HAE), ph);
        e_expect(BAR(B_HA), la ? NA : 0);
        if (c == 2 && la) {
          spin_until(clk32() + ADLY_);
          STAMP(18);
          paced_h(sb + M_H, g_h[0][s1 + 1], 0, NA, 4096, BAR(B_HA), AGAP_);
        }
        mbar_wait(BAR(B_OST), ph);
        e_expect(BAR(B_QK), c < 2 ? 2048 : cprev >= 0 ? 8192 : 4096);
        e_expect(BAR(B_V), c < 2 ? 10240 : 8192);
        e_expect(BAR(B_TOK), 16384);
        e_expect(BAR(B_OM), 4096);
        cprev = cd;
      }
    } else {
      const uint32_t mytok = sb + M_Q + c * 12288 + 2048, tb = BAR(c < 2 ? B_TOK : B_V);
#pragma unroll 1
      for (int T = 0; T < NSTEP - 1; T++) {
        const uint32_t ph = T & 1;
        uint8_t* const tok = g_tok[cta][ph ^ 1];
        mbar_wait(BAR(B_STG), ph ^ 1);
        fence_async_smem();
        if (cta == 0 && (T == 0 || T == NSEG || T == NSTEP - 2)) GSTAMP(0, T == 0 ? 2 : T == NSEG ? 3 : 4);
        if (T > 0) { mbar_wait(BAR(B_QK), ph); spin_until(clk32() + TDLY_); }
        STAMP(20);
        uint32_t t = clk32();
#pragma unroll 1
        for (uint32_t o = 0; o < 16384; o += 4096) { e_s2g(tok + o, sb + M_TST + o, 4096); spin_until(t += TGAP_); }
        bulk_wait();
        __syncwarp();
        e_arrive(BAR(B_TFREE));
        if (T == 0) e_mc(mytok, tok + 8192, 8192, tb, 1);
        STAMP(21);
        mbar_wait(BAR(c < 2 ? B_KFREE : B_VFREE), ph);
        if (c < 2) t += KDLY_; else t = uni(lds32(sb + M_BASE + ph * 4)) + LDLY_;
        wait_until(t);
        STAMP(23);
        e_mc(mytok, tok, 8192, tb, 1);
        spin_until(t + LGAP_);
        e_mc(mytok, tok + 8192, 8192, tb, 6);
        STAMP(24);
      }
    }
    __syncwarp();
    cluster_sync();
  }
}

constexpr uint32_t A_RING = 0;
constexpr int A_NST = 6;
constexpr uint32_t A_STG = A_RING + A_NST * 8192;
constexpr uint32_t A_WD = A_STG + 8192;
constexpr uint32_t A_WG = A_WD + 57344;
constexpr uint32_t A_WU = A_WG + 57344;
constexpr uint32_t A_XN = A_WU + 57344;
constexpr uint32_t A_BAR = A_XN + 2048;
constexpr uint32_t A_TOTAL = A_BAR + 256;
static_assert(A_TOTAL <= 232448, "aux smem");

__device__ __forceinline__ uint32_t ptag(int s) { return ((s / PRING) & 1) ^ 1; }
static_assert((NSEG / PRING) % 2 == 0, "tags");
__device__ __forceinline__ void load_row(uint32_t* v, const void* row, int lane) {
  const uint4 a = __ldcg((const uint4*)row + lane), b = __ldcg((const uint4*)row + 32 + lane);
  v[0] = a.x; v[1] = a.y; v[2] = a.z; v[3] = a.w; v[4] = b.x; v[5] = b.y; v[6] = b.z; v[7] = b.w;
}
__device__ __forceinline__ void store_row(void* row, const uint32_t* v, int lane) {
  ((uint4*)row)[lane] = make_uint4(v[0], v[1], v[2], v[3]); ((uint4*)row)[32 + lane] = make_uint4(v[4], v[5], v[6], v[7]);
}
__device__ __forceinline__ void store_img(uint8_t* img, int r, const uint32_t* v, int lane) {
  uint8_t* b = img + (lane >> 3) * 4096 + (r >> 3) * 1024 + (r & 7) * 128 + (((lane ^ r) & 7) << 4);
  *(uint4*)b = make_uint4(v[0], v[1], v[2], v[3]);
  *(uint4*)(b + 16384) = make_uint4(v[4], v[5], v[6], v[7]);
}
template <int NT> __device__ __forceinline__ void ln_rows(const uint32_t (*v)[8], uint32_t (*y)[8]) {
  float c[NT], sm[NT], sq[NT];
#pragma unroll
  for (int k = 0; k < NT; k++) {
    c[k] = blo(__shfl_sync(~0u, v[k][0], 0));
    float s0 = 0.f, s1 = 0.f, q0 = 0.f, q1 = 0.f;
#pragma unroll
    for (int i = 0; i < 8; i++) { const float a = blo(v[k][i]) - c[k], b = bhi(v[k][i]) - c[k]; s0 += a; s1 += b; q0 = fmaf(a, a, q0); q1 = fmaf(b, b, q1); }
    sm[k] = s0 + s1; sq[k] = q0 + q1;
  }
#pragma unroll
  for (int o = 16; o > 0; o >>= 1)
#pragma unroll
    for (int k = 0; k < NT; k++) {
      sm[k] += __shfl_xor_sync(~0u, sm[k], o); sq[k] += __shfl_xor_sync(~0u, sq[k], o);
    }
#pragma unroll
  for (int k = 0; k < NT; k++) {
    const float dm = sm[k] * (1.f / 512.f), var = fmaxf(fmaf(-dm, dm, sq[k] * (1.f / 512.f)), 0.f);
    const float mb = rbf(c[k] + dm), inv = rcp(rbf(sqrt_fast(rbf(rbf(var) + 1e-5f))));
#pragma unroll
    for (int i = 0; i < 8; i++) { const uint32_t a = pack2(blo(v[k][i]) - mb, bhi(v[k][i]) - mb); y[k][i] = pack2(blo(a) * inv, bhi(a) * inv); }
  }
}
__device__ __forceinline__ void input_ln_pair(const bf16* x, int s, int pr, int lane) {
  uint32_t v[2][8], y[2][8];
  load_row(v[0], x + (size_t)(s * 32 + 2 * pr) * 512, lane); load_row(v[1], x + (size_t)(s * 32 + 2 * pr + 1) * 512, lane);
  ln_rows<2>(v, y);
  store_img(g_h[0][s], 2 * pr, y[0], lane); store_img(g_h[0][s], 2 * pr + 1, y[1], lane);
}
__device__ __forceinline__ float load_wr(uint32_t* wv, const bf16* wr, int lane) {
  load_row(wv, wr, lane);
  float wsum = 0.f;
#pragma unroll
  for (int i = 0; i < 8; i++) wsum += blo(wv[i]) + bhi(wv[i]);
#pragma unroll
  for (int o = 16; o > 0; o >>= 1) wsum += __shfl_xor_sync(~0u, wsum, o);
  return wsum;
}

template <bool FAST>
__device__ __forceinline__ unsigned long long token_post(int st, int tk, const bf16* res, bf16* dst, bf16* req, unsigned long long best,
                                                         const uint32_t* wv, float wsum, uint32_t E, int lane) {
  const int s = tk >> 5;
  uint32_t x[8];
  load_row(x, res, lane);
  wait_hint(&f_acc[st][s * 8], E * 32u);
  if (tk == s * 32 && st == 0 && lane == 0) TSTAMP(4, s, 0);
  {
    const uint8_t* pp = g_pp[st][s % PRING] + (lane >> 4) * 8192 + (tk & 31) * 256 + (((lane & 15) ^ (tk & 7)) << 4);
    const uint32_t tag = ptag(s);
    uint4 q[8][2];
#define PLD(k, h) q[k][h] = ld_rlx128<(k) * 32768 + (h) * 16384>(pp)
#define PLD8(h) PLD(0, h); PLD(1, h); PLD(2, h); PLD(3, h); PLD(4, h); PLD(5, h); PLD(6, h); PLD(7, h)
#define PBAD(h) __any_sync(~0u, (or3(xo2(q[0][h].x, q[1][h].x, tag), xo2(q[2][h].x, q[3][h].x, tag), xo2(q[4][h].x, q[5][h].x, tag)) | xo2(q[6][h].x, q[7][h].x, tag)) & ~lane & 1u)
#define PAIR(k, h, m) add2(q[k][h].m, q[(k) + 4][h].m)
#define PSUM(f, h, m) (((f(q[0][h].m) + f(q[1][h].m)) + (f(q[2][h].m) + f(q[3][h].m))) + ((f(q[4][h].m) + f(q[5][h].m)) + (f(q[6][h].m) + f(q[7][h].m))))
#define PADD(i, h, m) if (!(PH_ & (FAST ? 1 : 2))) x[i] = add2(x[i], pack2(PSUM(blo, h, m), PSUM(bhi, h, m))); else \
                      { const uint32_t a = PAIR(0, h, m), b = PAIR(1, h, m), c = PAIR(2, h, m), d = PAIR(3, h, m); \
                        x[i] = add2(x[i], pack2((blo(a) + blo(b)) + (blo(c) + blo(d)), (bhi(a) + bhi(b)) + (bhi(c) + bhi(d)))); }
    int guard = 0;
    PLD8(0);
    if (FAST) { PLD8(1); }
    while (PBAD(0)) { if (++guard > (1 << 20)) TRAP(); PLD8(0); }
    PADD(0, 0, x); PADD(1, 0, y); PADD(2, 0, z); PADD(3, 0, w);
    if (!FAST) { PLD8(1); }
    while (PBAD(1)) { if (++guard > (1 << 20)) TRAP(); PLD8(1); }
    PADD(4, 1, x); PADD(5, 1, y); PADD(6, 1, z); PADD(7, 1, w);
  }
  const float c = blo(__shfl_sync(~0u, x[0], 0));
  float s0 = 0.f, s1 = 0.f, q0 = 0.f, q1 = 0.f, r0 = 0.f, r1 = 0.f;
#pragma unroll
  for (int i = 0; i < 8; i++) {
    const float a = blo(x[i]) - c, b = bhi(x[i]) - c;
    s0 += a; s1 += b; q0 = fmaf(a, a, q0); q1 = fmaf(b, b, q1); r0 = fmaf(a, blo(wv[i]), r0); r1 = fmaf(b, bhi(wv[i]), r1);
  }
  s0 += s1; q0 += q1; r0 += r1;
#pragma unroll
  for (int o = 16; o > 0; o >>= 1) { s0 += __shfl_xor_sync(~0u, s0, o); q0 += __shfl_xor_sync(~0u, q0, o); r0 += __shfl_xor_sync(~0u, r0, o); }
  const float dm = s0 * (1.f / 512.f), m = c + dm, var = fmaxf(fmaf(-dm, dm, q0 * (1.f / 512.f)), 0.f);
  const float mb = rbf(m), inv = rcp(rbf(sqrt_fast(rbf(rbf(var) + 1e-5f))));
  const uint32_t nmb = pack2(-mb, -mb);
  const unsigned long long wd = rword(E, tk, fmaf(c - mb, wsum, r0) * inv);
  uint32_t xn[8], x2[8];
#pragma unroll
  for (int i = 0; i < 8; i++) { const uint32_t d = add2(x[i], nmb); xn[i] = pack2(blo(d) * inv, bhi(d) * inv); x2[i] = add2(x[i], xn[i]); }
  if (st == 0) {
    const float mb2 = rbf(fmaf(m - mb, inv, m)), inv2 = rcp(rbf(sqrt_fast(rbf(rbf(var * (1.f + inv) * (1.f + inv)) + 1e-5f))));
    const uint32_t nmb2 = pack2(-mb2, -mb2);
    uint32_t h[8];
#pragma unroll
    for (int i = 0; i < 8; i++) { const uint32_t d2 = add2(x2[i], nmb2); h[i] = pack2(blo(d2) * inv2, bhi(d2) * inv2); }
    store_img(g_h[1][s], tk & 31, h, lane);
  }
  store_row(dst, x2, lane);
  if (wd > best) { store_row(req, xn, lane); store_row(req + 512, x, lane); }
  return wd;
}

__device__ __forceinline__ void ffn_slice(uint32_t sb, const bf16* xn, float* yacc, int t, bool urgent) {
  const int w = t >> 5, g = (t >> 2) & 7;
  if (t == 0 && urgent) sts32(sb + A_BAR + 160, 1);
  { const uint2 u = __ldcg((const uint2*)xn + t); asm volatile("st.shared.v2.u32 [%0], {%1,%2};" :: "r"(sb + A_XN + t * 8), "r"(u.x), "r"(u.y) : "memory"); }
  fence_async_smem();
  bar_sync(4, 128);
  float ga[4], ua[4];
  constexpr uint64_t da = mkdesc(A_WG, 896, 128, 0), db = mkdesc(A_XN, 16, 128, 0);
  wg_fence();
  wgmma_ss8<0, 1, 0>(ga, da, db); wgmma_ss8<0, 1, 0>(ua, da + (A_WU - A_WG) / 16, db);
#pragma unroll
  for (int ks = 1; ks < 32; ks++) { wgmma_ss8<1, 1, 0>(ga, da + ks * 112, db + ks * 2); wgmma_ss8<1, 1, 0>(ua, da + (A_WU - A_WG) / 16 + ks * 112, db + ks * 2); }
  wg_commit(); wg_wait<0>(); reg_fence(ga); reg_fence(ua);
  if ((t & 3) == 0) {
#pragma unroll
    for (int h = 0; h < 2; h++) {
      const float gs = rbf(ga[2 * h]), us = rbf(ua[2 * h]);
      const float v = 16 * w + 8 * h < 56 ? rbf(gs * rcp(1.f + __expf(-gs))) * us : 0.f;
      asm volatile("st.shared.u16 [%0], %1;" :: "r"(sb + A_XN + 1280 + (16 * w + 8 * h + g) * 2), "h"((unsigned short)pack2(v, 0.f)) : "memory");
    }
  }
  fence_async_smem();
  bar_sync(4, 128);
#pragma unroll 1
  for (int j = 0; j < 2; j++) {
    float y[4][4];
    const uint64_t dd = mkdesc(A_WD, 8192, 128, 0) + (uint64_t)(j * 256);
    wg_fence();
#pragma unroll
    for (int m = 0; m < 4; m++) {
      wgmma_ss8<0, 1, 0>(y[m], dd + m * 64, mkdesc(A_XN + 1280, 16, 128, 0));
#pragma unroll
      for (int ks = 1; ks < 4; ks++) wgmma_ss8<1, 1, 0>(y[m], dd + m * 64 + ks * 1024, mkdesc(A_XN + 1280 + ks * 32, 16, 128, 0));
    }
    wg_commit(); wg_wait<0>();
#pragma unroll
    for (int m = 0; m < 4; m++) {
      reg_fence(y[m]);
      if ((t & 3) == 0) { float* o = yacc + j * 256 + m * 64 + 16 * w + g; atomicAdd(o, y[m][0]); atomicAdd(o + 8, y[m][2]); }
    }
  }
  bar_sync(4, 128);
  if (t == 0) { sts32(sb + A_BAR + 160, 0); red_rel((uint32_t*)(yacc + 512), 1); }
  __syncwarp();
}

__device__ __forceinline__ void ffn_finish(int q, const bf16* req, float r, int lane, uint32_t* v) {
  uint32_t xn[8];
  load_row(xn, req, lane); load_row(v, req + 512, lane);
  const float rs = rbf(1.f / (1.f + __expf(-rbf(r))));
  wait_eq((const uint32_t*)&g_y[q][512], 32u);
  float4 y[4];
#pragma unroll
  for (int i = 0; i < 4; i++) y[i] = __ldcg((const float4*)g_y[q] + (i >> 1) * 64 + 2 * lane + (i & 1));
#pragma unroll
  for (int i = 0; i < 4; i++) {
    v[2 * i] = add2(v[2 * i], add2(xn[2 * i], pack2(rbf(y[i].x) * rs, rbf(y[i].y) * rs)));
    v[2 * i + 1] = add2(v[2 * i + 1], add2(xn[2 * i + 1], pack2(rbf(y[i].z) * rs, rbf(y[i].w) * rs)));
  }
}
__device__ __forceinline__ bool route2(int k, int ts, uint32_t E, int lane, unsigned long long& run) {
  unsigned long long m;
  if (k == 0) {
    if (lane < 2) wait_eq(&f_c2[(NSEG - LAG - 2 + lane) * 8], E * 64u);
    __syncwarp();
    const int s1 = min(lane + 32, NSEG - LAG - 1);
    const unsigned long long a = ld_rlxu64(&f_b2[lane < ts ? 0 : 1][lane]), b = ld_rlxu64(&f_b2[s1 < ts ? 0 : 1][s1]);
    m = warp_max<16>(a > b ? a : b);
  } else {
    const int s = NSEG - LAG + k - 1;
    wait_eq(&f_c2[s * 8], E * 64u);
    m = __shfl_sync(~0u, ld_rlxu64(&f_b2[s < ts ? 0 : 1][s]), 0);
  }
  if (k == 0 || m > run) { run = m; return true; }
  return false;
}

__global__ void __launch_bounds__(512, 1) aux_kernel(Params p) {
  extern __shared__ __align__(1024) uint8_t sm[];
  const uint32_t sb = smem_u32(sm);
  if ((sb & 0xFFFFFFu) != SBASE) TRAP();
  const int warp = __shfl_sync(~0u, threadIdx.x >> 5, 0);
  const int cta = blockIdx.x;
  const uint32_t E = __shfl_sync(~0u, *(volatile uint32_t*)&g_epoch + 1, 0);
  const uint32_t bars = sb + A_BAR;

  if (cta < 32) {
    const int cg = cta & 3, kg = cta >> 2;
    if (threadIdx.x == 0) {
      for (int i = 0; i < A_NST; i++) { mbar_init(bars + 8 * i, 1); mbar_init(bars + 64 + 8 * i, 2); }
      mbar_init(bars + 128, 8); mbar_init(bars + 136, 8); mbar_init(bars + 144, 1);
      sts32(bars + 160, 0);
      asm volatile("fence.mbarrier_init.release.cluster;" ::: "memory");
    }
    if (warp < 8) {
      asm volatile("setmaxnreg.inc.sync.aligned.u32 176;");
      const int tid = fresh_tid(), lane = tid & 31;
      uint32_t W[32][4];
      stage_weights(sb + A_WD, p.wo + (size_t)kg * 512 * 512 + cg * 128, 512, tid, 256);
      cp_async_wait();
      bar_sync(1, 256);
      load_frags(W, sb + A_WD, warp >> 2, warp & 3, lane);
      bar_sync(2, 512);
      const uint32_t so = sb + A_STG + ((lane >> 4) * 8 + (lane & 7)) * 256 + (((warp * 2 + ((lane >> 3) & 1)) ^ (lane & 7)) << 4);
      const uint32_t tm = lane < 4 ? 0x00010001u : 0u;
      int stage = 0; uint32_t ph = 0, job = 0;
#pragma unroll 1
      for (int T = 0; T < NSTEP; T++) {
#pragma unroll 1
        for (int k = 0; k < 3; k++) {
          const int st = k == 0 ? 0 : 3 - k, s = st == 0 ? T : T - LAG;
          if (s < 0 || s >= NSEG) continue;
          float d[16];
#pragma unroll
          for (int hh = 0; hh < 4; hh++) {
            mbar_wait(bars + 8 * stage, ph);
            while (uni(lds32(bars + 160))) __nanosleep(100);
            const uint64_t db = mkdesc(A_RING, 512, 128, 0) + (uint64_t)(stage * 512);
            wg_fence();
            if (hh == 0) wgmma_rs32<0, 0>(d, W[0], db); else wgmma_rs32<1, 0>(d, W[hh * 8], db);
#pragma unroll
            for (int ks = 1; ks < 8; ks++) wgmma_rs32<1, 0>(d, W[hh * 8 + ks], db + ks * 64);
            wg_commit();
            if (hh > 0) { wg_wait<1>(); if ((tid & 127) == 0) mbar_arrive(bars + 64 + 8 * (stage == 0 ? A_NST - 1 : stage - 1)); }
            if (++stage == A_NST) { stage = 0; ph ^= 1; }
          }
          mbar_wait(bars + 144, (job & 1) ^ 1);
          wg_wait<0>(); reg_fence(d);
          if ((tid & 127) == 0) mbar_arrive(bars + 64 + 8 * (stage == 0 ? A_NST - 1 : stage - 1));
          if (cta == 0 && tid == 0) TSTAMP(6, T, k);
          const uint32_t tv = tm * ptag(s);
#define TG(i) ((pack2(d[2 * (i)], d[2 * (i) + 1]) & ~tm) | tv)
          stmatrix4_t(so, TG(0), pack2(d[2], d[3]), TG(2), pack2(d[6], d[7]));
          stmatrix4_t(so + 4096, TG(4), pack2(d[10], d[11]), TG(6), pack2(d[14], d[15]));
          fence_async_smem();
          __syncwarp();
          if (lane == 0) mbar_arrive(bars + 128 + 8 * (job & 1));
          job++;
        }
      }
    } else if (warp < 12) {
      asm volatile("setmaxnreg.dec.sync.aligned.u32 120;");
      const int tid = fresh_tid(), lane = tid & 31;
      const int w = warp - 8, t = tid - 256;
#pragma unroll 1
      for (int s = cta + 4; s < NSEG; s += 32) {
#pragma unroll 1
        for (int pr = w; pr < 16; pr += 4) input_ln_pair(p.x, s, pr, lane);
        bar_sync(4, 128);
        if (t == 0) st_rel(&f_h1[s], E);
      }
      bar_sync(2, 512);
      { int guard = 0; while ((ld_rlx(&f_choice[cta * 3][0]) >> 1) != (E & 0x7FFFFFFFu)) { __nanosleep(200); if (++guard > (1 << 22)) TRAP(); } }
#pragma unroll 1
      for (int i = t; i < 512 * 7; i += 128) {
        const int k = i / 7, pc = i % 7;
        cp_async16(sb + A_WG + (k >> 3) * 896 + pc * 128 + (k & 7) * 16, p.wg + (size_t)k * 1792 + cta * 56 + pc * 8);
        cp_async16(sb + A_WU + (k >> 3) * 896 + pc * 128 + (k & 7) * 16, p.wu + (size_t)k * 1792 + cta * 56 + pc * 8);
        cp_async16(sb + A_WD + (i >> 9) * 8192 + (i & 63) * 128 + ((i >> 6) & 7) * 16, p.wd + (size_t)cta * 56 * 512 + i * 8);
      }
      uint32_t wv[8];
      const float wsum = load_wr(wv, p.wr, lane);
      cp_async_wait();
      fence_async_smem();
      wait_eq(&f_zero, E * 32u);
      bar_sync(4, 128);
      const int tj = (cta * 4 + w) & 31, st = 1 + ((cta >> 3) & 1), sq = cta >> 4;
      unsigned long long run = 0, run2 = 0, best = 0, hist = 0;
      uint32_t open = 0;
#pragma unroll 1
      for (int i = 0; i <= NSTEP; i++) {
        int tok = -1; const bf16* req = nullptr;
        if (i < NSEG) {
          const int cd = (int)uni(route_step(i, E, run));
          run = __shfl_sync(~0u, run, 0);
          hist = hist << 8 | (uint32_t)(cd + 1);
          if (cd >= 0) { tok = rtok(run); req = g_req1[tok][0]; }
        } else if (route2(i - NSEG, rtok(run) >> 5, E, lane, run2)) {
          tok = rtok(run2);
          req = g_req2[(tok >> 5) < (rtok(run) >> 5) ? 0 : 1][tok][0];
        }
        tok = __shfl_sync(~0u, tok, 0);
        if (tok >= 0) {
          if (cta == 0 && t == 0) TSTAMP(8, i, 0);
          ffn_slice(sb, req, g_y[i], t, i < NSEG);
          if (cta == 0 && t == 0) TSTAMP(8, i, 1);
        }
        const int s = i - LAG;
        if (s < 0 || i >= NSEG) continue;
        const int cd = (int)((hist >> (8 * LAG)) & 255) - 1;
        if (cd >= 0 && st == 2) best = 0;
        const int ts = rtok(run) >> 5;
        if ((s & 1) == sq) {
          const int tk = s * 32 + tj;
          if (st == 1 ? s < ts || i < NSEG - 1 : s >= ts) {
            if (st == 2 && cd == tj) wait_eq(&f_hc[s], E);
            const unsigned long long wd = token_post<false>(st, tk, st == 2 && cd == tj ? g_x2c[s] : g_x2 + (size_t)tk * 512,
                                                            (st == 2 || s < ts ? p.out : g_n) + (size_t)tk * 512, g_req2[st - 1][tk][0], best, wv, wsum, E, lane);
            best = max(best, wd);
            if (lane == 0) asm volatile("red.relaxed.gpu.global.max.u64 [%0], %1;" :: "l"(&f_b2[st - 1][s]), "l"(wd) : "memory");
            if (st == 1 && s >= ts) open |= 1u << (s >> 1);
          }
          __syncwarp();
          if (lane == 0) red_rel(&f_c2[s * 8], 1);
          __syncwarp();
        }
        if (st == 1) {
          if (i == NSEG - 1 && t == 0 && cta == 0) GSTAMP(1, 0);
#pragma unroll 1
          for (int n = i == NSEG - 1 ? 32 : 2; n > 0 && open; n--) {
            const int s0 = 2 * (__ffs(open) - 1) + sq;
            if (s0 >= ts) break;
            open &= open - 1;
            uint32_t v[8];
            load_row(v, g_n + (size_t)(s0 * 32 + tj) * 512, lane);
            wait_eq(&f_c2[s0 * 8], E * 64u);
            store_row(p.out + (size_t)(s0 * 32 + tj) * 512, v, lane);
          }
          if (i == NSEG - 1) {
            __syncwarp();
            if (lane == 0) red_rel(&f_cp, 1);
            if (t == 0 && cta == 0) GSTAMP(1, 3);
          }
        }
      }
    } else {
      asm volatile("setmaxnreg.dec.sync.aligned.u32 40;");
      const int tid = fresh_tid(), lane = tid & 31;
      const int t = tid - 384, w = warp - 12;
      for (int i = cta * 128 + t; i < (NSTEP + 1) * 544 / 4; i += 4096) ((float4*)&g_y[0][0])[i] = make_float4(0.f, 0.f, 0.f, 0.f);
      bar_sync(3, 128);
      if (t == 0) red_rel(&f_zero, 1);
      bar_sync(2, 512);
      if (w == 0) {
        const int k = lane >> 2, st = k == 0 ? 0 : 3 - k;
        int cnt = 0;
#pragma unroll 1
        for (int T = 0; T < NSTEP; T++) {
          const int s = st == 0 ? T : T - LAG;
          bool todo = lane < 12 && s >= 0 && s < NSEG;
          const int idx = cnt + lane - (T >= NSEG ? 4 : 0);
          const int stage = idx % A_NST; const uint32_t ph = ((idx / A_NST) & 1) ^ 1;
          const uint32_t* fl = &f_o[T][kg][st * 4 + (lane & 3)];
          const uint8_t* src = g_o[st][s % ORING][kg * 4 + (lane & 3)];
          bool ready = false; int guard = 0;
          uint32_t pend = __ballot_sync(~0u, todo);
          cnt += __popc(pend);
          while (pend) {
            if (todo && !ready) ready = ld_rlx(fl) == E;
            const bool go = todo && ready && (lane < A_NST || !((pend >> (lane - A_NST)) & 1)) && mbar_test(bars + 64 + 8 * stage, ph);
            if (go) { mbar_expect(bars + 8 * stage, OLOAD_); bulk_g2s(sb + A_RING + stage * 8192, src, OLOAD_, bars + 8 * stage); todo = false; }
            const uint32_t np = __ballot_sync(~0u, todo);
            if (np == pend) __nanosleep(40);
            pend = np;
            if (++guard > (1 << 22)) TRAP();
          }
          if (cta == 0 && lane == 0) TSTAMP(3, T, 0);
        }
      } else if (w < 3) {
        uint32_t job = 0;
#pragma unroll 1
        for (int T = 0; T < NSTEP; T++) {
#pragma unroll 1
          for (int k = 0; k < 3; k++) {
            const int st = k == 0 ? 0 : 3 - k, s = st == 0 ? T : T - LAG;
            if (s < 0 || s >= NSEG) continue;
            if ((job++ & 1) != w - 1) continue;
            if (s >= PRING && PCHK_) wait_eq(st == 0 ? (const uint32_t*)&f_h2[s - PRING][1] : &f_c2[(s - PRING) * 8], st == 0 ? E * 4u : E * 64u);
            mbar_wait(bars + 128 + 8 * (w - 1), ((job - 1) >> 1) & 1);
            if (cta == 0 && st == 0) TSTAMP(7, s, 0);
            e_s2g(g_pp[st][s % PRING] + cta * 8192, sb + A_STG, PST_);
            asm volatile("cp.async.bulk.commit_group;\n cp.async.bulk.wait_group.read 0;" ::: "memory");
            __syncwarp();
            e_arrive(bars + 144);
            bulk_wait();
            __syncwarp();
            if (lane == 0) asm volatile("red.relaxed.gpu.global.add.u32 [%0], 1;" :: "l"(&f_acc[st][s * 8]) : "memory");
            __syncwarp();
            if (cta == 0 && st == 0) TSTAMP(7, s, 1);
          }
        }
      }
    }
  } else {
    const int tid = fresh_tid(), lane = tid & 31;
    const int qd = cta - 32;
    input_ln_pair(p.x, qd, warp, lane);
    bar_sync(6, 512);
    if (tid == 0) st_rel(&f_h1[qd], E);
    volatile int* bc = (volatile int*)sm;
    if (warp == 15) {
      unsigned long long run = 0;
      wait_eq(&f_zero, E * 32u);
#pragma unroll 1
      for (int s = 0; s < NSEG; s++) {
        const int cd = route_step(s, E, run);
        if (cd >= 0 && qd == (s & 1)) {
          uint32_t v[1][8], h[1][8];
          ffn_finish(s, g_req1[s * 32 + cd][0], rscore(run), lane, v[0]);
          if (lane == 0) TSTAMP(8, s, 2);
          ln_rows<1>(v, h);
#pragma unroll
          for (int i = 0; i < 8; i++) st_rlx64(&g_hc[s][(i >> 2) * 128 + 4 * lane + (i & 3)], h[0][i], E);
          if (lane == 0) TSTAMP(8, s, 3);
          store_row(g_x2c[s], v[0], lane);
          __syncwarp();
          if (lane == 0) st_rel(&f_hc[s], E);
        }
      }
      wait_eq(&f_hc[rtok(run) >> 5], E);
      if (lane == 0) *bc = rtok(run);
      bar_sync(7, 288);
      if (qd == 1) {
        uint32_t v[8];
        const int ts = rtok(run) >> 5;
#pragma unroll 1
        for (int k = 0; k <= LAG; k++) {
          if (route2(k, ts, E, lane, run)) ffn_finish(NSEG + k, g_req2[(rtok(run) >> 5) < ts ? 0 : 1][rtok(run)][0], rscore(run), lane, v);
          if (k == LAG - 1) wait_eq(&f_cp, E * 64u);
        }
        if (lane == 0) GSTAMP(1, 1);
        store_row(p.out + (size_t)rtok(run) * 512, v, lane);
        if (lane == 0) GSTAMP(1, 2);
        asm volatile("griddepcontrol.wait;" ::: "memory");
        if (lane == 0) *(volatile uint32_t*)&g_epoch = E;
      }
    } else if (warp < 8) {
      uint32_t wv[8];
      const float wsum = load_wr(wv, p.wr, lane);
      unsigned long long best = 0;
      int ttok = 0;
#pragma unroll 1
      for (int i = 0; i < NSTEP; i++) {
        const bool last = i >= NSEG;
        if (i == NSEG) { bar_sync(7, 288); ttok = *bc; best = 0; }
        const int s = last ? i - LAG : i, st = !last ? 0 : s < (ttok >> 5) ? 1 : 2;
        const int tk = s * 32 + qd * 8 + warp;
        const unsigned long long wd = token_post<true>(st, tk, !last ? p.x + (size_t)tk * 512 : tk == ttok ? g_x2c[s] : g_x2 + (size_t)tk * 512,
                                                 (last ? p.out : g_x2) + (size_t)tk * 512, last ? g_req2[st - 1][tk][0] : g_req1[tk][0], best, wv, wsum, E, lane);
        best = max(best, wd);
        if (lane == 0) asm volatile("red.relaxed.gpu.global.max.u64 [%0], %1;" :: "l"(last ? &f_b2[st - 1][s] : f_h2[s]), "l"(wd) : "memory");
        bar_sync(5, 256);
        if (tid == 0) { if (qd == 0) TSTAMP(4, i, 1); red_rel(last ? &f_c2[s * 8] : (uint32_t*)(f_h2[s] + 1), last ? 16 : 1); if (qd == 0) TSTAMP(4, i, 2); }
        __syncwarp();
      }
    }
  }
}

}

extern "C" void kernel_launch(void* const* d_in, const int* in_sizes, int n_in, void* d_out, int out_size) {
  (void)in_sizes; (void)n_in; (void)out_size;
  static bool init = false;
  if (!init) {
    cudaFuncSetAttribute(main_kernel, cudaFuncAttributeMaxDynamicSharedMemorySize, M_TOTAL);
    cudaFuncSetAttribute(aux_kernel, cudaFuncAttributeMaxDynamicSharedMemorySize, A_TOTAL);
    init = true;
  }
  Params p;
  p.x = (const bf16*)d_in[0]; p.mem0 = (const bf16*)d_in[1]; p.wq = (const bf16*)d_in[2]; p.wk = (const bf16*)d_in[3];
  p.wv = (const bf16*)d_in[4]; p.wo = (const bf16*)d_in[5]; p.wr = (const bf16*)d_in[8]; p.wg = (const bf16*)d_in[9];
  p.wu = (const bf16*)d_in[10]; p.wd = (const bf16*)d_in[11]; p.out = (bf16*)d_out; p.zero = 0;
  cudaStream_t st = cudaStreamPerThread;
  main_kernel<<<96, 512, M_TOTAL, st>>>(p);
  cudaLaunchConfig_t cfg = {};
  cfg.gridDim = dim3(36); cfg.blockDim = dim3(512); cfg.dynamicSmemBytes = A_TOTAL; cfg.stream = st;
  cudaLaunchAttribute at[1];
  at[0].id = cudaLaunchAttributeProgrammaticStreamSerialization; at[0].val.programmaticStreamSerializationAllowed = 1;
  cfg.attrs = at; cfg.numAttrs = 1;
  cudaLaunchKernelEx(&cfg, aux_kernel, p);
}
```

```cpp
#include <cuda_runtime.h>
#include <cuda_bf16.h>
#include <stdint.h>

namespace {

typedef __nv_bfloat16 bf16;

constexpr int NSEG = 64;
#define LAG_ 5
constexpr int LAG = LAG_;
constexpr int NSTEP = NSEG + LAG;
constexpr int ORING = 8, PRING = 4;
#define E1_ 10
#define E2_ 0
#define E3_ 10
constexpr int E1 = E1_, E2 = E2_, E3 = E3_, EA = E1 + E2 + E3;
static_assert(EA % 4 == 0 && EA > 0 && EA < 32 && E1 > 0, "early part: whole 64-column chunks");
#define RW_ 176
#define RA_ 136
#define RC_ 24
#define STR2(x) #x
#define STR(x) STR2(x)
#define RED_ 30
#define ARR_ 7
#define HADD_ 1
#define PAUSE_ 21
#define PD1_ 3
#define PD2_ 7
#define DPOLL_ 0
#define SALT_ 0
#define KP1_ 1
#define EARLY_ 1
#define PRIV_ 1
#define OLOAD_ 8192
#define PST_ 8192
#define PCHK_ 1
#define ALT_ 1
#define PH_ 0
#define TQ_ 1
#define NOF_ 2
#define HAND_ 4
#define GO3_ 2
#define NPROBE_ 6
#define TP(i, v) (v)
#define XDLY_ TP(0, 2300)
#define YDLY_ TP(1, 3550)
#define X1_ TP(2, 100)
#define X2_ TP(3, 250)
#define Y1_ TP(4, 100)
#define Y2_ TP(5, 200)
#define HGAP_ TP(6, 50)
#define TGAP_ TP(7, 100)
#define ADLY_ TP(8, 600)
#define ODLY_ TP(9, 2700)
#define LDLY_ TP(10, 3800)
#define LGAP_ 200
#define HDLY_ TP(11, 0)
#define TDLY_ TP(15, 4200)
#define SDLY_ TP(12, 800)
#define AGAP_ TP(13, 100)
#define KDLY_ TP(14, 300)
__device__ uint32_t g_epoch;
__device__ __align__(1024) uint8_t g_h[2][NSEG][32768];
__device__ __align__(128) uint2 g_hc[NSEG][256];
__device__ __align__(128) bf16 g_x2[2048 * 512];
__device__ __align__(128) bf16 g_x2c[NSEG][512];
__device__ __align__(128) uint8_t g_o[3][ORING][32][8192];
__device__ __align__(128) uint8_t g_pp[3][PRING][8 * 32768];
__device__ __align__(128) bf16 g_n[2048 * 512];
__device__ __align__(128) uint8_t g_xch[96 * 16384 + 65536 + 8192];
__device__ __align__(128) bf16 g_req1[2048][2][512];
__device__ __align__(128) bf16 g_req2[2][2048][2][512];
__device__ __align__(128) float g_y[NSTEP + 1][512 + 32];
__device__ __align__(128) uint8_t g_tok[96][2][16384];
__device__ uint32_t f_choice[96][2];
__device__ uint32_t f_h1[NSEG], f_hc[NSEG];
__device__ __align__(128) unsigned long long f_h2[NSEG][16];
__device__ __align__(128) unsigned long long f_b2[2][NSEG];
__device__ uint32_t f_c2[NSEG * 8];
__device__ __align__(128) uint32_t f_o[NSTEP][8][16];
__device__ uint32_t f_acc[3][NSEG * 8];
__device__ uint32_t f_zero, f_cp;
__device__ __align__(128) unsigned long long g_sync[2][96];

#define TRAP() __trap()
__device__ __forceinline__ uint32_t smem_u32(const void* p) { return (uint32_t)__cvta_generic_to_shared(p); }
__device__ __forceinline__ int fresh_tid() { const int t = threadIdx.x; return __shfl_sync(~0u, t, t & 31); }
__device__ __forceinline__ unsigned long long gtime64() { unsigned long long t; asm volatile("mov.u64 %0, %%globaltimer;" : "=l"(t) :: "memory"); return t; }
__device__ __forceinline__ uint32_t clk() { unsigned long long c; asm volatile("mov.u64 %0, %%clock64;" : "=l"(c) :: "memory"); return (uint32_t)c; }
__device__ __forceinline__ void wait_until(uint32_t t) {
  while ((int)(t - clk()) > 450) __nanosleep(32);
  uint32_t c;
  do { asm volatile("mov.u32 %0, %%clock;" : "=r"(c) :: "memory"); } while ((int)(c - t) < 0);
}
__device__ __forceinline__ void mbar_init(uint32_t bar, uint32_t cnt) { asm volatile("mbarrier.init.shared::cta.b64 [%0], %1;" :: "r"(bar), "r"(cnt) : "memory"); }
__device__ __forceinline__ void mbar_arrive(uint32_t bar) { asm volatile("mbarrier.arrive.shared::cta.b64 _, [%0];" :: "r"(bar) : "memory"); }
__device__ __forceinline__ void mbar_arrive_remote(uint32_t bar) { asm volatile("mbarrier.arrive.relaxed.cluster.shared::cluster.b64 _, [%0];" :: "r"(bar) : "memory"); }
__device__ __forceinline__ void mbar_expect(uint32_t bar, uint32_t bytes) { asm volatile("mbarrier.arrive.expect_tx.shared::cta.b64 _, [%0], %1;" :: "r"(bar), "r"(bytes) : "memory"); }
__device__ __forceinline__ bool mbar_try(uint32_t bar, uint32_t parity) {
  uint32_t ok;
  asm volatile("{.reg .pred p; mbarrier.try_wait.parity.shared::cta.b64 p, [%1], %2; selp.u32 %0, 1, 0, p;}" : "=r"(ok) : "r"(bar), "r"(parity) : "memory");
  return ok;
}
__device__ __forceinline__ bool mbar_test(uint32_t bar, uint32_t parity) {
  uint32_t ok;
  asm volatile("{.reg .pred p; mbarrier.test_wait.parity.shared::cta.b64 p, [%1], %2; selp.u32 %0, 1, 0, p;}" : "=r"(ok) : "r"(bar), "r"(parity) : "memory");
  return ok;
}
__device__ __forceinline__ void mbar_wait(uint32_t bar, uint32_t parity) {
  asm volatile("{\n.reg .pred p;\nWAIT:\nmbarrier.try_wait.parity.shared::cta.b64 p, [%0], %1;\n@!p bra WAIT;\n}" :: "r"(bar), "r"(parity) : "memory");
}
__device__ __forceinline__ uint32_t ld_acq(const uint32_t* p) { uint32_t v; asm volatile("ld.acquire.gpu.global.u32 %0, [%1];" : "=r"(v) : "l"(p) : "memory"); return v; }
__device__ __forceinline__ unsigned long long ld_acq64(const unsigned long long* p) { unsigned long long v; asm volatile("ld.acquire.gpu.global.u64 %0, [%1];" : "=l"(v) : "l"(p) : "memory"); return v; }
__device__ __forceinline__ void st_rel(uint32_t* p, uint32_t v) { asm volatile("st.release.gpu.global.u32 [%0], %1;" :: "l"(p), "r"(v) : "memory"); }
__device__ __forceinline__ void st_rel64(unsigned long long* p, unsigned long long v) { asm volatile("st.release.gpu.global.u64 [%0], %1;" :: "l"(p), "l"(v) : "memory"); }
__device__ __forceinline__ void red_rel(uint32_t* p, uint32_t v) { asm volatile("red.release.gpu.global.add.u32 [%0], %1;" :: "l"(p), "r"(v) : "memory"); }
__device__ __forceinline__ uint32_t ld_rlx(const uint32_t* p) { uint32_t v; asm volatile("ld.relaxed.gpu.global.u32 %0, [%1];" : "=r"(v) : "l"(p) : "memory"); return v; }
__device__ __forceinline__ unsigned long long ld_rlxu64(const unsigned long long* p) { unsigned long long v; asm volatile("ld.relaxed.gpu.global.u64 %0, [%1];" : "=l"(v) : "l"(p) : "memory"); return v; }
__device__ __forceinline__ void st_rlx(uint32_t* p, uint32_t v) { asm volatile("st.relaxed.gpu.global.u32 [%0], %1;" :: "l"(p), "r"(v) : "memory"); }
__device__ __forceinline__ void bulk_wait() { asm volatile("cp.async.bulk.commit_group;\n cp.async.bulk.wait_group 0;" ::: "memory"); }
__device__ __forceinline__ void fence_acq() { asm volatile("fence.acquire.gpu;" ::: "memory"); }
__device__ __forceinline__ void wait_hint(const uint32_t* p, uint32_t v) {
  int guard = 0;
  while (ld_rlx(p) != v) { __nanosleep(32); if (++guard > (1 << 22)) TRAP(); }
}
__device__ __forceinline__ void wait_eq(const uint32_t* p, uint32_t v) {
  int guard = 0;
  while (ld_rlx(p) != v) { __nanosleep(64); if (++guard > (1 << 22)) TRAP(); }
  fence_acq();
}
__device__ __forceinline__ unsigned long long rword(uint32_t E, int tok, float r) {
  uint32_t u = __float_as_uint(r + 0.f);
  u = r != r ? 0u : (u >> 31) ? ~u : u | 0x80000000u;
  return (unsigned long long)E << 43 | (unsigned long long)u << 11 | (uint32_t)(2047 - tok);
}
__device__ __forceinline__ int rtok(unsigned long long v) { return 2047 - (int)(v & 2047u); }
__device__ __forceinline__ float rscore(unsigned long long v) { const uint32_t u = (uint32_t)(v >> 11); return __uint_as_float((u >> 31) ? u & 0x7fffffffu : ~u); }
__device__ __forceinline__ bool rfresh(unsigned long long v, uint32_t E) { return (uint32_t)(v >> 43) == (E & 0x1FFFFFu); }
template <int TOP> __device__ __forceinline__ unsigned long long warp_max(unsigned long long v) {
#pragma unroll
  for (int o = TOP; o > 0; o >>= 1) { const unsigned long long ov = __shfl_xor_sync(~0u, v, o); v = ov > v ? ov : v; }
  return v;
}
template <int off> __device__ __forceinline__ uint2 ld_rlx64(const void* p) { unsigned long long v; asm volatile("ld.relaxed.gpu.global.b64 %0, [%1+%2];" : "=l"(v) : "l"(p), "n"(off) : "memory"); return make_uint2((uint32_t)v, (uint32_t)(v >> 32)); }
template <int off> __device__ __forceinline__ uint4 ld_rlx128(const void* p) {
  unsigned long long a, b; asm volatile("ld.relaxed.gpu.global.v2.b64 {%0,%1}, [%2+%3];" : "=l"(a), "=l"(b) : "l"(p), "n"(off) : "memory");
  return make_uint4((uint32_t)a, (uint32_t)(a >> 32), (uint32_t)b, (uint32_t)(b >> 32));
}
__device__ __forceinline__ void st_rlx64(void* p, uint32_t lo, uint32_t hi) { asm volatile("{.reg .b64 t; mov.b64 t, {%1,%2}; st.relaxed.gpu.global.b64 [%0], t;}" :: "l"(p), "r"(lo), "r"(hi) : "memory"); }
__device__ __forceinline__ void cp_async16(uint32_t dst, const void* src) { asm volatile("cp.async.cg.shared.global [%0], [%1], 16;" :: "r"(dst), "l"(src) : "memory"); }
__device__ __forceinline__ void cp_async_wait() { asm volatile("cp.async.wait_all;" ::: "memory"); }
__device__ __forceinline__ void fence_async_smem() { asm volatile("fence.proxy.async.shared::cta;" ::: "memory"); }
__device__ __forceinline__ void fence_async_glob() { asm volatile("fence.proxy.async.global;" ::: "memory"); }
__device__ __forceinline__ void fence_async_acq() { asm volatile("fence.proxy.async::generic.acquire.sync_restrict::shared::cluster.cluster;" ::: "memory"); }
__device__ __forceinline__ float ex2(float x) { float y; asm("ex2.approx.ftz.f32 %0, %1;" : "=f"(y) : "f"(x)); return y; }
__device__ __forceinline__ float sqrt_fast(float x) { float y; asm("sqrt.approx.ftz.f32 %0, %1;" : "=f"(y) : "f"(x)); return y; }
__device__ __forceinline__ float rcp(float x) { float y; asm("rcp.approx.ftz.f32 %0, %1;" : "=f"(y) : "f"(x)); return y; }
__device__ __forceinline__ void bar_sync(int id, int n) { asm volatile("bar.sync %0, %1;" :: "r"(id), "r"(n) : "memory"); }
__device__ __forceinline__ bool bar_or(int id, int n, bool v) {
  uint32_t r;
  asm volatile("{.reg .pred p, q; setp.ne.u32 p, %3, 0; barrier.cta.red.or.aligned.pred q, %1, %2, p; selp.u32 %0, 1, 0, q;}" : "=r"(r) : "r"(id), "r"(n), "r"((uint32_t)v) : "memory");
  return r;
}
__device__ __forceinline__ uint32_t mapa(uint32_t a, uint32_t rank) { uint32_t r; asm volatile("mapa.shared::cluster.u32 %0, %1, %2;" : "=r"(r) : "r"(a), "r"(rank)); return r; }
__device__ __forceinline__ void cluster_sync() { asm volatile("barrier.cluster.arrive.release.aligned; barrier.cluster.wait.acquire.aligned;" ::: "memory"); }
__device__ __forceinline__ void st_async32(uint32_t dst, uint32_t v, uint32_t bar) { asm volatile("st.async.shared::cluster.mbarrier::complete_tx::bytes.b32 [%0], %1, [%2];" :: "r"(dst), "r"(v), "r"(bar) : "memory"); }
__device__ __forceinline__ void bulk_g2s(uint32_t dst, const void* src, uint32_t bytes, uint32_t bar) {
  asm volatile("cp.async.bulk.shared::cluster.global.mbarrier::complete_tx::bytes [%0], [%1], %2, [%3];" :: "r"(dst), "l"(src), "r"(bytes), "r"(bar) : "memory");
}
__device__ __forceinline__ void bulk_g2s_mc(uint32_t dst, const void* src, uint32_t bytes, uint32_t bar, uint16_t mask) {
  asm volatile("cp.async.bulk.shared::cluster.global.mbarrier::complete_tx::bytes.multicast::cluster [%0], [%1], %2, [%3], %4;"
               :: "r"(dst), "l"(src), "r"(bytes), "r"(bar), "h"(mask) : "memory");
}
__device__ __forceinline__ void bulk_s2c(uint32_t dst, uint32_t src, uint32_t bytes, uint32_t bar) {
  asm volatile("cp.async.bulk.shared::cluster.shared::cta.mbarrier::complete_tx::bytes [%0], [%1], %2, [%3];" :: "r"(dst), "r"(src), "r"(bytes), "r"(bar) : "memory");
}
__device__ __forceinline__ void bulk_s2g(void* dst, uint32_t src, uint32_t bytes) {
  asm volatile("cp.async.bulk.global.shared::cta.bulk_group [%0], [%1], %2;" :: "l"(dst), "r"(src), "r"(bytes) : "memory");
}
#define ELECT(op) "{.reg .pred p; elect.sync _|p, 0xffffffff; @p " op "}"
__device__ __forceinline__ void e_arrive(uint32_t bar) { asm volatile(ELECT("mbarrier.arrive.shared::cta.b64 _, [%0];") :: "r"(bar) : "memory"); }
__device__ __forceinline__ void e_expect(uint32_t bar, uint32_t bytes) { asm volatile(ELECT("mbarrier.arrive.expect_tx.shared::cta.b64 _, [%0], %1;") :: "r"(bar), "r"(bytes) : "memory"); }
__device__ __forceinline__ void e_g2s(uint32_t dst, const void* src, uint32_t bytes, uint32_t bar) {
  asm volatile(ELECT("cp.async.bulk.shared::cluster.global.mbarrier::complete_tx::bytes [%0], [%1], %2, [%3];") :: "r"(dst), "l"(src), "r"(bytes), "r"(bar) : "memory");
}
__device__ __forceinline__ void e_mc(uint32_t dst, const void* src, uint32_t bytes, uint32_t bar, uint16_t mask) {
  asm volatile(ELECT("cp.async.bulk.shared::cluster.global.mbarrier::complete_tx::bytes.multicast::cluster [%0], [%1], %2, [%3], %4;")
               :: "r"(dst), "l"(src), "r"(bytes), "r"(bar), "h"(mask) : "memory");
}
__device__ __forceinline__ void e_s2g(void* dst, uint32_t src, uint32_t bytes) {
  asm volatile(ELECT("cp.async.bulk.global.shared::cta.bulk_group [%0], [%1], %2;") :: "l"(dst), "r"(src), "r"(bytes) : "memory");
}
__device__ __forceinline__ void e_st_rel(uint32_t* p, uint32_t v) { asm volatile(ELECT("st.release.gpu.global.u32 [%0], %1;") :: "l"(p), "r"(v) : "memory"); }
__device__ __forceinline__ uint32_t clk32() { uint32_t c; asm volatile("mov.u32 %0, %%clock;" : "=r"(c) :: "memory"); return c; }
__device__ __forceinline__ void spin_until(uint32_t t) { while ((int)(clk32() - t) < 0) {} }
__device__ __forceinline__ uint32_t uni(uint32_t v) { return __shfl_sync(~0u, v, 0); }
__device__ __forceinline__ uint32_t pack2(float lo, float hi) { uint32_t r; asm("cvt.rn.bf16x2.f32 %0, %1, %2;" : "=r"(r) : "f"(hi), "f"(lo)); return r; }
__device__ __forceinline__ uint32_t add2(uint32_t a, uint32_t b) { uint32_t r; asm("add.rn.bf16x2 %0, %1, %2;" : "=r"(r) : "r"(a), "r"(b)); return r; }
__device__ __forceinline__ float rbf(float x) { return __bfloat162float(__float2bfloat16_rn(x)); }
__device__ __forceinline__ float blo(uint32_t u) { return __uint_as_float(u << 16); }
__device__ __forceinline__ float bhi(uint32_t u) { return __uint_as_float(u & 0xffff0000u); }
__device__ __forceinline__ uint32_t gentag(uint32_t g) { return (g & 1u) | (g & 2u) << 15; }
__device__ __forceinline__ uint32_t pack2_tag(float lo, float hi, uint32_t tag) {
  const uint32_t u = __byte_perm(__float_as_uint(lo), __float_as_uint(hi), 0x7632);
  return u + ((u ^ tag) & 0x10001u);
}
__device__ __forceinline__ uint32_t xo2(uint32_t a, uint32_t b, uint32_t t) { uint32_t r; asm("lop3.b32 %0, %1, %2, %3, 0x7e;" : "=r"(r) : "r"(a), "r"(b), "r"(t)); return r; }
__device__ __forceinline__ uint32_t or3(uint32_t a, uint32_t b, uint32_t c) { uint32_t r; asm("lop3.b32 %0, %1, %2, %3, 0xfe;" : "=r"(r) : "r"(a), "r"(b), "r"(c)); return r; }
__device__ __forceinline__ void stmatrix4(uint32_t a, uint32_t r0, uint32_t r1, uint32_t r2, uint32_t r3) {
  asm volatile("stmatrix.sync.aligned.m8n8.x4.shared.b16 [%0], {%1,%2,%3,%4};" :: "r"(a), "r"(r0), "r"(r1), "r"(r2), "r"(r3) : "memory");
}
__device__ __forceinline__ void stmatrix4_t(uint32_t a, uint32_t r0, uint32_t r1, uint32_t r2, uint32_t r3) {
  asm volatile("stmatrix.sync.aligned.m8n8.x4.trans.shared.b16 [%0], {%1,%2,%3,%4};" :: "r"(a), "r"(r0), "r"(r1), "r"(r2), "r"(r3) : "memory");
}
__device__ __forceinline__ void ldmatrix4_t(uint32_t* r, uint32_t a) {
  asm volatile("ldmatrix.sync.aligned.m8n8.x4.trans.shared.b16 {%0,%1,%2,%3}, [%4];" : "=r"(r[0]), "=r"(r[1]), "=r"(r[2]), "=r"(r[3]) : "r"(a) : "memory");
}
__device__ __forceinline__ void ldmatrix4(uint32_t* r, uint32_t a) {
  asm volatile("ldmatrix.sync.aligned.m8n8.x4.shared.b16 {%0,%1,%2,%3}, [%4];" : "=r"(r[0]), "=r"(r[1]), "=r"(r[2]), "=r"(r[3]) : "r"(a) : "memory");
}
__device__ __forceinline__ void hmma16(float* c, const uint32_t* a, uint32_t b0, uint32_t b1) {
  asm volatile("mma.sync.aligned.m16n8k16.row.col.f32.bf16.bf16.f32 {%0,%1,%2,%3}, {%4,%5,%6,%7}, {%8,%9}, {%0,%1,%2,%3};"
               : "+f"(c[0]), "+f"(c[1]), "+f"(c[2]), "+f"(c[3]) : "r"(a[0]), "r"(a[1]), "r"(a[2]), "r"(a[3]), "r"(b0), "r"(b1));
}
__device__ __forceinline__ void hmma8(float* c, uint32_t a0, uint32_t a1, uint32_t b0) {
  asm volatile("mma.sync.aligned.m16n8k8.row.col.f32.bf16.bf16.f32 {%0,%1,%2,%3}, {%4,%5}, {%6}, {%0,%1,%2,%3};"
               : "+f"(c[0]), "+f"(c[1]), "+f"(c[2]), "+f"(c[3]) : "r"(a0), "r"(a1), "r"(b0));
}
__device__ __forceinline__ uint4 lds128(uint32_t a) { uint4 v; asm volatile("ld.shared.v4.u32 {%0,%1,%2,%3}, [%4];" : "=r"(v.x), "=r"(v.y), "=r"(v.z), "=r"(v.w) : "r"(a) : "memory"); return v; }
__device__ __forceinline__ void sts128(uint32_t a, uint4 v) { asm volatile("st.shared.v4.u32 [%0], {%1,%2,%3,%4};" :: "r"(a), "r"(v.x), "r"(v.y), "r"(v.z), "r"(v.w) : "memory"); }
__device__ __forceinline__ void sts128f(uint32_t a, float x, float y, float z, float w) { asm volatile("st.shared.v4.f32 [%0], {%1,%2,%3,%4};" :: "r"(a), "f"(x), "f"(y), "f"(z), "f"(w) : "memory"); }
__device__ __forceinline__ void sts64f(uint32_t a, float x, float y) { asm volatile("st.shared.v2.f32 [%0], {%1,%2};" :: "r"(a), "f"(x), "f"(y) : "memory"); }
__device__ __forceinline__ uint32_t lds32(uint32_t a) { uint32_t v; asm volatile("ld.shared.u32 %0, [%1];" : "=r"(v) : "r"(a) : "memory"); return v; }
__device__ __forceinline__ void sts32(uint32_t a, uint32_t v) { asm volatile("st.shared.u32 [%0], %1;" :: "r"(a), "r"(v) : "memory"); }

constexpr uint32_t SBASE = 1024;
__host__ __device__ constexpr uint64_t mkdesc(uint32_t off, uint32_t lbo, uint32_t sbo, uint32_t swz) {
  return (uint64_t)(((SBASE + off) & 0x3FFFF) >> 4) | ((uint64_t)(lbo >> 4) << 16) | ((uint64_t)(sbo >> 4) << 32) | ((uint64_t)swz << 62);
}
__device__ __forceinline__ void wg_fence() { asm volatile("wgmma.fence.sync.aligned;" ::: "memory"); }
__device__ __forceinline__ void wg_commit() { asm volatile("wgmma.commit_group.sync.aligned;" ::: "memory"); }
template <int N> __device__ __forceinline__ void wg_wait() { asm volatile("wgmma.wait_group.sync.aligned %0;" :: "n"(N) : "memory"); }

template <int N> __device__ __forceinline__ void reg_fence(float (&d)[N], int n = N) {
#pragma unroll
  for (int i = 0; i < N; i++) if (i < n) asm volatile("" : "+f"(d[i]) :: "memory");
}
#define F4(b) "+f"(d[b]), "+f"(d[b + 1]), "+f"(d[b + 2]), "+f"(d[b + 3])
#define F8(b) F4(b), F4(b + 4)
#define F16(b) F8(b), F8(b + 8)
#define G4(b) "=f"(d[b]), "=f"(d[b + 1]), "=f"(d[b + 2]), "=f"(d[b + 3])
#define G8(b) G4(b), G4(b + 4)
#define G16(b) G8(b), G8(b + 8)
#define RS_IN "r"(a[0]), "r"(a[1]), "r"(a[2]), "r"(a[3]), "l"(db), "n"(SD), "n"(TB)
#define SS_IN "l"(da), "l"(db), "n"(SD), "n"(TA), "n"(TB)
#define WG_OP(str, out0, out1, in) do { if (SD || KEEP) asm volatile(str : out1 : in); else asm volatile(str : out0 : in); } while (0)
#define O12(X) X##8(0), X##4(8)
#define O20(X) X##16(0), X##4(16)
#define O32(X) X##16(0), X##16(16)
template <int SD, int TB, int KEEP = 0> __device__ __forceinline__ void wgmma_rs24(float* d, const uint32_t* a, uint64_t db) {
  WG_OP("wgmma.mma_async.sync.aligned.m64n24k16.f32.bf16.bf16 {%0,%1,%2,%3,%4,%5,%6,%7,%8,%9,%10,%11}, {%12,%13,%14,%15}, %16, %17, 1, 1, %18;", O12(G), O12(F), RS_IN);
}
template <int SD, int TB, int KEEP = 0> __device__ __forceinline__ void wgmma_rs32(float* d, const uint32_t* a, uint64_t db) {
  WG_OP("wgmma.mma_async.sync.aligned.m64n32k16.f32.bf16.bf16 {%0,%1,%2,%3,%4,%5,%6,%7,%8,%9,%10,%11,%12,%13,%14,%15}, {%16,%17,%18,%19}, %20, %21, 1, 1, %22;", G16(0), F16(0), RS_IN);
}
template <int SD, int TB, int KEEP = 0> __device__ __forceinline__ void wgmma_rs40(float* d, const uint32_t* a, uint64_t db) {
  WG_OP("wgmma.mma_async.sync.aligned.m64n40k16.f32.bf16.bf16 {%0,%1,%2,%3,%4,%5,%6,%7,%8,%9,%10,%11,%12,%13,%14,%15,"
        "%16,%17,%18,%19}, {%20,%21,%22,%23}, %24, %25, 1, 1, %26;", O20(G), O20(F), RS_IN);
}
template <int SD, int TB, int KEEP = 0> __device__ __forceinline__ void wgmma_rs64(float* d, const uint32_t* a, uint64_t db) {
  WG_OP("wgmma.mma_async.sync.aligned.m64n64k16.f32.bf16.bf16 {%0,%1,%2,%3,%4,%5,%6,%7,%8,%9,%10,%11,%12,%13,%14,%15,"
        "%16,%17,%18,%19,%20,%21,%22,%23,%24,%25,%26,%27,%28,%29,%30,%31}, {%32,%33,%34,%35}, %36, %37, 1, 1, %38;", O32(G), O32(F), RS_IN);
}
template <int SD, int TA, int TB, int KEEP = 0> __device__ __forceinline__ void wgmma_ss24(float* d, uint64_t da, uint64_t db) {
  WG_OP("wgmma.mma_async.sync.aligned.m64n24k16.f32.bf16.bf16 {%0,%1,%2,%3,%4,%5,%6,%7,%8,%9,%10,%11}, %12, %13, %14, 1, 1, %15, %16;", O12(G), O12(F), SS_IN);
}
template <int SD, int TA, int TB, int KEEP = 0> __device__ __forceinline__ void wgmma_ss8(float* d, uint64_t da, uint64_t db) {
  WG_OP("wgmma.mma_async.sync.aligned.m64n8k16.f32.bf16.bf16 {%0,%1,%2,%3}, %4, %5, %6, 1, 1, %7, %8;", G4(0), F4(0), SS_IN);
}
__device__ __forceinline__ void bar_arrive(int id, int n) { asm volatile("bar.arrive %0, %1;" :: "r"(id), "r"(n) : "memory"); }
__device__ __forceinline__ uint32_t vis_bits(int pos, int t) {
  uint32_t m = 0;
#pragma unroll
  for (int i = 0; i < 8; i++) m |= (8 * (i / 2 + 1) + 2 * t + (i & 1) <= pos) ? 1u << i : 0u;
  return m;
}

__device__ __forceinline__ int route_step(int s, uint32_t E, unsigned long long& run) {
  int guard = 0; unsigned long long m, n;
  for (;;) {
    asm volatile("ld.relaxed.gpu.global.v2.b64 {%0,%1}, [%2];" : "=l"(m), "=l"(n) : "l"(f_h2[s]) : "memory");
    if ((uint32_t)n == E * 4u) break;
    __nanosleep(40);
    if (++guard > (1 << 22)) TRAP();
  }
  fence_acq();
  if (s == 0 || m > run) { run = m; return rtok(m) & 31; }
  return -1;
}

struct Params {
  const bf16 *x, *mem0, *wq, *wk, *wv, *wo, *wr, *wg, *wu, *wd;
  bf16* out;
  uint32_t zero2;
  unsigned long long zero;
};

constexpr uint32_t WSTG_STRIDE = 272;
__device__ __forceinline__ void stage_weights(uint32_t stg, const bf16* src, int ld, int tid, int nthr) {
  for (int i = tid; i < 512 * 16; i += nthr) {
    int k = i >> 4, c = i & 15;
    cp_async16(stg + k * WSTG_STRIDE + c * 16, src + (size_t)k * ld + c * 8);
  }
}
__device__ __forceinline__ void load_frags(uint32_t (*W)[4], uint32_t stg, int wg, int w, int lane) {
  uint32_t a = stg + ((lane >> 4) * 8 + (lane & 7)) * WSTG_STRIDE + (64 * wg + 16 * w + ((lane >> 3) & 1) * 8) * 2;
#pragma unroll
  for (int ks = 0; ks < 32; ks++) ldmatrix4_t(W[ks], a + ks * 16 * WSTG_STRIDE);
}

constexpr uint32_t M_H = 0;
constexpr uint32_t M_MEM = 65536;
constexpr uint32_t M_Q = M_MEM + 24576;
constexpr uint32_t M_K = M_Q + 12288;
constexpr uint32_t M_V = M_K + 12288;
constexpr uint32_t M_OM = M_V + 12288;
constexpr uint32_t M_OST = M_OM + 6144;
constexpr uint32_t M_TST = M_OST + 8192;
constexpr uint32_t M_WO = M_TST + 16384;
constexpr uint32_t M_M0 = M_WO + 49152;
constexpr uint32_t M_PT = M_M0 + 2048;
constexpr uint32_t M_BAR = M_PT + 12288;
constexpr uint32_t M_TOTAL = M_BAR + 384;
static_assert(M_TOTAL <= 232448, "main smem");
static_assert(M_WO >= 512 * WSTG_STRIDE, "staging overlaps Wo");
enum { B_LAND = 0  , B_QK = 3, B_V, B_TOK, B_OM, B_HA, B_HB, B_HAE, B_HBE, B_OST, B_OFREE, B_SYNC,
       B_STG, B_STG1, B_SS, B_TFREE, B_KFREE, B_VFREE, B_FIX  , B_NUM = B_FIX + 8 };
static_assert(B_NUM * 8 <= 256, "barriers");
constexpr uint32_t M_CAND = M_BAR + 256;
constexpr uint32_t M_BASE = M_BAR + 272;
constexpr uint32_t M_ZERO = M_BAR + 280;
constexpr uint32_t M_NEAR = M_BAR + 288;
enum { N_GO1 = 2, N_GO2, N_GO3, N_GO4, N_AG, N_W };

#define GSTAMP(slot, i)
#define TSTAMP(slot, i, k)
#define STAMP(i)
#define ASTAMP(i)
#define WSTAMP(i)
#define CSTAMP(i, v)
#define PIN(x) asm volatile("" : "+r"(x))
#define SCHED(k) asm volatile("{\n.reg .pred p;\nsetp.ne.u32 p, %0, 0;\n@p trap;\n}" :: "r"(zz & (1u << (k))) : "memory")
#define HOLD(k, v) asm volatile("{\n.reg .pred p;\nsetp.ne.u32 p, %0, 0;\n@p st.shared.u32 [%0], %1;\n}" :: "r"(zz & (1u << (k))), "r"(v) : "memory")
#define DRAIN(a) (lds32((a) + zz) & zz)
#define BAR(i) (sb + M_BAR + 8 * (i))

__device__ __forceinline__ int probe_near(const uint8_t* p) {
  int best0 = 1 << 30, best1 = 1 << 30; uint32_t v = 0;
#pragma unroll 1
  for (int r = 0; r < NPROBE_; r++) {
    uint32_t t0 = clk();
    asm volatile("atom.relaxed.gpu.global.or.b32 %0, [%1], %2;" : "=r"(v) : "l"(p + (r & 1) * 4096 + 3968), "r"(v & 0u) : "memory");
    if (v == 0x7fffffffu) t0++;
    int d = (int)(clk() - t0);
    if (r & 1) best1 = min(best1, d); else best0 = min(best0, d);
  }
  return best1 < best0;
}
__device__ __forceinline__ void fill_mem0(uint32_t img, int w, int lane, int slot, const bf16* mem0) {
  PIN(w); PIN(lane);
  const int k0 = w + lane;
  uint4 u[2];
#pragma unroll
  for (int i = 0; i < 2; i++) {
    const unsigned short* m = (const unsigned short*)mem0 + k0 + 32 * i;
    u[i] = make_uint4(m[0] | (uint32_t)m[512] << 16, m[1024] | (uint32_t)m[1536] << 16, m[2048] | (uint32_t)m[2560] << 16, m[3072] | (uint32_t)m[3584] << 16);
  }
  __syncwarp();
#pragma unroll
  for (int i = 0; i < 2; i++) sts128(img + ((k0 >> 4) + 2 * i) * 768 + slot * 256 + (lane & 15) * 16, u[i]);
}

__device__ __forceinline__ void paced_h(uint32_t dst, const uint8_t* src, uint32_t o0, uint32_t o1, uint32_t piece, uint32_t bar, int gap) {
  uint32_t t = clk32();
#pragma unroll 1
  for (uint32_t o = o0; o < o1; o += piece) {
    e_mc(dst + o, src + o, piece, bar, 7);
    spin_until(t += gap);
  }
}

__device__ __forceinline__ void weight_role(const Params& p, const uint32_t sb, const int warp, const int cta, const int C, const uint32_t E,
                                            const uint8_t* const memg) {
  const int tid = fresh_tid(), lane = tid & 31;
  const int wg = warp >> 2, w = warp & 3;
  uint32_t W[32][4];
  cp_async_wait();
  bar_sync(1, 256);
  load_frags(W, sb, wg, w, lane);
  bar_sync(1, 256);
  if (tid < 128) sts128(sb + M_V + 5 * 2048 + tid * 16, make_uint4(0, 0, 0, 0));
  fence_async_smem();
  cluster_sync();
  if (tid == 0 && cta == 0) GSTAMP(0, 1);
  if (tid == 0) TSTAMP(13, cta, 0);

  const uint32_t rba = mapa(sb, C == 2 ? 0 : 2), rbc = mapa(sb, C == 1 ? 0 : 1);
  const uint32_t MYBAR = M_BAR + 8 * (C < 2 ? B_QK : B_V);
  uint32_t qoff = M_Q + C * 12288 + warp * 256 + lane * 4;
  uint32_t toff = sb + warp * 256 + (lane >> 4) * 2048 + (lane & 15) * 16;
  uint32_t rbar = mapa(sb + M_BAR, min(lane, 2));
  uint32_t sv = sb + M_MEM + lane * 32 + ((lane >> 2) & 3) * 8;
  PIN(qoff); PIN(toff); PIN(rbar); PIN(sv);
  const uint32_t gen0 = (E - 1) * (uint32_t)(NSTEP - 1);
  uint32_t fix = 0;
  const bool sig = w == 0 && lane < 3;
  const int pk = PAUSE_ + (cta < 36 ? 0 : cta < 72 ? PD1_ : PD2_);
  int cand = -1;
  float d[16];
#pragma unroll
  for (int i = 0; i < 16; i++) d[i] = 0.f;
  uint32_t tp[8];
#pragma unroll 1
  for (int T = -1; T < NSTEP; T++) {
    const uint32_t ph = T & 1;
    const uint64_t Z = p.zero << ph;
    const uint32_t zz = p.zero2;
    if (T >= 0) {
      WSTAMP(0);
      const uint64_t db = mkdesc(M_MEM, 128, 256, 0) + Z;
      stmatrix4(toff + M_TST + 8192, tp[0], tp[1], tp[2], tp[3]); stmatrix4(toff + M_TST + 12288, tp[4], tp[5], tp[6], tp[7]);
      if (sig) mbar_arrive_remote(rbar + 8 * B_HBE);
      mbar_wait(BAR(B_LAND), ph);
      WSTAMP(1);
      const uint32_t gt = gentag(gen0 + T);
      auto old = [&](uint32_t a) { return lds32(a) ^ gt; };
      uint32_t bad = 0;
      bool redo = false, ready = false;
      wg_fence();
      wgmma_rs24<0, 1, KP1_>(d, W[0], db);
#pragma unroll
      for (int ks = 1; ks < 32; ks++) {
        if (ks == 2 || ks == 14) bad |= xo2(lds32(sv + (ks == 2 ? 0 : 9) * 1024 + warp * 1024), lds32(sv + (ks == 2 ? 8 : 17) * 1024), gt);
        if (ks == 25) bad |= old(sv + (18 + min(warp, 5)) * 1024);
        if (ks == 6) {
          const uint32_t z5 = DRAIN(toff + M_TST);
          __syncwarp();
          if (lane == 0) mbar_arrive(BAR(B_STG) + z5);
        }
        if (ks == 27) ready = mbar_test(BAR(C < 2 ? B_KFREE : B_VFREE), ph ^ 1) & mbar_test(BAR(B_HA), ph);
        if ((EARLY_ && (ks == 9 || ks == 21)) || ks == RED_) redo = bar_or(N_W, 256, T > 0 && (bad & 0x10001u));
        if (ks == 12 || ks == 24) {
          if (EARLY_ && __builtin_expect(redo, 0)) break;
          mbar_wait(BAR(B_LAND + ks / 12), ph); WSTAMP(6 + ks / 12); wg_fence();
        }
        wgmma_rs24<1, 1>(d, W[ks], db + ks * 48);
      }
      wg_commit();
      uint32_t a0 = rba + qoff, a1 = a0 + 128, a2 = rbc + qoff, a3 = a2 + 128, ba = rba + MYBAR, bc = rbc + MYBAR;
      PIN(a0); PIN(a1); PIN(a2); PIN(a3); PIN(ba); PIN(bc);
      if (!ready) {
        mbar_wait(BAR(C < 2 ? B_KFREE : B_VFREE), ph ^ 1);
        if (T < NSTEP - 1) mbar_wait(BAR(B_HA), ph);
      }
      wg_wait<0>(); reg_fence(d);
      if (__builtin_expect(redo, 0)) {
        auto stale = [&]() { return __any_sync(~0u, (old(sv + warp * 3072) | old(sv + warp * 3072 + 1024) | old(sv + warp * 3072 + 2048)) & 0x10001u); };
        auto fetch = [&](int r) {
          e_expect(BAR(B_FIX + warp), 3072);
          e_g2s(sb + M_MEM + warp * 3072, memg + warp * 8192 + ((uni(lds32(sb + M_NEAR + warp * 4)) ^ r) & 1) * 4096, 3072, BAR(B_FIX + warp));
        };
        mbar_wait(BAR(B_LAND + warp / 3), ph);
        bool late = stale();
        if (late) fetch(0);
        constexpr uint64_t dc = mkdesc(M_MEM, 128, 256, 0);
#pragma unroll
        for (int ks = 0; ks < 32; ks++) {
          if (ks % 12 == 0) {
            if (ks) { wg_commit(); wg_wait<0>(); reg_fence(d); }
            if (warp / 3 == ks / 12) {
              for (int guard = 0; late; guard++) {
                mbar_wait(BAR(B_FIX + warp), fix); fix ^= 1;
                late = stale();
                if (late) fetch(ALT_ ? guard + 1 : 0);
                if (guard > (1 << 20)) TRAP();
              }
            }
            bar_sync(N_W, 256);
            wg_fence();
          }
          if (ks == 0) wgmma_rs24<0, 1, 1>(d, W[0], dc); else wgmma_rs24<1, 1>(d, W[ks], dc + ks * 48);
        }
        wg_commit();
        wg_wait<0>(); reg_fence(d);
      }
      WSTAMP(2);
      uint32_t lo[3], hi[3];
#pragma unroll
      for (int j = 0; j < 3; j++) { lo[j] = pack2(d[4 * j], d[4 * j + 1]); hi[j] = pack2(d[4 * j + 2], d[4 * j + 3]); }
      if (__builtin_expect(T == 0, 0)) { sts32(sb + M_M0 + tid * 8, lo[0]); sts32(sb + M_M0 + tid * 8 + 4, hi[0]); }
      if (__builtin_expect(cand >= 0, 0)) {
        if (T == LAG) { lo[1] = lds32(sb + M_M0 + tid * 8); hi[1] = lds32(sb + M_M0 + tid * 8 + 4); }
        if (C < 2) { st_async32(a0 + 5 * 2048, lo[2], ba); st_async32(a1 + 5 * 2048, hi[2], ba); }
        else { sts32(sb + qoff + 5 * 2048, lo[2]); sts32(sb + qoff + 5 * 2048 + 128, hi[2]); }
        lo[2] = lo[1]; hi[2] = hi[1];
      }
      uint32_t z5;
      if (C == 0) {
        sts32(sb + qoff, lo[0]); sts32(sb + qoff + 128, hi[0]); z5 = DRAIN(sb + qoff);
        st_async32(a0, lo[2], ba); st_async32(a1, hi[2], ba); st_async32(a2, lo[1], bc); st_async32(a3, hi[1], bc);
      } else if (C == 1) {
        sts32(sb + qoff, lo[1]); sts32(sb + qoff + 128, hi[1]); z5 = DRAIN(sb + qoff);
        st_async32(a0, lo[2], ba); st_async32(a1, hi[2], ba); st_async32(a2, lo[0], bc); st_async32(a3, hi[0], bc);
      } else {
        sts32(sb + qoff, lo[2]); sts32(sb + qoff + 128, hi[2]); z5 = DRAIN(sb + qoff);
        st_async32(a0, lo[0], ba); st_async32(a1, hi[0], ba); st_async32(a2, lo[1], bc); st_async32(a3, hi[1], bc);
      }
      __syncwarp();
      if (lane == 0) { mbar_arrive(sb + MYBAR + z5); if (w == 3) mbar_arrive(BAR(B_SS)); }
      if (T == NSTEP - 1) break;
    }
    {
      const uint64_t dh = mkdesc(M_H, 16, 1024, 1) + Z;
      if (T < 0) mbar_wait(BAR(B_HA), ph);
      WSTAMP(3);
      wg_fence();
      wgmma_rs32<0, 0, 1>(d, W[0], dh);
#pragma unroll
      for (int ks = 1; ks < EA; ks++) {
        if (ks == E1 || ks == E1 + E2) {
          wg_commit();
          if (T >= 0) { if (ks == E1 && E2 > 0) bar_sync(N_GO1, 384); if (ks == E1 + E2) bar_sync(N_GO2, 384); }
          wg_fence();
        }
        wgmma_rs32<1, 0>(d, W[ks], dh + (ks >> 2) * 256 + (ks & 3) * 2);
      }
      wg_commit();
      mbar_wait(BAR(B_HB), ph);
      wg_wait<0>();
      if (sig) mbar_arrive_remote(rbar + 8 * B_HAE);
      WSTAMP(4);
      if (T >= 0) bar_sync(N_GO3, 384);
      if (wg == 1) bar_sync(N_W, 256);
      wg_fence();
#pragma unroll
      for (int ks = EA; ks < 32; ks++) wgmma_rs32<1, 0>(d, W[ks], dh + (ks >> 2) * 256 + (ks & 3) * 2);
      wg_commit();
      if (wg == 0) bar_arrive(N_W, 256);
      mbar_wait(BAR(B_TFREE), ph ^ 1);
      wg_wait<0>(); reg_fence(d);
#pragma unroll
      for (int i = 0; i < 8; i++) { tp[i] = pack2(d[2 * i], d[2 * i + 1]); PIN(tp[i]); }
      wg_fence();
      wgmma_rs32<0, 0, 1>(d, W[0], dh + 2048);
      stmatrix4(toff + M_TST, tp[0], tp[1], tp[2], tp[3]); stmatrix4(toff + M_TST + 4096, tp[4], tp[5], tp[6], tp[7]);
#pragma unroll
      for (int ks = 1; ks < 32; ks++) {
        if (ks == 5) {
          const uint32_t z5 = DRAIN(toff + M_TST);
          __syncwarp();
          if (lane == 0) mbar_arrive(BAR(B_STG1) + z5);
        }
        if (PAUSE_ && (ks == PAUSE_ || ks == PAUSE_ + PD1_ || ks == PAUSE_ + PD2_)) {
          wg_commit();
          if (T >= 0 && ks == pk) bar_sync(N_GO4, 384);
          wg_fence();
        }
        wgmma_rs32<1, 0>(d, W[ks], dh + 2048 + (ks >> 2) * 256 + (ks & 3) * 2);
      }
      wg_commit();
      if (T >= 0) cand = __shfl_sync(~0u, (int)lds32(sb + M_CAND + ((T + 1) & 3) * 4), 0);
      wg_wait<0>(); reg_fence(d);
      if (T >= 0) WSTAMP(6);
#pragma unroll
      for (int i = 0; i < 8; i++) tp[i] = pack2(d[2 * i], d[2 * i + 1]);
    }
  }
  cluster_sync();
  if (tid == 0 && cta == 0) GSTAMP(0, 5);
}

__device__ __forceinline__ void attn_role(const Params& p, const uint32_t sb, const int w, const int cta, const int head, const int C, const uint32_t E,
                                          uint8_t* const part, uint8_t* const memg) {
  const int tid = fresh_tid(), lane = tid & 31;
  const int g = lane >> 2, t = lane & 3;
  uint32_t tag = ((E - 1) * (uint32_t)(NSTEP - 1)) & 1;
#pragma unroll 1
  for (int k = 0; k < 2; k++) {
#pragma unroll 1
    for (int i = 0; i < 6; i++) sts128(sb + M_MEM + (w + 4 * k) * 3072 + lane * 16 + i * 512, make_uint4(0, 0, 0, 0));
    fill_mem0(sb + M_MEM, (w + 4 * k) * 64, lane, 0, p.mem0);
  }
  fence_async_smem();
  bar_sync(N_AG, 128);
  if (w == 3 && lane < 3) mbar_arrive(BAR(B_LAND + lane));
  if (w < 2 && lane == 0) {
    const int n = probe_near(part + cta * 16384 + w * 8192);
    sts32(sb + M_NEAR + 32 + w * 4, n);
    st_rel(&f_choice[cta][w], (E << 1) | (uint32_t)n);
  }
  __syncwarp();
  uint32_t nb;
  {
    const int i = min(lane >> 1, C < 2 ? 8 : 5);
    const int r = ((i / 3 * 3 + C) * 4 + w) * 3 + i % 3;
    int guard = 0; uint32_t cw;
    while (__any_sync(~0u, ((cw = ld_acq(&f_choice[r][lane & 1])) >> 1) != (E & 0x7FFFFFFFu))) { if (++guard > (1 << 22)) TRAP(); }
    nb = __ballot_sync(~0u, cw & 1) >> (lane >> 4);
  }
  bar_sync(N_AG, 128);
  const uint32_t pt0 = sb + M_PT + (tid & 127) * 16;
  {
    const uint32_t po = (C * 4 + w) * 49152 + (lane >> 4) * 8192 + ((lane >> 3) & 1) * 2048 + head * 64 + (lane & 7) * 8;
    const uint8_t* in = part + (cta * 16384 + (w >> 1) * 8192 + lds32(sb + M_NEAR + 32 + (w >> 1) * 4) * 4096 + (w & 1) * 2048 + lane * 8);
    const uint8_t* outp = memg + ((cta / 12) * 8192 + (cta % 12) * 256 + w * 64 + (lane >> 4) * 4096 + (lane & 4) * 8 + (lane & 8) * 2 + (lane & 3) * 4);
#pragma unroll 1
    for (int i = 0; i < 12; i++) {
      const int j = i / 4 * 3 + (i & 3);
      const uint8_t* a = (i & 3) < 3 ? part + (po + i / 4 * 589824 + (i & 3) * 16384 + ((nb >> (2 * j)) & 1) * 4096) : i == 11 ? in : outp;
      asm volatile("st.shared.u64 [%0], %1;" :: "r"(pt0 + (i >> 1) * 2048 + (i & 1) * 8), "l"(a) : "memory");
    }
  }
  const int xd = __shfl_sync(~0u, XDLY_ + (cta < 36 ? 0 : cta < 72 ? X1_ : X2_), 0);
  const uint32_t rba = mapa(sb, C == 2 ? 0 : 2), rbc = mapa(sb, C == 1 ? 0 : 1);
  uint32_t vis = vis_bits(8 + 8 * w + g, t);
  uint32_t ln = lane;
#pragma unroll
  for (int i = 0; i < SALT_; i++) ln += lds32(sb + M_ZERO);
  PIN(vis); PIN(ln);
  uint32_t fa[8][4];
#pragma unroll
  for (int ks = 0; ks < 8; ks++) ldmatrix4_t(fa[ks], sb + M_WO + 32768 + w * 256 + (lane >> 4) * 1024 + (lane & 15) * 16 + ks * 2048);
#pragma unroll 1
  for (int T = 0; T < NSTEP; T++) {
    const uint32_t ph = T & 1;
    const uint32_t zz = uni(lds32(sb + M_ZERO));
    const bool more = T < NSTEP - 1;
    const float sc = 0.08838834764831845f * 1.4426950408889634f;
    tag ^= 1;
    float s[20];
    const uint8_t* in; int cnext = -1; uint32_t tx; bool synced;
    float x[10], tm, ts;
    uint32_t pt[5];
    auto tok_max = [&]() {
      PIN(vis);
      x[0] = s[2]; x[1] = s[3];
#pragma unroll
      for (int i = 0; i < 8; i++) x[2 + i] = (vis >> i & 1) ? s[4 * (i / 2 + 1) + 2 + (i & 1)] : -INFINITY;
      tm = fmaxf(fmaxf(fmaxf(fmaxf(x[0], x[1]), fmaxf(x[2], x[3])), fmaxf(fmaxf(x[4], x[5]), fmaxf(x[6], x[7]))), fmaxf(x[8], x[9]));
      HOLD(7, __float_as_uint(tm));
    };
    auto tok_exp1 = [&]() {
      tm = fmaxf(tm, __shfl_xor_sync(~0u, tm, 1));
      tm = fmaxf(tm, __shfl_xor_sync(~0u, tm, 2));
      const float b = -tm * sc;
#pragma unroll
      for (int i = 0; i < 10; i++) x[i] = fmaf(x[i], sc, b);
      HOLD(10, __float_as_uint(x[9]));
    };
    auto tok_exp2 = [&]() {
#pragma unroll
      for (int i = 0; i < 10; i++) x[i] = ex2(x[i]);
      ts = (((x[0] + x[1]) + (x[2] + x[3])) + ((x[4] + x[5]) + (x[6] + x[7]))) + (x[8] + x[9]);
#pragma unroll
      for (int k = 0; k < 5; k++) pt[k] = pack2(x[2 * k], x[2 * k + 1]);
      HOLD(8, __float_as_uint(ts));
    };
    {
      uint32_t q[8][4];
      auto load_q = [&](uint32_t a, int h) {
#pragma unroll
        for (int k2 = 0; k2 < 4; k2++) {
          uint32_t r[4];
          ldmatrix4_t(r, a + k2 * 512);
          q[2 * k2][h] = r[0]; q[2 * k2][h + 2] = r[1]; q[2 * k2 + 1][h] = r[2]; q[2 * k2 + 1][h + 2] = r[3];
        }
      };
      PIN(ln);
      const uint32_t qa = sb + M_Q + ln * 16;
      const int cand = C == 2 ? (int)uni(lds32(sb + M_CAND + (T & 3) * 4)) : -1;
      mbar_wait(BAR(B_TOK), ph);
      load_q(qa + (1 + w) * 2048, 1);
      mbar_wait(BAR(B_QK), ph);
      ASTAMP(0);
      if (__builtin_expect(cand >= 0, 0)) {
        mbar_wait(BAR(B_V), ph);
        PIN(ln);
        const int e = w * 32 + ln;
#pragma unroll
        for (int i = 0; i < 3; i++) {
          const uint32_t v = lds32(sb + M_Q + i * 12288 + 5 * 2048 + e * 16 + 4);
          asm volatile("st.shared.u16 [%0], %1;" :: "r"(sb + M_Q + i * 12288 + (1 + (cand >> 3)) * 2048 + e * 16 + (cand & 7) * 2), "h"((unsigned short)v) : "memory");
        }
        fence_async_smem();
        bar_sync(N_AG, 128);
        load_q(qa + (1 + w) * 2048, 1);
      }
      load_q(qa, 0);
      if (!(NOF_ & 1)) fence_async_smem();
      constexpr uint64_t dk = mkdesc(M_K, 128, 2048, 0);
      wg_fence();
      wgmma_rs40<0, 1>(s, q[0], dk);
#pragma unroll
      for (int ks = 1; ks < 8; ks++) wgmma_rs40<1, 1>(s, q[ks], dk + ks * 16);
      wg_commit();
    }
    if (more) {
      uint32_t v[5][4];
      PIN(ln);
      const uint32_t va = sb + M_V + w * 512 + ((ln >> 3) & 1) * 128 + (ln >> 4) * 2048 + (ln & 7) * 16;
      const uint32_t ooff = M_OM + w * 1536 + C * 256 + ln * 4;
      mbar_wait(BAR(B_V), ph);
      wg_wait<0>(); reg_fence(s);
      if (E2 > 0) bar_arrive(N_GO1, 384);
      if (ln < 3) mbar_arrive_remote(mapa(BAR(B_KFREE), ln));
      ldmatrix4(v[0], va); ldmatrix4(v[1], va + 256); ldmatrix4(v[2], va + 4096); ldmatrix4(v[3], va + 4096 + 256);
      ldmatrix4(v[4], sb + M_V + 8192 + w * 512 + ln * 16);
      ASTAMP(1);
      float m = fmaxf(fmaxf(fmaxf(fmaxf(s[0], s[1]), fmaxf(s[4], s[5])), fmaxf(fmaxf(s[8], s[9]), fmaxf(s[12], s[13]))), fmaxf(s[16], s[17]));
      m = fmaxf(m, __shfl_xor_sync(~0u, m, 1));
      m = fmaxf(m, __shfl_xor_sync(~0u, m, 2));
      const float b = -m * sc;
      uint32_t pm[5];
#pragma unroll
      for (int j = 0; j < 5; j++) pm[j] = pack2(ex2(fmaf(s[4 * j], sc, b)), ex2(fmaf(s[4 * j + 1], sc, b)));
      float o0[4] = {0.f, 0.f, 0.f, 0.f}, o1[4] = {0.f, 0.f, 0.f, 0.f}, l[4] = {0.f, 0.f, 0.f, 0.f};
      const uint32_t one[4] = {0x3f803f80u, 0x3f803f80u, 0x3f803f80u, 0x3f803f80u};
      hmma16(l, one, pm[0], pm[1]); hmma16(o0, v[0], pm[0], pm[1]); hmma16(o1, v[1], pm[0], pm[1]);
      hmma16(l, one, pm[2], pm[3]); hmma16(o0, v[2], pm[2], pm[3]); hmma16(o1, v[3], pm[2], pm[3]);
      hmma8(l, one[0], one[1], pm[4]); hmma8(o0, v[4][0], v[4][1], pm[4]); hmma8(o1, v[4][2], v[4][3], pm[4]);
      const float r0 = rcp(l[0]), r1 = rcp(l[1]);
      const uint32_t u0 = pack2(o0[0] * r0, o0[1] * r1), u1 = pack2(o0[2] * r0, o0[3] * r1), u2 = pack2(o1[0] * r0, o1[1] * r1), u3 = pack2(o1[2] * r0, o1[3] * r1);
      constexpr uint32_t OB = M_BAR + 8 * B_OM;
      const uint32_t a0 = rba + ooff, a1 = rbc + ooff;
      st_async32(a0, u0, rba + OB); st_async32(a1, u0, rbc + OB);
      st_async32(a0 + 128, u1, rba + OB); st_async32(a1 + 128, u1, rbc + OB);
      st_async32(a0 + 768, u2, rba + OB); st_async32(a1 + 768, u2, rbc + OB);
      st_async32(a0 + 896, u3, rba + OB); st_async32(a1 + 896, u3, rbc + OB);
      if (E3 > 0) bar_arrive(N_GO2, 384);
      sts32(sb + ooff, u0); sts32(sb + ooff + 128, u1); sts32(sb + ooff + 768, u2); sts32(sb + ooff + 896, u3);
      ASTAMP(2);
      uint32_t fb[8][4];
      const uint32_t wa = sb + M_WO + 16384 + w * 256 + (ln >> 4) * 1024 + (ln & 15) * 16 + zz;
      ldmatrix4_t(fb[0], wa);
      SCHED(3);
#pragma unroll
      for (int ks = 1; ks < 8; ks++) {
        ldmatrix4_t(fb[ks], wa + ks * 2048);
        if (ks == ARR_) { __syncwarp(); if (ln == 0) mbar_arrive(BAR(B_OM) + (fb[0][0] & zz)); }
      }
      if (C == 2) cnext = (int)uni(lds32(sb + M_CAND + ((T + 1) & 3) * 4));
      {
        float d[12], e[12];
        constexpr uint64_t ob = mkdesc(M_OM, 128, 256, 0);
        uint8_t* q[3][3];
        auto addr = [&](int i) {
          asm volatile("ld.shared.v2.u64 {%0,%1}, [%2];" : "=l"(q[i][0]), "=l"(q[i][1]) : "r"(pt0 + i * 4096) : "memory");
          if (i < 2) asm volatile("ld.shared.u64 %0, [%1];" : "=l"(q[i][2]) : "r"(pt0 + i * 4096 + 2048) : "memory");
          else asm volatile("ld.shared.v2.u64 {%0,%1}, [%2];" : "=l"(q[i][2]), "=l"(in) : "r"(pt0 + i * 4096 + 2048) : "memory");
        };
        auto put = [&](const float* d, int i) {
          st_rlx64(q[i][0], (pack2(d[0], d[1]) & ~1u) | tag, pack2(d[2], d[3]));
          st_rlx64(q[i][1], (pack2(d[4], d[5]) & ~1u) | tag, pack2(d[6], d[7]));
          st_rlx64(q[i][2], (pack2(d[8], d[9]) & ~1u) | tag, pack2(d[10], d[11]));
        };
        addr(0); addr(1);
        SCHED(6);
        tok_max();
        ASTAMP(3);
        mbar_wait(BAR(B_OM), ph);
        if (!(NOF_ & 2)) fence_async_smem();
        ASTAMP(4);
        constexpr uint64_t w0 = mkdesc(M_WO, 1024, 128, 0);
        float (&f)[12] = d;
        wg_fence();
        wgmma_ss24<0, 1, 1>(d, w0, ob);
#pragma unroll
        for (int ks = 1; ks < 8; ks++) wgmma_ss24<1, 1, 1>(d, w0 + ks * 128, ob + ks * 48);
        wg_commit();
        wgmma_rs24<0, 1>(e, fb[0], ob);
#pragma unroll
        for (int ks = 1; ks < HAND_; ks++) wgmma_rs24<1, 1>(e, fb[ks], ob + ks * 48);
        wg_commit();
        wg_wait<1>(); reg_fence(d);
        put(d, 0);
        addr(2);
        SCHED(4);
        ASTAMP(5);
        wg_fence();
#pragma unroll
        for (int ks = HAND_; ks < 8; ks++) wgmma_rs24<1, 1>(e, fb[ks], ob + ks * 48);
        wg_commit();
        wgmma_rs24<0, 1, 1>(f, fa[0], ob);
#pragma unroll
        for (int ks = 1; ks < HAND_; ks++) wgmma_rs24<1, 1>(f, fa[ks], ob + ks * 48);
        wg_commit();
        wg_wait<1>(); reg_fence(e);
        put(e, 1);
        SCHED(5);
        wg_fence();
#pragma unroll
        for (int ks = HAND_; ks < 8; ks++) wgmma_rs24<1, 1>(f, fa[ks], ob + ks * 48);
        wg_commit();
        if (GO3_ == 0) bar_arrive(N_GO3, 384);
        synced = __all_sync(~0u, mbar_test(BAR(B_SYNC), ph));
        tx = uni(lds32(sb + M_BASE + ph * 4)) + xd;
        wg_wait<0>(); reg_fence(f);
        if (GO3_ == 1) bar_arrive(N_GO3, 384);
        if (C < 2) put(f, 2);
        if (GO3_ == 2) bar_arrive(N_GO3, 384);
        ASTAMP(6);
      }
    } else {
      mbar_wait(BAR(B_V), ph);
      wg_wait<0>(); reg_fence(s);
      tok_max();
    }
    uint2 v[8];
#pragma unroll
    for (int i = 0; i < 8; i++) v[i] = make_uint2(zz, zz);
    auto poll = [&](uint2* v) {
      v[0] = ld_rlx64<0>(in); v[1] = ld_rlx64<256>(in); v[2] = ld_rlx64<512>(in); v[3] = ld_rlx64<768>(in);
      v[4] = ld_rlx64<1024>(in); v[5] = ld_rlx64<1280>(in); v[6] = ld_rlx64<1536>(in); v[7] = ld_rlx64<1792>(in);
    };
    uint8_t* outp;
    asm volatile("ld.shared.u64 %0, [%1];" : "=l"(outp) : "r"(pt0 + 2048 + 8) : "memory");
    const uint32_t itag = gentag((E - 1) * (uint32_t)(NSTEP - 1) + T + 1);
    const bool sum = more && cnext < 0;
    if (more) {
      if (!synced) { mbar_wait(BAR(B_SYNC), ph); tx = uni(lds32(sb + M_BASE + ph * 4)) + xd; }
      ASTAMP(7);
      if (__builtin_expect(cnext >= 0, 0)) {
        const unsigned long long* hp = (const unsigned long long*)&g_hc[T + 1 - LAG][0] + ((cta / 3) * 8 + 2 * w + ((ln >> 2) & 1));
        unsigned long long v0; int guard = 0;
        while (v0 = ld_rlxu64(hp), !__all_sync(~0u, (uint32_t)(v0 >> 32) == E)) { if (++guard > (1 << 22)) TRAP(); }
        st_rlx((uint32_t*)outp, (ln & 3) == 1 ? ((uint32_t)v0 >> ((ln & 8) * 2)) & 0xffffu : (ln & 1) ? 0u : itag);
      } else {
        spin_until(tx);
        ASTAMP(8);
        poll(v);
      }
    }
    auto late = [&](const uint2* v) {
      return __any_sync(~0u, (or3(xo2(v[0].x, v[1].x, tag), xo2(v[2].x, v[3].x, tag), xo2(v[4].x, v[5].x, tag)) | xo2(v[6].x, v[7].x, tag)) & 1u);
    };
    tok_exp1(); tok_exp2();
    if (sum) {
      ASTAMP(9);
      int guard = 0;
      while (late(v)) {
        if (++guard > (1 << 22)) TRAP();
        poll(v);
      }
#pragma unroll
      for (int i = 0; i < 4; i++) { v[i].x = add2(v[i].x, v[i + 4].x); v[i].y = add2(v[i].y, v[i + 4].y); }
#define SUM8(f, m) ((f(v[0].m) + f(v[1].m)) + (f(v[2].m) + f(v[3].m)))
      const float a0 = SUM8(blo, x), a1 = SUM8(bhi, x), b0 = SUM8(blo, y), b1 = SUM8(bhi, y);
      const bool hi = ln & 8;
      float k0 = (hi ? b0 : a0) + __shfl_xor_sync(~0u, hi ? a0 : b0, 8), k1 = (hi ? b1 : a1) + __shfl_xor_sync(~0u, hi ? a1 : b1, 8);
      k0 += __shfl_xor_sync(~0u, k0, 16); k1 += __shfl_xor_sync(~0u, k1, 16);
      st_rlx((uint32_t*)outp, (ln & 1) ? pack2(k0, k1) : pack2_tag(k0, k1, itag));
      ASTAMP(10);
      CSTAMP(12 + w, (clk() & ~15u) | min(guard + 1, 15));
    }
    if (PAUSE_ && more) bar_arrive(N_GO4, 384);
    {
      PIN(ln);
      const uint32_t oa = sb + M_OST + w * 128 + (ln >> 3) * 512 + (ln & 7) * 16;
      const uint32_t a[3][4] = {{0, pt[0], 0, pt[1]}, {0, pt[2], 0, pt[3]}, {0, pt[4], 0, 0}};
      constexpr uint64_t dv = mkdesc(M_V, 2048, 128, 0);
#pragma unroll 1
      for (int h = 0; h < 2; h++) {
        float o[32];
        const uint64_t dh = dv + (uint64_t)(h * 64);
        wg_fence();
        wgmma_rs64<0, 0>(o, a[0], dh); wgmma_rs64<1, 0>(o, a[1], dh + 256); wgmma_rs64<1, 0>(o, a[2], dh + 512);
        wg_commit();
        if (h == 0) {
          ts += __shfl_xor_sync(~0u, ts, 1);
          ts += __shfl_xor_sync(~0u, ts, 2);
          ts = rcp(ts);
          mbar_wait(BAR(B_OFREE), ph ^ 1);
        }
        wg_wait<0>(); reg_fence(o);
        if (h == 1 && ln < 3) mbar_arrive_remote(mapa(BAR(B_VFREE), ln));
#define OT(i) pack2(o[4 * (i) + 2] * ts, o[4 * (i) + 3] * ts)
        stmatrix4(oa + h * 4096, OT(0), OT(1), OT(2), OT(3));
        stmatrix4(oa + h * 4096 + 2048, OT(4), OT(5), OT(6), OT(7));
      }
      const uint32_t z5 = DRAIN(oa);
      __syncwarp();
      if (ln == 0) mbar_arrive(BAR(B_OST) + z5);
      ASTAMP(11);
    }
  }
}

__global__ void __cluster_dims__(3, 1, 1) __launch_bounds__(512, 1) main_kernel(Params p) {
  extern __shared__ __align__(1024) uint8_t sm[];
  const uint32_t sb = smem_u32(sm);
  if ((sb & 0xFFFFFFu) != SBASE) TRAP();
  asm volatile("griddepcontrol.launch_dependents;");
  const int warp = __shfl_sync(~0u, threadIdx.x >> 5, 0);
  const int cta = blockIdx.x, head = cta / 3, c = cta % 3;
  const uint32_t E = __shfl_sync(~0u, *(volatile uint32_t*)&g_epoch + 1, 0);
  uint8_t* const part = (uint8_t*)(((uintptr_t)g_xch + 8191) & ~(uintptr_t)8191);
  uint8_t* const memg = part + 96 * 16384;

  if (threadIdx.x == 0 && cta == 0) GSTAMP(0, 0);
  if (threadIdx.x < B_NUM) {
    const int i = threadIdx.x;
    const uint32_t cnt = i == B_STG || i == B_STG1 ? 8 : i == B_OST ? 4 : i == B_HAE || i == B_HBE ? 6 : i == B_KFREE || i == B_VFREE ? 12 : i == B_SS ? 2 : i == B_OM ? 5 :
                         i == B_QK ? (c < 2 ? 9 : 1) : i == B_V ? (c < 2 ? 1 : 9) : 1;
    mbar_init(BAR(i), cnt);
    if (i == B_HA || i == B_HB || i == B_STG || i == B_HAE || i == B_HBE || i == B_TFREE)
      asm volatile("mbarrier.arrive.shared::cta.b64 _, [%0], %1;" :: "r"(BAR(i)), "r"(cnt) : "memory");
    asm volatile("fence.mbarrier_init.release.cluster;" ::: "memory");
  }
  if (warp < 8) {
    const int tid = threadIdx.x;
    uint4 wa[6], wb[6];
#pragma unroll
    for (int i = 0; i < 6; i++) {
      const int mi = i >> 1, e = (tid >> 2) + (i & 1) * 64;
      const uint4* src = (const uint4*)(p.wo + (size_t)(head * 128 + e) * 512 + min(3 * mi + c, 7) * 64 + (tid & 3) * 16);
      wa[i] = __ldg(src); wb[i] = __ldg(src + 1);
    }
    stage_weights(sb, (c == 0 ? p.wq : c == 1 ? p.wk : p.wv) + head * 128, 4096, tid, 256);
#pragma unroll
    for (int i = 0; i < 6; i++) {
      const int mi = i >> 1, e = (tid >> 2) + (i & 1) * 64;
      const uint4 a = wa[i], b = wb[i];
      const uint32_t dst = sb + M_WO + mi * 16384 + (e >> 3) * 1024 + (tid & 3) * 256 + (e & 7) * 16;
      sts128(dst, make_uint4(__byte_perm(a.x, a.y, 0x5410), __byte_perm(a.z, a.w, 0x5410), __byte_perm(b.x, b.y, 0x5410), __byte_perm(b.z, b.w, 0x5410)));
      sts128(dst + 128, make_uint4(__byte_perm(a.x, a.y, 0x7632), __byte_perm(a.z, a.w, 0x7632), __byte_perm(b.x, b.y, 0x7632), __byte_perm(b.z, b.w, 0x7632)));
    }
  } else {
    const int i0 = threadIdx.x - 256;
    const uint32_t tag0 = ((E - 1) * (uint32_t)(NSTEP - 1)) & 1;
    for (int i = i0; i < 1024; i += 256) *(uint4*)(part + cta * 16384 + i * 16) = make_uint4(tag0, 0, tag0, 0);
    if (i0 < 16) *(uint32_t*)(memg + i0 * 4096 + 3968) = 0;
    if (i0 < 12) sts32(sb + M_ZERO + i0 * 4, 0);
    if (i0 < 2) sts32(sb + M_BASE + i0 * 4, clk32() - 65536);
  }

  if (warp < 8) {
    asm volatile("setmaxnreg.inc.sync.aligned.u32 " STR(RW_) ";");
    weight_role(p, sb, warp, cta, c, E, memg);
  } else if (warp < 12) {
    if (RA_ < 128) asm volatile("setmaxnreg.dec.sync.aligned.u32 " STR(RA_) ";");
    if (RA_ > 128) asm volatile("setmaxnreg.inc.sync.aligned.u32 " STR(RA_) ";");
    cluster_sync();
    attn_role(p, sb, warp - 8, cta, head, c, E, part, memg);
    cluster_sync();
  } else {
    asm volatile("setmaxnreg.dec.sync.aligned.u32 " STR(RC_) ";");
    const int tid = fresh_tid(), lane = tid & 31;
    const int w = warp - 12;
    cluster_sync();
    if (w < 3 && lane == 0) {
      const int tl = min(3 * w + c, 7);
      const int n = probe_near(memg + tl * 8192);
      for (int r = 0; r < 3; r++) asm volatile("st.shared::cluster.u32 [%0], %1;" :: "r"(mapa(sb + M_NEAR + tl * 4, r)), "r"(n) : "memory");
    }
    __syncwarp();
    if (w == 0) {
      uint32_t s0 = c * 8192, s1 = (3 + c) * 8192, s2 = min(6 + c, 7) * 8192;
#pragma unroll 1
      for (int T = 0; T < NSTEP - 1; T++) {
        const uint32_t ph = T & 1;
        mbar_wait(BAR(B_SS), ph);
        const uint32_t cq = clk();
        const uint32_t g0 = (uint32_t)gtime64(); uint32_t g1, ce;
        do { g1 = (uint32_t)gtime64(); ce = clk(); } while (g1 == g0);
        const uint32_t tn = g1 * 8 - (((ce - cq) * 37u) >> 3), id = E * 128u + T;
        if (lane == 0) st_rlx64(&g_sync[ph][cta], tn, id);
        if (lane < 3) mbar_expect(BAR(B_LAND + lane), lane < 2 ? 9216 : 6144);
        if (T == 0) { s0 += uni(lds32(sb + M_NEAR + c * 4)) * 4096; s1 += uni(lds32(sb + M_NEAR + (3 + c) * 4)) * 4096; s2 += uni(lds32(sb + M_NEAR + min(6 + c, 7) * 4)) * 4096; }
        wait_until(cq + SDLY_);
        int guard = 0; unsigned long long v0, v1, v2;
        for (;;) {
          v0 = ld_rlxu64(&g_sync[ph][lane]); v1 = ld_rlxu64(&g_sync[ph][lane + 32]); v2 = ld_rlxu64(&g_sync[ph][lane + 64]);
          if (__all_sync(~0u, (uint32_t)(v0 >> 32) == id && (uint32_t)(v1 >> 32) == id && (uint32_t)(v2 >> 32) == id)) break;
          if (++guard > (1 << 22)) TRAP();
        }
        const int dl = __reduce_max_sync(~0u, max(max((int)((uint32_t)v0 - tn), (int)((uint32_t)v1 - tn)), (int)((uint32_t)v2 - tn)));
        const uint32_t base = uni(cq + ((min(dl, 8 * 4096) * 7) >> 5));
        if (lane == 0) { sts32(sb + M_BASE + ph * 4, base); mbar_arrive(BAR(B_SYNC)); }
        CSTAMP(0, base); CSTAMP(1, clk());
        const uint32_t ts = base + YDLY_;
        uint32_t nr = 0;
        if (PRIV_) nr = __ballot_sync(~0u, lds32(sb + M_NEAR + (lane & 7) * 4) != 0);
        wait_until(ts);
        if (PRIV_ & 1) { for (int k = 0; k < 3; k++) e_g2s(sb + M_MEM + k * 3072, memg + k * 8192 + ((nr >> k) & 1) * 4096, 3072, BAR(B_LAND)); }
        else e_mc(sb + M_MEM + c * 3072, memg + s0, 3072, BAR(B_LAND), 7);
        CSTAMP(2, clk());
        spin_until(ts + Y1_);
        if (PRIV_ & 2) { for (int k = 3; k < 6; k++) e_g2s(sb + M_MEM + k * 3072, memg + k * 8192 + ((nr >> k) & 1) * 4096, 3072, BAR(B_LAND + 1)); }
        else e_mc(sb + M_MEM + (3 + c) * 3072, memg + s1, 3072, BAR(B_LAND + 1), 7);
        CSTAMP(3, clk());
        spin_until(ts + Y2_);
        if (PRIV_ & 4) { for (int k = 6; k < 8; k++) e_g2s(sb + M_MEM + k * 3072, memg + k * 8192 + ((nr >> k) & 1) * 4096, 3072, BAR(B_LAND + 2)); }
        else if (c < 2) e_mc(sb + M_MEM + (6 + c) * 3072, memg + s2, 3072, BAR(B_LAND + 2), 7);
        CSTAMP(4, clk());
      }
    } else if (w == 1) {
#pragma unroll 1
      for (int T = 0; T < NSTEP; T++) {
        const uint32_t ph = T & 1;
        const int s = c == 0 ? T : T - LAG;
        const bool act = s >= 0 && s < NSEG;
        mbar_wait(BAR(B_OST), ph);
        if (cta == 0) TSTAMP(2, T, 0);
        fence_async_smem();
        if (T < NSTEP - 1) wait_until(uni(lds32(sb + M_BASE + ph * 4)) + ODLY_);
        STAMP(22);
        if (act) { e_s2g(g_o[c][s % ORING][head], sb + M_OST, 8192); bulk_wait(); __syncwarp(); }
        e_arrive(BAR(B_OFREE));
        if (cta == 0) TSTAMP(2, T, 1);
        if (act) e_st_rel(&f_o[T][head >> 2][c * 4 + (head & 3)], E);
        if (cta == 0) TSTAMP(2, T, 2);
      }
    } else if (w == 2) {
      unsigned long long run = 0;
      static_assert(LAG >= 2, "config");
      constexpr uint32_t NA = EA / 4 * 4096;
      e_expect(BAR(B_QK), c < 2 ? 2048 : 4096); e_expect(BAR(B_V), c == 0 ? 10240 : c == 1 ? 2048 : 0);
      e_expect(BAR(B_TOK), c == 0 ? 16384 : 0); e_expect(BAR(B_OM), 4096);
      if (lane < 2) sts32(sb + M_CAND + lane * 4, (uint32_t)-1);
      e_expect(BAR(B_HA), NA); e_expect(BAR(B_HB), 65536 - NA);
      wait_eq(&f_h1[c == 1 ? 0 : 1], E); fence_async_glob();
      {
        const uint32_t o0 = c == 0 ? NA : 0, o1 = c == 2 ? NA : 32768;
        e_mc(sb + M_H + (c == 1 ? 32768 : 0) + o0, g_h[0][c == 1 ? 0 : 1] + o0, o1 - o0, BAR(c == 2 ? B_HA : B_HB), 7);
      }
      if (c == 2) wait_eq(&f_h1[2], E);
      mbar_wait(BAR(B_HAE), 1);
      e_expect(BAR(B_HA), NA);
      if (c == 2) { fence_async_glob(); e_mc(sb + M_H, g_h[0][2], NA, BAR(B_HA), 7); }
      int cprev = -1;
#pragma unroll 1
      for (int T = 0; T < NSTEP - 1; T++) {
        const int s1 = T + 2, s2 = T + 2 - LAG;
        const uint32_t ph = T & 1;
        const bool l1 = s1 < NSEG, l2 = s2 >= 0 && s2 < NSEG, la = s1 + 1 < NSEG;
        const bool mine = c == 0 ? l1 : c == 1 ? l2 : la;
        const uint32_t* fl = c != 1 ? &f_h1[min(s1 + (c >> 1), NSEG - 1)] : (const uint32_t*)&f_h2[max(s2, 0)][1];
        const uint32_t want = c != 1 ? E : E * 4u;
        mbar_wait(BAR(B_HBE), ph ^ 1);
        const bool early = uni(ld_acq(fl)) == want;
        mbar_wait(BAR(B_LAND + 2), ph);
        STAMP(16);
        e_expect(BAR(B_HB), (l1 ? 32768 - NA : 0) + (l2 ? 32768 : 0));
        if (mine) {
          if (!early) wait_eq(fl, want);
          fence_async_glob();
          if (c == 1) { mbar_wait(BAR(B_QK), ph); spin_until(clk32() + HDLY_); }
          if (c < 2) paced_h(sb + M_H + c * 32768, g_h[c][c ? s2 : s1], c ? 0 : NA, 32768, 4096, BAR(B_HB), HGAP_);
        }
        int cd = -1;
        if (l2) { cd = route_step(s2, E, run); if (cta == 0) TSTAMP(5, s2, 0); }
        if (lane == 0) sts32(sb + M_CAND + ((T + 2) & 3) * 4, (uint32_t)cd);
        __syncwarp();
        STAMP(17);
        mbar_wait(BAR(B_HAE), ph);
        e_expect(BAR(B_HA), la ? NA : 0);
        if (c == 2 && la) {
          spin_until(clk32() + ADLY_);
          STAMP(18);
          paced_h(sb + M_H, g_h[0][s1 + 1], 0, NA, 4096, BAR(B_HA), AGAP_);
        }
        mbar_wait(BAR(B_OST), ph);
        e_expect(BAR(B_QK), c < 2 ? 2048 : cprev >= 0 ? 8192 : 4096);
        e_expect(BAR(B_V), c < 2 ? 10240 : 8192);
        e_expect(BAR(B_TOK), 16384);
        e_expect(BAR(B_OM), 4096);
        cprev = cd;
      }
    } else {
      const uint32_t mytok = sb + M_Q + c * 12288 + 2048, tb = BAR(c < 2 ? B_TOK : B_V);
      mbar_wait(BAR(B_STG1), 0);
      fence_async_smem();
      e_s2g(g_tok[cta][1], sb + M_TST, 8192);
#pragma unroll 1
      for (int T = 0; T < NSTEP - 1; T++) {
        const uint32_t ph = T & 1;
        uint8_t* const tok = g_tok[cta][ph ^ 1];
        mbar_wait(BAR(B_STG), ph ^ 1);
        fence_async_smem();
        if (cta == 0 && (T == 0 || T == NSEG || T == NSTEP - 2)) GSTAMP(0, T == 0 ? 2 : T == NSEG ? 3 : 4);
        if (T > 0 && TQ_) mbar_wait(BAR(B_QK), ph);
        STAMP(20);
        uint32_t t = clk32();
        e_s2g(tok + 8192, sb + M_TST + 8192, 4096);
        spin_until(t + TGAP_);
        e_s2g(tok + 12288, sb + M_TST + 12288, 4096);
        bulk_wait();
        __syncwarp();
        e_arrive(BAR(B_TFREE));
        if (T == 0) e_mc(mytok, tok + 8192, 8192, tb, 1);
        STAMP(21);
#pragma unroll 1
        for (int k = 0; k < 2; k++) {
          if (k == 1) {
            mbar_wait(BAR(B_STG1), ph ^ 1);
            fence_async_smem();
            t = uni(lds32(sb + M_BASE + ph * 4));
            wait_until(t + TDLY_);
            e_s2g(g_tok[cta][ph], sb + M_TST, 8192);
          }
          if (k == (c >> 1)) {
            mbar_wait(BAR(c < 2 ? B_KFREE : B_VFREE), ph);
            t = k ? t + LDLY_ : clk32() + KDLY_;
            wait_until(t);
            STAMP(23);
            e_mc(mytok, tok, 8192, tb, 1);
            spin_until(t + LGAP_);
            e_mc(mytok, tok + 8192, 8192, tb, 6);
            STAMP(24);
          }
        }
      }
      bulk_wait();
    }
    __syncwarp();
    cluster_sync();
  }
}

constexpr uint32_t A_RING = 0;
constexpr int A_NST = 6;
constexpr uint32_t A_STG = A_RING + A_NST * 8192;
constexpr uint32_t A_WD = A_STG + 8192;
constexpr uint32_t A_WG = A_WD + 57344;
constexpr uint32_t A_WU = A_WG + 57344;
constexpr uint32_t A_XN = A_WU + 57344;
constexpr uint32_t A_BAR = A_XN + 2048;
constexpr uint32_t A_TOTAL = A_BAR + 256;
static_assert(A_TOTAL <= 232448, "aux smem");

__device__ __forceinline__ uint32_t ptag(int s) { return ((s / PRING) & 1) ^ 1; }
static_assert((NSEG / PRING) % 2 == 0, "tags");
__device__ __forceinline__ void load_row(uint32_t* v, const void* row, int lane) {
  const uint4 a = __ldcg((const uint4*)row + lane), b = __ldcg((const uint4*)row + 32 + lane);
  v[0] = a.x; v[1] = a.y; v[2] = a.z; v[3] = a.w; v[4] = b.x; v[5] = b.y; v[6] = b.z; v[7] = b.w;
}
__device__ __forceinline__ void store_row(void* row, const uint32_t* v, int lane) {
  ((uint4*)row)[lane] = make_uint4(v[0], v[1], v[2], v[3]); ((uint4*)row)[32 + lane] = make_uint4(v[4], v[5], v[6], v[7]);
}
__device__ __forceinline__ void store_img(uint8_t* img, int r, const uint32_t* v, int lane) {
  uint8_t* b = img + (lane >> 3) * 4096 + (r >> 3) * 1024 + (r & 7) * 128 + (((lane ^ r) & 7) << 4);
  *(uint4*)b = make_uint4(v[0], v[1], v[2], v[3]);
  *(uint4*)(b + 16384) = make_uint4(v[4], v[5], v[6], v[7]);
}
template <int NT> __device__ __forceinline__ void ln_rows(const uint32_t (*v)[8], uint32_t (*y)[8]) {
  float c[NT], sm[NT], sq[NT];
#pragma unroll
  for (int k = 0; k < NT; k++) {
    c[k] = blo(__shfl_sync(~0u, v[k][0], 0));
    float s0 = 0.f, s1 = 0.f, q0 = 0.f, q1 = 0.f;
#pragma unroll
    for (int i = 0; i < 8; i++) { const float a = blo(v[k][i]) - c[k], b = bhi(v[k][i]) - c[k]; s0 += a; s1 += b; q0 = fmaf(a, a, q0); q1 = fmaf(b, b, q1); }
    sm[k] = s0 + s1; sq[k] = q0 + q1;
  }
#pragma unroll
  for (int o = 16; o > 0; o >>= 1)
#pragma unroll
    for (int k = 0; k < NT; k++) {
      sm[k] += __shfl_xor_sync(~0u, sm[k], o); sq[k] += __shfl_xor_sync(~0u, sq[k], o);
    }
#pragma unroll
  for (int k = 0; k < NT; k++) {
    const float dm = sm[k] * (1.f / 512.f), var = fmaxf(fmaf(-dm, dm, sq[k] * (1.f / 512.f)), 0.f);
    const float mb = rbf(c[k] + dm), inv = rcp(rbf(sqrt_fast(rbf(rbf(var) + 1e-5f))));
#pragma unroll
    for (int i = 0; i < 8; i++) { const uint32_t a = pack2(blo(v[k][i]) - mb, bhi(v[k][i]) - mb); y[k][i] = pack2(blo(a) * inv, bhi(a) * inv); }
  }
}
__device__ __forceinline__ void input_ln_pair(const bf16* x, int s, int pr, int lane) {
  uint32_t v[2][8], y[2][8];
  load_row(v[0], x + (size_t)(s * 32 + 2 * pr) * 512, lane); load_row(v[1], x + (size_t)(s * 32 + 2 * pr + 1) * 512, lane);
  ln_rows<2>(v, y);
  store_img(g_h[0][s], 2 * pr, y[0], lane); store_img(g_h[0][s], 2 * pr + 1, y[1], lane);
}
__device__ __forceinline__ float load_wr(uint32_t* wv, const bf16* wr, int lane) {
  load_row(wv, wr, lane);
  float wsum = 0.f;
#pragma unroll
  for (int i = 0; i < 8; i++) wsum += blo(wv[i]) + bhi(wv[i]);
#pragma unroll
  for (int o = 16; o > 0; o >>= 1) wsum += __shfl_xor_sync(~0u, wsum, o);
  return wsum;
}

template <bool FAST>
__device__ __forceinline__ unsigned long long token_post(int st, int tk, const bf16* res, bf16* dst, bf16* req, unsigned long long best,
                                                         const uint32_t* wv, float wsum, uint32_t E, int lane) {
  const int s = tk >> 5;
  uint32_t x[8];
  load_row(x, res, lane);
  wait_hint(&f_acc[st][s * 8], E * 32u);
  if (tk == s * 32 && st == 0 && lane == 0) TSTAMP(4, s, 0);
  {
    const uint8_t* pp = g_pp[st][s % PRING] + (lane >> 4) * 8192 + (tk & 31) * 256 + (((lane & 15) ^ (tk & 7)) << 4);
    const uint32_t tag = ptag(s);
    uint4 q[8][2];
#define PLD(k, h) q[k][h] = ld_rlx128<(k) * 32768 + (h) * 16384>(pp)
#define PLD8(h) PLD(0, h); PLD(1, h); PLD(2, h); PLD(3, h); PLD(4, h); PLD(5, h); PLD(6, h); PLD(7, h)
#define PBAD(h) __any_sync(~0u, (or3(xo2(q[0][h].x, q[1][h].x, tag), xo2(q[2][h].x, q[3][h].x, tag), xo2(q[4][h].x, q[5][h].x, tag)) | xo2(q[6][h].x, q[7][h].x, tag)) & ~lane & (PST_ == 8192 ? 1u : 0u))
#define PAIR(k, h, m) add2(q[k][h].m, q[(k) + 4][h].m)
#define PSUM(f, h, m) (((f(q[0][h].m) + f(q[1][h].m)) + (f(q[2][h].m) + f(q[3][h].m))) + ((f(q[4][h].m) + f(q[5][h].m)) + (f(q[6][h].m) + f(q[7][h].m))))
#define PADD(i, h, m) if (!(PH_ & (FAST ? 1 : 2))) x[i] = add2(x[i], pack2(PSUM(blo, h, m), PSUM(bhi, h, m))); else \
                      { const uint32_t a = PAIR(0, h, m), b = PAIR(1, h, m), c = PAIR(2, h, m), d = PAIR(3, h, m); \
                        x[i] = add2(x[i], pack2((blo(a) + blo(b)) + (blo(c) + blo(d)), (bhi(a) + bhi(b)) + (bhi(c) + bhi(d)))); }
    int guard = 0;
    PLD8(0);
    if (FAST) { PLD8(1); }
    while (PBAD(0)) { if (++guard > (1 << 20)) TRAP(); PLD8(0); }
    PADD(0, 0, x); PADD(1, 0, y); PADD(2, 0, z); PADD(3, 0, w);
    if (!FAST) { PLD8(1); }
    while (PBAD(1)) { if (++guard > (1 << 20)) TRAP(); PLD8(1); }
    PADD(4, 1, x); PADD(5, 1, y); PADD(6, 1, z); PADD(7, 1, w);
  }
  const float c = blo(__shfl_sync(~0u, x[0], 0));
  float s0 = 0.f, s1 = 0.f, q0 = 0.f, q1 = 0.f, r0 = 0.f, r1 = 0.f;
#pragma unroll
  for (int i = 0; i < 8; i++) {
    const float a = blo(x[i]) - c, b = bhi(x[i]) - c;
    s0 += a; s1 += b; q0 = fmaf(a, a, q0); q1 = fmaf(b, b, q1); r0 = fmaf(a, blo(wv[i]), r0); r1 = fmaf(b, bhi(wv[i]), r1);
  }
  s0 += s1; q0 += q1; r0 += r1;
#pragma unroll
  for (int o = 16; o > 0; o >>= 1) { s0 += __shfl_xor_sync(~0u, s0, o); q0 += __shfl_xor_sync(~0u, q0, o); r0 += __shfl_xor_sync(~0u, r0, o); }
  const float dm = s0 * (1.f / 512.f), m = c + dm, var = fmaxf(fmaf(-dm, dm, q0 * (1.f / 512.f)), 0.f);
  const float mb = rbf(m), inv = rcp(rbf(sqrt_fast(rbf(rbf(var) + 1e-5f))));
  const uint32_t nmb = pack2(-mb, -mb);
  const unsigned long long wd = rword(E, tk, fmaf(c - mb, wsum, r0) * inv);
  uint32_t xn[8], x2[8];
#pragma unroll
  for (int i = 0; i < 8; i++) { const uint32_t d = add2(x[i], nmb); xn[i] = pack2(blo(d) * inv, bhi(d) * inv); x2[i] = add2(x[i], xn[i]); }
  if (st == 0) {
    const float mb2 = rbf(fmaf(m - mb, inv, m)), inv2 = rcp(rbf(sqrt_fast(rbf(rbf(var * (1.f + inv) * (1.f + inv)) + 1e-5f))));
    const uint32_t nmb2 = pack2(-mb2, -mb2);
    uint32_t h[8];
#pragma unroll
    for (int i = 0; i < 8; i++) { const uint32_t d2 = add2(x2[i], nmb2); h[i] = pack2(blo(d2) * inv2, bhi(d2) * inv2); }
    store_img(g_h[1][s], tk & 31, h, lane);
  }
  store_row(dst, x2, lane);
  if (wd > best) { store_row(req, xn, lane); store_row(req + 512, x, lane); }
  return wd;
}

__device__ __forceinline__ void ffn_slice(uint32_t sb, const bf16* xn, float* yacc, int t, bool urgent) {
  const int w = t >> 5, g = (t >> 2) & 7;
  if (t == 0 && urgent) sts32(sb + A_BAR + 160, 1);
  { const uint2 u = __ldcg((const uint2*)xn + t); asm volatile("st.shared.v2.u32 [%0], {%1,%2};" :: "r"(sb + A_XN + t * 8), "r"(u.x), "r"(u.y) : "memory"); }
  fence_async_smem();
  bar_sync(4, 128);
  float ga[4], ua[4];
  constexpr uint64_t da = mkdesc(A_WG, 896, 128, 0), db = mkdesc(A_XN, 16, 128, 0);
  wg_fence();
  wgmma_ss8<0, 1, 0>(ga, da, db); wgmma_ss8<0, 1, 0>(ua, da + (A_WU - A_WG) / 16, db);
#pragma unroll
  for (int ks = 1; ks < 32; ks++) { wgmma_ss8<1, 1, 0>(ga, da + ks * 112, db + ks * 2); wgmma_ss8<1, 1, 0>(ua, da + (A_WU - A_WG) / 16 + ks * 112, db + ks * 2); }
  wg_commit(); wg_wait<0>(); reg_fence(ga); reg_fence(ua);
  if ((t & 3) == 0) {
#pragma unroll
    for (int h = 0; h < 2; h++) {
      const float gs = rbf(ga[2 * h]), us = rbf(ua[2 * h]);
      const float v = 16 * w + 8 * h < 56 ? rbf(gs * rcp(1.f + __expf(-gs))) * us : 0.f;
      asm volatile("st.shared.u16 [%0], %1;" :: "r"(sb + A_XN + 1280 + (16 * w + 8 * h + g) * 2), "h"((unsigned short)pack2(v, 0.f)) : "memory");
    }
  }
  fence_async_smem();
  bar_sync(4, 128);
#pragma unroll 1
  for (int j = 0; j < 2; j++) {
    float y[4][4];
    const uint64_t dd = mkdesc(A_WD, 8192, 128, 0) + (uint64_t)(j * 256);
    wg_fence();
#pragma unroll
    for (int m = 0; m < 4; m++) {
      wgmma_ss8<0, 1, 0>(y[m], dd + m * 64, mkdesc(A_XN + 1280, 16, 128, 0));
#pragma unroll
      for (int ks = 1; ks < 4; ks++) wgmma_ss8<1, 1, 0>(y[m], dd + m * 64 + ks * 1024, mkdesc(A_XN + 1280 + ks * 32, 16, 128, 0));
    }
    wg_commit(); wg_wait<0>();
#pragma unroll
    for (int m = 0; m < 4; m++) {
      reg_fence(y[m]);
      if ((t & 3) == 0) { float* o = yacc + j * 256 + m * 64 + 16 * w + g; atomicAdd(o, y[m][0]); atomicAdd(o + 8, y[m][2]); }
    }
  }
  bar_sync(4, 128);
  if (t == 0) { sts32(sb + A_BAR + 160, 0); red_rel((uint32_t*)(yacc + 512), 1); }
  __syncwarp();
}

__device__ __forceinline__ void ffn_finish(int q, const bf16* req, float r, int lane, uint32_t* v) {
  uint32_t xn[8];
  load_row(xn, req, lane); load_row(v, req + 512, lane);
  const float rs = rbf(1.f / (1.f + __expf(-rbf(r))));
  wait_eq((const uint32_t*)&g_y[q][512], 32u);
  float4 y[4];
#pragma unroll
  for (int i = 0; i < 4; i++) y[i] = __ldcg((const float4*)g_y[q] + (i >> 1) * 64 + 2 * lane + (i & 1));
#pragma unroll
  for (int i = 0; i < 4; i++) {
    v[2 * i] = add2(v[2 * i], add2(xn[2 * i], pack2(rbf(y[i].x) * rs, rbf(y[i].y) * rs)));
    v[2 * i + 1] = add2(v[2 * i + 1], add2(xn[2 * i + 1], pack2(rbf(y[i].z) * rs, rbf(y[i].w) * rs)));
  }
}
__device__ __forceinline__ bool route2(int k, int ts, uint32_t E, int lane, unsigned long long& run) {
  unsigned long long m;
  if (k == 0) {
    if (lane < 2) wait_eq(&f_c2[(NSEG - LAG - 2 + lane) * 8], E * 64u);
    __syncwarp();
    const int s1 = min(lane + 32, NSEG - LAG - 1);
    const unsigned long long a = ld_rlxu64(&f_b2[lane < ts ? 0 : 1][lane]), b = ld_rlxu64(&f_b2[s1 < ts ? 0 : 1][s1]);
    m = warp_max<16>(a > b ? a : b);
  } else {
    const int s = NSEG - LAG + k - 1;
    wait_eq(&f_c2[s * 8], E * 64u);
    m = __shfl_sync(~0u, ld_rlxu64(&f_b2[s < ts ? 0 : 1][s]), 0);
  }
  if (k == 0 || m > run) { run = m; return true; }
  return false;
}

__global__ void __launch_bounds__(512, 1) aux_kernel(Params p) {
  extern __shared__ __align__(1024) uint8_t sm[];
  const uint32_t sb = smem_u32(sm);
  if ((sb & 0xFFFFFFu) != SBASE) TRAP();
  const int warp = __shfl_sync(~0u, threadIdx.x >> 5, 0);
  const int cta = blockIdx.x;
  const uint32_t E = __shfl_sync(~0u, *(volatile uint32_t*)&g_epoch + 1, 0);
  const uint32_t bars = sb + A_BAR;

  if (cta < 32) {
    const int cg = cta & 3, kg = cta >> 2;
    if (threadIdx.x == 0) {
      for (int i = 0; i < A_NST; i++) { mbar_init(bars + 8 * i, 1); mbar_init(bars + 64 + 8 * i, 2); }
      mbar_init(bars + 128, 8); mbar_init(bars + 136, 8); mbar_init(bars + 144, 1);
      sts32(bars + 160, 0);
      asm volatile("fence.mbarrier_init.release.cluster;" ::: "memory");
    }
    if (warp < 8) {
      asm volatile("setmaxnreg.inc.sync.aligned.u32 176;");
      const int tid = fresh_tid(), lane = tid & 31;
      uint32_t W[32][4];
      stage_weights(sb + A_WD, p.wo + (size_t)kg * 512 * 512 + cg * 128, 512, tid, 256);
      cp_async_wait();
      bar_sync(1, 256);
      load_frags(W, sb + A_WD, warp >> 2, warp & 3, lane);
      bar_sync(2, 512);
      const uint32_t so = sb + A_STG + ((lane >> 4) * 8 + (lane & 7)) * 256 + (((warp * 2 + ((lane >> 3) & 1)) ^ (lane & 7)) << 4);
      const uint32_t tm = lane < 4 ? 0x00010001u : 0u;
      int stage = 0; uint32_t ph = 0, job = 0;
#pragma unroll 1
      for (int T = 0; T < NSTEP; T++) {
#pragma unroll 1
        for (int k = 0; k < 3; k++) {
          const int st = k == 0 ? 0 : 3 - k, s = st == 0 ? T : T - LAG;
          if (s < 0 || s >= NSEG) continue;
          float d[16];
#pragma unroll
          for (int hh = 0; hh < 4; hh++) {
            mbar_wait(bars + 8 * stage, ph);
            while (uni(lds32(bars + 160))) __nanosleep(100);
            const uint64_t db = mkdesc(A_RING, 512, 128, 0) + (uint64_t)(stage * 512);
            wg_fence();
            if (hh == 0) wgmma_rs32<0, 0>(d, W[0], db); else wgmma_rs32<1, 0>(d, W[hh * 8], db);
#pragma unroll
            for (int ks = 1; ks < 8; ks++) wgmma_rs32<1, 0>(d, W[hh * 8 + ks], db + ks * 64);
            wg_commit();
            if (hh > 0) { wg_wait<1>(); if ((tid & 127) == 0) mbar_arrive(bars + 64 + 8 * (stage == 0 ? A_NST - 1 : stage - 1)); }
            if (++stage == A_NST) { stage = 0; ph ^= 1; }
          }
          mbar_wait(bars + 144, (job & 1) ^ 1);
          wg_wait<0>(); reg_fence(d);
          if ((tid & 127) == 0) mbar_arrive(bars + 64 + 8 * (stage == 0 ? A_NST - 1 : stage - 1));
          if (cta == 0 && tid == 0) TSTAMP(6, T, k);
          const uint32_t tv = tm * ptag(s);
#define TG(i) ((pack2(d[2 * (i)], d[2 * (i) + 1]) & ~tm) | tv)
          stmatrix4_t(so, TG(0), pack2(d[2], d[3]), TG(2), pack2(d[6], d[7]));
          stmatrix4_t(so + 4096, TG(4), pack2(d[10], d[11]), TG(6), pack2(d[14], d[15]));
          fence_async_smem();
          __syncwarp();
          if (lane == 0) mbar_arrive(bars + 128 + 8 * (job & 1));
          job++;
        }
      }
    } else if (warp < 12) {
      asm volatile("setmaxnreg.dec.sync.aligned.u32 120;");
      const int tid = fresh_tid(), lane = tid & 31;
      const int w = warp - 8, t = tid - 256;
#pragma unroll 1
      for (int s = cta + 4; s < NSEG; s += 32) {
#pragma unroll 1
        for (int pr = w; pr < 16; pr += 4) input_ln_pair(p.x, s, pr, lane);
        bar_sync(4, 128);
        if (t == 0) st_rel(&f_h1[s], E);
      }
      bar_sync(2, 512);
      { int guard = 0; while ((ld_rlx(&f_choice[cta * 3][0]) >> 1) != (E & 0x7FFFFFFFu)) { __nanosleep(200); if (++guard > (1 << 22)) TRAP(); } }
#pragma unroll 1
      for (int i = t; i < 512 * 7; i += 128) {
        const int k = i / 7, pc = i % 7;
        cp_async16(sb + A_WG + (k >> 3) * 896 + pc * 128 + (k & 7) * 16, p.wg + (size_t)k * 1792 + cta * 56 + pc * 8);
        cp_async16(sb + A_WU + (k >> 3) * 896 + pc * 128 + (k & 7) * 16, p.wu + (size_t)k * 1792 + cta * 56 + pc * 8);
        cp_async16(sb + A_WD + (i >> 9) * 8192 + (i & 63) * 128 + ((i >> 6) & 7) * 16, p.wd + (size_t)cta * 56 * 512 + i * 8);
      }
      uint32_t wv[8];
      const float wsum = load_wr(wv, p.wr, lane);
      cp_async_wait();
      fence_async_smem();
      wait_eq(&f_zero, E * 32u);
      bar_sync(4, 128);
      const int tj = (cta * 4 + w) & 31, st = 1 + ((cta >> 3) & 1), sq = cta >> 4;
      unsigned long long run = 0, run2 = 0, best = 0, hist = 0;
      uint32_t open = 0;
#pragma unroll 1
      for (int i = 0; i <= NSTEP; i++) {
        int tok = -1; const bf16* req = nullptr;
        if (i < NSEG) {
          const int cd = (int)uni(route_step(i, E, run));
          run = __shfl_sync(~0u, run, 0);
          hist = hist << 8 | (uint32_t)(cd + 1);
          if (cd >= 0) { tok = rtok(run); req = g_req1[tok][0]; }
        } else if (route2(i - NSEG, rtok(run) >> 5, E, lane, run2)) {
          tok = rtok(run2);
          req = g_req2[(tok >> 5) < (rtok(run) >> 5) ? 0 : 1][tok][0];
        }
        tok = __shfl_sync(~0u, tok, 0);
        if (tok >= 0) {
          if (cta == 0 && t == 0) TSTAMP(8, i, 0);
          ffn_slice(sb, req, g_y[i], t, i < NSEG);
          if (cta == 0 && t == 0) TSTAMP(8, i, 1);
        }
        const int s = i - LAG;
        if (s < 0 || i >= NSEG) continue;
        const int cd = (int)((hist >> (8 * LAG)) & 255) - 1;
        if (cd >= 0 && st == 2) best = 0;
        const int ts = rtok(run) >> 5;
        if ((s & 1) == sq) {
          const int tk = s * 32 + tj;
          if (st == 1 ? s < ts || i < NSEG - 1 : s >= ts) {
            if (st == 2 && cd == tj) wait_eq(&f_hc[s], E);
            const unsigned long long wd = token_post<false>(st, tk, st == 2 && cd == tj ? g_x2c[s] : g_x2 + (size_t)tk * 512,
                                                            (st == 2 || s < ts ? p.out : g_n) + (size_t)tk * 512, g_req2[st - 1][tk][0], best, wv, wsum, E, lane);
            best = max(best, wd);
            if (lane == 0) asm volatile("red.relaxed.gpu.global.max.u64 [%0], %1;" :: "l"(&f_b2[st - 1][s]), "l"(wd) : "memory");
            if (st == 1 && s >= ts) open |= 1u << (s >> 1);
          }
          __syncwarp();
          if (lane == 0) red_rel(&f_c2[s * 8], 1);
          __syncwarp();
        }
        if (st == 1) {
          if (i == NSEG - 1 && t == 0 && cta == 0) GSTAMP(1, 0);
#pragma unroll 1
          for (int n = i == NSEG - 1 ? 32 : 2; n > 0 && open; n--) {
            const int s0 = 2 * (__ffs(open) - 1) + sq;
            if (s0 >= ts) break;
            open &= open - 1;
            uint32_t v[8];
            load_row(v, g_n + (size_t)(s0 * 32 + tj) * 512, lane);
            wait_eq(&f_c2[s0 * 8], E * 64u);
            store_row(p.out + (size_t)(s0 * 32 + tj) * 512, v, lane);
          }
          if (i == NSEG - 1) {
            __syncwarp();
            if (lane == 0) red_rel(&f_cp, 1);
            if (t == 0 && cta == 0) GSTAMP(1, 3);
          }
        }
      }
    } else {
      asm volatile("setmaxnreg.dec.sync.aligned.u32 40;");
      const int tid = fresh_tid(), lane = tid & 31;
      const int t = tid - 384, w = warp - 12;
      for (int i = cta * 128 + t; i < (NSTEP + 1) * 544 / 4; i += 4096) ((float4*)&g_y[0][0])[i] = make_float4(0.f, 0.f, 0.f, 0.f);
      bar_sync(3, 128);
      if (t == 0) red_rel(&f_zero, 1);
      bar_sync(2, 512);
      if (w == 0) {
        const int k = lane >> 2, st = k == 0 ? 0 : 3 - k;
        int cnt = 0;
#pragma unroll 1
        for (int T = 0; T < NSTEP; T++) {
          const int s = st == 0 ? T : T - LAG;
          bool todo = lane < 12 && s >= 0 && s < NSEG;
          const int idx = cnt + lane - (T >= NSEG ? 4 : 0);
          const int stage = idx % A_NST; const uint32_t ph = ((idx / A_NST) & 1) ^ 1;
          const uint32_t* fl = &f_o[T][kg][st * 4 + (lane & 3)];
          const uint8_t* src = g_o[st][s % ORING][kg * 4 + (lane & 3)];
          bool ready = false; int guard = 0;
          uint32_t pend = __ballot_sync(~0u, todo);
          cnt += __popc(pend);
          while (pend) {
            if (todo && !ready) ready = ld_rlx(fl) == E;
            const bool go = todo && ready && (lane < A_NST || !((pend >> (lane - A_NST)) & 1)) && mbar_test(bars + 64 + 8 * stage, ph);
            if (go) { mbar_expect(bars + 8 * stage, OLOAD_); bulk_g2s(sb + A_RING + stage * 8192, src, OLOAD_, bars + 8 * stage); todo = false; }
            const uint32_t np = __ballot_sync(~0u, todo);
            if (np == pend) __nanosleep(40);
            pend = np;
            if (++guard > (1 << 22)) TRAP();
          }
          if (cta == 0 && lane == 0) TSTAMP(3, T, 0);
        }
      } else if (w < 3) {
        uint32_t job = 0;
#pragma unroll 1
        for (int T = 0; T < NSTEP; T++) {
#pragma unroll 1
          for (int k = 0; k < 3; k++) {
            const int st = k == 0 ? 0 : 3 - k, s = st == 0 ? T : T - LAG;
            if (s < 0 || s >= NSEG) continue;
            if ((job++ & 1) != w - 1) continue;
            if (s >= PRING && PCHK_) wait_eq(st == 0 ? (const uint32_t*)&f_h2[s - PRING][1] : &f_c2[(s - PRING) * 8], st == 0 ? E * 4u : E * 64u);
            mbar_wait(bars + 128 + 8 * (w - 1), ((job - 1) >> 1) & 1);
            if (cta == 0 && st == 0) TSTAMP(7, s, 0);
            e_s2g(g_pp[st][s % PRING] + cta * 8192, sb + A_STG, PST_);
            asm volatile("cp.async.bulk.commit_group;\n cp.async.bulk.wait_group.read 0;" ::: "memory");
            __syncwarp();
            e_arrive(bars + 144);
            bulk_wait();
            __syncwarp();
            if (lane == 0) asm volatile("red.relaxed.gpu.global.add.u32 [%0], 1;" :: "l"(&f_acc[st][s * 8]) : "memory");
            __syncwarp();
            if (cta == 0 && st == 0) TSTAMP(7, s, 1);
          }
        }
      }
    }
  } else {
    const int tid = fresh_tid(), lane = tid & 31;
    const int qd = cta - 32;
    input_ln_pair(p.x, qd, warp, lane);
    bar_sync(6, 512);
    if (tid == 0) st_rel(&f_h1[qd], E);
    volatile int* bc = (volatile int*)sm;
    if (warp == 15) {
      unsigned long long run = 0;
      wait_eq(&f_zero, E * 32u);
#pragma unroll 1
      for (int s = 0; s < NSEG; s++) {
        const int cd = route_step(s, E, run);
        if (cd >= 0 && qd == (s & 1)) {
          uint32_t v[1][8], h[1][8];
          ffn_finish(s, g_req1[s * 32 + cd][0], rscore(run), lane, v[0]);
          if (lane == 0) TSTAMP(8, s, 2);
          ln_rows<1>(v, h);
#pragma unroll
          for (int i = 0; i < 8; i++) st_rlx64(&g_hc[s][(i >> 2) * 128 + 4 * lane + (i & 3)], h[0][i], E);
          if (lane == 0) TSTAMP(8, s, 3);
          store_row(g_x2c[s], v[0], lane);
          __syncwarp();
          if (lane == 0) st_rel(&f_hc[s], E);
        }
      }
      wait_eq(&f_hc[rtok(run) >> 5], E);
      if (lane == 0) *bc = rtok(run);
      bar_sync(7, 288);
      if (qd == 1) {
        uint32_t v[8];
        const int ts = rtok(run) >> 5;
#pragma unroll 1
        for (int k = 0; k <= LAG; k++) {
          if (route2(k, ts, E, lane, run)) ffn_finish(NSEG + k, g_req2[(rtok(run) >> 5) < ts ? 0 : 1][rtok(run)][0], rscore(run), lane, v);
          if (k == LAG - 1) wait_eq(&f_cp, E * 64u);
        }
        if (lane == 0) GSTAMP(1, 1);
        store_row(p.out + (size_t)rtok(run) * 512, v, lane);
        if (lane == 0) GSTAMP(1, 2);
        asm volatile("griddepcontrol.wait;" ::: "memory");
        if (lane == 0) *(volatile uint32_t*)&g_epoch = E;
      }
    } else if (warp < 8) {
      uint32_t wv[8];
      const float wsum = load_wr(wv, p.wr, lane);
      unsigned long long best = 0;
      int ttok = 0;
#pragma unroll 1
      for (int i = 0; i < NSTEP; i++) {
        const bool last = i >= NSEG;
        if (i == NSEG) { bar_sync(7, 288); ttok = *bc; best = 0; }
        const int s = last ? i - LAG : i, st = !last ? 0 : s < (ttok >> 5) ? 1 : 2;
        const int tk = s * 32 + qd * 8 + warp;
        const unsigned long long wd = token_post<true>(st, tk, !last ? p.x + (size_t)tk * 512 : tk == ttok ? g_x2c[s] : g_x2 + (size_t)tk * 512,
                                                 (last ? p.out : g_x2) + (size_t)tk * 512, last ? g_req2[st - 1][tk][0] : g_req1[tk][0], best, wv, wsum, E, lane);
        best = max(best, wd);
        if (lane == 0) asm volatile("red.relaxed.gpu.global.max.u64 [%0], %1;" :: "l"(last ? &f_b2[st - 1][s] : f_h2[s]), "l"(wd) : "memory");
        bar_sync(5, 256);
        if (tid == 0) { if (qd == 0) TSTAMP(4, i, 1); red_rel(last ? &f_c2[s * 8] : (uint32_t*)(f_h2[s] + 1), last ? 16 : 1); if (qd == 0) TSTAMP(4, i, 2); }
        __syncwarp();
      }
    }
  }
}

}

extern "C" void kernel_launch(void* const* d_in, const int* in_sizes, int n_in, void* d_out, int out_size) {
  (void)in_sizes; (void)n_in; (void)out_size;
  static bool init = false;
  if (!init) {
    cudaFuncSetAttribute(main_kernel, cudaFuncAttributeMaxDynamicSharedMemorySize, M_TOTAL);
    cudaFuncSetAttribute(aux_kernel, cudaFuncAttributeMaxDynamicSharedMemorySize, A_TOTAL);
    init = true;
  }
  Params p;
  p.x = (const bf16*)d_in[0]; p.mem0 = (const bf16*)d_in[1]; p.wq = (const bf16*)d_in[2]; p.wk = (const bf16*)d_in[3];
  p.wv = (const bf16*)d_in[4]; p.wo = (const bf16*)d_in[5]; p.wr = (const bf16*)d_in[8]; p.wg = (const bf16*)d_in[9];
  p.wu = (const bf16*)d_in[10]; p.wd = (const bf16*)d_in[11]; p.out = (bf16*)d_out; p.zero = 0; p.zero2 = 0;
  cudaStream_t st = cudaStreamPerThread;
  main_kernel<<<96, 512, M_TOTAL, st>>>(p);
  cudaLaunchConfig_t cfg = {};
  cfg.gridDim = dim3(36); cfg.blockDim = dim3(512); cfg.dynamicSmemBytes = A_TOTAL; cfg.stream = st;
  cudaLaunchAttribute at[1];
  at[0].id = cudaLaunchAttributeProgrammaticStreamSerialization; at[0].val.programmaticStreamSerializationAllowed = 1;
  cfg.attrs = at; cfg.numAttrs = 1;
  cudaLaunchKernelEx(&cfg, aux_kernel, p);
}
```

```cpp
#include <cuda_runtime.h>
#include <cuda_bf16.h>
#include <stdint.h>

namespace {

typedef __nv_bfloat16 bf16;

constexpr int NSEG = 64;
#define LAG_ 5
constexpr int LAG = LAG_;
constexpr int NSTEP = NSEG + LAG;
constexpr int ORING = 8, PRING = 4;
#define E1_ 10
#define E2_ 0
#define E3_ 10
constexpr int E1 = E1_, E2 = E2_, E3 = E3_, EA = E1 + E2 + E3;
static_assert(EA % 4 == 0 && EA > 0 && EA < 32 && E1 > 0, "early part: whole 64-column chunks");
#define RW_ 176
#define RA_ 136
#define RC_ 24
#define STR2(x) #x
#define STR(x) STR2(x)
#define RED_ 30
#define ARR_ 7
#define HADD_ 1
#define PAUSE_ 21
#define PD1_ 4
#define PST2_ 2
#define PGR_ PD1_
#define DPOLL_ 0
#define SALT_ 0
#define KP1_ 1
#define EARLY_ 0
#define PRIV_ 1
#define OLOAD_ 8192
#define PST_ 8192
#define ALT_ 1
#define TQ_ 1
#define NOF_ 2
#define EXPQ_ 0
#define XT1_ 8192
#define XT2_ 4096
#define XO_ 8192
#define HINT_ 1
#define HAND_ 4
#define GO3_ 2
#define NPROBE_ 6
#define TP(i, v) (v)
#define XDLY_ TP(0, 2300)
#define YDLY_ TP(1, 3550)
#define X1_ TP(2, 100)
#define X2_ TP(3, 250)
#define Y1_ TP(4, 100)
#define Y2_ TP(5, 200)
#define HGAP_ TP(6, 50)
#define TGAP_ TP(7, 100)
#define ADLY_ TP(8, 600)
#define ODLY_ TP(9, 2700)
#define LDLY_ TP(10, 3800)
#define LGAP_ 200
#define HDLY_ TP(11, 0)
#define TDLY_ TP(15, 4200)
#define SDLY_ TP(12, 800)
#define AGAP_ 100
#define BOFF_ TP(13, 200)
#define YOFF_ TP(16, 200)
#define CDLY_ TP(17, 350)
#define SLOW0_ TP(18, 600)
#define SLOW1_ TP(19, 200)
#define KDLY_ TP(14, 300)
__device__ uint32_t g_epoch;
__device__ __align__(1024) uint8_t g_h[2][NSEG][32768];
__device__ __align__(128) uint2 g_hc[NSEG][256];
__device__ __align__(128) bf16 g_x2[2048 * 512];
__device__ __align__(128) bf16 g_x2c[NSEG][512];
__device__ __align__(128) uint8_t g_o[3][ORING][32][8192];
__device__ __align__(128) uint8_t g_pp[3][PRING][8 * 32768];
__device__ __align__(128) bf16 g_n[2048 * 512];
__device__ __align__(128) uint8_t g_xch[96 * 16384 + 65536 + 8192];
__device__ __align__(128) bf16 g_req1[2048][2][512];
__device__ __align__(128) bf16 g_req2[2][2048][2][512];
__device__ __align__(128) float g_y[NSTEP + 1][512];
__device__ __align__(128) uint8_t g_tok[96][2][16384];
__device__ uint32_t f_choice[96][2], f_loaded[32];
__device__ uint32_t f_h1[NSEG], f_hc[NSEG];
__device__ __align__(128) unsigned long long f_h2[NSEG][4][4];
__device__ __align__(128) unsigned long long f_w2[2][NSEG][32][4];
__device__ __align__(128) unsigned long long f_l2[LAG + 1][4];
__device__ __align__(128) uint32_t f_o[NSTEP][8][12][8];
__device__ __align__(128) uint32_t f_acc[3][NSEG][32][8], f_y[NSTEP + 1][32][8], f_zero[32], f_cp[64];
__device__ __align__(128) unsigned long long g_sync[2][96][4];

#define TRAP() __trap()
__device__ __forceinline__ uint32_t smem_u32(const void* p) { return (uint32_t)__cvta_generic_to_shared(p); }
__device__ __forceinline__ int fresh_tid() { const int t = threadIdx.x; return __shfl_sync(~0u, t, t & 31); }
__device__ __forceinline__ unsigned long long gtime64() { unsigned long long t; asm volatile("mov.u64 %0, %%globaltimer;" : "=l"(t) :: "memory"); return t; }
__device__ __forceinline__ uint32_t clk() { unsigned long long c; asm volatile("mov.u64 %0, %%clock64;" : "=l"(c) :: "memory"); return (uint32_t)c; }
__device__ __forceinline__ void wait_until(uint32_t t) {
  while ((int)(t - clk()) > 450) __nanosleep(32);
  uint32_t c;
  do { asm volatile("mov.u32 %0, %%clock;" : "=r"(c) :: "memory"); } while ((int)(c - t) < 0);
}
__device__ __forceinline__ void mbar_init(uint32_t bar, uint32_t cnt) { asm volatile("mbarrier.init.shared::cta.b64 [%0], %1;" :: "r"(bar), "r"(cnt) : "memory"); }
__device__ __forceinline__ void mbar_arrive(uint32_t bar) { asm volatile("mbarrier.arrive.shared::cta.b64 _, [%0];" :: "r"(bar) : "memory"); }
__device__ __forceinline__ void mbar_arrive_remote(uint32_t bar) { asm volatile("mbarrier.arrive.relaxed.cluster.shared::cluster.b64 _, [%0];" :: "r"(bar) : "memory"); }
__device__ __forceinline__ void mbar_expect(uint32_t bar, uint32_t bytes) { asm volatile("mbarrier.arrive.expect_tx.shared::cta.b64 _, [%0], %1;" :: "r"(bar), "r"(bytes) : "memory"); }
__device__ __forceinline__ bool mbar_try(uint32_t bar, uint32_t parity) {
  uint32_t ok;
  asm volatile("{.reg .pred p; mbarrier.try_wait.parity.shared::cta.b64 p, [%1], %2; selp.u32 %0, 1, 0, p;}" : "=r"(ok) : "r"(bar), "r"(parity) : "memory");
  return ok;
}
__device__ __forceinline__ bool mbar_test(uint32_t bar, uint32_t parity) {
  uint32_t ok;
  asm volatile("{.reg .pred p; mbarrier.test_wait.parity.shared::cta.b64 p, [%1], %2; selp.u32 %0, 1, 0, p;}" : "=r"(ok) : "r"(bar), "r"(parity) : "memory");
  return ok;
}
__device__ __forceinline__ void mbar_wait(uint32_t bar, uint32_t parity) {
  asm volatile("{\n.reg .pred p;\nWAIT:\nmbarrier.try_wait.parity.shared::cta.b64 p, [%0], %1;\n@!p bra WAIT;\n}" :: "r"(bar), "r"(parity) : "memory");
}
__device__ __forceinline__ uint32_t ld_acq(const uint32_t* p) { uint32_t v; asm volatile("ld.acquire.gpu.global.u32 %0, [%1];" : "=r"(v) : "l"(p) : "memory"); return v; }
__device__ __forceinline__ unsigned long long ld_acq64(const unsigned long long* p) { unsigned long long v; asm volatile("ld.acquire.gpu.global.u64 %0, [%1];" : "=l"(v) : "l"(p) : "memory"); return v; }
__device__ __forceinline__ void st_rel(uint32_t* p, uint32_t v) { asm volatile("st.release.gpu.global.u32 [%0], %1;" :: "l"(p), "r"(v) : "memory"); }
__device__ __forceinline__ void st_rel64(unsigned long long* p, unsigned long long v) { asm volatile("st.release.gpu.global.u64 [%0], %1;" :: "l"(p), "l"(v) : "memory"); }
__device__ __forceinline__ void red_rel(uint32_t* p, uint32_t v) { asm volatile("red.release.gpu.global.add.u32 [%0], %1;" :: "l"(p), "r"(v) : "memory"); }
__device__ __forceinline__ uint32_t ld_rlx(const uint32_t* p) { uint32_t v; asm volatile("ld.relaxed.gpu.global.u32 %0, [%1];" : "=r"(v) : "l"(p) : "memory"); return v; }
__device__ __forceinline__ unsigned long long ld_rlxu64(const unsigned long long* p) { unsigned long long v; asm volatile("ld.relaxed.gpu.global.u64 %0, [%1];" : "=l"(v) : "l"(p) : "memory"); return v; }
__device__ __forceinline__ void st_rlx(uint32_t* p, uint32_t v) { asm volatile("st.relaxed.gpu.global.u32 [%0], %1;" :: "l"(p), "r"(v) : "memory"); }
__device__ __forceinline__ void bulk_wait() { asm volatile("cp.async.bulk.commit_group;\n cp.async.bulk.wait_group 0;" ::: "memory"); }
__device__ __forceinline__ void fence_acq() { asm volatile("fence.acquire.gpu;" ::: "memory"); }
__device__ __forceinline__ void wait_all(const uint32_t* p, uint32_t v, bool acquire = true) {
  int guard = 0;
  while (!__all_sync(~0u, ld_rlx(p) == v)) { __nanosleep(32); if (++guard > (1 << 22)) TRAP(); }
  if (acquire) fence_acq();
}
__device__ __forceinline__ void wait_eq(const uint32_t* p, uint32_t v) {
  int guard = 0;
  while (ld_rlx(p) != v) { __nanosleep(64); if (++guard > (1 << 22)) TRAP(); }
  fence_acq();
}
__device__ __forceinline__ unsigned long long rword(uint32_t E, int tok, float r) {
  uint32_t u = __float_as_uint(r + 0.f);
  u = r != r ? 0u : (u >> 31) ? ~u : u | 0x80000000u;
  return (unsigned long long)(E & 0x1FFFFFu) << 43 | (unsigned long long)u << 11 | (uint32_t)(2047 - tok);
}
__device__ __forceinline__ int rtok(unsigned long long v) { return 2047 - (int)(v & 2047u); }
__device__ __forceinline__ float rscore(unsigned long long v) { const uint32_t u = (uint32_t)(v >> 11); return __uint_as_float((u >> 31) ? u & 0x7fffffffu : ~u); }
__device__ __forceinline__ bool rfresh(unsigned long long v, uint32_t E) { return (uint32_t)(v >> 43) == (E & 0x1FFFFFu); }
template <int TOP> __device__ __forceinline__ unsigned long long warp_max(unsigned long long v) {
#pragma unroll
  for (int o = TOP; o > 0; o >>= 1) { const unsigned long long ov = __shfl_xor_sync(~0u, v, o); v = ov > v ? ov : v; }
  return v;
}
template <int off> __device__ __forceinline__ uint2 ld_rlx64(const void* p) { unsigned long long v; asm volatile("ld.relaxed.gpu.global.b64 %0, [%1+%2];" : "=l"(v) : "l"(p), "n"(off) : "memory"); return make_uint2((uint32_t)v, (uint32_t)(v >> 32)); }
template <int off> __device__ __forceinline__ uint4 ld_rlx128(const void* p) {
  unsigned long long a, b; asm volatile("ld.relaxed.gpu.global.v2.b64 {%0,%1}, [%2+%3];" : "=l"(a), "=l"(b) : "l"(p), "n"(off) : "memory");
  return make_uint4((uint32_t)a, (uint32_t)(a >> 32), (uint32_t)b, (uint32_t)(b >> 32));
}
__device__ __forceinline__ void st_rlx64(void* p, uint32_t lo, uint32_t hi) { asm volatile("{.reg .b64 t; mov.b64 t, {%1,%2}; st.relaxed.gpu.global.b64 [%0], t;}" :: "l"(p), "r"(lo), "r"(hi) : "memory"); }
__device__ __forceinline__ void cp_async16(uint32_t dst, const void* src) { asm volatile("cp.async.cg.shared.global [%0], [%1], 16;" :: "r"(dst), "l"(src) : "memory"); }
__device__ __forceinline__ void cp_async_wait() { asm volatile("cp.async.wait_all;" ::: "memory"); }
__device__ __forceinline__ void fence_async_smem() { asm volatile("fence.proxy.async.shared::cta;" ::: "memory"); }
__device__ __forceinline__ void fence_async_glob() { asm volatile("fence.proxy.async.global;" ::: "memory"); }
__device__ __forceinline__ void fence_async_acq() { asm volatile("fence.proxy.async::generic.acquire.sync_restrict::shared::cluster.cluster;" ::: "memory"); }
__device__ __forceinline__ float ex2(float x) { float y; asm("ex2.approx.ftz.f32 %0, %1;" : "=f"(y) : "f"(x)); return y; }
__device__ __forceinline__ float sqrt_fast(float x) { float y; asm("sqrt.approx.ftz.f32 %0, %1;" : "=f"(y) : "f"(x)); return y; }
__device__ __forceinline__ float rcp(float x) { float y; asm("rcp.approx.ftz.f32 %0, %1;" : "=f"(y) : "f"(x)); return y; }
__device__ __forceinline__ void bar_sync(int id, int n) { asm volatile("bar.sync %0, %1;" :: "r"(id), "r"(n) : "memory"); }
__device__ __forceinline__ bool bar_or(int id, int n, bool v) {
  uint32_t r;
  asm volatile("{.reg .pred p, q; setp.ne.u32 p, %3, 0; barrier.cta.red.or.aligned.pred q, %1, %2, p; selp.u32 %0, 1, 0, q;}" : "=r"(r) : "r"(id), "r"(n), "r"((uint32_t)v) : "memory");
  return r;
}
__device__ __forceinline__ uint32_t mapa(uint32_t a, uint32_t rank) { uint32_t r; asm volatile("mapa.shared::cluster.u32 %0, %1, %2;" : "=r"(r) : "r"(a), "r"(rank)); return r; }
__device__ __forceinline__ void cluster_sync() { asm volatile("barrier.cluster.arrive.release.aligned; barrier.cluster.wait.acquire.aligned;" ::: "memory"); }
__device__ __forceinline__ void st_async32(uint32_t dst, uint32_t v, uint32_t bar) { asm volatile("st.async.shared::cluster.mbarrier::complete_tx::bytes.b32 [%0], %1, [%2];" :: "r"(dst), "r"(v), "r"(bar) : "memory"); }
__device__ __forceinline__ void bulk_g2s(uint32_t dst, const void* src, uint32_t bytes, uint32_t bar) {
  asm volatile("cp.async.bulk.shared::cluster.global.mbarrier::complete_tx::bytes [%0], [%1], %2, [%3];" :: "r"(dst), "l"(src), "r"(bytes), "r"(bar) : "memory");
}
__device__ __forceinline__ void bulk_g2s_mc(uint32_t dst, const void* src, uint32_t bytes, uint32_t bar, uint16_t mask) {
  asm volatile("cp.async.bulk.shared::cluster.global.mbarrier::complete_tx::bytes.multicast::cluster [%0], [%1], %2, [%3], %4;"
               :: "r"(dst), "l"(src), "r"(bytes), "r"(bar), "h"(mask) : "memory");
}
__device__ __forceinline__ void bulk_s2c(uint32_t dst, uint32_t src, uint32_t bytes, uint32_t bar) {
  asm volatile("cp.async.bulk.shared::cluster.shared::cta.mbarrier::complete_tx::bytes [%0], [%1], %2, [%3];" :: "r"(dst), "r"(src), "r"(bytes), "r"(bar) : "memory");
}
__device__ __forceinline__ void bulk_s2g(void* dst, uint32_t src, uint32_t bytes) {
  asm volatile("cp.async.bulk.global.shared::cta.bulk_group [%0], [%1], %2;" :: "l"(dst), "r"(src), "r"(bytes) : "memory");
}
#define ELECT(op) "{.reg .pred p; elect.sync _|p, 0xffffffff; @p " op "}"
__device__ __forceinline__ void e_arrive(uint32_t bar) { asm volatile(ELECT("mbarrier.arrive.shared::cta.b64 _, [%0];") :: "r"(bar) : "memory"); }
__device__ __forceinline__ void e_expect(uint32_t bar, uint32_t bytes) { asm volatile(ELECT("mbarrier.arrive.expect_tx.shared::cta.b64 _, [%0], %1;") :: "r"(bar), "r"(bytes) : "memory"); }
__device__ __forceinline__ void e_g2s(uint32_t dst, const void* src, uint32_t bytes, uint32_t bar) {
  asm volatile(ELECT("cp.async.bulk.shared::cluster.global.mbarrier::complete_tx::bytes [%0], [%1], %2, [%3];") :: "r"(dst), "l"(src), "r"(bytes), "r"(bar) : "memory");
}
__device__ __forceinline__ void e_mc(uint32_t dst, const void* src, uint32_t bytes, uint32_t bar, uint16_t mask) {
  asm volatile(ELECT("cp.async.bulk.shared::cluster.global.mbarrier::complete_tx::bytes.multicast::cluster [%0], [%1], %2, [%3], %4;")
               :: "r"(dst), "l"(src), "r"(bytes), "r"(bar), "h"(mask) : "memory");
}
__device__ __forceinline__ void e_s2g(void* dst, uint32_t src, uint32_t bytes) {
  asm volatile(ELECT("cp.async.bulk.global.shared::cta.bulk_group [%0], [%1], %2;") :: "l"(dst), "r"(src), "r"(bytes) : "memory");
}
__device__ __forceinline__ void e_st_rel(uint32_t* p, uint32_t v) { asm volatile(ELECT("st.release.gpu.global.u32 [%0], %1;") :: "l"(p), "r"(v) : "memory"); }
__device__ __forceinline__ uint32_t clk32() { uint32_t c; asm volatile("mov.u32 %0, %%clock;" : "=r"(c) :: "memory"); return c; }
__device__ __forceinline__ void spin_until(uint32_t t) { while ((int)(clk32() - t) < 0) {} }
__device__ __forceinline__ uint32_t uni(uint32_t v) { return __shfl_sync(~0u, v, 0); }
__device__ __forceinline__ uint32_t pack2(float lo, float hi) { uint32_t r; asm("cvt.rn.bf16x2.f32 %0, %1, %2;" : "=r"(r) : "f"(hi), "f"(lo)); return r; }
__device__ __forceinline__ uint32_t add2(uint32_t a, uint32_t b) { uint32_t r; asm("add.rn.bf16x2 %0, %1, %2;" : "=r"(r) : "r"(a), "r"(b)); return r; }
__device__ __forceinline__ float rbf(float x) { return __bfloat162float(__float2bfloat16_rn(x)); }
__device__ __forceinline__ float blo(uint32_t u) { return __uint_as_float(u << 16); }
__device__ __forceinline__ float bhi(uint32_t u) { return __uint_as_float(u & 0xffff0000u); }
__device__ __forceinline__ uint32_t gentag(uint32_t g) { return (g & 1u) | (g & 2u) << 15; }
__device__ __forceinline__ uint32_t pack2_tag(float lo, float hi, uint32_t tag) {
  const uint32_t u = __byte_perm(__float_as_uint(lo), __float_as_uint(hi), 0x7632);
  return u + ((u ^ tag) & 0x10001u);
}
__device__ __forceinline__ uint32_t xo2(uint32_t a, uint32_t b, uint32_t t) { uint32_t r; asm("lop3.b32 %0, %1, %2, %3, 0x7e;" : "=r"(r) : "r"(a), "r"(b), "r"(t)); return r; }
__device__ __forceinline__ uint32_t or3(uint32_t a, uint32_t b, uint32_t c) { uint32_t r; asm("lop3.b32 %0, %1, %2, %3, 0xfe;" : "=r"(r) : "r"(a), "r"(b), "r"(c)); return r; }
__device__ __forceinline__ void stmatrix4(uint32_t a, uint32_t r0, uint32_t r1, uint32_t r2, uint32_t r3) {
  asm volatile("stmatrix.sync.aligned.m8n8.x4.shared.b16 [%0], {%1,%2,%3,%4};" :: "r"(a), "r"(r0), "r"(r1), "r"(r2), "r"(r3) : "memory");
}
__device__ __forceinline__ void stmatrix4_t(uint32_t a, uint32_t r0, uint32_t r1, uint32_t r2, uint32_t r3) {
  asm volatile("stmatrix.sync.aligned.m8n8.x4.trans.shared.b16 [%0], {%1,%2,%3,%4};" :: "r"(a), "r"(r0), "r"(r1), "r"(r2), "r"(r3) : "memory");
}
__device__ __forceinline__ void ldmatrix4_t(uint32_t* r, uint32_t a) {
  asm volatile("ldmatrix.sync.aligned.m8n8.x4.trans.shared.b16 {%0,%1,%2,%3}, [%4];" : "=r"(r[0]), "=r"(r[1]), "=r"(r[2]), "=r"(r[3]) : "r"(a) : "memory");
}
__device__ __forceinline__ void ldmatrix4(uint32_t* r, uint32_t a) {
  asm volatile("ldmatrix.sync.aligned.m8n8.x4.shared.b16 {%0,%1,%2,%3}, [%4];" : "=r"(r[0]), "=r"(r[1]), "=r"(r[2]), "=r"(r[3]) : "r"(a) : "memory");
}
__device__ __forceinline__ void hmma16(float* c, const uint32_t* a, uint32_t b0, uint32_t b1) {
  asm volatile("mma.sync.aligned.m16n8k16.row.col.f32.bf16.bf16.f32 {%0,%1,%2,%3}, {%4,%5,%6,%7}, {%8,%9}, {%0,%1,%2,%3};"
               : "+f"(c[0]), "+f"(c[1]), "+f"(c[2]), "+f"(c[3]) : "r"(a[0]), "r"(a[1]), "r"(a[2]), "r"(a[3]), "r"(b0), "r"(b1));
}
__device__ __forceinline__ void hmma8(float* c, uint32_t a0, uint32_t a1, uint32_t b0) {
  asm volatile("mma.sync.aligned.m16n8k8.row.col.f32.bf16.bf16.f32 {%0,%1,%2,%3}, {%4,%5}, {%6}, {%0,%1,%2,%3};"
               : "+f"(c[0]), "+f"(c[1]), "+f"(c[2]), "+f"(c[3]) : "r"(a0), "r"(a1), "r"(b0));
}
__device__ __forceinline__ uint4 lds128(uint32_t a) { uint4 v; asm volatile("ld.shared.v4.u32 {%0,%1,%2,%3}, [%4];" : "=r"(v.x), "=r"(v.y), "=r"(v.z), "=r"(v.w) : "r"(a) : "memory"); return v; }
__device__ __forceinline__ void sts128(uint32_t a, uint4 v) { asm volatile("st.shared.v4.u32 [%0], {%1,%2,%3,%4};" :: "r"(a), "r"(v.x), "r"(v.y), "r"(v.z), "r"(v.w) : "memory"); }
__device__ __forceinline__ void sts128f(uint32_t a, float x, float y, float z, float w) { asm volatile("st.shared.v4.f32 [%0], {%1,%2,%3,%4};" :: "r"(a), "f"(x), "f"(y), "f"(z), "f"(w) : "memory"); }
__device__ __forceinline__ void sts64f(uint32_t a, float x, float y) { asm volatile("st.shared.v2.f32 [%0], {%1,%2};" :: "r"(a), "f"(x), "f"(y) : "memory"); }
__device__ __forceinline__ uint32_t lds32(uint32_t a) { uint32_t v; asm volatile("ld.shared.u32 %0, [%1];" : "=r"(v) : "r"(a) : "memory"); return v; }
__device__ __forceinline__ void sts32(uint32_t a, uint32_t v) { asm volatile("st.shared.u32 [%0], %1;" :: "r"(a), "r"(v) : "memory"); }

constexpr uint32_t SBASE = 1024;
__host__ __device__ constexpr uint64_t mkdesc(uint32_t off, uint32_t lbo, uint32_t sbo, uint32_t swz) {
  return (uint64_t)(((SBASE + off) & 0x3FFFF) >> 4) | ((uint64_t)(lbo >> 4) << 16) | ((uint64_t)(sbo >> 4) << 32) | ((uint64_t)swz << 62);
}
__device__ __forceinline__ void wg_fence() { asm volatile("wgmma.fence.sync.aligned;" ::: "memory"); }
__device__ __forceinline__ void wg_commit() { asm volatile("wgmma.commit_group.sync.aligned;" ::: "memory"); }
template <int N> __device__ __forceinline__ void wg_wait() { asm volatile("wgmma.wait_group.sync.aligned %0;" :: "n"(N) : "memory"); }

template <int N> __device__ __forceinline__ void reg_fence(float (&d)[N], int n = N) {
#pragma unroll
  for (int i = 0; i < N; i++) if (i < n) asm volatile("" : "+f"(d[i]) :: "memory");
}
#define F4(b) "+f"(d[b]), "+f"(d[b + 1]), "+f"(d[b + 2]), "+f"(d[b + 3])
#define F8(b) F4(b), F4(b + 4)
#define F16(b) F8(b), F8(b + 8)
#define G4(b) "=f"(d[b]), "=f"(d[b + 1]), "=f"(d[b + 2]), "=f"(d[b + 3])
#define G8(b) G4(b), G4(b + 4)
#define G16(b) G8(b), G8(b + 8)
#define RS_IN "r"(a[0]), "r"(a[1]), "r"(a[2]), "r"(a[3]), "l"(db), "n"(SD), "n"(TB)
#define SS_IN "l"(da), "l"(db), "n"(SD), "n"(TA), "n"(TB)
#define WG_OP(str, out0, out1, in) do { if (SD || KEEP) asm volatile(str : out1 : in); else asm volatile(str : out0 : in); } while (0)
#define O12(X) X##8(0), X##4(8)
#define O20(X) X##16(0), X##4(16)
#define O32(X) X##16(0), X##16(16)
template <int SD, int TB, int KEEP = 0> __device__ __forceinline__ void wgmma_rs24(float* d, const uint32_t* a, uint64_t db) {
  WG_OP("wgmma.mma_async.sync.aligned.m64n24k16.f32.bf16.bf16 {%0,%1,%2,%3,%4,%5,%6,%7,%8,%9,%10,%11}, {%12,%13,%14,%15}, %16, %17, 1, 1, %18;", O12(G), O12(F), RS_IN);
}
template <int SD, int TB, int KEEP = 0> __device__ __forceinline__ void wgmma_rs32(float* d, const uint32_t* a, uint64_t db) {
  WG_OP("wgmma.mma_async.sync.aligned.m64n32k16.f32.bf16.bf16 {%0,%1,%2,%3,%4,%5,%6,%7,%8,%9,%10,%11,%12,%13,%14,%15}, {%16,%17,%18,%19}, %20, %21, 1, 1, %22;", G16(0), F16(0), RS_IN);
}
template <int SD, int TB, int KEEP = 0> __device__ __forceinline__ void wgmma_rs40(float* d, const uint32_t* a, uint64_t db) {
  WG_OP("wgmma.mma_async.sync.aligned.m64n40k16.f32.bf16.bf16 {%0,%1,%2,%3,%4,%5,%6,%7,%8,%9,%10,%11,%12,%13,%14,%15,"
        "%16,%17,%18,%19}, {%20,%21,%22,%23}, %24, %25, 1, 1, %26;", O20(G), O20(F), RS_IN);
}
template <int SD, int TB, int KEEP = 0> __device__ __forceinline__ void wgmma_rs64(float* d, const uint32_t* a, uint64_t db) {
  WG_OP("wgmma.mma_async.sync.aligned.m64n64k16.f32.bf16.bf16 {%0,%1,%2,%3,%4,%5,%6,%7,%8,%9,%10,%11,%12,%13,%14,%15,"
        "%16,%17,%18,%19,%20,%21,%22,%23,%24,%25,%26,%27,%28,%29,%30,%31}, {%32,%33,%34,%35}, %36, %37, 1, 1, %38;", O32(G), O32(F), RS_IN);
}
template <int SD, int TA, int TB, int KEEP = 0> __device__ __forceinline__ void wgmma_ss24(float* d, uint64_t da, uint64_t db) {
  WG_OP("wgmma.mma_async.sync.aligned.m64n24k16.f32.bf16.bf16 {%0,%1,%2,%3,%4,%5,%6,%7,%8,%9,%10,%11}, %12, %13, %14, 1, 1, %15, %16;", O12(G), O12(F), SS_IN);
}
template <int SD, int TA, int TB, int KEEP = 0> __device__ __forceinline__ void wgmma_ss8(float* d, uint64_t da, uint64_t db) {
  WG_OP("wgmma.mma_async.sync.aligned.m64n8k16.f32.bf16.bf16 {%0,%1,%2,%3}, %4, %5, %6, 1, 1, %7, %8;", G4(0), F4(0), SS_IN);
}
__device__ __forceinline__ void bar_arrive(int id, int n) { asm volatile("bar.arrive %0, %1;" :: "r"(id), "r"(n) : "memory"); }
__device__ __forceinline__ uint32_t vis_bits(int pos, int t) {
  uint32_t m = 0;
#pragma unroll
  for (int i = 0; i < 8; i++) m |= (8 * (i / 2 + 1) + 2 * t + (i & 1) <= pos) ? 1u << i : 0u;
  return m;
}

__device__ __forceinline__ unsigned long long wait_words(const unsigned long long* p, uint32_t E) {
  int guard = 0; unsigned long long m;
  while (m = ld_rlxu64(p), !__all_sync(~0u, rfresh(m, E))) { __nanosleep(32); if (++guard > (1 << 22)) TRAP(); }
  fence_acq();
  return m;
}
__device__ __forceinline__ int route_step(int s, uint32_t E, int lane, unsigned long long& run) {
  const unsigned long long m = warp_max<2>(wait_words(f_h2[s][lane & 3], E));
  if (s == 0 || m > run) { run = m; return rtok(m) & 31; }
  return -1;
}

struct Params {
  const bf16 *x, *mem0, *wq, *wk, *wv, *wo, *wr, *wg, *wu, *wd;
  bf16* out;
  uint32_t zero2;
  unsigned long long zero;
};

constexpr uint32_t WSTG_STRIDE = 272;
__device__ __forceinline__ void stage_weights(uint32_t stg, const bf16* src, int ld, int tid, int nthr) {
  for (int i = tid; i < 512 * 16; i += nthr) {
    int k = i >> 4, c = i & 15;
    cp_async16(stg + k * WSTG_STRIDE + c * 16, src + (size_t)k * ld + c * 8);
  }
}
__device__ __forceinline__ void load_frags(uint32_t (*W)[4], uint32_t stg, int wg, int w, int lane) {
  uint32_t a = stg + ((lane >> 4) * 8 + (lane & 7)) * WSTG_STRIDE + (64 * wg + 16 * w + ((lane >> 3) & 1) * 8) * 2;
#pragma unroll
  for (int ks = 0; ks < 32; ks++) ldmatrix4_t(W[ks], a + ks * 16 * WSTG_STRIDE);
}

constexpr uint32_t M_H = 0;
constexpr uint32_t M_MEM = 65536;
constexpr uint32_t M_Q = M_MEM + 24576;
constexpr uint32_t M_K = M_Q + 12288;
constexpr uint32_t M_V = M_K + 12288;
constexpr uint32_t M_OM = M_V + 12288;
constexpr uint32_t M_OST = M_OM + 6144;
constexpr uint32_t M_TST = M_OST + 8192;
constexpr uint32_t M_WO = M_TST + 16384;
constexpr uint32_t M_M0 = M_WO + 49152;
constexpr uint32_t M_PT = M_M0 + 2048;
constexpr uint32_t M_BAR = M_PT + 12288;
constexpr uint32_t M_TOTAL = M_BAR + 384;
static_assert(M_TOTAL <= 232448, "main smem");
static_assert(M_WO >= 512 * WSTG_STRIDE, "staging overlaps Wo");
enum { B_LAND = 0  , B_QK = 3, B_V, B_TOK, B_OM, B_HA, B_HB, B_HAE, B_HBE, B_OST, B_OFREE, B_SYNC,
       B_STG, B_STG1, B_SS, B_TFREE, B_KFREE, B_VFREE, B_FIX  , B_NUM = B_FIX + 8 };
static_assert(B_NUM * 8 <= 256, "barriers");
constexpr uint32_t M_CAND = M_BAR + 256;
constexpr uint32_t M_BASE = M_BAR + 272;
constexpr uint32_t M_ZERO = M_BAR + 280;
constexpr uint32_t M_NEAR = M_BAR + 288;
enum { N_GO1 = 2, N_GO2, N_GO3, N_GO4, N_AG, N_W };

#define GSTAMP(slot, i)
#define TSTAMP(slot, i, k)
#define STAMP(i)
#define ASTAMP(i)
#define WSTAMP(i)
#define CSTAMP(i, v)
#define PIN(x) asm volatile("" : "+r"(x))
#define SCHED(k) asm volatile("{\n.reg .pred p;\nsetp.ne.u32 p, %0, 0;\n@p trap;\n}" :: "r"(zz & (1u << (k))) : "memory")
#define HOLD(k, v) asm volatile("{\n.reg .pred p;\nsetp.ne.u32 p, %0, 0;\n@p st.shared.u32 [%0], %1;\n}" :: "r"(zz & (1u << (k))), "r"(v) : "memory")
#define DRAIN(a) (lds32((a) + zz) & zz)
#define BAR(i) (sb + M_BAR + 8 * (i))

__device__ __forceinline__ int probe(const uint8_t* p, int n) {
  int best = 1 << 30; uint32_t v = 0;
#pragma unroll 1
  for (int r = 0; r < n; r++) {
    uint32_t t0 = clk();
    asm volatile("atom.relaxed.gpu.global.or.b32 %0, [%1], %2;" : "=r"(v) : "l"(p + 3968), "r"(v & 0u) : "memory");
    if (v == 0x7fffffffu) t0++;
    best = min(best, (int)(clk() - t0));
  }
  return best;
}
__device__ __forceinline__ void load_mem0(uint4* u, int k0, int lane, const bf16* mem0) {
#pragma unroll
  for (int i = 0; i < 2; i++) {
    const unsigned short* m = (const unsigned short*)mem0 + k0 + lane + 32 * i;
    u[i] = make_uint4(m[0] | (uint32_t)m[512] << 16, m[1024] | (uint32_t)m[1536] << 16, m[2048] | (uint32_t)m[2560] << 16, m[3072] | (uint32_t)m[3584] << 16);
  }
}

__device__ __forceinline__ void paced_h(uint32_t dst, const uint8_t* src, uint32_t o0, uint32_t o1, uint32_t piece, uint32_t bar, int gap) {
  uint32_t t = clk32();
#pragma unroll 1
  for (uint32_t o = o0; o < o1; o += piece) {
    e_mc(dst + o, src + o, piece, bar, 7);
    spin_until(t += gap);
  }
}

__device__ __forceinline__ void weight_role(const Params& p, const uint32_t sb, const int warp, const int cta, const int C, const uint32_t E,
                                            const uint8_t* const memg) {
  const int tid = fresh_tid(), lane = tid & 31;
  const int wg = warp >> 2, w = warp & 3;
  uint32_t W[32][4];
  cp_async_wait();
  bar_sync(1, 256);
  load_frags(W, sb, wg, w, lane);
  bar_sync(1, 256);
  if (tid < 128) sts128(sb + M_V + 5 * 2048 + tid * 16, make_uint4(0, 0, 0, 0));
  fence_async_smem();
  cluster_sync();
  if (tid == 0 && cta == 0) GSTAMP(0, 1);
  if (tid == 0) TSTAMP(13, cta, 0);

  const uint32_t rba = mapa(sb, C == 2 ? 0 : 2), rbc = mapa(sb, C == 1 ? 0 : 1);
  const uint32_t MYBAR = M_BAR + 8 * (C < 2 ? B_QK : B_V);
  uint32_t qoff = M_Q + C * 12288 + warp * 256 + lane * 4;
  uint32_t toff = sb + warp * 256 + (lane >> 4) * 2048 + (lane & 15) * 16;
  uint32_t rbar = mapa(sb + M_BAR, min(lane, 2));
  uint32_t sv = sb + M_MEM + lane * 32 + ((lane >> 2) & 3) * 8;
  PIN(qoff); PIN(toff); PIN(rbar); PIN(sv);
  const uint32_t gen0 = (E - 1) * (uint32_t)(NSTEP - 1);
  uint32_t fix = 0;
  const bool sig = w == 0 && lane < 3;
  const int pk = PAUSE_ + (cta < 36 ? 0 : cta < 72 ? PD1_ : 2 * PD1_) + (wg ? -PST2_ : PST2_);
  int cand = -1;
  float d[16];
#pragma unroll
  for (int i = 0; i < 16; i++) d[i] = 0.f;
  uint32_t tp[8];
#pragma unroll 1
  for (int T = -1; T < NSTEP; T++) {
    const uint32_t ph = T & 1;
    const uint64_t Z = p.zero << ph;
    const uint32_t zz = p.zero2;
    if (T >= 0) {
      WSTAMP(0);
      const uint64_t db = mkdesc(M_MEM, 128, 256, 0) + Z;
      stmatrix4(toff + M_TST + 8192, tp[0], tp[1], tp[2], tp[3]); stmatrix4(toff + M_TST + 12288, tp[4], tp[5], tp[6], tp[7]);
      if (sig) mbar_arrive_remote(rbar + 8 * B_HBE);
      mbar_wait(BAR(B_LAND), ph);
      WSTAMP(1);
      const uint32_t gt = gentag(gen0 + T);
      auto old = [&](uint32_t a) { return lds32(a) ^ gt; };
      uint32_t bad = 0;
      bool redo = false, ready = false;
      wg_fence();
      wgmma_rs24<0, 1, KP1_>(d, W[0], db);
#pragma unroll
      for (int ks = 1; ks < 32; ks++) {
        if (ks == 2 || ks == 14) bad |= xo2(lds32(sv + (ks == 2 ? 0 : 9) * 1024 + warp * 1024), lds32(sv + (ks == 2 ? 8 : 17) * 1024), gt);
        if (ks == 25) bad |= old(sv + (18 + min(warp, 5)) * 1024);
        if (ks == 6) {
          const uint32_t z5 = DRAIN(toff + M_TST);
          __syncwarp();
          if (lane == 0) mbar_arrive(BAR(B_STG) + z5);
        }
        if (ks == 27) ready = mbar_test(BAR(C < 2 ? B_KFREE : B_VFREE), ph ^ 1) & mbar_test(BAR(B_HA), ph);
        if ((EARLY_ && (ks == 9 || ks == 21)) || ks == RED_) redo = bar_or(N_W, 256, T > 0 && (bad & 0x10001u));
        if (ks == 12 || ks == 24) {
          if (EARLY_ && __builtin_expect(redo, 0)) break;
          mbar_wait(BAR(B_LAND + ks / 12), ph); WSTAMP(6 + ks / 12); wg_fence();
        }
        wgmma_rs24<1, 1>(d, W[ks], db + ks * 48);
      }
      wg_commit();
      uint32_t a0 = rba + qoff, a1 = a0 + 128, a2 = rbc + qoff, a3 = a2 + 128, ba = rba + MYBAR, bc = rbc + MYBAR;
      PIN(a0); PIN(a1); PIN(a2); PIN(a3); PIN(ba); PIN(bc);
      if (!ready) {
        mbar_wait(BAR(C < 2 ? B_KFREE : B_VFREE), ph ^ 1);
        if (T < NSTEP - 1) mbar_wait(BAR(B_HA), ph);
      }
      wg_wait<0>(); reg_fence(d);
      if (__builtin_expect(redo, 0)) {
        auto stale = [&]() { return __any_sync(~0u, (old(sv + warp * 3072) | old(sv + warp * 3072 + 1024) | old(sv + warp * 3072 + 2048)) & 0x10001u); };
        auto fetch = [&](int r) {
          e_expect(BAR(B_FIX + warp), 3072);
          e_g2s(sb + M_MEM + warp * 3072, memg + warp * 8192 + ((uni(lds32(sb + M_NEAR + warp * 4)) ^ r) & 1) * 4096, 3072, BAR(B_FIX + warp));
        };
        mbar_wait(BAR(B_LAND + warp / 3), ph);
        bool late = stale();
        if (late) fetch(0);
        constexpr uint64_t dc = mkdesc(M_MEM, 128, 256, 0);
#pragma unroll
        for (int ks = 0; ks < 32; ks++) {
          if (ks % 12 == 0) {
            if (ks) { wg_commit(); wg_wait<0>(); reg_fence(d); }
            if (warp / 3 == ks / 12) {
              for (int guard = 0; late; guard++) {
                mbar_wait(BAR(B_FIX + warp), fix); fix ^= 1;
                late = stale();
                if (late) fetch(ALT_ ? guard + 1 : 0);
                if (guard > (1 << 20)) TRAP();
              }
            }
            bar_sync(N_W, 256);
            wg_fence();
          }
          if (ks == 0) wgmma_rs24<0, 1, 1>(d, W[0], dc); else wgmma_rs24<1, 1>(d, W[ks], dc + ks * 48);
        }
        wg_commit();
        wg_wait<0>(); reg_fence(d);
      }
      WSTAMP(2);
      if (T == 0 && tid == 0) TSTAMP(13, cta, 2);
      uint32_t lo[3], hi[3];
#pragma unroll
      for (int j = 0; j < 3; j++) { lo[j] = pack2(d[4 * j], d[4 * j + 1]); hi[j] = pack2(d[4 * j + 2], d[4 * j + 3]); }
      if (__builtin_expect(T == 0, 0)) { sts32(sb + M_M0 + tid * 8, lo[0]); sts32(sb + M_M0 + tid * 8 + 4, hi[0]); }
      if (__builtin_expect(cand >= 0, 0)) {
        if (T == LAG) { lo[1] = lds32(sb + M_M0 + tid * 8); hi[1] = lds32(sb + M_M0 + tid * 8 + 4); }
        if (C < 2) { st_async32(a0 + 5 * 2048, lo[2], ba); st_async32(a1 + 5 * 2048, hi[2], ba); }
        else { sts32(sb + qoff + 5 * 2048, lo[2]); sts32(sb + qoff + 5 * 2048 + 128, hi[2]); }
        lo[2] = lo[1]; hi[2] = hi[1];
      }
      uint32_t z5;
      if (C == 0) {
        sts32(sb + qoff, lo[0]); sts32(sb + qoff + 128, hi[0]); z5 = DRAIN(sb + qoff);
        st_async32(a0, lo[2], ba); st_async32(a1, hi[2], ba); st_async32(a2, lo[1], bc); st_async32(a3, hi[1], bc);
      } else if (C == 1) {
        sts32(sb + qoff, lo[1]); sts32(sb + qoff + 128, hi[1]); z5 = DRAIN(sb + qoff);
        st_async32(a0, lo[2], ba); st_async32(a1, hi[2], ba); st_async32(a2, lo[0], bc); st_async32(a3, hi[0], bc);
      } else {
        sts32(sb + qoff, lo[2]); sts32(sb + qoff + 128, hi[2]); z5 = DRAIN(sb + qoff);
        st_async32(a0, lo[0], ba); st_async32(a1, hi[0], ba); st_async32(a2, lo[1], bc); st_async32(a3, hi[1], bc);
      }
      __syncwarp();
      if (lane == 0) { mbar_arrive(sb + MYBAR + z5); if (w == 3) mbar_arrive(BAR(B_SS)); }
      if (T == NSTEP - 1) break;
    }
    {
      const uint64_t dh = mkdesc(M_H, 16, 1024, 1) + Z;
      static_assert(E2 == 0 && E3 > 0 && PAUSE_ > 0, "config");
      if (T + 2 < NSEG) {
        if (T < 0) mbar_wait(BAR(B_HA), ph);
        WSTAMP(3);
        wg_fence();
        wgmma_rs32<0, 0, 1>(d, W[0], dh);
#pragma unroll
        for (int ks = 1; ks < EA; ks++) {
          if (ks == E1) { wg_commit(); if (T >= 0) bar_sync(N_GO2, 384); wg_fence(); }
          wgmma_rs32<1, 0>(d, W[ks], dh + (ks >> 2) * 256 + (ks & 3) * 2);
        }
        wg_commit();
        mbar_wait(BAR(B_HB), ph);
        wg_wait<0>();
        if (sig) mbar_arrive_remote(rbar + 8 * B_HAE);
        WSTAMP(4);
        if (T >= 0) bar_sync(N_GO3, 384);
        if (wg == 1) bar_sync(N_W, 256);
        wg_fence();
#pragma unroll
        for (int ks = EA; ks < 32; ks++) wgmma_rs32<1, 0>(d, W[ks], dh + (ks >> 2) * 256 + (ks & 3) * 2);
        wg_commit();
        if (wg == 0) bar_arrive(N_W, 256);
        mbar_wait(BAR(B_TFREE), ph ^ 1);
        wg_wait<0>(); reg_fence(d);
      } else {
        bar_sync(N_GO2, 384);
        mbar_wait(BAR(B_HB), ph);
        if (sig) mbar_arrive_remote(rbar + 8 * B_HAE);
        bar_sync(N_GO3, 384);
        mbar_wait(BAR(B_TFREE), ph ^ 1);
      }
#pragma unroll
      for (int i = 0; i < 8; i++) { tp[i] = pack2(d[2 * i], d[2 * i + 1]); PIN(tp[i]); }
      auto staged = [&]() {
        const uint32_t z5 = DRAIN(toff + M_TST);
        __syncwarp();
        if (lane == 0) mbar_arrive(BAR(B_STG1) + z5);
      };
      if (T < 0 || (T + 2 >= LAG && T + 2 < NSTEP)) {
        wg_fence();
        wgmma_rs32<0, 0, 1>(d, W[0], dh + 2048);
        stmatrix4(toff + M_TST, tp[0], tp[1], tp[2], tp[3]); stmatrix4(toff + M_TST + 4096, tp[4], tp[5], tp[6], tp[7]);
#pragma unroll
        for (int ks = 1; ks < 32; ks++) {
          if (ks == 5) staged();
          if (ks >= PAUSE_ - PST2_ && ks <= PAUSE_ + 2 * PD1_ + PST2_ && (ks - PAUSE_ + PST2_) % PGR_ == 0) {
            wg_commit();
            if (T >= 0 && ks == pk) bar_sync(N_GO4, 384);
            wg_fence();
          }
          wgmma_rs32<1, 0>(d, W[ks], dh + 2048 + (ks >> 2) * 256 + (ks & 3) * 2);
        }
        wg_commit();
      } else {
        stmatrix4(toff + M_TST, tp[0], tp[1], tp[2], tp[3]); stmatrix4(toff + M_TST + 4096, tp[4], tp[5], tp[6], tp[7]);
        staged();
        bar_sync(N_GO4, 384);
      }
      if (T >= 0) cand = __shfl_sync(~0u, (int)lds32(sb + M_CAND + ((T + 1) & 3) * 4), 0);
      wg_wait<0>(); reg_fence(d);
      if (T >= 0) WSTAMP(6);
      if (T < 0 && tid == 0) TSTAMP(13, cta, 1);
#pragma unroll
      for (int i = 0; i < 8; i++) tp[i] = pack2(d[2 * i], d[2 * i + 1]);
    }
  }
  cluster_sync();
  if (tid == 0 && cta == 0) GSTAMP(0, 5);
}

__device__ __forceinline__ void attn_role(const Params& p, const uint32_t sb, const int w, const int cta, const int head, const int C, const uint32_t E,
                                          uint8_t* const part, uint8_t* const memg) {
  const int tid = fresh_tid(), lane = tid & 31;
  const int g = lane >> 2, t = lane & 3;
  uint32_t tag = ((E - 1) * (uint32_t)(NSTEP - 1)) & 1;
  uint4 m0[2][2];
  load_mem0(m0[0], w * 64, lane, p.mem0); load_mem0(m0[1], w * 64 + 256, lane, p.mem0);
  cluster_sync();
#pragma unroll
  for (int k = 0; k < 2; k++) {
#pragma unroll 1
    for (int i = 0; i < 6; i++) sts128(sb + M_MEM + (w + 4 * k) * 3072 + lane * 16 + i * 512, make_uint4(0, 0, 0, 0));
    __syncwarp();
#pragma unroll
    for (int i = 0; i < 2; i++) sts128(sb + M_MEM + ((w + 4 * k) * 4 + (lane >> 4) + 2 * i) * 768 + (lane & 15) * 16, m0[k][i]);
  }
  fence_async_smem();
  bar_sync(N_AG, 128);
  if (w == 3 && lane < 3) mbar_arrive(BAR(B_LAND + lane));
  if (lane == 0) {
    if (w == 0) TSTAMP(15, cta, 0);
    sts32(sb + M_PT + w * 4, probe(part + cta * 16384 + w * 4096, NPROBE_ / 2));
    if (w == 0) TSTAMP(15, cta, 1);
  }
  bar_sync(N_AG, 128);
  const uint32_t inear = lds32(sb + M_PT + (w >> 1) * 8 + 4) < lds32(sb + M_PT + (w >> 1) * 8);
  if (lane == 0 && !(w & 1)) st_rlx(&f_choice[cta][w >> 1], (E << 1) | inear);
  if (w == 0) TSTAMP(15, cta, 2);
  uint32_t nb;
  {
    const int i = min(lane >> 1, C < 2 ? 8 : 5);
    const int r = ((i / 3 * 3 + C) * 4 + w) * 3 + i % 3;
    int guard = 0; uint32_t cw;
    while (__any_sync(~0u, ((cw = ld_rlx(&f_choice[r][lane & 1])) >> 1) != (E & 0x7FFFFFFFu))) { if (++guard > (1 << 22)) TRAP(); }
    nb = __ballot_sync(~0u, cw & 1) >> (lane >> 4);
    if (w == 0) TSTAMP(15, cta, 3);
  }
  bar_sync(N_AG, 128);
  const uint32_t pt0 = sb + M_PT + (tid & 127) * 16;
  {
    const uint32_t po = (C * 4 + w) * 49152 + (lane >> 4) * 8192 + ((lane >> 3) & 1) * 2048 + head * 64 + (lane & 7) * 8;
    const uint8_t* in = part + (cta * 16384 + (w >> 1) * 8192 + inear * 4096 + (w & 1) * 2048 + lane * 8);
    const uint8_t* outp = memg + ((cta / 12) * 8192 + (cta % 12) * 256 + w * 64 + (lane >> 4) * 4096 + (lane & 4) * 8 + (lane & 8) * 2 + (lane & 3) * 4);
#pragma unroll
    for (int i = 0; i < 12; i++) {
      const int j = i / 4 * 3 + (i & 3);
      const uint8_t* a = (i & 3) < 3 ? part + (po + i / 4 * 589824 + (i & 3) * 16384 + ((nb >> (2 * j)) & 1) * 4096) : i == 11 ? in : outp;
      asm volatile("st.shared.u64 [%0], %1;" :: "r"(pt0 + (i >> 1) * 2048 + (i & 1) * 8), "l"(a) : "memory");
    }
  }
  const int xd = __shfl_sync(~0u, XDLY_ + (cta < 36 ? 0 : cta < 72 ? X1_ : X2_), 0);
  const uint32_t rba = mapa(sb, C == 2 ? 0 : 2), rbc = mapa(sb, C == 1 ? 0 : 1);
  uint32_t vis = vis_bits(8 + 8 * w + g, t);
  uint32_t ln = lane;
#pragma unroll
  for (int i = 0; i < SALT_; i++) ln += lds32(sb + M_ZERO);
  PIN(vis); PIN(ln);
  if (tid == 256 && C == 0) st_rlx(&f_loaded[head], E);
  uint32_t fa[8][4];
#pragma unroll
  for (int ks = 0; ks < 8; ks++) ldmatrix4_t(fa[ks], sb + M_WO + 32768 + w * 256 + (lane >> 4) * 1024 + (lane & 15) * 16 + ks * 2048);
  if (w == 0) TSTAMP(14, cta, 0);
#pragma unroll 1
  for (int T = 0; T < NSTEP; T++) {
    const uint32_t ph = T & 1;
    const uint32_t zz = uni(lds32(sb + M_ZERO));
    const bool more = T < NSTEP - 1;
    const float sc = 0.08838834764831845f * 1.4426950408889634f;
    tag ^= 1;
    float s[20];
    const uint8_t* in; int cnext = -1; uint32_t tx; bool synced;
    float x[10], tm, ts;
    uint32_t pt[5];
    auto tok_max = [&]() {
      PIN(vis);
      x[0] = s[2]; x[1] = s[3];
#pragma unroll
      for (int i = 0; i < 8; i++) x[2 + i] = (vis >> i & 1) ? s[4 * (i / 2 + 1) + 2 + (i & 1)] : -INFINITY;
      tm = fmaxf(fmaxf(fmaxf(fmaxf(x[0], x[1]), fmaxf(x[2], x[3])), fmaxf(fmaxf(x[4], x[5]), fmaxf(x[6], x[7]))), fmaxf(x[8], x[9]));
      HOLD(7, __float_as_uint(tm));
    };
    auto tok_exp1 = [&]() {
      tm = fmaxf(tm, __shfl_xor_sync(~0u, tm, 1));
      tm = fmaxf(tm, __shfl_xor_sync(~0u, tm, 2));
      const float b = -tm * sc;
#pragma unroll
      for (int i = 0; i < 10; i++) x[i] = fmaf(x[i], sc, b);
      HOLD(10, __float_as_uint(x[9]));
    };
    auto tok_exp2 = [&]() {
#pragma unroll
      for (int i = 0; i < 10; i++) x[i] = ex2(x[i]);
      ts = (((x[0] + x[1]) + (x[2] + x[3])) + ((x[4] + x[5]) + (x[6] + x[7]))) + (x[8] + x[9]);
#pragma unroll
      for (int k = 0; k < 5; k++) pt[k] = pack2(x[2 * k], x[2 * k + 1]);
      HOLD(8, __float_as_uint(ts));
    };
    {
      uint32_t q[8][4];
      auto load_q = [&](uint32_t a, int h) {
#pragma unroll
        for (int k2 = 0; k2 < 4; k2++) {
          uint32_t r[4];
          ldmatrix4_t(r, a + k2 * 512);
          q[2 * k2][h] = r[0]; q[2 * k2][h + 2] = r[1]; q[2 * k2 + 1][h] = r[2]; q[2 * k2 + 1][h + 2] = r[3];
        }
      };
      PIN(ln);
      const uint32_t qa = sb + M_Q + ln * 16;
      const int cand = C == 2 ? (int)uni(lds32(sb + M_CAND + (T & 3) * 4)) : -1;
      mbar_wait(BAR(B_TOK), ph);
      load_q(qa + (1 + w) * 2048, 1);
      mbar_wait(BAR(B_QK), ph);
      ASTAMP(0);
      if (T == 0 && w == 0) TSTAMP(13, cta, 3);
      if (__builtin_expect(cand >= 0, 0)) {
        mbar_wait(BAR(B_V), ph);
        PIN(ln);
        const int e = w * 32 + ln;
#pragma unroll
        for (int i = 0; i < 3; i++) {
          const uint32_t v = lds32(sb + M_Q + i * 12288 + 5 * 2048 + e * 16 + 4);
          asm volatile("st.shared.u16 [%0], %1;" :: "r"(sb + M_Q + i * 12288 + (1 + (cand >> 3)) * 2048 + e * 16 + (cand & 7) * 2), "h"((unsigned short)v) : "memory");
        }
        fence_async_smem();
        bar_sync(N_AG, 128);
        load_q(qa + (1 + w) * 2048, 1);
      }
      load_q(qa, 0);
      if (!(NOF_ & 1)) fence_async_smem();
      constexpr uint64_t dk = mkdesc(M_K, 128, 2048, 0);
      wg_fence();
      wgmma_rs40<0, 1>(s, q[0], dk);
#pragma unroll
      for (int ks = 1; ks < 8; ks++) wgmma_rs40<1, 1>(s, q[ks], dk + ks * 16);
      wg_commit();
    }
    if (more) {
      uint32_t v[5][4];
      PIN(ln);
      const uint32_t va = sb + M_V + w * 512 + ((ln >> 3) & 1) * 128 + (ln >> 4) * 2048 + (ln & 7) * 16;
      const uint32_t ooff = M_OM + w * 1536 + C * 256 + ln * 4;
      mbar_wait(BAR(B_V), ph);
      wg_wait<0>(); reg_fence(s);
      if (ln < 3) mbar_arrive_remote(mapa(BAR(B_KFREE), ln));
      ldmatrix4(v[0], va); ldmatrix4(v[1], va + 256); ldmatrix4(v[2], va + 4096); ldmatrix4(v[3], va + 4096 + 256);
      ldmatrix4(v[4], sb + M_V + 8192 + w * 512 + ln * 16);
      ASTAMP(1);
      float m = fmaxf(fmaxf(fmaxf(fmaxf(s[0], s[1]), fmaxf(s[4], s[5])), fmaxf(fmaxf(s[8], s[9]), fmaxf(s[12], s[13]))), fmaxf(s[16], s[17]));
      m = fmaxf(m, __shfl_xor_sync(~0u, m, 1));
      m = fmaxf(m, __shfl_xor_sync(~0u, m, 2));
      const float b = -m * sc;
      uint32_t pm[5];
#pragma unroll
      for (int j = 0; j < 5; j++) pm[j] = pack2(ex2(fmaf(s[4 * j], sc, b)), ex2(fmaf(s[4 * j + 1], sc, b)));
      float o0[4] = {0.f, 0.f, 0.f, 0.f}, o1[4] = {0.f, 0.f, 0.f, 0.f}, l[4] = {0.f, 0.f, 0.f, 0.f};
      const uint32_t one[4] = {0x3f803f80u, 0x3f803f80u, 0x3f803f80u, 0x3f803f80u};
      hmma16(l, one, pm[0], pm[1]); hmma16(o0, v[0], pm[0], pm[1]); hmma16(o1, v[1], pm[0], pm[1]);
      hmma16(l, one, pm[2], pm[3]); hmma16(o0, v[2], pm[2], pm[3]); hmma16(o1, v[3], pm[2], pm[3]);
      hmma8(l, one[0], one[1], pm[4]); hmma8(o0, v[4][0], v[4][1], pm[4]); hmma8(o1, v[4][2], v[4][3], pm[4]);
      const float r0 = rcp(l[0]), r1 = rcp(l[1]);
      const uint32_t u0 = pack2(o0[0] * r0, o0[1] * r1), u1 = pack2(o0[2] * r0, o0[3] * r1), u2 = pack2(o1[0] * r0, o1[1] * r1), u3 = pack2(o1[2] * r0, o1[3] * r1);
      constexpr uint32_t OB = M_BAR + 8 * B_OM;
      const uint32_t a0 = rba + ooff, a1 = rbc + ooff;
      st_async32(a0, u0, rba + OB); st_async32(a1, u0, rbc + OB);
      st_async32(a0 + 128, u1, rba + OB); st_async32(a1 + 128, u1, rbc + OB);
      st_async32(a0 + 768, u2, rba + OB); st_async32(a1 + 768, u2, rbc + OB);
      st_async32(a0 + 896, u3, rba + OB); st_async32(a1 + 896, u3, rbc + OB);
      bar_arrive(N_GO2, 384);
      sts32(sb + ooff, u0); sts32(sb + ooff + 128, u1); sts32(sb + ooff + 768, u2); sts32(sb + ooff + 896, u3);
      ASTAMP(2);
      uint32_t fb[8][4];
      const uint32_t wa = sb + M_WO + 16384 + w * 256 + (ln >> 4) * 1024 + (ln & 15) * 16 + zz;
      ldmatrix4_t(fb[0], wa);
      SCHED(3);
#pragma unroll
      for (int ks = 1; ks < 8; ks++) {
        ldmatrix4_t(fb[ks], wa + ks * 2048);
        if (ks == ARR_) { __syncwarp(); if (ln == 0) mbar_arrive(BAR(B_OM) + (fb[0][0] & zz)); }
      }
      if (C == 2) cnext = (int)uni(lds32(sb + M_CAND + ((T + 1) & 3) * 4));
      {
        float d[12], e[12];
        constexpr uint64_t ob = mkdesc(M_OM, 128, 256, 0);
        uint8_t* q[3][3];
        auto addr = [&](int i) {
          asm volatile("ld.shared.v2.u64 {%0,%1}, [%2];" : "=l"(q[i][0]), "=l"(q[i][1]) : "r"(pt0 + i * 4096) : "memory");
          if (i < 2) asm volatile("ld.shared.u64 %0, [%1];" : "=l"(q[i][2]) : "r"(pt0 + i * 4096 + 2048) : "memory");
          else asm volatile("ld.shared.v2.u64 {%0,%1}, [%2];" : "=l"(q[i][2]), "=l"(in) : "r"(pt0 + i * 4096 + 2048) : "memory");
        };
        auto put = [&](const float* d, int i) {
          st_rlx64(q[i][0], (pack2(d[0], d[1]) & ~1u) | tag, pack2(d[2], d[3]));
          st_rlx64(q[i][1], (pack2(d[4], d[5]) & ~1u) | tag, pack2(d[6], d[7]));
          st_rlx64(q[i][2], (pack2(d[8], d[9]) & ~1u) | tag, pack2(d[10], d[11]));
        };
        addr(0); addr(1);
        SCHED(6);
        tok_max();
        ASTAMP(3);
        mbar_wait(BAR(B_OM), ph);
        if (!(NOF_ & 2)) fence_async_smem();
        ASTAMP(4);
        constexpr uint64_t w0 = mkdesc(M_WO, 1024, 128, 0);
        float (&f)[12] = d;
        wg_fence();
        wgmma_ss24<0, 1, 1>(d, w0, ob);
#pragma unroll
        for (int ks = 1; ks < 8; ks++) wgmma_ss24<1, 1, 1>(d, w0 + ks * 128, ob + ks * 48);
        wg_commit();
        wgmma_rs24<0, 1>(e, fb[0], ob);
#pragma unroll
        for (int ks = 1; ks < HAND_; ks++) wgmma_rs24<1, 1>(e, fb[ks], ob + ks * 48);
        wg_commit();
        wg_wait<1>(); reg_fence(d);
        put(d, 0);
        addr(2);
        SCHED(4);
        ASTAMP(5);
        wg_fence();
#pragma unroll
        for (int ks = HAND_; ks < 8; ks++) wgmma_rs24<1, 1>(e, fb[ks], ob + ks * 48);
        wg_commit();
        wgmma_rs24<0, 1, 1>(f, fa[0], ob);
#pragma unroll
        for (int ks = 1; ks < HAND_; ks++) wgmma_rs24<1, 1>(f, fa[ks], ob + ks * 48);
        wg_commit();
        wg_wait<1>(); reg_fence(e);
        put(e, 1);
        SCHED(5);
        wg_fence();
#pragma unroll
        for (int ks = HAND_; ks < 8; ks++) wgmma_rs24<1, 1>(f, fa[ks], ob + ks * 48);
        wg_commit();
        if (GO3_ == 0) bar_arrive(N_GO3, 384);
        synced = __all_sync(~0u, mbar_test(BAR(B_SYNC), ph));
        tx = uni(lds32(sb + M_BASE + ph * 4)) + xd;
        wg_wait<0>(); reg_fence(f);
        if (GO3_ == 1) bar_arrive(N_GO3, 384);
        if (C < 2) put(f, 2);
        if (GO3_ == 2) bar_arrive(N_GO3, 384);
        ASTAMP(6);
        if (T == 0 && w == 0) TSTAMP(14, cta, 1);
      }
    } else {
      mbar_wait(BAR(B_V), ph);
      wg_wait<0>(); reg_fence(s);
      tok_max();
    }
    uint2 v[8];
#pragma unroll
    for (int i = 0; i < 8; i++) v[i] = make_uint2(zz, zz);
    auto poll = [&](uint2* v) {
      v[0] = ld_rlx64<0>(in); v[1] = ld_rlx64<256>(in); v[2] = ld_rlx64<512>(in); v[3] = ld_rlx64<768>(in);
      v[4] = ld_rlx64<1024>(in); v[5] = ld_rlx64<1280>(in); v[6] = ld_rlx64<1536>(in); v[7] = ld_rlx64<1792>(in);
    };
    uint8_t* outp;
    asm volatile("ld.shared.u64 %0, [%1];" : "=l"(outp) : "r"(pt0 + 2048 + 8) : "memory");
    const uint32_t itag = gentag((E - 1) * (uint32_t)(NSTEP - 1) + T + 1);
    const bool sum = more && cnext < 0;
    if (more) {
      if (!synced) { mbar_wait(BAR(B_SYNC), ph); tx = uni(lds32(sb + M_BASE + ph * 4)) + xd; }
      ASTAMP(7);
      if (__builtin_expect(cnext >= 0, 0)) {
        const unsigned long long* hp = (const unsigned long long*)&g_hc[T + 1 - LAG][0] + ((cta / 3) * 8 + 2 * w + ((ln >> 2) & 1));
        unsigned long long v0; int guard = 0;
        while (v0 = ld_rlxu64(hp), !__all_sync(~0u, (uint32_t)(v0 >> 32) == E)) { if (++guard > (1 << 22)) TRAP(); }
        st_rlx((uint32_t*)outp, (ln & 3) == 1 ? ((uint32_t)v0 >> ((ln & 8) * 2)) & 0xffffu : (ln & 1) ? 0u : itag);
      } else {
        spin_until(tx);
        ASTAMP(8);
        poll(v);
      }
    }
    auto late = [&](const uint2* v) {
      return __any_sync(~0u, (or3(xo2(v[0].x, v[1].x, tag), xo2(v[2].x, v[3].x, tag), xo2(v[4].x, v[5].x, tag)) | xo2(v[6].x, v[7].x, tag)) & 1u);
    };
    tok_exp1(); tok_exp2();
    if (sum) {
      ASTAMP(9);
      int guard = 0;
      while (late(v)) {
        if (++guard > (1 << 22)) TRAP();
        poll(v);
      }
#pragma unroll
      for (int i = 0; i < 4; i++) { v[i].x = add2(v[i].x, v[i + 4].x); v[i].y = add2(v[i].y, v[i + 4].y); }
#define SUM8(f, m) ((f(v[0].m) + f(v[1].m)) + (f(v[2].m) + f(v[3].m)))
      const float a0 = SUM8(blo, x), a1 = SUM8(bhi, x), b0 = SUM8(blo, y), b1 = SUM8(bhi, y);
      const bool hi = ln & 8;
      float k0 = (hi ? b0 : a0) + __shfl_xor_sync(~0u, hi ? a0 : b0, 8), k1 = (hi ? b1 : a1) + __shfl_xor_sync(~0u, hi ? a1 : b1, 8);
      k0 += __shfl_xor_sync(~0u, k0, 16); k1 += __shfl_xor_sync(~0u, k1, 16);
      st_rlx((uint32_t*)outp, (ln & 1) ? pack2(k0, k1) : pack2_tag(k0, k1, itag));
      ASTAMP(10);
      if (T == 0 && w == 0) TSTAMP(14, cta, 2);
      CSTAMP(12 + w, (clk() & ~15u) | min(guard + 1, 15));
    }
    if (more) bar_arrive(N_GO4, 384);
    {
      PIN(ln);
      const uint32_t oa = sb + M_OST + w * 128 + (ln >> 3) * 512 + (ln & 7) * 16;
      const uint32_t a[3][4] = {{0, pt[0], 0, pt[1]}, {0, pt[2], 0, pt[3]}, {0, pt[4], 0, 0}};
      constexpr uint64_t dv = mkdesc(M_V, 2048, 128, 0);
#pragma unroll 1
      for (int h = 0; h < 2; h++) {
        float o[32];
        const uint64_t dh = dv + (uint64_t)(h * 64);
        wg_fence();
        wgmma_rs64<0, 0>(o, a[0], dh); wgmma_rs64<1, 0>(o, a[1], dh + 256); wgmma_rs64<1, 0>(o, a[2], dh + 512);
        wg_commit();
        if (h == 0) {
          ts += __shfl_xor_sync(~0u, ts, 1);
          ts += __shfl_xor_sync(~0u, ts, 2);
          ts = rcp(ts);
          mbar_wait(BAR(B_OFREE), ph ^ 1);
        }
        wg_wait<0>(); reg_fence(o);
        if (h == 1 && ln < 3) mbar_arrive_remote(mapa(BAR(B_VFREE), ln));
#define OT(i) pack2(o[4 * (i) + 2] * ts, o[4 * (i) + 3] * ts)
        stmatrix4(oa + h * 4096, OT(0), OT(1), OT(2), OT(3));
        stmatrix4(oa + h * 4096 + 2048, OT(4), OT(5), OT(6), OT(7));
      }
      const uint32_t z5 = DRAIN(oa);
      __syncwarp();
      if (ln == 0) mbar_arrive(BAR(B_OST) + z5);
      ASTAMP(11);
    }
  }
}

__global__ void __cluster_dims__(3, 1, 1) __launch_bounds__(512, 1) main_kernel(Params p) {
  extern __shared__ __align__(1024) uint8_t sm[];
  const uint32_t sb = smem_u32(sm);
  if ((sb & 0xFFFFFFu) != SBASE) TRAP();
  asm volatile("griddepcontrol.launch_dependents;");
  const int warp = __shfl_sync(~0u, threadIdx.x >> 5, 0);
  const int cta = blockIdx.x, head = cta / 3, c = cta % 3;
  const uint32_t E = __shfl_sync(~0u, *(volatile uint32_t*)&g_epoch + 1, 0);
  uint8_t* const part = (uint8_t*)(((uintptr_t)g_xch + 8191) & ~(uintptr_t)8191);
  uint8_t* const memg = part + 96 * 16384;

  if (threadIdx.x == 0 && cta == 0) GSTAMP(0, 0);
  if (threadIdx.x < B_NUM) {
    const int i = threadIdx.x;
    const uint32_t cnt = i == B_STG || i == B_STG1 ? 8 : i == B_OST ? 4 : i == B_HAE || i == B_HBE ? 6 : i == B_KFREE || i == B_VFREE ? 12 : i == B_SS ? 2 : i == B_OM ? 5 :
                         i == B_QK ? (c < 2 ? 9 : 1) : i == B_V ? (c < 2 ? 1 : 9) : 1;
    mbar_init(BAR(i), cnt);
    if (i == B_HA || i == B_HB || i == B_STG || i == B_HAE || i == B_HBE || i == B_TFREE)
      asm volatile("mbarrier.arrive.shared::cta.b64 _, [%0], %1;" :: "r"(BAR(i)), "r"(cnt) : "memory");
    asm volatile("fence.mbarrier_init.release.cluster;" ::: "memory");
  }
  if (warp < 8) {
    const int tid = threadIdx.x;
    uint4 wa[6], wb[6];
#pragma unroll
    for (int i = 0; i < 6; i++) {
      const int mi = i >> 1, e = (tid >> 2) + (i & 1) * 64;
      const uint4* src = (const uint4*)(p.wo + (size_t)(head * 128 + e) * 512 + min(3 * mi + c, 7) * 64 + (tid & 3) * 16);
      wa[i] = __ldg(src); wb[i] = __ldg(src + 1);
    }
    stage_weights(sb, (c == 0 ? p.wq : c == 1 ? p.wk : p.wv) + head * 128, 4096, tid, 256);
#pragma unroll
    for (int i = 0; i < 6; i++) {
      const int mi = i >> 1, e = (tid >> 2) + (i & 1) * 64;
      const uint4 a = wa[i], b = wb[i];
      const uint32_t dst = sb + M_WO + mi * 16384 + (e >> 3) * 1024 + (tid & 3) * 256 + (e & 7) * 16;
      sts128(dst, make_uint4(__byte_perm(a.x, a.y, 0x5410), __byte_perm(a.z, a.w, 0x5410), __byte_perm(b.x, b.y, 0x5410), __byte_perm(b.z, b.w, 0x5410)));
      sts128(dst + 128, make_uint4(__byte_perm(a.x, a.y, 0x7632), __byte_perm(a.z, a.w, 0x7632), __byte_perm(b.x, b.y, 0x7632), __byte_perm(b.z, b.w, 0x7632)));
    }
  } else {
    const int i0 = threadIdx.x - 256;
    const uint32_t tag0 = ((E - 1) * (uint32_t)(NSTEP - 1)) & 1;
    for (int i = i0; i < 1024; i += 256) *(uint4*)(part + cta * 16384 + i * 16) = make_uint4(tag0, 0, tag0, 0);
    if (i0 < 16) *(uint32_t*)(memg + i0 * 4096 + 3968) = 0;
    if (i0 < 2) st_rlx(&f_choice[cta][i0], 0);
    if (i0 < 8) st_rlx64(&g_sync[i0 >> 2][cta][i0 & 3], 0, 0);
    __threadfence();
    if (i0 < 12) sts32(sb + M_ZERO + i0 * 4, 0);
    if (i0 < 2) { sts32(sb + M_BASE + i0 * 4, clk32() - 65536); sts32(sb + M_CAND + i0 * 4, (uint32_t)-1); }
  }

  if (warp < 8) {
    asm volatile("setmaxnreg.inc.sync.aligned.u32 " STR(RW_) ";");
    weight_role(p, sb, warp, cta, c, E, memg);
  } else if (warp < 12) {
    if (RA_ < 128) asm volatile("setmaxnreg.dec.sync.aligned.u32 " STR(RA_) ";");
    if (RA_ > 128) asm volatile("setmaxnreg.inc.sync.aligned.u32 " STR(RA_) ";");
    attn_role(p, sb, warp - 8, cta, head, c, E, part, memg);
    cluster_sync();
  } else {
    asm volatile("setmaxnreg.dec.sync.aligned.u32 " STR(RC_) ";");
    const int tid = fresh_tid(), lane = tid & 31;
    const int w = warp - 12;
    cluster_sync();
    if (w != 2) {
      const int tl = min(3 * min(w, 2) + c, 7);
      int near = 0;
      if (lane == 0) { const int t0 = probe(memg + tl * 8192, NPROBE_ / 2); near = probe(memg + tl * 8192 + 4096, NPROBE_ / 2) < t0; }
      near = uni(near);
      if (lane < 3) asm volatile("st.shared::cluster.u32 [%0], %1;" :: "r"(mapa(sb + M_NEAR + tl * 4, lane)), "r"(near) : "memory");
      __syncwarp();
    }
    if (w == 0) {
      uint32_t s0 = c * 8192, s1 = (3 + c) * 8192, s2 = min(6 + c, 7) * 8192;
#pragma unroll 1
      for (int T = 0; T < NSTEP - 1; T++) {
        const uint32_t ph = T & 1;
        mbar_wait(BAR(B_SS), ph);
        const uint32_t cq = clk();
        const uint32_t g0 = (uint32_t)gtime64(); uint32_t g1, ce;
        do { g1 = (uint32_t)gtime64(); ce = clk(); } while (g1 == g0);
        const uint32_t tn = g1 * 8 - (((ce - cq) * 37u) >> 3), id = E * 128u + T;
        if (lane < 4) st_rlx64(&g_sync[ph][cta][lane], tn, id);
        if (lane < 3) mbar_expect(BAR(B_LAND + lane), lane < 2 ? 9216 : 6144);
        if (T == 0) { s0 += uni(lds32(sb + M_NEAR + c * 4)) * 4096; s1 += uni(lds32(sb + M_NEAR + (3 + c) * 4)) * 4096; s2 += uni(lds32(sb + M_NEAR + min(6 + c, 7) * 4)) * 4096; }
        wait_until(cq + SDLY_);
        int guard = 0; unsigned long long v0, v1, v2;
        for (;;) {
          v0 = ld_rlxu64(g_sync[ph][lane]); v1 = ld_rlxu64(g_sync[ph][lane + 32]); v2 = ld_rlxu64(g_sync[ph][lane + 64]);
          if (__all_sync(~0u, (uint32_t)(v0 >> 32) == id && (uint32_t)(v1 >> 32) == id && (uint32_t)(v2 >> 32) == id)) break;
          if (++guard > (1 << 22)) TRAP();
        }
        const int dl = __reduce_max_sync(~0u, max(max((int)((uint32_t)v0 - tn), (int)((uint32_t)v1 - tn)), (int)((uint32_t)v2 - tn)));
        const uint32_t base = uni(cq + ((min(dl, 8 * 4096) * 7) >> 5)) + (T == 0 ? SLOW0_ : T == 1 ? SLOW1_ : 0) +
                              ((int)uni(lds32(sb + M_CAND + (T & 3) * 4)) >= 0 ? CDLY_ : 0) - (T + 2 < NSEG ? 0 : BOFF_);
        if (lane == 0) { sts32(sb + M_BASE + ph * 4, base); mbar_arrive(BAR(B_SYNC)); }
        CSTAMP(0, base); CSTAMP(1, clk());
        const uint32_t ts = base + YDLY_ - (T + 2 >= LAG && T + 2 < NSEG ? 0 : YOFF_);
        uint32_t nr = 0;
        if (PRIV_) nr = __ballot_sync(~0u, lds32(sb + M_NEAR + (lane & 7) * 4) != 0);
        wait_until(ts);
        if (PRIV_ & 1) { for (int k = 0; k < 3; k++) e_g2s(sb + M_MEM + k * 3072, memg + k * 8192 + ((nr >> k) & 1) * 4096, 3072, BAR(B_LAND)); }
        else e_mc(sb + M_MEM + c * 3072, memg + s0, 3072, BAR(B_LAND), 7);
        CSTAMP(2, clk());
        spin_until(ts + Y1_);
        if (PRIV_ & 2) { for (int k = 3; k < 6; k++) e_g2s(sb + M_MEM + k * 3072, memg + k * 8192 + ((nr >> k) & 1) * 4096, 3072, BAR(B_LAND + 1)); }
        else e_mc(sb + M_MEM + (3 + c) * 3072, memg + s1, 3072, BAR(B_LAND + 1), 7);
        CSTAMP(3, clk());
        spin_until(ts + Y2_);
        if (PRIV_ & 4) { for (int k = 6; k < 8; k++) e_g2s(sb + M_MEM + k * 3072, memg + k * 8192 + ((nr >> k) & 1) * 4096, 3072, BAR(B_LAND + 2)); }
        else if (c < 2) e_mc(sb + M_MEM + (6 + c) * 3072, memg + s2, 3072, BAR(B_LAND + 2), 7);
        CSTAMP(4, clk());
      }
    } else if (w == 1) {
#pragma unroll 1
      for (int T = 0; T < NSTEP; T++) {
        const uint32_t ph = T & 1;
        const int s = c == 0 ? T : T - LAG;
        const bool act = s >= 0 && s < NSEG;
        mbar_wait(BAR(B_OST), ph);
        if (cta == 0) TSTAMP(2, T, 0);
        fence_async_smem();
        if (T < NSTEP - 1) wait_until(uni(lds32(sb + M_BASE + ph * 4)) + ODLY_);
        STAMP(22);
        if (act) { e_s2g(g_o[c][s % ORING][head], sb + M_OST, XO_); bulk_wait(); __syncwarp(); }
        e_arrive(BAR(B_OFREE));
        if (cta == 0) TSTAMP(2, T, 1);
        if (act && lane < 8) st_rel(&f_o[T][head >> 2][c * 4 + (head & 3)][lane], E);
        __syncwarp();
        if (cta == 0) TSTAMP(2, T, 2);
      }
    } else if (w == 2) {
      unsigned long long run = 0;
      static_assert(LAG >= 2, "config");
      constexpr uint32_t NA = EA / 4 * 4096;
      e_expect(BAR(B_QK), c < 2 ? 2048 : 4096); e_expect(BAR(B_V), c == 0 ? 10240 : c == 1 ? 2048 : 0);
      e_expect(BAR(B_TOK), c == 0 ? 16384 : 0); e_expect(BAR(B_OM), 4096);
      e_expect(BAR(B_HA), NA); e_expect(BAR(B_HB), 65536 - NA);
      wait_eq(&f_h1[c == 1 ? 0 : 1], E); fence_async_glob();
      {
        const uint32_t o0 = c == 0 ? NA : 0, o1 = c == 2 ? NA : 32768;
        e_mc(sb + M_H + (c == 1 ? 32768 : 0) + o0, g_h[0][c == 1 ? 0 : 1] + o0, o1 - o0, BAR(c == 2 ? B_HA : B_HB), 7);
      }
      TSTAMP(14, cta, 3);
      if (c == 2) wait_eq(&f_h1[2], E);
      mbar_wait(BAR(B_HAE), 1);
      e_expect(BAR(B_HA), NA);
      if (c == 2) { fence_async_glob(); e_mc(sb + M_H, g_h[0][2], NA, BAR(B_HA), 7); }
      int cprev = -1;
#pragma unroll 1
      for (int T = 0; T < NSTEP - 1; T++) {
        const int s1 = T + 2, s2 = T + 2 - LAG;
        const uint32_t ph = T & 1;
        const bool l1 = s1 < NSEG, l2 = s2 >= 0 && s2 < NSEG, la = s1 + 1 < NSEG;
        const bool mine = c == 0 ? l1 : c == 1 ? l2 : la;
        const uint32_t* fl = c != 1 ? &f_h1[min(s1 + (c >> 1), NSEG - 1)] : (const uint32_t*)f_h2[max(s2, 0)][lane & 3] + 1;
        const uint32_t want = E & 0x1FFFFFu, sh = c != 1 ? 0 : 11;
        mbar_wait(BAR(B_HBE), ph ^ 1);
        const bool early = __all_sync(~0u, ((ld_acq(fl) >> sh) & 0x1FFFFFu) == want);
        mbar_wait(BAR(B_LAND + 2), ph);
        STAMP(16);
        e_expect(BAR(B_HB), (l1 ? 32768 - NA : 0) + (l2 ? 32768 : 0));
        if (mine) {
          if (!early) {
            int guard = 0;
            while (!__all_sync(~0u, ((ld_acq(fl) >> sh) & 0x1FFFFFu) == want)) { __nanosleep(32); if (++guard > (1 << 22)) TRAP(); }
          }
          fence_async_glob();
          if (c == 1) { mbar_wait(BAR(B_QK), ph); spin_until(clk32() + HDLY_); }
          if (c < 2) paced_h(sb + M_H + c * 32768, g_h[c][c ? s2 : s1], c ? 0 : NA, 32768, 4096, BAR(B_HB), HGAP_);
        }
        int cd = -1;
        if (l2) { cd = route_step(s2, E, lane, run); if (cta == 0) TSTAMP(5, s2, 0); }
        if (lane == 0) sts32(sb + M_CAND + ((T + 2) & 3) * 4, (uint32_t)cd);
        __syncwarp();
        STAMP(17);
        mbar_wait(BAR(B_HAE), ph);
        e_expect(BAR(B_HA), la ? NA : 0);
        if (c == 2 && la) {
          spin_until(clk32() + ADLY_);
          STAMP(18);
          paced_h(sb + M_H, g_h[0][s1 + 1], 0, NA, 4096, BAR(B_HA), AGAP_);
        }
        mbar_wait(BAR(B_OST), ph);
        e_expect(BAR(B_QK), c < 2 ? 2048 : cprev >= 0 ? 8192 : 4096);
        e_expect(BAR(B_V), c < 2 ? 10240 : 8192);
        e_expect(BAR(B_TOK), 16384);
        e_expect(BAR(B_OM), 4096);
        cprev = cd;
      }
    } else {
      const uint32_t mytok = sb + M_Q + c * 12288 + 2048, tb = BAR(c < 2 ? B_TOK : B_V);
      mbar_wait(BAR(B_STG1), 0);
      fence_async_smem();
      e_s2g(g_tok[cta][1], sb + M_TST, 8192);
#pragma unroll 1
      for (int T = 0; T < NSTEP - 1; T++) {
        const uint32_t ph = T & 1;
        uint8_t* const tok = g_tok[cta][ph ^ 1];
        mbar_wait(BAR(B_STG), ph ^ 1);
        fence_async_smem();
        if (cta == 0 && (T == 0 || T == NSEG || T == NSTEP - 2)) GSTAMP(0, T == 0 ? 2 : T == NSEG ? 3 : 4);
        if (T > 0 && TQ_) mbar_wait(BAR(B_QK), ph);
        STAMP(20);
        uint32_t t = clk32();
        e_s2g(tok + 8192, sb + M_TST + 8192, XT2_);
        spin_until(t + TGAP_);
        e_s2g(tok + 12288, sb + M_TST + 12288, XT2_);
        bulk_wait();
        __syncwarp();
        e_arrive(BAR(B_TFREE));
        if (T == 0) e_mc(mytok, tok + 8192, 8192, tb, 1);
        STAMP(21);
#pragma unroll 1
        for (int k = 0; k < 2; k++) {
          if (k == 1) {
            mbar_wait(BAR(B_STG1), ph ^ 1);
            fence_async_smem();
            t = uni(lds32(sb + M_BASE + ph * 4));
            wait_until(t + TDLY_);
            e_s2g(g_tok[cta][ph], sb + M_TST, XT1_);
          }
          if (k == (c >> 1)) {
            mbar_wait(BAR(c < 2 ? B_KFREE : B_VFREE), ph);
            t = k ? t + LDLY_ : clk32() + KDLY_;
            wait_until(t);
            STAMP(23);
            e_mc(mytok, tok, 8192, tb, 1);
            spin_until(t + LGAP_);
            e_mc(mytok, tok + 8192, 8192, tb, 6);
            STAMP(24);
          }
        }
      }
      bulk_wait();
    }
    __syncwarp();
    cluster_sync();
  }
}

constexpr uint32_t A_RING = 0;
constexpr int A_NST = 6;
constexpr uint32_t A_STG = A_RING + A_NST * 8192;
constexpr uint32_t A_WD = A_STG + 8192;
constexpr uint32_t A_WG = A_WD + 57344;
constexpr uint32_t A_WU = A_WG + 57344;
constexpr uint32_t A_XN = A_WU + 57344;
constexpr uint32_t A_BAR = A_XN + 2048;
constexpr uint32_t A_TOTAL = A_BAR + 256;
static_assert(A_TOTAL <= 232448, "aux smem");

__device__ __forceinline__ uint32_t ptag(int s) { return ((s / PRING) & 1) ^ 1; }
static_assert((NSEG / PRING) % 2 == 0, "tags");
__device__ __forceinline__ void load_row(uint32_t* v, const void* row, int lane) {
  const uint4 a = __ldcg((const uint4*)row + lane), b = __ldcg((const uint4*)row + 32 + lane);
  v[0] = a.x; v[1] = a.y; v[2] = a.z; v[3] = a.w; v[4] = b.x; v[5] = b.y; v[6] = b.z; v[7] = b.w;
}
__device__ __forceinline__ void store_row(void* row, const uint32_t* v, int lane) {
  ((uint4*)row)[lane] = make_uint4(v[0], v[1], v[2], v[3]); ((uint4*)row)[32 + lane] = make_uint4(v[4], v[5], v[6], v[7]);
}
__device__ __forceinline__ void store_img(uint8_t* img, int r, const uint32_t* v, int lane) {
  uint8_t* b = img + (lane >> 3) * 4096 + (r >> 3) * 1024 + (r & 7) * 128 + (((lane ^ r) & 7) << 4);
  *(uint4*)b = make_uint4(v[0], v[1], v[2], v[3]);
  *(uint4*)(b + 16384) = make_uint4(v[4], v[5], v[6], v[7]);
}
template <int NT> __device__ __forceinline__ void ln_rows(const uint32_t (*v)[8], uint32_t (*y)[8]) {
  float c[NT], sm[NT], sq[NT];
#pragma unroll
  for (int k = 0; k < NT; k++) {
    c[k] = blo(__shfl_sync(~0u, v[k][0], 0));
    float s0 = 0.f, s1 = 0.f, q0 = 0.f, q1 = 0.f;
#pragma unroll
    for (int i = 0; i < 8; i++) { const float a = blo(v[k][i]) - c[k], b = bhi(v[k][i]) - c[k]; s0 += a; s1 += b; q0 = fmaf(a, a, q0); q1 = fmaf(b, b, q1); }
    sm[k] = s0 + s1; sq[k] = q0 + q1;
  }
#pragma unroll
  for (int o = 16; o > 0; o >>= 1)
#pragma unroll
    for (int k = 0; k < NT; k++) {
      sm[k] += __shfl_xor_sync(~0u, sm[k], o); sq[k] += __shfl_xor_sync(~0u, sq[k], o);
    }
#pragma unroll
  for (int k = 0; k < NT; k++) {
    const float dm = sm[k] * (1.f / 512.f), var = fmaxf(fmaf(-dm, dm, sq[k] * (1.f / 512.f)), 0.f);
    const float mb = rbf(c[k] + dm), inv = rcp(rbf(sqrt_fast(rbf(rbf(var) + 1e-5f))));
#pragma unroll
    for (int i = 0; i < 8; i++) { const uint32_t a = pack2(blo(v[k][i]) - mb, bhi(v[k][i]) - mb); y[k][i] = pack2(blo(a) * inv, bhi(a) * inv); }
  }
}
__device__ __forceinline__ void input_ln_pair(const bf16* x, int s, int pr, int lane) {
  uint32_t v[2][8], y[2][8];
  load_row(v[0], x + (size_t)(s * 32 + 2 * pr) * 512, lane); load_row(v[1], x + (size_t)(s * 32 + 2 * pr + 1) * 512, lane);
  ln_rows<2>(v, y);
  store_img(g_h[0][s], 2 * pr, y[0], lane); store_img(g_h[0][s], 2 * pr + 1, y[1], lane);
}
__device__ __forceinline__ float load_wr(uint32_t* wv, const bf16* wr, int lane) {
  load_row(wv, wr, lane);
  float wsum = 0.f;
#pragma unroll
  for (int i = 0; i < 8; i++) wsum += blo(wv[i]) + bhi(wv[i]);
#pragma unroll
  for (int o = 16; o > 0; o >>= 1) wsum += __shfl_xor_sync(~0u, wsum, o);
  return wsum;
}

template <bool FAST>
__device__ __forceinline__ unsigned long long token_post(int st, int tk, const bf16* res, bf16* dst, bf16* req, unsigned long long best,
                                                         const uint32_t* wv, float wsum, uint32_t E, int lane) {
  const int s = tk >> 5;
  uint32_t x[8];
  load_row(x, res, lane);
  wait_all(f_acc[st][s][lane], E, false);
  if (tk == s * 32 && st == 0 && lane == 0) TSTAMP(4, s, 0);
  {
    const uint8_t* pp = g_pp[st][s % PRING] + (lane >> 4) * 8192 + (tk & 31) * 256 + (((lane & 15) ^ (tk & 7)) << 4);
    const uint32_t tag = ptag(s);
    uint4 q[8][2];
#define PLD(k, h) q[k][h] = ld_rlx128<(k) * 32768 + (h) * 16384>(pp)
#define PLD8(h) PLD(0, h); PLD(1, h); PLD(2, h); PLD(3, h); PLD(4, h); PLD(5, h); PLD(6, h); PLD(7, h)
#define PBAD(h) __any_sync(~0u, (or3(xo2(q[0][h].x, q[1][h].x, tag), xo2(q[2][h].x, q[3][h].x, tag), xo2(q[4][h].x, q[5][h].x, tag)) | xo2(q[6][h].x, q[7][h].x, tag)) & ~lane & (PST_ == 8192 ? 1u : 0u))
#define PSUM(f, h, m) (((f(q[0][h].m) + f(q[1][h].m)) + (f(q[2][h].m) + f(q[3][h].m))) + ((f(q[4][h].m) + f(q[5][h].m)) + (f(q[6][h].m) + f(q[7][h].m))))
    const uint32_t eye = (lane >> 2) == 2 * (lane & 3) ? 0x3f80u : (lane >> 2) == 2 * (lane & 3) + 1 ? 0x3f800000u : 0u;
    auto padd = [&](int h) {
      if (FAST) {
        float u[4] = {0.f, 0.f, 0.f, 0.f}, v[4] = {0.f, 0.f, 0.f, 0.f};
#pragma unroll
        for (int k = 0; k < 8; k++) { hmma8(u, q[k][h].x, q[k][h].y, eye); hmma8(v, q[k][h].z, q[k][h].w, eye); }
        x[4 * h] = add2(x[4 * h], pack2(u[0], u[1])); x[4 * h + 1] = add2(x[4 * h + 1], pack2(u[2], u[3]));
        x[4 * h + 2] = add2(x[4 * h + 2], pack2(v[0], v[1])); x[4 * h + 3] = add2(x[4 * h + 3], pack2(v[2], v[3]));
      } else {
        x[4 * h] = add2(x[4 * h], pack2(PSUM(blo, h, x), PSUM(bhi, h, x))); x[4 * h + 1] = add2(x[4 * h + 1], pack2(PSUM(blo, h, y), PSUM(bhi, h, y)));
        x[4 * h + 2] = add2(x[4 * h + 2], pack2(PSUM(blo, h, z), PSUM(bhi, h, z))); x[4 * h + 3] = add2(x[4 * h + 3], pack2(PSUM(blo, h, w), PSUM(bhi, h, w)));
      }
    };
    int guard = 0;
    PLD8(0);
    if (FAST) { PLD8(1); }
    while (PBAD(0)) { if (++guard > (1 << 20)) TRAP(); PLD8(0); }
    padd(0);
    if (!FAST) { PLD8(1); }
    while (PBAD(1)) { if (++guard > (1 << 20)) TRAP(); PLD8(1); }
    padd(1);
  }
  const float c = blo(__shfl_sync(~0u, x[0], 0));
  float s0 = 0.f, s1 = 0.f, q0 = 0.f, q1 = 0.f, r0 = 0.f, r1 = 0.f;
#pragma unroll
  for (int i = 0; i < 8; i++) {
    const float a = blo(x[i]) - c, b = bhi(x[i]) - c;
    s0 += a; s1 += b; q0 = fmaf(a, a, q0); q1 = fmaf(b, b, q1); r0 = fmaf(a, blo(wv[i]), r0); r1 = fmaf(b, bhi(wv[i]), r1);
  }
  s0 += s1; q0 += q1; r0 += r1;
#pragma unroll
  for (int o = 16; o > 0; o >>= 1) { s0 += __shfl_xor_sync(~0u, s0, o); q0 += __shfl_xor_sync(~0u, q0, o); r0 += __shfl_xor_sync(~0u, r0, o); }
  const float dm = s0 * (1.f / 512.f), m = c + dm, var = fmaxf(fmaf(-dm, dm, q0 * (1.f / 512.f)), 0.f);
  const float mb = rbf(m), inv = rcp(rbf(sqrt_fast(rbf(rbf(var) + 1e-5f))));
  const uint32_t nmb = pack2(-mb, -mb);
  const unsigned long long wd = rword(E, tk, fmaf(c - mb, wsum, r0) * inv);
  uint32_t xn[8], x2[8];
#pragma unroll
  for (int i = 0; i < 8; i++) { const uint32_t d = add2(x[i], nmb); xn[i] = pack2(blo(d) * inv, bhi(d) * inv); x2[i] = add2(x[i], xn[i]); }
  if (st == 0) {
    const float mb2 = rbf(fmaf(m - mb, inv, m)), inv2 = rcp(rbf(sqrt_fast(rbf(rbf(var * (1.f + inv) * (1.f + inv)) + 1e-5f))));
    const uint32_t nmb2 = pack2(-mb2, -mb2);
    uint32_t h[8];
#pragma unroll
    for (int i = 0; i < 8; i++) { const uint32_t d2 = add2(x2[i], nmb2); h[i] = pack2(blo(d2) * inv2, bhi(d2) * inv2); }
    store_img(g_h[1][s], tk & 31, h, lane);
  }
  store_row(dst, x2, lane);
  if (wd > best && !(EXPQ_ & (st == 0 ? 1 : 2))) { store_row(req, xn, lane); store_row(req + 512, x, lane); }
  return wd;
}

__device__ __forceinline__ void ffn_slice(uint32_t sb, const bf16* xn, float* yacc, uint32_t* flag, uint32_t E, int t, bool urgent) {
  const int w = t >> 5, g = (t >> 2) & 7;
  if (t == 0 && urgent) sts32(sb + A_BAR + 160, 1);
  { const uint2 u = __ldcg((const uint2*)xn + t); asm volatile("st.shared.v2.u32 [%0], {%1,%2};" :: "r"(sb + A_XN + t * 8), "r"(u.x), "r"(u.y) : "memory"); }
  fence_async_smem();
  bar_sync(4, 128);
  float ga[4], ua[4];
  constexpr uint64_t da = mkdesc(A_WG, 896, 128, 0), db = mkdesc(A_XN, 16, 128, 0);
  wg_fence();
  wgmma_ss8<0, 1, 0>(ga, da, db); wgmma_ss8<0, 1, 0>(ua, da + (A_WU - A_WG) / 16, db);
#pragma unroll
  for (int ks = 1; ks < 32; ks++) { wgmma_ss8<1, 1, 0>(ga, da + ks * 112, db + ks * 2); wgmma_ss8<1, 1, 0>(ua, da + (A_WU - A_WG) / 16 + ks * 112, db + ks * 2); }
  wg_commit(); wg_wait<0>(); reg_fence(ga); reg_fence(ua);
  if ((t & 3) == 0) {
#pragma unroll
    for (int h = 0; h < 2; h++) {
      const float gs = rbf(ga[2 * h]), us = rbf(ua[2 * h]);
      const float v = 16 * w + 8 * h < 56 ? rbf(gs * rcp(1.f + __expf(-gs))) * us : 0.f;
      asm volatile("st.shared.u16 [%0], %1;" :: "r"(sb + A_XN + 1280 + (16 * w + 8 * h + g) * 2), "h"((unsigned short)pack2(v, 0.f)) : "memory");
    }
  }
  fence_async_smem();
  bar_sync(4, 128);
#pragma unroll 1
  for (int j = 0; j < 2; j++) {
    float y[4][4];
    const uint64_t dd = mkdesc(A_WD, 8192, 128, 0) + (uint64_t)(j * 256);
    wg_fence();
#pragma unroll
    for (int m = 0; m < 4; m++) {
      wgmma_ss8<0, 1, 0>(y[m], dd + m * 64, mkdesc(A_XN + 1280, 16, 128, 0));
#pragma unroll
      for (int ks = 1; ks < 4; ks++) wgmma_ss8<1, 1, 0>(y[m], dd + m * 64 + ks * 1024, mkdesc(A_XN + 1280 + ks * 32, 16, 128, 0));
    }
    wg_commit(); wg_wait<0>();
#pragma unroll
    for (int m = 0; m < 4; m++) {
      reg_fence(y[m]);
      if ((t & 3) == 0) { float* o = yacc + j * 256 + m * 64 + 16 * w + g; atomicAdd(o, y[m][0]); atomicAdd(o + 8, y[m][2]); }
    }
  }
  bar_sync(4, 128);
  if (t < 8) { sts32(sb + A_BAR + 160, 0); st_rel(flag + t, E); }
  __syncwarp();
}

__device__ __forceinline__ void ffn_finish(int q, const bf16* req, float r, uint32_t E, int lane, uint32_t* v) {
  uint32_t xn[8];
  load_row(xn, req, lane); load_row(v, req + 512, lane);
  const float rs = rbf(1.f / (1.f + __expf(-rbf(r))));
  wait_all(f_y[q][lane], E);
  float4 y[4];
#pragma unroll
  for (int i = 0; i < 4; i++) y[i] = __ldcg((const float4*)g_y[q] + (i >> 1) * 64 + 2 * lane + (i & 1));
#pragma unroll
  for (int i = 0; i < 4; i++) {
    v[2 * i] = add2(v[2 * i], add2(xn[2 * i], pack2(rbf(y[i].x) * rs, rbf(y[i].y) * rs)));
    v[2 * i + 1] = add2(v[2 * i + 1], add2(xn[2 * i + 1], pack2(rbf(y[i].z) * rs, rbf(y[i].w) * rs)));
  }
}
__global__ void __launch_bounds__(512, 1) aux_kernel(Params p) {
  extern __shared__ __align__(1024) uint8_t sm[];
  const uint32_t sb = smem_u32(sm);
  if ((sb & 0xFFFFFFu) != SBASE) TRAP();
  const int warp = __shfl_sync(~0u, threadIdx.x >> 5, 0);
  const int cta = blockIdx.x;
  const uint32_t E = __shfl_sync(~0u, *(volatile uint32_t*)&g_epoch + 1, 0);
  const uint32_t bars = sb + A_BAR;

  if (cta < 32) {
    const int cg = cta & 3, kg = cta >> 2;
    if (threadIdx.x == 0) {
      for (int i = 0; i < A_NST; i++) { mbar_init(bars + 8 * i, 1); mbar_init(bars + 64 + 8 * i, 2); }
      mbar_init(bars + 128, 8); mbar_init(bars + 136, 8); mbar_init(bars + 144, 1);
      sts32(bars + 160, 0);
      asm volatile("fence.mbarrier_init.release.cluster;" ::: "memory");
    }
    if (warp < 8) {
      asm volatile("setmaxnreg.inc.sync.aligned.u32 176;");
      const int tid = fresh_tid(), lane = tid & 31;
      uint32_t W[32][4];
      stage_weights(sb + A_WD, p.wo + (size_t)kg * 512 * 512 + cg * 128, 512, tid, 256);
      cp_async_wait();
      bar_sync(1, 256);
      load_frags(W, sb + A_WD, warp >> 2, warp & 3, lane);
      bar_sync(2, 512);
      const uint32_t so = sb + A_STG + ((lane >> 4) * 8 + (lane & 7)) * 256 + (((warp * 2 + ((lane >> 3) & 1)) ^ (lane & 7)) << 4);
      const uint32_t tm = lane < 4 ? 0x00010001u : 0u;
      int stage = 0; uint32_t ph = 0, job = 0;
#pragma unroll 1
      for (int T = 0; T < NSTEP; T++) {
#pragma unroll 1
        for (int k = 0; k < 3; k++) {
          const int st = k == 0 ? 0 : 3 - k, s = st == 0 ? T : T - LAG;
          if (s < 0 || s >= NSEG) continue;
          float d[16];
#pragma unroll
          for (int hh = 0; hh < 4; hh++) {
            mbar_wait(bars + 8 * stage, ph);
            while (uni(lds32(bars + 160))) __nanosleep(100);
            const uint64_t db = mkdesc(A_RING, 512, 128, 0) + (uint64_t)(stage * 512);
            wg_fence();
            if (hh == 0) wgmma_rs32<0, 0>(d, W[0], db); else wgmma_rs32<1, 0>(d, W[hh * 8], db);
#pragma unroll
            for (int ks = 1; ks < 8; ks++) wgmma_rs32<1, 0>(d, W[hh * 8 + ks], db + ks * 64);
            wg_commit();
            if (hh > 0) { wg_wait<1>(); if ((tid & 127) == 0) mbar_arrive(bars + 64 + 8 * (stage == 0 ? A_NST - 1 : stage - 1)); }
            if (++stage == A_NST) { stage = 0; ph ^= 1; }
          }
          mbar_wait(bars + 144, (job & 1) ^ 1);
          wg_wait<0>(); reg_fence(d);
          if ((tid & 127) == 0) mbar_arrive(bars + 64 + 8 * (stage == 0 ? A_NST - 1 : stage - 1));
          if (cta == 0 && tid == 0) TSTAMP(6, T, k);
          const uint32_t tv = tm * ptag(s);
#define TG(i) ((pack2(d[2 * (i)], d[2 * (i) + 1]) & ~tm) | tv)
          stmatrix4_t(so, TG(0), pack2(d[2], d[3]), TG(2), pack2(d[6], d[7]));
          stmatrix4_t(so + 4096, TG(4), pack2(d[10], d[11]), TG(6), pack2(d[14], d[15]));
          fence_async_smem();
          __syncwarp();
          if (lane == 0) mbar_arrive(bars + 128 + 8 * (job & 1));
          job++;
        }
      }
    } else if (warp < 12) {
      asm volatile("setmaxnreg.dec.sync.aligned.u32 120;");
      const int tid = fresh_tid(), lane = tid & 31;
      const int w = warp - 8, t = tid - 256;
#pragma unroll 1
      for (int s = cta + 4; s < NSEG; s += 32) {
#pragma unroll 1
        for (int pr = w; pr < 16; pr += 4) input_ln_pair(p.x, s, pr, lane);
        bar_sync(4, 128);
        if (t == 0) st_rel(&f_h1[s], E);
      }
      bar_sync(2, 512);
      { int guard = 0; while (ld_rlx(&f_loaded[cta]) != E) { __nanosleep(200); if (++guard > (1 << 22)) TRAP(); } }
#pragma unroll 1
      for (int i = t; i < 512 * 7; i += 128) {
        const int k = i / 7, pc = i % 7;
        cp_async16(sb + A_WG + (k >> 3) * 896 + pc * 128 + (k & 7) * 16, p.wg + (size_t)k * 1792 + cta * 56 + pc * 8);
        cp_async16(sb + A_WU + (k >> 3) * 896 + pc * 128 + (k & 7) * 16, p.wu + (size_t)k * 1792 + cta * 56 + pc * 8);
        cp_async16(sb + A_WD + (i >> 9) * 8192 + (i & 63) * 128 + ((i >> 6) & 7) * 16, p.wd + (size_t)cta * 56 * 512 + i * 8);
      }
      uint32_t wv[8];
      const float wsum = load_wr(wv, p.wr, lane);
      cp_async_wait();
      fence_async_smem();
      wait_all(&f_zero[lane], E);
      bar_sync(4, 128);
      const int tj = (cta * 4 + w) & 31, st = 1 + ((cta >> 3) & 1), sq = cta >> 4;
      unsigned long long run = 0, run2 = 0, best = 0, hist = 0;
      uint32_t open = 0;
#pragma unroll 1
      for (int i = 0; i <= NSTEP; i++) {
        int tok = -1; const bf16* req = nullptr;
        if (i < NSEG) {
          const int cd = (int)uni(route_step(i, E, lane, run));
          run = __shfl_sync(~0u, run, 0);
          hist = hist << 8 | (uint32_t)(cd + 1);
          if (cd >= 0) { tok = rtok(run); req = g_req1[tok][0]; }
        } else {
          const unsigned long long m = wait_words(f_l2[i - NSEG], E);
          if (m != run2) { run2 = m; tok = rtok(m); req = g_req2[(tok >> 5) < (rtok(run) >> 5) ? 0 : 1][tok][0]; }
        }
        tok = __shfl_sync(~0u, tok, 0);
        if (tok >= 0) {
          if (cta == 0 && t == 0) TSTAMP(8, i, 0);
          ffn_slice(sb, req, g_y[i], f_y[i][cta], E, t, i < NSEG);
          if (cta == 0 && t == 0) TSTAMP(8, i, 1);
        }
        const int s = i - LAG;
        if (s < 0 || i >= NSEG) continue;
        const int cd = (int)((hist >> (8 * LAG)) & 255) - 1;
        if (cd >= 0 && st == 2) best = 0;
        const int ts = rtok(run) >> 5;
        if ((s & 1) == sq) {
          const int tk = s * 32 + tj;
          unsigned long long wd = (unsigned long long)E << 43;
          if (st == 1 ? s < ts || i < NSEG - 1 : s >= ts) {
            if (st == 2 && cd == tj) wait_eq(&f_hc[s], E);
            wd = token_post<false>(st, tk, st == 2 && cd == tj ? g_x2c[s] : g_x2 + (size_t)tk * 512,
                                   (st == 2 || s < ts ? p.out : g_n) + (size_t)tk * 512, g_req2[st - 1][tk][0], best, wv, wsum, E, lane);
            best = max(best, wd);
            if (st == 1 && s >= ts) open |= 1u << (s >> 1);
          }
          __syncwarp();
          if (lane < 4) st_rel64(&f_w2[st - 1][s][tj][lane], wd);
          __syncwarp();
        }
        if (st == 1) {
          if (i == NSEG - 1 && t == 0 && cta == 0) GSTAMP(1, 0);
#pragma unroll 1
          for (int n = i == NSEG - 1 ? 32 : 2; n > 0 && open; n--) {
            const int s0 = 2 * (__ffs(open) - 1) + sq;
            if (s0 >= ts) break;
            open &= open - 1;
            uint32_t v[8];
            load_row(v, g_n + (size_t)(s0 * 32 + tj) * 512, lane);
            wait_words(f_w2[1][s0][tj], E);
            store_row(p.out + (size_t)(s0 * 32 + tj) * 512, v, lane);
          }
          if (i == NSEG - 1) {
            __syncwarp();
            if (lane == 0) st_rel(&f_cp[sq * 32 + tj], E);
            if (t == 0 && cta == 0) GSTAMP(1, 3);
          }
        }
      }
    } else {
      asm volatile("setmaxnreg.dec.sync.aligned.u32 40;");
      const int tid = fresh_tid(), lane = tid & 31;
      const int t = tid - 384, w = warp - 12;
      for (int i = cta * 128 + t; i < (NSTEP + 1) * 128; i += 4096) ((float4*)&g_y[0][0])[i] = make_float4(0.f, 0.f, 0.f, 0.f);
      bar_sync(3, 128);
      if (t == 0) st_rel(&f_zero[cta], E);
      bar_sync(2, 512);
      if (w == 0) {
        int stage = 0; uint32_t ph = 1;
#pragma unroll 1
        for (int T = 0; T < NSTEP; T++) {
#pragma unroll 1
          for (int k = 0; k < 3; k++) {
            const int st = k == 0 ? 0 : 3 - k, s = st == 0 ? T : T - LAG;
            if (s < 0 || s >= NSEG) continue;
            const uint32_t* fl = f_o[T][kg][st * 4 + (lane & 3)];
            uint32_t ready = 0; int guard = 0;
#pragma unroll 1
            for (int hh = 0; hh < 4; hh++) {
              while (!((ready >> hh) & 1)) {
                ready = __ballot_sync(~0u, ld_rlx(fl) == E);
                if (++guard > (1 << 23)) TRAP();
              }
              fence_async_glob();
              mbar_wait(bars + 64 + 8 * stage, ph);
              e_expect(bars + 8 * stage, OLOAD_);
              e_g2s(sb + A_RING + stage * 8192, g_o[st][s % ORING][kg * 4 + hh], OLOAD_, bars + 8 * stage);
              if (++stage == A_NST) { stage = 0; ph ^= 1; }
            }
          }
          if (cta == 0 && lane == 0) TSTAMP(3, T, 0);
        }
      } else if (w < 3) {
        uint32_t job = 0;
#pragma unroll 1
        for (int T = 0; T < NSTEP; T++) {
#pragma unroll 1
          for (int k = 0; k < 3; k++) {
            const int st = k == 0 ? 0 : 3 - k, s = st == 0 ? T : T - LAG;
            if (s < 0 || s >= NSEG) continue;
            if ((job++ & 1) != w - 1) continue;
            if (s >= PRING) wait_words(st == 0 ? f_h2[s - PRING][lane & 3] : f_w2[st - 1][s - PRING][lane], E);
            mbar_wait(bars + 128 + 8 * (w - 1), ((job - 1) >> 1) & 1);
            if (cta == 0 && st == 0) TSTAMP(7, s, 0);
            e_s2g(g_pp[st][s % PRING] + cta * 8192, sb + A_STG, PST_);
            asm volatile("cp.async.bulk.commit_group;\n cp.async.bulk.wait_group.read 0;" ::: "memory");
            __syncwarp();
            e_arrive(bars + 144);
            if (!HINT_) bulk_wait();
            __syncwarp();
            if (lane < 8) st_rlx(&f_acc[st][s][cta][lane], E);
            __syncwarp();
            if (cta == 0 && st == 0) TSTAMP(7, s, 1);
          }
        }
        bulk_wait();
      }
    }
  } else {
    const int tid = fresh_tid(), lane = tid & 31;
    const int qd = cta - 32;
    input_ln_pair(p.x, qd, warp, lane);
    bar_sync(6, 512);
    if (tid == 0) st_rel(&f_h1[qd], E);
    volatile int* bc = (volatile int*)sm;
    if (warp == 15) {
      unsigned long long run = 0;
      wait_all(&f_zero[lane], E);
      unsigned long long b2[2][2] = {{0, 0}, {0, 0}};
      auto track = [&](int s) {
#pragma unroll
        for (int k = 0; k < 2; k++) {
          const unsigned long long m = warp_max<16>(wait_words(f_w2[k][s][lane], E));
          if (lane == (s & 31)) { if (s < 32) b2[k][0] = m; else b2[k][1] = m; }
        }
      };
#pragma unroll 1
      for (int s = 0; s < NSEG; s++) {
        const int cd = route_step(s, E, lane, run);
        if (cd >= 0 && qd == (s & 1)) {
          uint32_t v[1][8], h[1][8];
          ffn_finish(s, g_req1[s * 32 + cd][0], rscore(run), E, lane, v[0]);
          if (lane == 0) TSTAMP(8, s, 2);
          ln_rows<1>(v, h);
#pragma unroll
          for (int i = 0; i < 8; i++) st_rlx64(&g_hc[s][(i >> 2) * 128 + 4 * lane + (i & 3)], h[0][i], E);
          if (lane == 0) TSTAMP(8, s, 3);
          store_row(g_x2c[s], v[0], lane);
          __syncwarp();
          if (lane == 0) st_rel(&f_hc[s], E);
        }
        if (qd == 2 && s > LAG) track(s - LAG - 1);
      }
      wait_eq(&f_hc[rtok(run) >> 5], E);
      if (lane == 0) *bc = rtok(run);
      bar_sync(7, 288);
      if (qd == 2) {
        uint32_t v[8];
        const int ts = rtok(run) >> 5;
        track(NSEG - LAG - 1);
        run = 0;
#pragma unroll 1
        for (int k = 0; k <= LAG; k++) {
          const int s = NSEG - LAG - 1 + k;
          const unsigned long long m = warp_max<16>(k == 0 ? max(lane < ts ? b2[0][0] : b2[1][0], lane + 32 < ts ? b2[0][1] : b2[1][1])
                                                           : wait_words(f_w2[s < ts ? 0 : 1][s][lane], E));
          const bool lead = m > run;
          if (lead) { run = m; __threadfence(); }
          if (lane < 4) st_rlx64(&f_l2[k][lane], (uint32_t)run, (uint32_t)(run >> 32));
          if (lead) ffn_finish(NSEG + k, g_req2[(rtok(run) >> 5) < ts ? 0 : 1][rtok(run)][0], rscore(run), E, lane, v);
          if (k == 0) { wait_all(&f_cp[lane], E); wait_all(&f_cp[32 + lane], E); }
        }
        if (lane == 0) GSTAMP(1, 1);
        store_row(p.out + (size_t)rtok(run) * 512, v, lane);
        if (lane == 0) GSTAMP(1, 2);
        asm volatile("griddepcontrol.wait;" ::: "memory");
        if (lane == 0) *(volatile uint32_t*)&g_epoch = E;
      }
    } else if (warp < 8) {
      uint32_t wv[8];
      const float wsum = load_wr(wv, p.wr, lane);
      unsigned long long best = 0;
      int ttok = 0;
#pragma unroll 1
      for (int i = 0; i < NSTEP; i++) {
        const bool last = i >= NSEG;
        if (i == NSEG) { bar_sync(7, 288); ttok = *bc; best = 0; }
        const int s = last ? i - LAG : i, st = !last ? 0 : s < (ttok >> 5) ? 1 : 2;
        const int tk = s * 32 + qd * 8 + warp;
        const unsigned long long wd = token_post<true>(st, tk, !last ? p.x + (size_t)tk * 512 : tk == ttok ? g_x2c[s] : g_x2 + (size_t)tk * 512,
                                                 (last ? p.out : g_x2) + (size_t)tk * 512, last ? g_req2[st - 1][tk][0] : g_req1[tk][0], best, wv, wsum, E, lane);
        best = max(best, wd);
        volatile unsigned long long* ws = (volatile unsigned long long*)(sm + 64) + (i & 1) * 8;
        if (lane == 0) ws[warp] = wd;
        bar_sync(5, 256);
        if (warp == 0) {
          if (qd == 0 && lane == 0) TSTAMP(4, i, 1);
          if (!last) { const unsigned long long m = warp_max<4>(ws[lane & 7]); if (lane < 4) st_rel64(&f_h2[s][qd][lane], m); }
          else {
            st_rel64(&f_w2[st - 1][s][qd * 8 + (lane >> 2)][lane & 3], ws[lane >> 2]);
            asm volatile("st.relaxed.gpu.global.u64 [%0], %1;" :: "l"(&f_w2[2 - st][s][qd * 8 + (lane >> 2)][lane & 3]), "l"((unsigned long long)E << 43) : "memory");
          }
          if (qd == 0 && lane == 0) TSTAMP(4, i, 2);
        }
        __syncwarp();
      }
    }
  }
}

}

extern "C" void kernel_launch(void* const* d_in, const int* in_sizes, int n_in, void* d_out, int out_size) {
  (void)in_sizes; (void)n_in; (void)out_size;
  static bool init = false;
  if (!init) {
    cudaFuncSetAttribute(main_kernel, cudaFuncAttributeMaxDynamicSharedMemorySize, M_TOTAL);
    cudaFuncSetAttribute(aux_kernel, cudaFuncAttributeMaxDynamicSharedMemorySize, A_TOTAL);
    init = true;
  }
  Params p;
  p.x = (const bf16*)d_in[0]; p.mem0 = (const bf16*)d_in[1]; p.wq = (const bf16*)d_in[2]; p.wk = (const bf16*)d_in[3];
  p.wv = (const bf16*)d_in[4]; p.wo = (const bf16*)d_in[5]; p.wr = (const bf16*)d_in[8]; p.wg = (const bf16*)d_in[9];
  p.wu = (const bf16*)d_in[10]; p.wd = (const bf16*)d_in[11]; p.out = (bf16*)d_out; p.zero = 0; p.zero2 = 0;
  cudaStream_t st = cudaStreamPerThread;
  main_kernel<<<96, 512, M_TOTAL, st>>>(p);
  cudaLaunchConfig_t cfg = {};
  cfg.gridDim = dim3(36); cfg.blockDim = dim3(512); cfg.dynamicSmemBytes = A_TOTAL; cfg.stream = st;
  cudaLaunchAttribute at[1];
  at[0].id = cudaLaunchAttributeProgrammaticStreamSerialization; at[0].val.programmaticStreamSerializationAllowed = 1;
  cfg.attrs = at; cfg.numAttrs = 1;
  cudaLaunchKernelEx(&cfg, aux_kernel, p);
}
```

```cpp
#include <cuda_runtime.h>
#include <cuda_bf16.h>
#include <stdint.h>

namespace {

typedef __nv_bfloat16 bf16;

constexpr int NSEG = 64;
#define LAG_ 5
constexpr int LAG = LAG_;
constexpr int NSTEP = NSEG + LAG;
constexpr int ORING = 8, PRING = 4;
#define E1_ 10
#define E2_ 0
#define E3_ 10
constexpr int E1 = E1_, E2 = E2_, E3 = E3_, EA = E1 + E2 + E3;
static_assert(EA % 4 == 0 && EA > 0 && EA < 32 && E1 > 0, "early part: whole 64-column chunks");
#define RW_ 176
#define RA_ 136
#define RC_ 24
#define STR2(x) #x
#define STR(x) STR2(x)
#define RED_ 30
#define ARR_ 7
#define HADD_ 1
#define PAUSE_ 19
#define PD1_ 4
#define PST2_ 2
#define PGR_ PD1_
#define DPOLL_ 0
#define SALT_ 0
#define KP1_ 1
#define EARLY_ 0
#define PRIV_ 1
#define OLOAD_ 8192
#define PST_ 8192
#define ALT_ 1
#define TQ_ 1
#define NOF_ 2
#define EXPQ_ 0
#define XT1_ 8192
#define XT2_ 4096
#define XO_ 8192
#define HINT_ 1
#define HAND_ 4
#define GO3_ 2
#define NPROBE_ 6
#define TP(i, v) (v)
#define XDLY_ TP(0, 2250)
#define YDLY_ TP(1, 3425)
#define X1_ TP(2, 100)
#define X2_ TP(3, 250)
#define Y1_ TP(4, 150)
#define Y2_ TP(5, 200)
#define HGAP_ TP(6, 50)
#define TGAP_ TP(7, 200)
#define ADLY_ TP(8, 600)
#define ODLY_ TP(9, 2800)
#define LDLY_ TP(10, 3800)
#define LGAP_ 200
#define HDLY_ TP(11, 0)
#define TDLY_ TP(15, 4000)
#define SDLY_ TP(12, 800)
#define AGAP_ 100
#define BOFF_ TP(13, 200)
#define YOFF_ TP(16, 150)
#define CDLY_ TP(17, 300)
#define SLOW0_ TP(18, 400)
#define SLOW1_ TP(19, 300)
#define KDLY_ TP(14, 300)
__device__ uint32_t g_epoch;
__device__ __align__(1024) uint8_t g_h[2][NSEG][32768];
__device__ __align__(128) uint2 g_hc[NSEG][256];
__device__ __align__(128) bf16 g_x2[2048 * 512];
__device__ __align__(128) bf16 g_x2c[NSEG][512];
__device__ __align__(128) uint8_t g_o[3][ORING][32][8192];
__device__ __align__(128) uint8_t g_pp[3][PRING][8 * 32768];
__device__ __align__(128) bf16 g_n[2048 * 512];
__device__ __align__(128) uint8_t g_xch[96 * 16384 + 65536 + 8192];
__device__ __align__(128) bf16 g_req1[2048][2][512];
__device__ __align__(128) bf16 g_req2[2][2048][2][512];
__device__ __align__(128) float g_y[NSTEP + 1][512];
__device__ __align__(128) uint8_t g_tok[96][2][16384];
__device__ uint32_t f_choice[96][2], f_loaded[32];
__device__ uint32_t f_h1[NSEG], f_hc[NSEG];
__device__ __align__(128) unsigned long long f_h2[NSEG][4][4];
__device__ __align__(128) unsigned long long f_w2[2][NSEG][32][4];
__device__ __align__(128) unsigned long long f_l2[LAG + 1][4];
__device__ __align__(128) uint32_t f_o[NSTEP][8][12][8];
__device__ __align__(128) uint32_t f_acc[3][NSEG][32][8], f_y[NSTEP + 1][32][8], f_zero[32], f_cp[64];
__device__ __align__(128) unsigned long long g_sync[2][96][4];

#define TRAP() __trap()
__device__ __forceinline__ uint32_t smem_u32(const void* p) { return (uint32_t)__cvta_generic_to_shared(p); }
__device__ __forceinline__ int fresh_tid() { const int t = threadIdx.x; return __shfl_sync(~0u, t, t & 31); }
__device__ __forceinline__ unsigned long long gtime64() { unsigned long long t; asm volatile("mov.u64 %0, %%globaltimer;" : "=l"(t) :: "memory"); return t; }
__device__ __forceinline__ uint32_t clk() { unsigned long long c; asm volatile("mov.u64 %0, %%clock64;" : "=l"(c) :: "memory"); return (uint32_t)c; }
__device__ __forceinline__ void wait_until(uint32_t t) {
  while ((int)(t - clk()) > 450) __nanosleep(32);
  uint32_t c;
  do { asm volatile("mov.u32 %0, %%clock;" : "=r"(c) :: "memory"); } while ((int)(c - t) < 0);
}
__device__ __forceinline__ void mbar_init(uint32_t bar, uint32_t cnt) { asm volatile("mbarrier.init.shared::cta.b64 [%0], %1;" :: "r"(bar), "r"(cnt) : "memory"); }
__device__ __forceinline__ void mbar_arrive(uint32_t bar) { asm volatile("mbarrier.arrive.shared::cta.b64 _, [%0];" :: "r"(bar) : "memory"); }
__device__ __forceinline__ void mbar_arrive_remote(uint32_t bar) { asm volatile("mbarrier.arrive.relaxed.cluster.shared::cluster.b64 _, [%0];" :: "r"(bar) : "memory"); }
__device__ __forceinline__ void mbar_expect(uint32_t bar, uint32_t bytes) { asm volatile("mbarrier.arrive.expect_tx.shared::cta.b64 _, [%0], %1;" :: "r"(bar), "r"(bytes) : "memory"); }
__device__ __forceinline__ bool mbar_try(uint32_t bar, uint32_t parity) {
  uint32_t ok;
  asm volatile("{.reg .pred p; mbarrier.try_wait.parity.shared::cta.b64 p, [%1], %2; selp.u32 %0, 1, 0, p;}" : "=r"(ok) : "r"(bar), "r"(parity) : "memory");
  return ok;
}
__device__ __forceinline__ bool mbar_test(uint32_t bar, uint32_t parity) {
  uint32_t ok;
  asm volatile("{.reg .pred p; mbarrier.test_wait.parity.shared::cta.b64 p, [%1], %2; selp.u32 %0, 1, 0, p;}" : "=r"(ok) : "r"(bar), "r"(parity) : "memory");
  return ok;
}
__device__ __forceinline__ void mbar_wait(uint32_t bar, uint32_t parity) {
  asm volatile("{\n.reg .pred p;\nWAIT:\nmbarrier.try_wait.parity.shared::cta.b64 p, [%0], %1;\n@!p bra WAIT;\n}" :: "r"(bar), "r"(parity) : "memory");
}
__device__ __forceinline__ uint32_t ld_acq(const uint32_t* p) { uint32_t v; asm volatile("ld.acquire.gpu.global.u32 %0, [%1];" : "=r"(v) : "l"(p) : "memory"); return v; }
__device__ __forceinline__ unsigned long long ld_acq64(const unsigned long long* p) { unsigned long long v; asm volatile("ld.acquire.gpu.global.u64 %0, [%1];" : "=l"(v) : "l"(p) : "memory"); return v; }
__device__ __forceinline__ void st_rel(uint32_t* p, uint32_t v) { asm volatile("st.release.gpu.global.u32 [%0], %1;" :: "l"(p), "r"(v) : "memory"); }
__device__ __forceinline__ void st_rel64(unsigned long long* p, unsigned long long v) { asm volatile("st.release.gpu.global.u64 [%0], %1;" :: "l"(p), "l"(v) : "memory"); }
__device__ __forceinline__ void red_rel(uint32_t* p, uint32_t v) { asm volatile("red.release.gpu.global.add.u32 [%0], %1;" :: "l"(p), "r"(v) : "memory"); }
__device__ __forceinline__ uint32_t ld_rlx(const uint32_t* p) { uint32_t v; asm volatile("ld.relaxed.gpu.global.u32 %0, [%1];" : "=r"(v) : "l"(p) : "memory"); return v; }
__device__ __forceinline__ unsigned long long ld_rlxu64(const unsigned long long* p) { unsigned long long v; asm volatile("ld.relaxed.gpu.global.u64 %0, [%1];" : "=l"(v) : "l"(p) : "memory"); return v; }
__device__ __forceinline__ void st_rlx(uint32_t* p, uint32_t v) { asm volatile("st.relaxed.gpu.global.u32 [%0], %1;" :: "l"(p), "r"(v) : "memory"); }
__device__ __forceinline__ void bulk_wait() { asm volatile("cp.async.bulk.commit_group;\n cp.async.bulk.wait_group 0;" ::: "memory"); }
__device__ __forceinline__ void fence_acq() { asm volatile("fence.acquire.gpu;" ::: "memory"); }
__device__ __forceinline__ void wait_all(const uint32_t* p, uint32_t v, bool acquire = true) {
  int guard = 0;
  while (!__all_sync(~0u, ld_rlx(p) == v)) { __nanosleep(32); if (++guard > (1 << 22)) TRAP(); }
  if (acquire) fence_acq();
}
__device__ __forceinline__ void wait_eq(const uint32_t* p, uint32_t v) {
  int guard = 0;
  while (ld_rlx(p) != v) { __nanosleep(64); if (++guard > (1 << 22)) TRAP(); }
  fence_acq();
}
__device__ __forceinline__ unsigned long long rword(uint32_t E, int tok, float r) {
  uint32_t u = __float_as_uint(r + 0.f);
  u = r != r ? 0u : (u >> 31) ? ~u : u | 0x80000000u;
  return (unsigned long long)(E & 0x1FFFFFu) << 43 | (unsigned long long)u << 11 | (uint32_t)(2047 - tok);
}
__device__ __forceinline__ int rtok(unsigned long long v) { return 2047 - (int)(v & 2047u); }
__device__ __forceinline__ float rscore(unsigned long long v) { const uint32_t u = (uint32_t)(v >> 11); return __uint_as_float((u >> 31) ? u & 0x7fffffffu : ~u); }
__device__ __forceinline__ bool rfresh(unsigned long long v, uint32_t E) { return (uint32_t)(v >> 43) == (E & 0x1FFFFFu); }
template <int TOP> __device__ __forceinline__ unsigned long long warp_max(unsigned long long v) {
#pragma unroll
  for (int o = TOP; o > 0; o >>= 1) { const unsigned long long ov = __shfl_xor_sync(~0u, v, o); v = ov > v ? ov : v; }
  return v;
}
template <int off> __device__ __forceinline__ uint2 ld_rlx64(const void* p) { unsigned long long v; asm volatile("ld.relaxed.gpu.global.b64 %0, [%1+%2];" : "=l"(v) : "l"(p), "n"(off) : "memory"); return make_uint2((uint32_t)v, (uint32_t)(v >> 32)); }
template <int off> __device__ __forceinline__ uint4 ld_rlx128(const void* p) {
  unsigned long long a, b; asm volatile("ld.relaxed.gpu.global.v2.b64 {%0,%1}, [%2+%3];" : "=l"(a), "=l"(b) : "l"(p), "n"(off) : "memory");
  return make_uint4((uint32_t)a, (uint32_t)(a >> 32), (uint32_t)b, (uint32_t)(b >> 32));
}
__device__ __forceinline__ void st_rlx64(void* p, uint32_t lo, uint32_t hi) { asm volatile("{.reg .b64 t; mov.b64 t, {%1,%2}; st.relaxed.gpu.global.b64 [%0], t;}" :: "l"(p), "r"(lo), "r"(hi) : "memory"); }
__device__ __forceinline__ void cp_async16(uint32_t dst, const void* src) { asm volatile("cp.async.cg.shared.global [%0], [%1], 16;" :: "r"(dst), "l"(src) : "memory"); }
__device__ __forceinline__ void cp_async_wait() { asm volatile("cp.async.wait_all;" ::: "memory"); }
__device__ __forceinline__ void fence_async_smem() { asm volatile("fence.proxy.async.shared::cta;" ::: "memory"); }
__device__ __forceinline__ void fence_async_glob() { asm volatile("fence.proxy.async.global;" ::: "memory"); }
__device__ __forceinline__ void fence_async_acq() { asm volatile("fence.proxy.async::generic.acquire.sync_restrict::shared::cluster.cluster;" ::: "memory"); }
__device__ __forceinline__ float ex2(float x) { float y; asm("ex2.approx.ftz.f32 %0, %1;" : "=f"(y) : "f"(x)); return y; }
__device__ __forceinline__ float sqrt_fast(float x) { float y; asm("sqrt.approx.ftz.f32 %0, %1;" : "=f"(y) : "f"(x)); return y; }
__device__ __forceinline__ float rcp(float x) { float y; asm("rcp.approx.ftz.f32 %0, %1;" : "=f"(y) : "f"(x)); return y; }
__device__ __forceinline__ void bar_sync(int id, int n) { asm volatile("bar.sync %0, %1;" :: "r"(id), "r"(n) : "memory"); }
__device__ __forceinline__ bool bar_or(int id, int n, bool v) {
  uint32_t r;
  asm volatile("{.reg .pred p, q; setp.ne.u32 p, %3, 0; barrier.cta.red.or.aligned.pred q, %1, %2, p; selp.u32 %0, 1, 0, q;}" : "=r"(r) : "r"(id), "r"(n), "r"((uint32_t)v) : "memory");
  return r;
}
__device__ __forceinline__ uint32_t mapa(uint32_t a, uint32_t rank) { uint32_t r; asm volatile("mapa.shared::cluster.u32 %0, %1, %2;" : "=r"(r) : "r"(a), "r"(rank)); return r; }
__device__ __forceinline__ void cluster_sync() { asm volatile("barrier.cluster.arrive.release.aligned; barrier.cluster.wait.acquire.aligned;" ::: "memory"); }
__device__ __forceinline__ void st_async32(uint32_t dst, uint32_t v, uint32_t bar) { asm volatile("st.async.shared::cluster.mbarrier::complete_tx::bytes.b32 [%0], %1, [%2];" :: "r"(dst), "r"(v), "r"(bar) : "memory"); }
__device__ __forceinline__ void bulk_g2s(uint32_t dst, const void* src, uint32_t bytes, uint32_t bar) {
  asm volatile("cp.async.bulk.shared::cluster.global.mbarrier::complete_tx::bytes [%0], [%1], %2, [%3];" :: "r"(dst), "l"(src), "r"(bytes), "r"(bar) : "memory");
}
__device__ __forceinline__ void bulk_g2s_mc(uint32_t dst, const void* src, uint32_t bytes, uint32_t bar, uint16_t mask) {
  asm volatile("cp.async.bulk.shared::cluster.global.mbarrier::complete_tx::bytes.multicast::cluster [%0], [%1], %2, [%3], %4;"
               :: "r"(dst), "l"(src), "r"(bytes), "r"(bar), "h"(mask) : "memory");
}
__device__ __forceinline__ void bulk_s2c(uint32_t dst, uint32_t src, uint32_t bytes, uint32_t bar) {
  asm volatile("cp.async.bulk.shared::cluster.shared::cta.mbarrier::complete_tx::bytes [%0], [%1], %2, [%3];" :: "r"(dst), "r"(src), "r"(bytes), "r"(bar) : "memory");
}
__device__ __forceinline__ void bulk_s2g(void* dst, uint32_t src, uint32_t bytes) {
  asm volatile("cp.async.bulk.global.shared::cta.bulk_group [%0], [%1], %2;" :: "l"(dst), "r"(src), "r"(bytes) : "memory");
}
#define ELECT(op) "{.reg .pred p; elect.sync _|p, 0xffffffff; @p " op "}"
__device__ __forceinline__ void e_arrive(uint32_t bar) { asm volatile(ELECT("mbarrier.arrive.shared::cta.b64 _, [%0];") :: "r"(bar) : "memory"); }
__device__ __forceinline__ void e_expect(uint32_t bar, uint32_t bytes) { asm volatile(ELECT("mbarrier.arrive.expect_tx.shared::cta.b64 _, [%0], %1;") :: "r"(bar), "r"(bytes) : "memory"); }
__device__ __forceinline__ void e_g2s(uint32_t dst, const void* src, uint32_t bytes, uint32_t bar) {
  asm volatile(ELECT("cp.async.bulk.shared::cluster.global.mbarrier::complete_tx::bytes [%0], [%1], %2, [%3];") :: "r"(dst), "l"(src), "r"(bytes), "r"(bar) : "memory");
}
__device__ __forceinline__ void e_mc(uint32_t dst, const void* src, uint32_t bytes, uint32_t bar, uint16_t mask) {
  asm volatile(ELECT("cp.async.bulk.shared::cluster.global.mbarrier::complete_tx::bytes.multicast::cluster [%0], [%1], %2, [%3], %4;")
               :: "r"(dst), "l"(src), "r"(bytes), "r"(bar), "h"(mask) : "memory");
}
__device__ __forceinline__ void e_s2g(void* dst, uint32_t src, uint32_t bytes) {
  asm volatile(ELECT("cp.async.bulk.global.shared::cta.bulk_group [%0], [%1], %2;") :: "l"(dst), "r"(src), "r"(bytes) : "memory");
}
__device__ __forceinline__ void e_st_rel(uint32_t* p, uint32_t v) { asm volatile(ELECT("st.release.gpu.global.u32 [%0], %1;") :: "l"(p), "r"(v) : "memory"); }
__device__ __forceinline__ uint32_t clk32() { uint32_t c; asm volatile("mov.u32 %0, %%clock;" : "=r"(c) :: "memory"); return c; }
__device__ __forceinline__ void spin_until(uint32_t t) { while ((int)(clk32() - t) < 0) {} }
__device__ __forceinline__ uint32_t uni(uint32_t v) { return __shfl_sync(~0u, v, 0); }
__device__ __forceinline__ uint32_t pack2(float lo, float hi) { uint32_t r; asm("cvt.rn.bf16x2.f32 %0, %1, %2;" : "=r"(r) : "f"(hi), "f"(lo)); return r; }
__device__ __forceinline__ uint32_t add2(uint32_t a, uint32_t b) { uint32_t r; asm("add.rn.bf16x2 %0, %1, %2;" : "=r"(r) : "r"(a), "r"(b)); return r; }
__device__ __forceinline__ float rbf(float x) { return __bfloat162float(__float2bfloat16_rn(x)); }
__device__ __forceinline__ float blo(uint32_t u) { return __uint_as_float(u << 16); }
__device__ __forceinline__ float bhi(uint32_t u) { return __uint_as_float(u & 0xffff0000u); }
__device__ __forceinline__ uint32_t gentag(uint32_t g) { return (g & 1u) | (g & 2u) << 15; }
__device__ __forceinline__ uint32_t pack2_tag(float lo, float hi, uint32_t tag) {
  const uint32_t u = __byte_perm(__float_as_uint(lo), __float_as_uint(hi), 0x7632);
  return u + ((u ^ tag) & 0x10001u);
}
__device__ __forceinline__ uint32_t xo2(uint32_t a, uint32_t b, uint32_t t) { uint32_t r; asm("lop3.b32 %0, %1, %2, %3, 0x7e;" : "=r"(r) : "r"(a), "r"(b), "r"(t)); return r; }
__device__ __forceinline__ uint32_t or3(uint32_t a, uint32_t b, uint32_t c) { uint32_t r; asm("lop3.b32 %0, %1, %2, %3, 0xfe;" : "=r"(r) : "r"(a), "r"(b), "r"(c)); return r; }
__device__ __forceinline__ void stmatrix4(uint32_t a, uint32_t r0, uint32_t r1, uint32_t r2, uint32_t r3) {
  asm volatile("stmatrix.sync.aligned.m8n8.x4.shared.b16 [%0], {%1,%2,%3,%4};" :: "r"(a), "r"(r0), "r"(r1), "r"(r2), "r"(r3) : "memory");
}
__device__ __forceinline__ void stmatrix4_t(uint32_t a, uint32_t r0, uint32_t r1, uint32_t r2, uint32_t r3) {
  asm volatile("stmatrix.sync.aligned.m8n8.x4.trans.shared.b16 [%0], {%1,%2,%3,%4};" :: "r"(a), "r"(r0), "r"(r1), "r"(r2), "r"(r3) : "memory");
}
__device__ __forceinline__ void ldmatrix4_t(uint32_t* r, uint32_t a) {
  asm volatile("ldmatrix.sync.aligned.m8n8.x4.trans.shared.b16 {%0,%1,%2,%3}, [%4];" : "=r"(r[0]), "=r"(r[1]), "=r"(r[2]), "=r"(r[3]) : "r"(a) : "memory");
}
__device__ __forceinline__ void ldmatrix4(uint32_t* r, uint32_t a) {
  asm volatile("ldmatrix.sync.aligned.m8n8.x4.shared.b16 {%0,%1,%2,%3}, [%4];" : "=r"(r[0]), "=r"(r[1]), "=r"(r[2]), "=r"(r[3]) : "r"(a) : "memory");
}
__device__ __forceinline__ void hmma16(float* c, const uint32_t* a, uint32_t b0, uint32_t b1) {
  asm volatile("mma.sync.aligned.m16n8k16.row.col.f32.bf16.bf16.f32 {%0,%1,%2,%3}, {%4,%5,%6,%7}, {%8,%9}, {%0,%1,%2,%3};"
               : "+f"(c[0]), "+f"(c[1]), "+f"(c[2]), "+f"(c[3]) : "r"(a[0]), "r"(a[1]), "r"(a[2]), "r"(a[3]), "r"(b0), "r"(b1));
}
__device__ __forceinline__ void hmma8(float* c, uint32_t a0, uint32_t a1, uint32_t b0) {
  asm volatile("mma.sync.aligned.m16n8k8.row.col.f32.bf16.bf16.f32 {%0,%1,%2,%3}, {%4,%5}, {%6}, {%0,%1,%2,%3};"
               : "+f"(c[0]), "+f"(c[1]), "+f"(c[2]), "+f"(c[3]) : "r"(a0), "r"(a1), "r"(b0));
}
__device__ __forceinline__ uint4 lds128(uint32_t a) { uint4 v; asm volatile("ld.shared.v4.u32 {%0,%1,%2,%3}, [%4];" : "=r"(v.x), "=r"(v.y), "=r"(v.z), "=r"(v.w) : "r"(a) : "memory"); return v; }
__device__ __forceinline__ void sts128(uint32_t a, uint4 v) { asm volatile("st.shared.v4.u32 [%0], {%1,%2,%3,%4};" :: "r"(a), "r"(v.x), "r"(v.y), "r"(v.z), "r"(v.w) : "memory"); }
__device__ __forceinline__ void sts128f(uint32_t a, float x, float y, float z, float w) { asm volatile("st.shared.v4.f32 [%0], {%1,%2,%3,%4};" :: "r"(a), "f"(x), "f"(y), "f"(z), "f"(w) : "memory"); }
__device__ __forceinline__ void sts64f(uint32_t a, float x, float y) { asm volatile("st.shared.v2.f32 [%0], {%1,%2};" :: "r"(a), "f"(x), "f"(y) : "memory"); }
__device__ __forceinline__ uint32_t lds32(uint32_t a) { uint32_t v; asm volatile("ld.shared.u32 %0, [%1];" : "=r"(v) : "r"(a) : "memory"); return v; }
__device__ __forceinline__ void sts32(uint32_t a, uint32_t v) { asm volatile("st.shared.u32 [%0], %1;" :: "r"(a), "r"(v) : "memory"); }

constexpr uint32_t SBASE = 1024;
__host__ __device__ constexpr uint64_t mkdesc(uint32_t off, uint32_t lbo, uint32_t sbo, uint32_t swz) {
  return (uint64_t)(((SBASE + off) & 0x3FFFF) >> 4) | ((uint64_t)(lbo >> 4) << 16) | ((uint64_t)(sbo >> 4) << 32) | ((uint64_t)swz << 62);
}
__device__ __forceinline__ void wg_fence() { asm volatile("wgmma.fence.sync.aligned;" ::: "memory"); }
__device__ __forceinline__ void wg_commit() { asm volatile("wgmma.commit_group.sync.aligned;" ::: "memory"); }
template <int N> __device__ __forceinline__ void wg_wait() { asm volatile("wgmma.wait_group.sync.aligned %0;" :: "n"(N) : "memory"); }

template <int N> __device__ __forceinline__ void reg_fence(float (&d)[N], int n = N) {
#pragma unroll
  for (int i = 0; i < N; i++) if (i < n) asm volatile("" : "+f"(d[i]) :: "memory");
}
#define F4(b) "+f"(d[b]), "+f"(d[b + 1]), "+f"(d[b + 2]), "+f"(d[b + 3])
#define F8(b) F4(b), F4(b + 4)
#define F16(b) F8(b), F8(b + 8)
#define G4(b) "=f"(d[b]), "=f"(d[b + 1]), "=f"(d[b + 2]), "=f"(d[b + 3])
#define G8(b) G4(b), G4(b + 4)
#define G16(b) G8(b), G8(b + 8)
#define RS_IN "r"(a[0]), "r"(a[1]), "r"(a[2]), "r"(a[3]), "l"(db), "n"(SD), "n"(TB)
#define SS_IN "l"(da), "l"(db), "n"(SD), "n"(TA), "n"(TB)
#define WG_OP(str, out0, out1, in) do { if (SD || KEEP) asm volatile(str : out1 : in); else asm volatile(str : out0 : in); } while (0)
#define O12(X) X##8(0), X##4(8)
#define O20(X) X##16(0), X##4(16)
#define O32(X) X##16(0), X##16(16)
template <int SD, int TB, int KEEP = 0> __device__ __forceinline__ void wgmma_rs24(float* d, const uint32_t* a, uint64_t db) {
  WG_OP("wgmma.mma_async.sync.aligned.m64n24k16.f32.bf16.bf16 {%0,%1,%2,%3,%4,%5,%6,%7,%8,%9,%10,%11}, {%12,%13,%14,%15}, %16, %17, 1, 1, %18;", O12(G), O12(F), RS_IN);
}
template <int SD, int TB, int KEEP = 0> __device__ __forceinline__ void wgmma_rs32(float* d, const uint32_t* a, uint64_t db) {
  WG_OP("wgmma.mma_async.sync.aligned.m64n32k16.f32.bf16.bf16 {%0,%1,%2,%3,%4,%5,%6,%7,%8,%9,%10,%11,%12,%13,%14,%15}, {%16,%17,%18,%19}, %20, %21, 1, 1, %22;", G16(0), F16(0), RS_IN);
}
template <int SD, int TB, int KEEP = 0> __device__ __forceinline__ void wgmma_rs40(float* d, const uint32_t* a, uint64_t db) {
  WG_OP("wgmma.mma_async.sync.aligned.m64n40k16.f32.bf16.bf16 {%0,%1,%2,%3,%4,%5,%6,%7,%8,%9,%10,%11,%12,%13,%14,%15,"
        "%16,%17,%18,%19}, {%20,%21,%22,%23}, %24, %25, 1, 1, %26;", O20(G), O20(F), RS_IN);
}
template <int SD, int TB, int KEEP = 0> __device__ __forceinline__ void wgmma_rs64(float* d, const uint32_t* a, uint64_t db) {
  WG_OP("wgmma.mma_async.sync.aligned.m64n64k16.f32.bf16.bf16 {%0,%1,%2,%3,%4,%5,%6,%7,%8,%9,%10,%11,%12,%13,%14,%15,"
        "%16,%17,%18,%19,%20,%21,%22,%23,%24,%25,%26,%27,%28,%29,%30,%31}, {%32,%33,%34,%35}, %36, %37, 1, 1, %38;", O32(G), O32(F), RS_IN);
}
template <int SD, int TA, int TB, int KEEP = 0> __device__ __forceinline__ void wgmma_ss24(float* d, uint64_t da, uint64_t db) {
  WG_OP("wgmma.mma_async.sync.aligned.m64n24k16.f32.bf16.bf16 {%0,%1,%2,%3,%4,%5,%6,%7,%8,%9,%10,%11}, %12, %13, %14, 1, 1, %15, %16;", O12(G), O12(F), SS_IN);
}
template <int SD, int TA, int TB, int KEEP = 0> __device__ __forceinline__ void wgmma_ss8(float* d, uint64_t da, uint64_t db) {
  WG_OP("wgmma.mma_async.sync.aligned.m64n8k16.f32.bf16.bf16 {%0,%1,%2,%3}, %4, %5, %6, 1, 1, %7, %8;", G4(0), F4(0), SS_IN);
}
__device__ __forceinline__ void bar_arrive(int id, int n) { asm volatile("bar.arrive %0, %1;" :: "r"(id), "r"(n) : "memory"); }
__device__ __forceinline__ uint32_t vis_bits(int pos, int t) {
  uint32_t m = 0;
#pragma unroll
  for (int i = 0; i < 8; i++) m |= (8 * (i / 2 + 1) + 2 * t + (i & 1) <= pos) ? 1u << i : 0u;
  return m;
}

__device__ __forceinline__ unsigned long long wait_words(const unsigned long long* p, uint32_t E) {
  int guard = 0; unsigned long long m;
  while (m = ld_rlxu64(p), !__all_sync(~0u, rfresh(m, E))) { __nanosleep(32); if (++guard > (1 << 22)) TRAP(); }
  fence_acq();
  return m;
}
__device__ __forceinline__ int route_step(int s, uint32_t E, int lane, unsigned long long& run) {
  const unsigned long long m = warp_max<2>(wait_words(f_h2[s][lane & 3], E));
  if (s == 0 || m > run) { run = m; return rtok(m) & 31; }
  return -1;
}

struct Params {
  const bf16 *x, *mem0, *wq, *wk, *wv, *wo, *wr, *wg, *wu, *wd;
  bf16* out;
  uint32_t zero2;
  unsigned long long zero;
};

constexpr uint32_t WSTG_STRIDE = 272;
__device__ __forceinline__ void stage_weights(uint32_t stg, const bf16* src, int ld, int tid, int nthr) {
  for (int i = tid; i < 512 * 16; i += nthr) {
    int k = i >> 4, c = i & 15;
    cp_async16(stg + k * WSTG_STRIDE + c * 16, src + (size_t)k * ld + c * 8);
  }
}
__device__ __forceinline__ void load_frags(uint32_t (*W)[4], uint32_t stg, int wg, int w, int lane) {
  uint32_t a = stg + ((lane >> 4) * 8 + (lane & 7)) * WSTG_STRIDE + (64 * wg + 16 * w + ((lane >> 3) & 1) * 8) * 2;
#pragma unroll
  for (int ks = 0; ks < 32; ks++) ldmatrix4_t(W[ks], a + ks * 16 * WSTG_STRIDE);
}

constexpr uint32_t M_H = 0;
constexpr uint32_t M_MEM = 65536;
constexpr uint32_t M_Q = M_MEM + 24576;
constexpr uint32_t M_K = M_Q + 12288;
constexpr uint32_t M_V = M_K + 12288;
constexpr uint32_t M_OM = M_V + 12288;
constexpr uint32_t M_OST = M_OM + 6144;
constexpr uint32_t M_TST = M_OST + 8192;
constexpr uint32_t M_WO = M_TST + 16384;
constexpr uint32_t M_M0 = M_WO + 49152;
constexpr uint32_t M_PT = M_M0 + 2048;
constexpr uint32_t M_BAR = M_PT + 12288;
constexpr uint32_t M_TOTAL = M_BAR + 384;
static_assert(M_TOTAL <= 232448, "main smem");
static_assert(M_WO >= 512 * WSTG_STRIDE, "staging overlaps Wo");
enum { B_LAND = 0  , B_QK = 3, B_V, B_TOK, B_OM, B_HA, B_HB, B_HAE, B_HBE, B_OST, B_OFREE, B_SYNC,
       B_STG, B_STG1, B_SS, B_TFREE, B_KFREE, B_VFREE, B_FIX  , B_NUM = B_FIX + 8 };
static_assert(B_NUM * 8 <= 256, "barriers");
constexpr uint32_t M_CAND = M_BAR + 256;
constexpr uint32_t M_BASE = M_BAR + 272;
constexpr uint32_t M_ZERO = M_BAR + 280;
constexpr uint32_t M_NEAR = M_BAR + 288;
enum { N_GO1 = 2, N_GO2, N_GO3, N_GO4, N_AG, N_W };

#define GSTAMP(slot, i)
#define TSTAMP(slot, i, k)
#define STAMP(i)
#define ASTAMP(i)
#define WSTAMP(i)
#define CSTAMP(i, v)
#define PIN(x) asm volatile("" : "+r"(x))
#define SCHED(k) asm volatile("{\n.reg .pred p;\nsetp.ne.u32 p, %0, 0;\n@p trap;\n}" :: "r"(zz & (1u << (k))) : "memory")
#define HOLD(k, v) asm volatile("{\n.reg .pred p;\nsetp.ne.u32 p, %0, 0;\n@p st.shared.u32 [%0], %1;\n}" :: "r"(zz & (1u << (k))), "r"(v) : "memory")
#define DRAIN(a) (lds32((a) + zz) & zz)
#define BAR(i) (sb + M_BAR + 8 * (i))

__device__ __forceinline__ int probe(const uint8_t* p, int n) {
  int best = 1 << 30; uint32_t v = 0;
#pragma unroll 1
  for (int r = 0; r < n; r++) {
    uint32_t t0 = clk();
    asm volatile("atom.relaxed.gpu.global.or.b32 %0, [%1], %2;" : "=r"(v) : "l"(p + 3968), "r"(v & 0u) : "memory");
    if (v == 0x7fffffffu) t0++;
    best = min(best, (int)(clk() - t0));
  }
  return best;
}
__device__ __forceinline__ void load_mem0(uint4* u, int k0, int lane, const bf16* mem0) {
#pragma unroll
  for (int i = 0; i < 2; i++) {
    const unsigned short* m = (const unsigned short*)mem0 + k0 + lane + 32 * i;
    u[i] = make_uint4(m[0] | (uint32_t)m[512] << 16, m[1024] | (uint32_t)m[1536] << 16, m[2048] | (uint32_t)m[2560] << 16, m[3072] | (uint32_t)m[3584] << 16);
  }
}

__device__ __forceinline__ void paced_h(uint32_t dst, const uint8_t* src, uint32_t o0, uint32_t o1, uint32_t piece, uint32_t bar, int gap) {
  uint32_t t = clk32();
#pragma unroll 1
  for (uint32_t o = o0; o < o1; o += piece) {
    e_mc(dst + o, src + o, piece, bar, 7);
    spin_until(t += gap);
  }
}

__device__ __forceinline__ void weight_role(const Params& p, const uint32_t sb, const int warp, const int cta, const int C, const uint32_t E,
                                            const uint8_t* const memg) {
  const int tid = fresh_tid(), lane = tid & 31;
  const int wg = warp >> 2, w = warp & 3;
  uint32_t W[32][4];
  cp_async_wait();
  bar_sync(1, 256);
  load_frags(W, sb, wg, w, lane);
  bar_sync(1, 256);
  if (tid < 128) sts128(sb + M_V + 5 * 2048 + tid * 16, make_uint4(0, 0, 0, 0));
  fence_async_smem();
  cluster_sync();
  if (tid == 0 && cta == 0) GSTAMP(0, 1);
  if (tid == 0) TSTAMP(13, cta, 0);

  const uint32_t rba = mapa(sb, C == 2 ? 0 : 2), rbc = mapa(sb, C == 1 ? 0 : 1);
  const uint32_t MYBAR = M_BAR + 8 * (C < 2 ? B_QK : B_V);
  uint32_t qoff = M_Q + C * 12288 + warp * 256 + lane * 4;
  uint32_t toff = sb + warp * 256 + (lane >> 4) * 2048 + (lane & 15) * 16;
  uint32_t rbar = mapa(sb + M_BAR, min(lane, 2));
  uint32_t sv = sb + M_MEM + lane * 32 + ((lane >> 2) & 3) * 8;
  PIN(qoff); PIN(toff); PIN(rbar); PIN(sv);
  const uint32_t gen0 = (E - 1) * (uint32_t)(NSTEP - 1);
  uint32_t fix = 0;
  const bool sig = w == 0 && lane < 3;
  const int pk = PAUSE_ + (cta < 36 ? 0 : cta < 72 ? PD1_ : 2 * PD1_) + (wg ? -PST2_ : PST2_);
  int cand = -1;
  float d[16];
#pragma unroll
  for (int i = 0; i < 16; i++) d[i] = 0.f;
  uint32_t tp[8];
#pragma unroll 1
  for (int T = -1; T < NSTEP; T++) {
    const uint32_t ph = T & 1;
    const uint64_t Z = p.zero << ph;
    const uint32_t zz = p.zero2;
    if (T >= 0) {
      WSTAMP(0);
      const uint64_t db = mkdesc(M_MEM, 128, 256, 0) + Z;
      stmatrix4(toff + M_TST + 8192, tp[0], tp[1], tp[2], tp[3]); stmatrix4(toff + M_TST + 12288, tp[4], tp[5], tp[6], tp[7]);
      if (sig) mbar_arrive_remote(rbar + 8 * B_HBE);
      mbar_wait(BAR(B_LAND), ph);
      WSTAMP(1);
      const uint32_t gt = gentag(gen0 + T);
      auto old = [&](uint32_t a) { return lds32(a) ^ gt; };
      uint32_t bad = 0;
      bool redo = false, ready = false;
      wg_fence();
      wgmma_rs24<0, 1, KP1_>(d, W[0], db);
#pragma unroll
      for (int ks = 1; ks < 32; ks++) {
        if (ks == 2 || ks == 14) bad |= xo2(lds32(sv + (ks == 2 ? 0 : 9) * 1024 + warp * 1024), lds32(sv + (ks == 2 ? 8 : 17) * 1024), gt);
        if (ks == 25) bad |= old(sv + (18 + min(warp, 5)) * 1024);
        if (ks == 6) {
          const uint32_t z5 = DRAIN(toff + M_TST);
          __syncwarp();
          if (lane == 0) mbar_arrive(BAR(B_STG) + z5);
        }
        if (ks == 27) ready = mbar_test(BAR(C < 2 ? B_KFREE : B_VFREE), ph ^ 1) & mbar_test(BAR(B_HA), ph);
        if ((EARLY_ && (ks == 9 || ks == 21)) || ks == RED_) redo = bar_or(N_W, 256, T > 0 && (bad & 0x10001u));
        if (ks == 12 || ks == 24) {
          if (EARLY_ && __builtin_expect(redo, 0)) break;
          mbar_wait(BAR(B_LAND + ks / 12), ph); WSTAMP(6 + ks / 12); wg_fence();
        }
        wgmma_rs24<1, 1>(d, W[ks], db + ks * 48);
      }
      wg_commit();
      uint32_t a0 = rba + qoff, a1 = a0 + 128, a2 = rbc + qoff, a3 = a2 + 128, ba = rba + MYBAR, bc = rbc + MYBAR;
      PIN(a0); PIN(a1); PIN(a2); PIN(a3); PIN(ba); PIN(bc);
      if (!ready) {
        mbar_wait(BAR(C < 2 ? B_KFREE : B_VFREE), ph ^ 1);
        if (T < NSTEP - 1) mbar_wait(BAR(B_HA), ph);
      }
      wg_wait<0>(); reg_fence(d);
      if (__builtin_expect(redo, 0)) {
        auto stale = [&]() { return __any_sync(~0u, (old(sv + warp * 3072) | old(sv + warp * 3072 + 1024) | old(sv + warp * 3072 + 2048)) & 0x10001u); };
        auto fetch = [&](int r) {
          e_expect(BAR(B_FIX + warp), 3072);
          e_g2s(sb + M_MEM + warp * 3072, memg + warp * 8192 + ((uni(lds32(sb + M_NEAR + warp * 4)) ^ r) & 1) * 4096, 3072, BAR(B_FIX + warp));
        };
        mbar_wait(BAR(B_LAND + warp / 3), ph);
        bool late = stale();
        if (late) fetch(0);
        constexpr uint64_t dc = mkdesc(M_MEM, 128, 256, 0);
#pragma unroll
        for (int ks = 0; ks < 32; ks++) {
          if (ks % 12 == 0) {
            if (ks) { wg_commit(); wg_wait<0>(); reg_fence(d); }
            if (warp / 3 == ks / 12) {
              for (int guard = 0; late; guard++) {
                mbar_wait(BAR(B_FIX + warp), fix); fix ^= 1;
                late = stale();
                if (late) fetch(ALT_ ? guard + 1 : 0);
                if (guard > (1 << 20)) TRAP();
              }
            }
            bar_sync(N_W, 256);
            wg_fence();
          }
          if (ks == 0) wgmma_rs24<0, 1, 1>(d, W[0], dc); else wgmma_rs24<1, 1>(d, W[ks], dc + ks * 48);
        }
        wg_commit();
        wg_wait<0>(); reg_fence(d);
      }
      WSTAMP(2);
      if (T == 0 && tid == 0) TSTAMP(13, cta, 2);
      uint32_t lo[3], hi[3];
#pragma unroll
      for (int j = 0; j < 3; j++) { lo[j] = pack2(d[4 * j], d[4 * j + 1]); hi[j] = pack2(d[4 * j + 2], d[4 * j + 3]); }
      if (__builtin_expect(T == 0, 0)) { sts32(sb + M_M0 + tid * 8, lo[0]); sts32(sb + M_M0 + tid * 8 + 4, hi[0]); }
      if (__builtin_expect(cand >= 0, 0)) {
        if (T == LAG) { lo[1] = lds32(sb + M_M0 + tid * 8); hi[1] = lds32(sb + M_M0 + tid * 8 + 4); }
        if (C < 2) { st_async32(a0 + 5 * 2048, lo[2], ba); st_async32(a1 + 5 * 2048, hi[2], ba); }
        else { sts32(sb + qoff + 5 * 2048, lo[2]); sts32(sb + qoff + 5 * 2048 + 128, hi[2]); }
        lo[2] = lo[1]; hi[2] = hi[1];
      }
      uint32_t z5;
      if (C == 0) {
        sts32(sb + qoff, lo[0]); sts32(sb + qoff + 128, hi[0]); z5 = DRAIN(sb + qoff);
        st_async32(a0, lo[2], ba); st_async32(a1, hi[2], ba); st_async32(a2, lo[1], bc); st_async32(a3, hi[1], bc);
      } else if (C == 1) {
        sts32(sb + qoff, lo[1]); sts32(sb + qoff + 128, hi[1]); z5 = DRAIN(sb + qoff);
        st_async32(a0, lo[2], ba); st_async32(a1, hi[2], ba); st_async32(a2, lo[0], bc); st_async32(a3, hi[0], bc);
      } else {
        sts32(sb + qoff, lo[2]); sts32(sb + qoff + 128, hi[2]); z5 = DRAIN(sb + qoff);
        st_async32(a0, lo[0], ba); st_async32(a1, hi[0], ba); st_async32(a2, lo[1], bc); st_async32(a3, hi[1], bc);
      }
      __syncwarp();
      if (lane == 0) { mbar_arrive(sb + MYBAR + z5); if (w == 3) mbar_arrive(BAR(B_SS)); }
      if (T == NSTEP - 1) break;
    }
    {
      const uint64_t dh = mkdesc(M_H, 16, 1024, 1) + Z;
      static_assert(E2 == 0 && E3 > 0 && PAUSE_ > 0, "config");
      if (T + 2 < NSEG) {
        if (T < 0) mbar_wait(BAR(B_HA), ph);
        WSTAMP(3);
        wg_fence();
        wgmma_rs32<0, 0, 1>(d, W[0], dh);
#pragma unroll
        for (int ks = 1; ks < EA; ks++) {
          if (ks == E1) { wg_commit(); if (T >= 0) bar_sync(N_GO2, 384); wg_fence(); }
          wgmma_rs32<1, 0>(d, W[ks], dh + (ks >> 2) * 256 + (ks & 3) * 2);
        }
        wg_commit();
        mbar_wait(BAR(B_HB), ph);
        wg_wait<0>();
        if (sig) mbar_arrive_remote(rbar + 8 * B_HAE);
        WSTAMP(4);
        if (T >= 0) bar_sync(N_GO3, 384);
        if (wg == 1) bar_sync(N_W, 256);
        wg_fence();
#pragma unroll
        for (int ks = EA; ks < 32; ks++) wgmma_rs32<1, 0>(d, W[ks], dh + (ks >> 2) * 256 + (ks & 3) * 2);
        wg_commit();
        if (wg == 0) bar_arrive(N_W, 256);
        mbar_wait(BAR(B_TFREE), ph ^ 1);
        wg_wait<0>(); reg_fence(d);
      } else {
        bar_sync(N_GO2, 384);
        mbar_wait(BAR(B_HB), ph);
        if (sig) mbar_arrive_remote(rbar + 8 * B_HAE);
        bar_sync(N_GO3, 384);
        mbar_wait(BAR(B_TFREE), ph ^ 1);
      }
#pragma unroll
      for (int i = 0; i < 8; i++) { tp[i] = pack2(d[2 * i], d[2 * i + 1]); PIN(tp[i]); }
      auto staged = [&]() {
        const uint32_t z5 = DRAIN(toff + M_TST);
        __syncwarp();
        if (lane == 0) mbar_arrive(BAR(B_STG1) + z5);
      };
      if (T < 0 || (T + 2 >= LAG && T + 2 < NSTEP)) {
        wg_fence();
        wgmma_rs32<0, 0, 1>(d, W[0], dh + 2048);
        stmatrix4(toff + M_TST, tp[0], tp[1], tp[2], tp[3]); stmatrix4(toff + M_TST + 4096, tp[4], tp[5], tp[6], tp[7]);
#pragma unroll
        for (int ks = 1; ks < 32; ks++) {
          if (ks == 5) staged();
          if (ks >= PAUSE_ - PST2_ && ks <= PAUSE_ + 2 * PD1_ + PST2_ && (ks - PAUSE_ + PST2_) % PGR_ == 0) {
            wg_commit();
            if (T >= 0 && ks == pk) bar_sync(N_GO4, 384);
            wg_fence();
          }
          wgmma_rs32<1, 0>(d, W[ks], dh + 2048 + (ks >> 2) * 256 + (ks & 3) * 2);
        }
        wg_commit();
      } else {
        stmatrix4(toff + M_TST, tp[0], tp[1], tp[2], tp[3]); stmatrix4(toff + M_TST + 4096, tp[4], tp[5], tp[6], tp[7]);
        staged();
        bar_sync(N_GO4, 384);
      }
      if (T >= 0) cand = __shfl_sync(~0u, (int)lds32(sb + M_CAND + ((T + 1) & 3) * 4), 0);
      wg_wait<0>(); reg_fence(d);
      if (T >= 0) WSTAMP(6);
      if (T < 0 && tid == 0) TSTAMP(13, cta, 1);
#pragma unroll
      for (int i = 0; i < 8; i++) tp[i] = pack2(d[2 * i], d[2 * i + 1]);
    }
  }
  cluster_sync();
  if (tid == 0 && cta == 0) GSTAMP(0, 5);
}

__device__ __forceinline__ void attn_role(const Params& p, const uint32_t sb, const int w, const int cta, const int head, const int C, const uint32_t E,
                                          uint8_t* const part, uint8_t* const memg) {
  const int tid = fresh_tid(), lane = tid & 31;
  const int g = lane >> 2, t = lane & 3;
  uint32_t tag = ((E - 1) * (uint32_t)(NSTEP - 1)) & 1;
  uint4 m0[2][2];
  load_mem0(m0[0], w * 64, lane, p.mem0); load_mem0(m0[1], w * 64 + 256, lane, p.mem0);
  cluster_sync();
#pragma unroll
  for (int k = 0; k < 2; k++) {
#pragma unroll 1
    for (int i = 0; i < 6; i++) sts128(sb + M_MEM + (w + 4 * k) * 3072 + lane * 16 + i * 512, make_uint4(0, 0, 0, 0));
    __syncwarp();
#pragma unroll
    for (int i = 0; i < 2; i++) sts128(sb + M_MEM + ((w + 4 * k) * 4 + (lane >> 4) + 2 * i) * 768 + (lane & 15) * 16, m0[k][i]);
  }
  fence_async_smem();
  bar_sync(N_AG, 128);
  if (w == 3 && lane < 3) mbar_arrive(BAR(B_LAND + lane));
  if (lane == 0) {
    if (w == 0) TSTAMP(15, cta, 0);
    sts32(sb + M_PT + w * 4, probe(part + cta * 16384 + w * 4096, NPROBE_ / 2));
    if (w == 0) TSTAMP(15, cta, 1);
  }
  bar_sync(N_AG, 128);
  const uint32_t inear = lds32(sb + M_PT + (w >> 1) * 8 + 4) < lds32(sb + M_PT + (w >> 1) * 8);
  if (lane == 0 && !(w & 1)) st_rlx(&f_choice[cta][w >> 1], (E << 1) | inear);
  if (w == 0) TSTAMP(15, cta, 2);
  uint32_t nb;
  {
    const int i = min(lane >> 1, C < 2 ? 8 : 5);
    const int r = ((i / 3 * 3 + C) * 4 + w) * 3 + i % 3;
    int guard = 0; uint32_t cw;
    while (__any_sync(~0u, ((cw = ld_rlx(&f_choice[r][lane & 1])) >> 1) != (E & 0x7FFFFFFFu))) { if (++guard > (1 << 22)) TRAP(); }
    nb = __ballot_sync(~0u, cw & 1) >> (lane >> 4);
    if (w == 0) TSTAMP(15, cta, 3);
  }
  bar_sync(N_AG, 128);
  const uint32_t pt0 = sb + M_PT + (tid & 127) * 16;
  {
    const uint32_t po = (C * 4 + w) * 49152 + (lane >> 4) * 8192 + ((lane >> 3) & 1) * 2048 + head * 64 + (lane & 7) * 8;
    const uint8_t* in = part + (cta * 16384 + (w >> 1) * 8192 + inear * 4096 + (w & 1) * 2048 + lane * 8);
    const uint8_t* outp = memg + ((cta / 12) * 8192 + (cta % 12) * 256 + w * 64 + (lane >> 4) * 4096 + (lane & 4) * 8 + (lane & 8) * 2 + (lane & 3) * 4);
#pragma unroll
    for (int i = 0; i < 12; i++) {
      const int j = i / 4 * 3 + (i & 3);
      const uint8_t* a = (i & 3) < 3 ? part + (po + i / 4 * 589824 + (i & 3) * 16384 + ((nb >> (2 * j)) & 1) * 4096) : i == 11 ? in : outp;
      asm volatile("st.shared.u64 [%0], %1;" :: "r"(pt0 + (i >> 1) * 2048 + (i & 1) * 8), "l"(a) : "memory");
    }
  }
  const int xd = __shfl_sync(~0u, XDLY_ + (cta < 36 ? 0 : cta < 72 ? X1_ : X2_), 0);
  const uint32_t rba = mapa(sb, C == 2 ? 0 : 2), rbc = mapa(sb, C == 1 ? 0 : 1);
  uint32_t vis = vis_bits(8 + 8 * w + g, t);
  uint32_t ln = lane;
#pragma unroll
  for (int i = 0; i < SALT_; i++) ln += lds32(sb + M_ZERO);
  PIN(vis); PIN(ln);
  if (tid == 256 && C == 0) st_rlx(&f_loaded[head], E);
  uint32_t fa[8][4];
#pragma unroll
  for (int ks = 0; ks < 8; ks++) ldmatrix4_t(fa[ks], sb + M_WO + 32768 + w * 256 + (lane >> 4) * 1024 + (lane & 15) * 16 + ks * 2048);
  if (w == 0) TSTAMP(14, cta, 0);
#pragma unroll 1
  for (int T = 0; T < NSTEP; T++) {
    const uint32_t ph = T & 1;
    const uint32_t zz = uni(lds32(sb + M_ZERO));
    const bool more = T < NSTEP - 1;
    const float sc = 0.08838834764831845f * 1.4426950408889634f;
    tag ^= 1;
    float s[20];
    const uint8_t* in; int cnext = -1; uint32_t tx; bool synced;
    float x[10], tm, ts;
    uint32_t pt[5];
    auto tok_max = [&]() {
      PIN(vis);
      x[0] = s[2]; x[1] = s[3];
#pragma unroll
      for (int i = 0; i < 8; i++) x[2 + i] = (vis >> i & 1) ? s[4 * (i / 2 + 1) + 2 + (i & 1)] : -INFINITY;
      tm = fmaxf(fmaxf(fmaxf(fmaxf(x[0], x[1]), fmaxf(x[2], x[3])), fmaxf(fmaxf(x[4], x[5]), fmaxf(x[6], x[7]))), fmaxf(x[8], x[9]));
      HOLD(7, __float_as_uint(tm));
    };
    auto tok_exp1 = [&]() {
      tm = fmaxf(tm, __shfl_xor_sync(~0u, tm, 1));
      tm = fmaxf(tm, __shfl_xor_sync(~0u, tm, 2));
      const float b = -tm * sc;
#pragma unroll
      for (int i = 0; i < 10; i++) x[i] = fmaf(x[i], sc, b);
      HOLD(10, __float_as_uint(x[9]));
    };
    auto tok_exp2 = [&]() {
#pragma unroll
      for (int i = 0; i < 10; i++) x[i] = ex2(x[i]);
      ts = (((x[0] + x[1]) + (x[2] + x[3])) + ((x[4] + x[5]) + (x[6] + x[7]))) + (x[8] + x[9]);
#pragma unroll
      for (int k = 0; k < 5; k++) pt[k] = pack2(x[2 * k], x[2 * k + 1]);
      HOLD(8, __float_as_uint(ts));
    };
    {
      uint32_t q[8][4];
      auto load_q = [&](uint32_t a, int h) {
#pragma unroll
        for (int k2 = 0; k2 < 4; k2++) {
          uint32_t r[4];
          ldmatrix4_t(r, a + k2 * 512);
          q[2 * k2][h] = r[0]; q[2 * k2][h + 2] = r[1]; q[2 * k2 + 1][h] = r[2]; q[2 * k2 + 1][h + 2] = r[3];
        }
      };
      PIN(ln);
      const uint32_t qa = sb + M_Q + ln * 16;
      const int cand = C == 2 ? (int)uni(lds32(sb + M_CAND + (T & 3) * 4)) : -1;
      mbar_wait(BAR(B_TOK), ph);
      load_q(qa + (1 + w) * 2048, 1);
      mbar_wait(BAR(B_QK), ph);
      ASTAMP(0);
      if (T == 0 && w == 0) TSTAMP(13, cta, 3);
      if (__builtin_expect(cand >= 0, 0)) {
        mbar_wait(BAR(B_V), ph);
        PIN(ln);
        const int e = w * 32 + ln;
#pragma unroll
        for (int i = 0; i < 3; i++) {
          const uint32_t v = lds32(sb + M_Q + i * 12288 + 5 * 2048 + e * 16 + 4);
          asm volatile("st.shared.u16 [%0], %1;" :: "r"(sb + M_Q + i * 12288 + (1 + (cand >> 3)) * 2048 + e * 16 + (cand & 7) * 2), "h"((unsigned short)v) : "memory");
        }
        fence_async_smem();
        bar_sync(N_AG, 128);
        load_q(qa + (1 + w) * 2048, 1);
      }
      load_q(qa, 0);
      if (!(NOF_ & 1)) fence_async_smem();
      constexpr uint64_t dk = mkdesc(M_K, 128, 2048, 0);
      wg_fence();
      wgmma_rs40<0, 1>(s, q[0], dk);
#pragma unroll
      for (int ks = 1; ks < 8; ks++) wgmma_rs40<1, 1>(s, q[ks], dk + ks * 16);
      wg_commit();
    }
    if (more) {
      uint32_t v[5][4];
      PIN(ln);
      const uint32_t va = sb + M_V + w * 512 + ((ln >> 3) & 1) * 128 + (ln >> 4) * 2048 + (ln & 7) * 16;
      const uint32_t ooff = M_OM + w * 1536 + C * 256 + ln * 4;
      mbar_wait(BAR(B_V), ph);
      wg_wait<0>(); reg_fence(s);
      if (ln < 3) mbar_arrive_remote(mapa(BAR(B_KFREE), ln));
      ldmatrix4(v[0], va); ldmatrix4(v[1], va + 256); ldmatrix4(v[2], va + 4096); ldmatrix4(v[3], va + 4096 + 256);
      ldmatrix4(v[4], sb + M_V + 8192 + w * 512 + ln * 16);
      ASTAMP(1);
      float m = fmaxf(fmaxf(fmaxf(fmaxf(s[0], s[1]), fmaxf(s[4], s[5])), fmaxf(fmaxf(s[8], s[9]), fmaxf(s[12], s[13]))), fmaxf(s[16], s[17]));
      m = fmaxf(m, __shfl_xor_sync(~0u, m, 1));
      m = fmaxf(m, __shfl_xor_sync(~0u, m, 2));
      const float b = -m * sc;
      uint32_t pm[5];
#pragma unroll
      for (int j = 0; j < 5; j++) pm[j] = pack2(ex2(fmaf(s[4 * j], sc, b)), ex2(fmaf(s[4 * j + 1], sc, b)));
      float o0[4] = {0.f, 0.f, 0.f, 0.f}, o1[4] = {0.f, 0.f, 0.f, 0.f}, l[4] = {0.f, 0.f, 0.f, 0.f};
      const uint32_t one[4] = {0x3f803f80u, 0x3f803f80u, 0x3f803f80u, 0x3f803f80u};
      hmma16(l, one, pm[0], pm[1]); hmma16(o0, v[0], pm[0], pm[1]); hmma16(o1, v[1], pm[0], pm[1]);
      hmma16(l, one, pm[2], pm[3]); hmma16(o0, v[2], pm[2], pm[3]); hmma16(o1, v[3], pm[2], pm[3]);
      hmma8(l, one[0], one[1], pm[4]); hmma8(o0, v[4][0], v[4][1], pm[4]); hmma8(o1, v[4][2], v[4][3], pm[4]);
      const float r0 = rcp(l[0]), r1 = rcp(l[1]);
      const uint32_t u0 = pack2(o0[0] * r0, o0[1] * r1), u1 = pack2(o0[2] * r0, o0[3] * r1), u2 = pack2(o1[0] * r0, o1[1] * r1), u3 = pack2(o1[2] * r0, o1[3] * r1);
      constexpr uint32_t OB = M_BAR + 8 * B_OM;
      const uint32_t a0 = rba + ooff, a1 = rbc + ooff;
      st_async32(a0, u0, rba + OB); st_async32(a1, u0, rbc + OB);
      st_async32(a0 + 128, u1, rba + OB); st_async32(a1 + 128, u1, rbc + OB);
      st_async32(a0 + 768, u2, rba + OB); st_async32(a1 + 768, u2, rbc + OB);
      st_async32(a0 + 896, u3, rba + OB); st_async32(a1 + 896, u3, rbc + OB);
      bar_arrive(N_GO2, 384);
      sts32(sb + ooff, u0); sts32(sb + ooff + 128, u1); sts32(sb + ooff + 768, u2); sts32(sb + ooff + 896, u3);
      ASTAMP(2);
      uint32_t fb[8][4];
      const uint32_t wa = sb + M_WO + 16384 + w * 256 + (ln >> 4) * 1024 + (ln & 15) * 16 + zz;
      ldmatrix4_t(fb[0], wa);
      SCHED(3);
#pragma unroll
      for (int ks = 1; ks < 8; ks++) {
        ldmatrix4_t(fb[ks], wa + ks * 2048);
        if (ks == ARR_) { __syncwarp(); if (ln == 0) mbar_arrive(BAR(B_OM) + (fb[0][0] & zz)); }
      }
      if (C == 2) cnext = (int)uni(lds32(sb + M_CAND + ((T + 1) & 3) * 4));
      {
        float d[12], e[12];
        constexpr uint64_t ob = mkdesc(M_OM, 128, 256, 0);
        uint8_t* q[3][3];
        auto addr = [&](int i) {
          asm volatile("ld.shared.v2.u64 {%0,%1}, [%2];" : "=l"(q[i][0]), "=l"(q[i][1]) : "r"(pt0 + i * 4096) : "memory");
          if (i < 2) asm volatile("ld.shared.u64 %0, [%1];" : "=l"(q[i][2]) : "r"(pt0 + i * 4096 + 2048) : "memory");
          else asm volatile("ld.shared.v2.u64 {%0,%1}, [%2];" : "=l"(q[i][2]), "=l"(in) : "r"(pt0 + i * 4096 + 2048) : "memory");
        };
        auto put = [&](const float* d, int i) {
          st_rlx64(q[i][0], (pack2(d[0], d[1]) & ~1u) | tag, pack2(d[2], d[3]));
          st_rlx64(q[i][1], (pack2(d[4], d[5]) & ~1u) | tag, pack2(d[6], d[7]));
          st_rlx64(q[i][2], (pack2(d[8], d[9]) & ~1u) | tag, pack2(d[10], d[11]));
        };
        addr(0); addr(1);
        SCHED(6);
        tok_max();
        ASTAMP(3);
        mbar_wait(BAR(B_OM), ph);
        if (!(NOF_ & 2)) fence_async_smem();
        ASTAMP(4);
        constexpr uint64_t w0 = mkdesc(M_WO, 1024, 128, 0);
        float (&f)[12] = d;
        wg_fence();
        wgmma_ss24<0, 1, 1>(d, w0, ob);
#pragma unroll
        for (int ks = 1; ks < 8; ks++) wgmma_ss24<1, 1, 1>(d, w0 + ks * 128, ob + ks * 48);
        wg_commit();
        wgmma_rs24<0, 1>(e, fb[0], ob);
#pragma unroll
        for (int ks = 1; ks < HAND_; ks++) wgmma_rs24<1, 1>(e, fb[ks], ob + ks * 48);
        wg_commit();
        wg_wait<1>(); reg_fence(d);
        put(d, 0);
        addr(2);
        SCHED(4);
        ASTAMP(5);
        wg_fence();
#pragma unroll
        for (int ks = HAND_; ks < 8; ks++) wgmma_rs24<1, 1>(e, fb[ks], ob + ks * 48);
        wg_commit();
        wgmma_rs24<0, 1, 1>(f, fa[0], ob);
#pragma unroll
        for (int ks = 1; ks < HAND_; ks++) wgmma_rs24<1, 1>(f, fa[ks], ob + ks * 48);
        wg_commit();
        wg_wait<1>(); reg_fence(e);
        put(e, 1);
        SCHED(5);
        wg_fence();
#pragma unroll
        for (int ks = HAND_; ks < 8; ks++) wgmma_rs24<1, 1>(f, fa[ks], ob + ks * 48);
        wg_commit();
        if (GO3_ == 0) bar_arrive(N_GO3, 384);
        synced = __all_sync(~0u, mbar_test(BAR(B_SYNC), ph));
        tx = uni(lds32(sb + M_BASE + ph * 4)) + xd;
        wg_wait<0>(); reg_fence(f);
        if (GO3_ == 1) bar_arrive(N_GO3, 384);
        if (C < 2) put(f, 2);
        if (GO3_ == 2) bar_arrive(N_GO3, 384);
        ASTAMP(6);
        if (T == 0 && w == 0) TSTAMP(14, cta, 1);
      }
    } else {
      mbar_wait(BAR(B_V), ph);
      wg_wait<0>(); reg_fence(s);
      tok_max();
    }
    uint2 v[8];
#pragma unroll
    for (int i = 0; i < 8; i++) v[i] = make_uint2(zz, zz);
    auto poll = [&](uint2* v) {
      v[0] = ld_rlx64<0>(in); v[1] = ld_rlx64<256>(in); v[2] = ld_rlx64<512>(in); v[3] = ld_rlx64<768>(in);
      v[4] = ld_rlx64<1024>(in); v[5] = ld_rlx64<1280>(in); v[6] = ld_rlx64<1536>(in); v[7] = ld_rlx64<1792>(in);
    };
    uint8_t* outp;
    asm volatile("ld.shared.u64 %0, [%1];" : "=l"(outp) : "r"(pt0 + 2048 + 8) : "memory");
    const uint32_t itag = gentag((E - 1) * (uint32_t)(NSTEP - 1) + T + 1);
    const bool sum = more && cnext < 0;
    if (more) {
      if (!synced) { mbar_wait(BAR(B_SYNC), ph); tx = uni(lds32(sb + M_BASE + ph * 4)) + xd; }
      ASTAMP(7);
      if (__builtin_expect(cnext >= 0, 0)) {
        const unsigned long long* hp = (const unsigned long long*)&g_hc[T + 1 - LAG][0] + ((cta / 3) * 8 + 2 * w + ((ln >> 2) & 1));
        unsigned long long v0; int guard = 0;
        while (v0 = ld_rlxu64(hp), !__all_sync(~0u, (uint32_t)(v0 >> 32) == E)) { if (++guard > (1 << 22)) TRAP(); }
        st_rlx((uint32_t*)outp, (ln & 3) == 1 ? ((uint32_t)v0 >> ((ln & 8) * 2)) & 0xffffu : (ln & 1) ? 0u : itag);
      } else {
        spin_until(tx);
        ASTAMP(8);
        poll(v);
      }
    }
    auto late = [&](const uint2* v) {
      return __any_sync(~0u, (or3(xo2(v[0].x, v[1].x, tag), xo2(v[2].x, v[3].x, tag), xo2(v[4].x, v[5].x, tag)) | xo2(v[6].x, v[7].x, tag)) & 1u);
    };
    tok_exp1(); tok_exp2();
    if (sum) {
      ASTAMP(9);
      int guard = 0;
      while (late(v)) {
        if (++guard > (1 << 22)) TRAP();
        poll(v);
      }
#pragma unroll
      for (int i = 0; i < 4; i++) { v[i].x = add2(v[i].x, v[i + 4].x); v[i].y = add2(v[i].y, v[i + 4].y); }
#define SUM8(f, m) ((f(v[0].m) + f(v[1].m)) + (f(v[2].m) + f(v[3].m)))
      const float a0 = SUM8(blo, x), a1 = SUM8(bhi, x), b0 = SUM8(blo, y), b1 = SUM8(bhi, y);
      const bool hi = ln & 8;
      float k0 = (hi ? b0 : a0) + __shfl_xor_sync(~0u, hi ? a0 : b0, 8), k1 = (hi ? b1 : a1) + __shfl_xor_sync(~0u, hi ? a1 : b1, 8);
      k0 += __shfl_xor_sync(~0u, k0, 16); k1 += __shfl_xor_sync(~0u, k1, 16);
      st_rlx((uint32_t*)outp, (ln & 1) ? pack2(k0, k1) : pack2_tag(k0, k1, itag));
      ASTAMP(10);
      if (T == 0 && w == 0) TSTAMP(14, cta, 2);
      CSTAMP(12 + w, (clk() & ~15u) | min(guard + 1, 15));
    }
    if (more) bar_arrive(N_GO4, 384);
    {
      PIN(ln);
      const uint32_t oa = sb + M_OST + w * 128 + (ln >> 3) * 512 + (ln & 7) * 16;
      const uint32_t a[3][4] = {{0, pt[0], 0, pt[1]}, {0, pt[2], 0, pt[3]}, {0, pt[4], 0, 0}};
      constexpr uint64_t dv = mkdesc(M_V, 2048, 128, 0);
#pragma unroll 1
      for (int h = 0; h < 2; h++) {
        float o[32];
        const uint64_t dh = dv + (uint64_t)(h * 64);
        wg_fence();
        wgmma_rs64<0, 0>(o, a[0], dh); wgmma_rs64<1, 0>(o, a[1], dh + 256); wgmma_rs64<1, 0>(o, a[2], dh + 512);
        wg_commit();
        if (h == 0) {
          ts += __shfl_xor_sync(~0u, ts, 1);
          ts += __shfl_xor_sync(~0u, ts, 2);
          ts = rcp(ts);
          mbar_wait(BAR(B_OFREE), ph ^ 1);
        }
        wg_wait<0>(); reg_fence(o);
        if (h == 1 && ln < 3) mbar_arrive_remote(mapa(BAR(B_VFREE), ln));
#define OT(i) pack2(o[4 * (i) + 2] * ts, o[4 * (i) + 3] * ts)
        stmatrix4(oa + h * 4096, OT(0), OT(1), OT(2), OT(3));
        stmatrix4(oa + h * 4096 + 2048, OT(4), OT(5), OT(6), OT(7));
      }
      const uint32_t z5 = DRAIN(oa);
      __syncwarp();
      if (ln == 0) mbar_arrive(BAR(B_OST) + z5);
      ASTAMP(11);
    }
  }
}

__global__ void __cluster_dims__(3, 1, 1) __launch_bounds__(512, 1) main_kernel(Params p) {
  extern __shared__ __align__(1024) uint8_t sm[];
  const uint32_t sb = smem_u32(sm);
  if ((sb & 0xFFFFFFu) != SBASE) TRAP();
  asm volatile("griddepcontrol.launch_dependents;");
  const int warp = __shfl_sync(~0u, threadIdx.x >> 5, 0);
  const int cta = blockIdx.x, head = cta / 3, c = cta % 3;
  const uint32_t E = __shfl_sync(~0u, *(volatile uint32_t*)&g_epoch + 1, 0);
  uint8_t* const part = (uint8_t*)(((uintptr_t)g_xch + 8191) & ~(uintptr_t)8191);
  uint8_t* const memg = part + 96 * 16384;

  if (threadIdx.x == 0 && cta == 0) GSTAMP(0, 0);
  if (threadIdx.x < B_NUM) {
    const int i = threadIdx.x;
    const uint32_t cnt = i == B_STG || i == B_STG1 ? 8 : i == B_OST ? 4 : i == B_HAE || i == B_HBE ? 6 : i == B_KFREE || i == B_VFREE ? 12 : i == B_SS ? 2 : i == B_OM ? 5 :
                         i == B_QK ? (c < 2 ? 9 : 1) : i == B_V ? (c < 2 ? 1 : 9) : 1;
    mbar_init(BAR(i), cnt);
    if (i == B_HA || i == B_HB || i == B_STG || i == B_HAE || i == B_HBE || i == B_TFREE)
      asm volatile("mbarrier.arrive.shared::cta.b64 _, [%0], %1;" :: "r"(BAR(i)), "r"(cnt) : "memory");
    asm volatile("fence.mbarrier_init.release.cluster;" ::: "memory");
  }
  if (warp < 8) {
    const int tid = threadIdx.x;
    uint4 wa[6], wb[6];
#pragma unroll
    for (int i = 0; i < 6; i++) {
      const int mi = i >> 1, e = (tid >> 2) + (i & 1) * 64;
      const uint4* src = (const uint4*)(p.wo + (size_t)(head * 128 + e) * 512 + min(3 * mi + c, 7) * 64 + (tid & 3) * 16);
      wa[i] = __ldg(src); wb[i] = __ldg(src + 1);
    }
    stage_weights(sb, (c == 0 ? p.wq : c == 1 ? p.wk : p.wv) + head * 128, 4096, tid, 256);
#pragma unroll
    for (int i = 0; i < 6; i++) {
      const int mi = i >> 1, e = (tid >> 2) + (i & 1) * 64;
      const uint4 a = wa[i], b = wb[i];
      const uint32_t dst = sb + M_WO + mi * 16384 + (e >> 3) * 1024 + (tid & 3) * 256 + (e & 7) * 16;
      sts128(dst, make_uint4(__byte_perm(a.x, a.y, 0x5410), __byte_perm(a.z, a.w, 0x5410), __byte_perm(b.x, b.y, 0x5410), __byte_perm(b.z, b.w, 0x5410)));
      sts128(dst + 128, make_uint4(__byte_perm(a.x, a.y, 0x7632), __byte_perm(a.z, a.w, 0x7632), __byte_perm(b.x, b.y, 0x7632), __byte_perm(b.z, b.w, 0x7632)));
    }
  } else {
    const int i0 = threadIdx.x - 256;
    const uint32_t tag0 = ((E - 1) * (uint32_t)(NSTEP - 1)) & 1;
    for (int i = i0; i < 1024; i += 256) *(uint4*)(part + cta * 16384 + i * 16) = make_uint4(tag0, 0, tag0, 0);
    if (i0 < 16) *(uint32_t*)(memg + i0 * 4096 + 3968) = 0;
    if (i0 < 2) st_rlx(&f_choice[cta][i0], 0);
    if (i0 < 8) st_rlx64(&g_sync[i0 >> 2][cta][i0 & 3], 0, 0);
    __threadfence();
    if (i0 < 12) sts32(sb + M_ZERO + i0 * 4, 0);
    if (i0 < 2) { sts32(sb + M_BASE + i0 * 4, clk32() - 65536); sts32(sb + M_CAND + i0 * 4, (uint32_t)-1); }
  }

  if (warp < 8) {
    asm volatile("setmaxnreg.inc.sync.aligned.u32 " STR(RW_) ";");
    weight_role(p, sb, warp, cta, c, E, memg);
  } else if (warp < 12) {
    if (RA_ < 128) asm volatile("setmaxnreg.dec.sync.aligned.u32 " STR(RA_) ";");
    if (RA_ > 128) asm volatile("setmaxnreg.inc.sync.aligned.u32 " STR(RA_) ";");
    attn_role(p, sb, warp - 8, cta, head, c, E, part, memg);
    cluster_sync();
  } else {
    asm volatile("setmaxnreg.dec.sync.aligned.u32 " STR(RC_) ";");
    const int tid = fresh_tid(), lane = tid & 31;
    const int w = warp - 12;
    cluster_sync();
    if (w != 2) {
      const int tl = min(3 * min(w, 2) + c, 7);
      int near = 0;
      if (lane == 0) { const int t0 = probe(memg + tl * 8192, NPROBE_ / 2); near = probe(memg + tl * 8192 + 4096, NPROBE_ / 2) < t0; }
      near = uni(near);
      if (lane < 3) asm volatile("st.shared::cluster.u32 [%0], %1;" :: "r"(mapa(sb + M_NEAR + tl * 4, lane)), "r"(near) : "memory");
      __syncwarp();
    }
    if (w == 0) {
      uint32_t s0 = c * 8192, s1 = (3 + c) * 8192, s2 = min(6 + c, 7) * 8192;
#pragma unroll 1
      for (int T = 0; T < NSTEP - 1; T++) {
        const uint32_t ph = T & 1;
        mbar_wait(BAR(B_SS), ph);
        const uint32_t cq = clk();
        const uint32_t g0 = (uint32_t)gtime64(); uint32_t g1, ce;
        do { g1 = (uint32_t)gtime64(); ce = clk(); } while (g1 == g0);
        const uint32_t tn = g1 * 8 - (((ce - cq) * 37u) >> 3), id = E * 128u + T;
        if (lane < 4) st_rlx64(&g_sync[ph][cta][lane], tn, id);
        if (lane < 3) mbar_expect(BAR(B_LAND + lane), lane < 2 ? 9216 : 6144);
        if (T == 0) { s0 += uni(lds32(sb + M_NEAR + c * 4)) * 4096; s1 += uni(lds32(sb + M_NEAR + (3 + c) * 4)) * 4096; s2 += uni(lds32(sb + M_NEAR + min(6 + c, 7) * 4)) * 4096; }
        wait_until(cq + SDLY_);
        int guard = 0; unsigned long long v0, v1, v2;
        for (;;) {
          v0 = ld_rlxu64(g_sync[ph][lane]); v1 = ld_rlxu64(g_sync[ph][lane + 32]); v2 = ld_rlxu64(g_sync[ph][lane + 64]);
          if (__all_sync(~0u, (uint32_t)(v0 >> 32) == id && (uint32_t)(v1 >> 32) == id && (uint32_t)(v2 >> 32) == id)) break;
          if (++guard > (1 << 22)) TRAP();
        }
        const int dl = __reduce_max_sync(~0u, max(max((int)((uint32_t)v0 - tn), (int)((uint32_t)v1 - tn)), (int)((uint32_t)v2 - tn)));
        const uint32_t base = uni(cq + ((min(dl, 8 * 4096) * 7) >> 5)) + (T == 0 ? SLOW0_ : T == 1 ? SLOW1_ : 0) +
                              ((int)uni(lds32(sb + M_CAND + (T & 3) * 4)) >= 0 ? CDLY_ : 0) - (T + 2 < NSEG ? 0 : BOFF_);
        if (lane == 0) { sts32(sb + M_BASE + ph * 4, base); mbar_arrive(BAR(B_SYNC)); }
        CSTAMP(0, base); CSTAMP(1, clk());
        const uint32_t ts = base + YDLY_ - (T + 2 >= LAG && T + 2 < NSEG ? 0 : YOFF_);
        uint32_t nr = 0;
        if (PRIV_) nr = __ballot_sync(~0u, lds32(sb + M_NEAR + (lane & 7) * 4) != 0);
        wait_until(ts);
        if (PRIV_ & 1) { for (int k = 0; k < 3; k++) e_g2s(sb + M_MEM + k * 3072, memg + k * 8192 + ((nr >> k) & 1) * 4096, 3072, BAR(B_LAND)); }
        else e_mc(sb + M_MEM + c * 3072, memg + s0, 3072, BAR(B_LAND), 7);
        CSTAMP(2, clk());
        spin_until(ts + Y1_);
        if (PRIV_ & 2) { for (int k = 3; k < 6; k++) e_g2s(sb + M_MEM + k * 3072, memg + k * 8192 + ((nr >> k) & 1) * 4096, 3072, BAR(B_LAND + 1)); }
        else e_mc(sb + M_MEM + (3 + c) * 3072, memg + s1, 3072, BAR(B_LAND + 1), 7);
        CSTAMP(3, clk());
        spin_until(ts + Y2_);
        if (PRIV_ & 4) { for (int k = 6; k < 8; k++) e_g2s(sb + M_MEM + k * 3072, memg + k * 8192 + ((nr >> k) & 1) * 4096, 3072, BAR(B_LAND + 2)); }
        else if (c < 2) e_mc(sb + M_MEM + (6 + c) * 3072, memg + s2, 3072, BAR(B_LAND + 2), 7);
        CSTAMP(4, clk());
      }
    } else if (w == 1) {
#pragma unroll 1
      for (int T = 0; T < NSTEP; T++) {
        const uint32_t ph = T & 1;
        const int s = c == 0 ? T : T - LAG;
        const bool act = s >= 0 && s < NSEG;
        mbar_wait(BAR(B_OST), ph);
        if (cta == 0) TSTAMP(2, T, 0);
        fence_async_smem();
        if (T < NSTEP - 1) wait_until(uni(lds32(sb + M_BASE + ph * 4)) + ODLY_);
        STAMP(22);
        if (act) { e_s2g(g_o[c][s % ORING][head], sb + M_OST, XO_); bulk_wait(); __syncwarp(); }
        e_arrive(BAR(B_OFREE));
        if (cta == 0) TSTAMP(2, T, 1);
        if (act && lane < 8) st_rel(&f_o[T][head >> 2][c * 4 + (head & 3)][lane], E);
        __syncwarp();
        if (cta == 0) TSTAMP(2, T, 2);
      }
    } else if (w == 2) {
      unsigned long long run = 0;
      static_assert(LAG >= 2, "config");
      constexpr uint32_t NA = EA / 4 * 4096;
      e_expect(BAR(B_QK), c < 2 ? 2048 : 4096); e_expect(BAR(B_V), c == 0 ? 10240 : c == 1 ? 2048 : 0);
      e_expect(BAR(B_TOK), c == 0 ? 16384 : 0); e_expect(BAR(B_OM), 4096);
      e_expect(BAR(B_HA), NA); e_expect(BAR(B_HB), 65536 - NA);
      wait_eq(&f_h1[c == 1 ? 0 : 1], E); fence_async_glob();
      {
        const uint32_t o0 = c == 0 ? NA : 0, o1 = c == 2 ? NA : 32768;
        e_mc(sb + M_H + (c == 1 ? 32768 : 0) + o0, g_h[0][c == 1 ? 0 : 1] + o0, o1 - o0, BAR(c == 2 ? B_HA : B_HB), 7);
      }
      TSTAMP(14, cta, 3);
      if (c == 2) wait_eq(&f_h1[2], E);
      mbar_wait(BAR(B_HAE), 1);
      e_expect(BAR(B_HA), NA);
      if (c == 2) { fence_async_glob(); e_mc(sb + M_H, g_h[0][2], NA, BAR(B_HA), 7); }
      int cprev = -1;
#pragma unroll 1
      for (int T = 0; T < NSTEP - 1; T++) {
        const int s1 = T + 2, s2 = T + 2 - LAG;
        const uint32_t ph = T & 1;
        const bool l1 = s1 < NSEG, l2 = s2 >= 0 && s2 < NSEG, la = s1 + 1 < NSEG;
        const bool mine = c == 0 ? l1 : c == 1 ? l2 : la;
        const uint32_t* fl = c != 1 ? &f_h1[min(s1 + (c >> 1), NSEG - 1)] : (const uint32_t*)f_h2[max(s2, 0)][lane & 3] + 1;
        const uint32_t want = E & 0x1FFFFFu, sh = c != 1 ? 0 : 11;
        mbar_wait(BAR(B_HBE), ph ^ 1);
        const bool early = __all_sync(~0u, ((ld_acq(fl) >> sh) & 0x1FFFFFu) == want);
        mbar_wait(BAR(B_LAND + 2), ph);
        STAMP(16);
        e_expect(BAR(B_HB), (l1 ? 32768 - NA : 0) + (l2 ? 32768 : 0));
        if (mine) {
          if (!early) {
            int guard = 0;
            while (!__all_sync(~0u, ((ld_acq(fl) >> sh) & 0x1FFFFFu) == want)) { __nanosleep(32); if (++guard > (1 << 22)) TRAP(); }
          }
          fence_async_glob();
          if (c == 1) { mbar_wait(BAR(B_QK), ph); spin_until(clk32() + HDLY_); }
          if (c < 2) paced_h(sb + M_H + c * 32768, g_h[c][c ? s2 : s1], c ? 0 : NA, 32768, 4096, BAR(B_HB), HGAP_);
        }
        int cd = -1;
        if (l2) { cd = route_step(s2, E, lane, run); if (cta == 0) TSTAMP(5, s2, 0); }
        if (lane == 0) sts32(sb + M_CAND + ((T + 2) & 3) * 4, (uint32_t)cd);
        __syncwarp();
        STAMP(17);
        mbar_wait(BAR(B_HAE), ph);
        e_expect(BAR(B_HA), la ? NA : 0);
        if (c == 2 && la) {
          spin_until(clk32() + ADLY_);
          STAMP(18);
          paced_h(sb + M_H, g_h[0][s1 + 1], 0, NA, 4096, BAR(B_HA), AGAP_);
        }
        mbar_wait(BAR(B_OST), ph);
        e_expect(BAR(B_QK), c < 2 ? 2048 : cprev >= 0 ? 8192 : 4096);
        e_expect(BAR(B_V), c < 2 ? 10240 : 8192);
        e_expect(BAR(B_TOK), 16384);
        e_expect(BAR(B_OM), 4096);
        cprev = cd;
      }
    } else {
      const uint32_t mytok = sb + M_Q + c * 12288 + 2048, tb = BAR(c < 2 ? B_TOK : B_V);
      mbar_wait(BAR(B_STG1), 0);
      fence_async_smem();
      e_s2g(g_tok[cta][1], sb + M_TST, 8192);
#pragma unroll 1
      for (int T = 0; T < NSTEP - 1; T++) {
        const uint32_t ph = T & 1;
        uint8_t* const tok = g_tok[cta][ph ^ 1];
        mbar_wait(BAR(B_STG), ph ^ 1);
        fence_async_smem();
        if (cta == 0 && (T == 0 || T == NSEG || T == NSTEP - 2)) GSTAMP(0, T == 0 ? 2 : T == NSEG ? 3 : 4);
        if (T > 0 && TQ_) mbar_wait(BAR(B_QK), ph);
        STAMP(20);
        uint32_t t = clk32();
        e_s2g(tok + 8192, sb + M_TST + 8192, XT2_);
        spin_until(t + TGAP_);
        e_s2g(tok + 12288, sb + M_TST + 12288, XT2_);
        bulk_wait();
        __syncwarp();
        e_arrive(BAR(B_TFREE));
        if (T == 0) e_mc(mytok, tok + 8192, 8192, tb, 1);
        STAMP(21);
#pragma unroll 1
        for (int k = 0; k < 2; k++) {
          if (k == 1) {
            mbar_wait(BAR(B_STG1), ph ^ 1);
            fence_async_smem();
            t = uni(lds32(sb + M_BASE + ph * 4));
            wait_until(t + TDLY_);
            e_s2g(g_tok[cta][ph], sb + M_TST, XT1_);
          }
          if (k == (c >> 1)) {
            mbar_wait(BAR(c < 2 ? B_KFREE : B_VFREE), ph);
            t = k ? t + LDLY_ : clk32() + KDLY_;
            wait_until(t);
            STAMP(23);
            e_mc(mytok, tok, 8192, tb, 1);
            spin_until(t + LGAP_);
            e_mc(mytok, tok + 8192, 8192, tb, 6);
            STAMP(24);
          }
        }
      }
      bulk_wait();
    }
    __syncwarp();
    cluster_sync();
  }
}

constexpr uint32_t A_RING = 0;
constexpr int A_NST = 6;
constexpr uint32_t A_STG = A_RING + A_NST * 8192;
constexpr uint32_t A_WD = A_STG + 8192;
constexpr uint32_t A_WG = A_WD + 57344;
constexpr uint32_t A_WU = A_WG + 57344;
constexpr uint32_t A_XN = A_WU + 57344;
constexpr uint32_t A_BAR = A_XN + 2048;
constexpr uint32_t A_TOTAL = A_BAR + 256;
static_assert(A_TOTAL <= 232448, "aux smem");

__device__ __forceinline__ uint32_t ptag(int s) { return ((s / PRING) & 1) ^ 1; }
static_assert((NSEG / PRING) % 2 == 0, "tags");
__device__ __forceinline__ void load_row(uint32_t* v, const void* row, int lane) {
  const uint4 a = __ldcg((const uint4*)row + lane), b = __ldcg((const uint4*)row + 32 + lane);
  v[0] = a.x; v[1] = a.y; v[2] = a.z; v[3] = a.w; v[4] = b.x; v[5] = b.y; v[6] = b.z; v[7] = b.w;
}
__device__ __forceinline__ void store_row(void* row, const uint32_t* v, int lane) {
  ((uint4*)row)[lane] = make_uint4(v[0], v[1], v[2], v[3]); ((uint4*)row)[32 + lane] = make_uint4(v[4], v[5], v[6], v[7]);
}
__device__ __forceinline__ void store_img(uint8_t* img, int r, const uint32_t* v, int lane) {
  uint8_t* b = img + (lane >> 3) * 4096 + (r >> 3) * 1024 + (r & 7) * 128 + (((lane ^ r) & 7) << 4);
  *(uint4*)b = make_uint4(v[0], v[1], v[2], v[3]);
  *(uint4*)(b + 16384) = make_uint4(v[4], v[5], v[6], v[7]);
}
template <int NT> __device__ __forceinline__ void ln_rows(const uint32_t (*v)[8], uint32_t (*y)[8]) {
  float c[NT], sm[NT], sq[NT];
#pragma unroll
  for (int k = 0; k < NT; k++) {
    c[k] = blo(__shfl_sync(~0u, v[k][0], 0));
    float s0 = 0.f, s1 = 0.f, q0 = 0.f, q1 = 0.f;
#pragma unroll
    for (int i = 0; i < 8; i++) { const float a = blo(v[k][i]) - c[k], b = bhi(v[k][i]) - c[k]; s0 += a; s1 += b; q0 = fmaf(a, a, q0); q1 = fmaf(b, b, q1); }
    sm[k] = s0 + s1; sq[k] = q0 + q1;
  }
#pragma unroll
  for (int o = 16; o > 0; o >>= 1)
#pragma unroll
    for (int k = 0; k < NT; k++) {
      sm[k] += __shfl_xor_sync(~0u, sm[k], o); sq[k] += __shfl_xor_sync(~0u, sq[k], o);
    }
#pragma unroll
  for (int k = 0; k < NT; k++) {
    const float dm = sm[k] * (1.f / 512.f), var = fmaxf(fmaf(-dm, dm, sq[k] * (1.f / 512.f)), 0.f);
    const float mb = rbf(c[k] + dm), inv = rcp(rbf(sqrt_fast(rbf(rbf(var) + 1e-5f))));
#pragma unroll
    for (int i = 0; i < 8; i++) { const uint32_t a = pack2(blo(v[k][i]) - mb, bhi(v[k][i]) - mb); y[k][i] = pack2(blo(a) * inv, bhi(a) * inv); }
  }
}
__device__ __forceinline__ void input_ln_pair(const bf16* x, int s, int pr, int lane) {
  uint32_t v[2][8], y[2][8];
  load_row(v[0], x + (size_t)(s * 32 + 2 * pr) * 512, lane); load_row(v[1], x + (size_t)(s * 32 + 2 * pr + 1) * 512, lane);
  ln_rows<2>(v, y);
  store_img(g_h[0][s], 2 * pr, y[0], lane); store_img(g_h[0][s], 2 * pr + 1, y[1], lane);
}
__device__ __forceinline__ float load_wr(uint32_t* wv, const bf16* wr, int lane) {
  load_row(wv, wr, lane);
  float wsum = 0.f;
#pragma unroll
  for (int i = 0; i < 8; i++) wsum += blo(wv[i]) + bhi(wv[i]);
#pragma unroll
  for (int o = 16; o > 0; o >>= 1) wsum += __shfl_xor_sync(~0u, wsum, o);
  return wsum;
}

template <bool FAST>
__device__ __forceinline__ unsigned long long token_post(int st, int tk, const bf16* res, bf16* dst, bf16* req, unsigned long long best,
                                                         const uint32_t* wv, float wsum, uint32_t E, int lane) {
  const int s = tk >> 5;
  uint32_t x[8];
  load_row(x, res, lane);
  wait_all(f_acc[st][s][lane], E, false);
  if (tk == s * 32 && st == 0 && lane == 0) TSTAMP(4, s, 0);
  {
    const uint8_t* pp = g_pp[st][s % PRING] + (lane >> 4) * 8192 + (tk & 31) * 256 + (((lane & 15) ^ (tk & 7)) << 4);
    const uint32_t tag = ptag(s);
    uint4 q[8][2];
#define PLD(k, h) q[k][h] = ld_rlx128<(k) * 32768 + (h) * 16384>(pp)
#define PLD8(h) PLD(0, h); PLD(1, h); PLD(2, h); PLD(3, h); PLD(4, h); PLD(5, h); PLD(6, h); PLD(7, h)
#define PBAD(h) __any_sync(~0u, (or3(xo2(q[0][h].x, q[1][h].x, tag), xo2(q[2][h].x, q[3][h].x, tag), xo2(q[4][h].x, q[5][h].x, tag)) | xo2(q[6][h].x, q[7][h].x, tag)) & ~lane & (PST_ == 8192 ? 1u : 0u))
#define PSUM(f, h, m) (((f(q[0][h].m) + f(q[1][h].m)) + (f(q[2][h].m) + f(q[3][h].m))) + ((f(q[4][h].m) + f(q[5][h].m)) + (f(q[6][h].m) + f(q[7][h].m))))
    const uint32_t eye = (lane >> 2) == 2 * (lane & 3) ? 0x3f80u : (lane >> 2) == 2 * (lane & 3) + 1 ? 0x3f800000u : 0u;
    auto padd = [&](int h) {
      if (FAST) {
        float u[4] = {0.f, 0.f, 0.f, 0.f}, v[4] = {0.f, 0.f, 0.f, 0.f};
#pragma unroll
        for (int k = 0; k < 8; k++) { hmma8(u, q[k][h].x, q[k][h].y, eye); hmma8(v, q[k][h].z, q[k][h].w, eye); }
        x[4 * h] = add2(x[4 * h], pack2(u[0], u[1])); x[4 * h + 1] = add2(x[4 * h + 1], pack2(u[2], u[3]));
        x[4 * h + 2] = add2(x[4 * h + 2], pack2(v[0], v[1])); x[4 * h + 3] = add2(x[4 * h + 3], pack2(v[2], v[3]));
      } else {
        x[4 * h] = add2(x[4 * h], pack2(PSUM(blo, h, x), PSUM(bhi, h, x))); x[4 * h + 1] = add2(x[4 * h + 1], pack2(PSUM(blo, h, y), PSUM(bhi, h, y)));
        x[4 * h + 2] = add2(x[4 * h + 2], pack2(PSUM(blo, h, z), PSUM(bhi, h, z))); x[4 * h + 3] = add2(x[4 * h + 3], pack2(PSUM(blo, h, w), PSUM(bhi, h, w)));
      }
    };
    int guard = 0;
    PLD8(0);
    if (FAST) { PLD8(1); }
    while (PBAD(0)) { if (++guard > (1 << 20)) TRAP(); PLD8(0); }
    padd(0);
    if (!FAST) { PLD8(1); }
    while (PBAD(1)) { if (++guard > (1 << 20)) TRAP(); PLD8(1); }
    padd(1);
  }
  const float c = blo(__shfl_sync(~0u, x[0], 0));
  float s0 = 0.f, s1 = 0.f, q0 = 0.f, q1 = 0.f, r0 = 0.f, r1 = 0.f;
#pragma unroll
  for (int i = 0; i < 8; i++) {
    const float a = blo(x[i]) - c, b = bhi(x[i]) - c;
    s0 += a; s1 += b; q0 = fmaf(a, a, q0); q1 = fmaf(b, b, q1); r0 = fmaf(a, blo(wv[i]), r0); r1 = fmaf(b, bhi(wv[i]), r1);
  }
  s0 += s1; q0 += q1; r0 += r1;
#pragma unroll
  for (int o = 16; o > 0; o >>= 1) { s0 += __shfl_xor_sync(~0u, s0, o); q0 += __shfl_xor_sync(~0u, q0, o); r0 += __shfl_xor_sync(~0u, r0, o); }
  const float dm = s0 * (1.f / 512.f), m = c + dm, var = fmaxf(fmaf(-dm, dm, q0 * (1.f / 512.f)), 0.f);
  const float mb = rbf(m), inv = rcp(rbf(sqrt_fast(rbf(rbf(var) + 1e-5f))));
  const uint32_t nmb = pack2(-mb, -mb);
  const unsigned long long wd = rword(E, tk, fmaf(c - mb, wsum, r0) * inv);
  uint32_t xn[8], x2[8];
#pragma unroll
  for (int i = 0; i < 8; i++) { const uint32_t d = add2(x[i], nmb); xn[i] = pack2(blo(d) * inv, bhi(d) * inv); x2[i] = add2(x[i], xn[i]); }
  if (st == 0) {
    const float mb2 = rbf(fmaf(m - mb, inv, m)), inv2 = rcp(rbf(sqrt_fast(rbf(rbf(var * (1.f + inv) * (1.f + inv)) + 1e-5f))));
    const uint32_t nmb2 = pack2(-mb2, -mb2);
    uint32_t h[8];
#pragma unroll
    for (int i = 0; i < 8; i++) { const uint32_t d2 = add2(x2[i], nmb2); h[i] = pack2(blo(d2) * inv2, bhi(d2) * inv2); }
    store_img(g_h[1][s], tk & 31, h, lane);
  }
  store_row(dst, x2, lane);
  if (wd > best && !(EXPQ_ & (st == 0 ? 1 : 2))) { store_row(req, xn, lane); store_row(req + 512, x, lane); }
  return wd;
}

__device__ __forceinline__ void ffn_slice(uint32_t sb, const bf16* xn, float* yacc, uint32_t* flag, uint32_t E, int t, bool urgent) {
  const int w = t >> 5, g = (t >> 2) & 7;
  if (t == 0 && urgent) sts32(sb + A_BAR + 160, 1);
  { const uint2 u = __ldcg((const uint2*)xn + t); asm volatile("st.shared.v2.u32 [%0], {%1,%2};" :: "r"(sb + A_XN + t * 8), "r"(u.x), "r"(u.y) : "memory"); }
  fence_async_smem();
  bar_sync(4, 128);
  float ga[4], ua[4];
  constexpr uint64_t da = mkdesc(A_WG, 896, 128, 0), db = mkdesc(A_XN, 16, 128, 0);
  wg_fence();
  wgmma_ss8<0, 1, 0>(ga, da, db); wgmma_ss8<0, 1, 0>(ua, da + (A_WU - A_WG) / 16, db);
#pragma unroll
  for (int ks = 1; ks < 32; ks++) { wgmma_ss8<1, 1, 0>(ga, da + ks * 112, db + ks * 2); wgmma_ss8<1, 1, 0>(ua, da + (A_WU - A_WG) / 16 + ks * 112, db + ks * 2); }
  wg_commit(); wg_wait<0>(); reg_fence(ga); reg_fence(ua);
  if ((t & 3) == 0) {
#pragma unroll
    for (int h = 0; h < 2; h++) {
      const float gs = rbf(ga[2 * h]), us = rbf(ua[2 * h]);
      const float v = 16 * w + 8 * h < 56 ? rbf(gs * rcp(1.f + __expf(-gs))) * us : 0.f;
      asm volatile("st.shared.u16 [%0], %1;" :: "r"(sb + A_XN + 1280 + (16 * w + 8 * h + g) * 2), "h"((unsigned short)pack2(v, 0.f)) : "memory");
    }
  }
  fence_async_smem();
  bar_sync(4, 128);
#pragma unroll 1
  for (int j = 0; j < 2; j++) {
    float y[4][4];
    const uint64_t dd = mkdesc(A_WD, 8192, 128, 0) + (uint64_t)(j * 256);
    wg_fence();
#pragma unroll
    for (int m = 0; m < 4; m++) {
      wgmma_ss8<0, 1, 0>(y[m], dd + m * 64, mkdesc(A_XN + 1280, 16, 128, 0));
#pragma unroll
      for (int ks = 1; ks < 4; ks++) wgmma_ss8<1, 1, 0>(y[m], dd + m * 64 + ks * 1024, mkdesc(A_XN + 1280 + ks * 32, 16, 128, 0));
    }
    wg_commit(); wg_wait<0>();
#pragma unroll
    for (int m = 0; m < 4; m++) {
      reg_fence(y[m]);
      if ((t & 3) == 0) { float* o = yacc + j * 256 + m * 64 + 16 * w + g; atomicAdd(o, y[m][0]); atomicAdd(o + 8, y[m][2]); }
    }
  }
  bar_sync(4, 128);
  if (t < 8) { sts32(sb + A_BAR + 160, 0); st_rel(flag + t, E); }
  __syncwarp();
}

__device__ __forceinline__ void ffn_finish(int q, const bf16* req, float r, uint32_t E, int lane, uint32_t* v) {
  uint32_t xn[8];
  load_row(xn, req, lane); load_row(v, req + 512, lane);
  const float rs = rbf(1.f / (1.f + __expf(-rbf(r))));
  wait_all(f_y[q][lane], E);
  float4 y[4];
#pragma unroll
  for (int i = 0; i < 4; i++) y[i] = __ldcg((const float4*)g_y[q] + (i >> 1) * 64 + 2 * lane + (i & 1));
#pragma unroll
  for (int i = 0; i < 4; i++) {
    v[2 * i] = add2(v[2 * i], add2(xn[2 * i], pack2(rbf(y[i].x) * rs, rbf(y[i].y) * rs)));
    v[2 * i + 1] = add2(v[2 * i + 1], add2(xn[2 * i + 1], pack2(rbf(y[i].z) * rs, rbf(y[i].w) * rs)));
  }
}
__global__ void __launch_bounds__(512, 1) aux_kernel(Params p) {
  extern __shared__ __align__(1024) uint8_t sm[];
  const uint32_t sb = smem_u32(sm);
  if ((sb & 0xFFFFFFu) != SBASE) TRAP();
  const int warp = __shfl_sync(~0u, threadIdx.x >> 5, 0);
  const int cta = blockIdx.x;
  const uint32_t E = __shfl_sync(~0u, *(volatile uint32_t*)&g_epoch + 1, 0);
  const uint32_t bars = sb + A_BAR;

  if (cta < 32) {
    const int cg = cta & 3, kg = cta >> 2;
    if (threadIdx.x == 0) {
      for (int i = 0; i < A_NST; i++) { mbar_init(bars + 8 * i, 1); mbar_init(bars + 64 + 8 * i, 2); }
      mbar_init(bars + 128, 8); mbar_init(bars + 136, 8); mbar_init(bars + 144, 1);
      sts32(bars + 160, 0);
      asm volatile("fence.mbarrier_init.release.cluster;" ::: "memory");
    }
    if (warp < 8) {
      asm volatile("setmaxnreg.inc.sync.aligned.u32 176;");
      const int tid = fresh_tid(), lane = tid & 31;
      uint32_t W[32][4];
      stage_weights(sb + A_WD, p.wo + (size_t)kg * 512 * 512 + cg * 128, 512, tid, 256);
      cp_async_wait();
      bar_sync(1, 256);
      load_frags(W, sb + A_WD, warp >> 2, warp & 3, lane);
      bar_sync(2, 512);
      const uint32_t so = sb + A_STG + ((lane >> 4) * 8 + (lane & 7)) * 256 + (((warp * 2 + ((lane >> 3) & 1)) ^ (lane & 7)) << 4);
      const uint32_t tm = lane < 4 ? 0x00010001u : 0u;
      int stage = 0; uint32_t ph = 0, job = 0;
#pragma unroll 1
      for (int T = 0; T < NSTEP; T++) {
#pragma unroll 1
        for (int k = 0; k < 3; k++) {
          const int st = k == 0 ? 0 : 3 - k, s = st == 0 ? T : T - LAG;
          if (s < 0 || s >= NSEG) continue;
          float d[16];
#pragma unroll
          for (int hh = 0; hh < 4; hh++) {
            mbar_wait(bars + 8 * stage, ph);
            while (uni(lds32(bars + 160))) __nanosleep(100);
            const uint64_t db = mkdesc(A_RING, 512, 128, 0) + (uint64_t)(stage * 512);
            wg_fence();
            if (hh == 0) wgmma_rs32<0, 0>(d, W[0], db); else wgmma_rs32<1, 0>(d, W[hh * 8], db);
#pragma unroll
            for (int ks = 1; ks < 8; ks++) wgmma_rs32<1, 0>(d, W[hh * 8 + ks], db + ks * 64);
            wg_commit();
            if (hh > 0) { wg_wait<1>(); if ((tid & 127) == 0) mbar_arrive(bars + 64 + 8 * (stage == 0 ? A_NST - 1 : stage - 1)); }
            if (++stage == A_NST) { stage = 0; ph ^= 1; }
          }
          mbar_wait(bars + 144, (job & 1) ^ 1);
          wg_wait<0>(); reg_fence(d);
          if ((tid & 127) == 0) mbar_arrive(bars + 64 + 8 * (stage == 0 ? A_NST - 1 : stage - 1));
          if (cta == 0 && tid == 0) TSTAMP(6, T, k);
          const uint32_t tv = tm * ptag(s);
#define TG(i) ((pack2(d[2 * (i)], d[2 * (i) + 1]) & ~tm) | tv)
          stmatrix4_t(so, TG(0), pack2(d[2], d[3]), TG(2), pack2(d[6], d[7]));
          stmatrix4_t(so + 4096, TG(4), pack2(d[10], d[11]), TG(6), pack2(d[14], d[15]));
          fence_async_smem();
          __syncwarp();
          if (lane == 0) mbar_arrive(bars + 128 + 8 * (job & 1));
          job++;
        }
      }
    } else if (warp < 12) {
      asm volatile("setmaxnreg.dec.sync.aligned.u32 120;");
      const int tid = fresh_tid(), lane = tid & 31;
      const int w = warp - 8, t = tid - 256;
#pragma unroll 1
      for (int s = cta + 4; s < NSEG; s += 32) {
#pragma unroll 1
        for (int pr = w; pr < 16; pr += 4) input_ln_pair(p.x, s, pr, lane);
        bar_sync(4, 128);
        if (t == 0) st_rel(&f_h1[s], E);
      }
      bar_sync(2, 512);
      { int guard = 0; while (ld_rlx(&f_loaded[cta]) != E) { __nanosleep(200); if (++guard > (1 << 22)) TRAP(); } }
#pragma unroll 1
      for (int i = t; i < 512 * 7; i += 128) {
        const int k = i / 7, pc = i % 7;
        cp_async16(sb + A_WG + (k >> 3) * 896 + pc * 128 + (k & 7) * 16, p.wg + (size_t)k * 1792 + cta * 56 + pc * 8);
        cp_async16(sb + A_WU + (k >> 3) * 896 + pc * 128 + (k & 7) * 16, p.wu + (size_t)k * 1792 + cta * 56 + pc * 8);
        cp_async16(sb + A_WD + (i >> 9) * 8192 + (i & 63) * 128 + ((i >> 6) & 7) * 16, p.wd + (size_t)cta * 56 * 512 + i * 8);
      }
      uint32_t wv[8];
      const float wsum = load_wr(wv, p.wr, lane);
      cp_async_wait();
      fence_async_smem();
      wait_all(&f_zero[lane], E);
      bar_sync(4, 128);
      const int tj = (cta * 4 + w) & 31, st = 1 + ((cta >> 3) & 1), sq = cta >> 4;
      unsigned long long run = 0, run2 = 0, best = 0, hist = 0;
      uint32_t open = 0;
#pragma unroll 1
      for (int i = 0; i <= NSTEP; i++) {
        int tok = -1; const bf16* req = nullptr;
        if (i < NSEG) {
          const int cd = (int)uni(route_step(i, E, lane, run));
          run = __shfl_sync(~0u, run, 0);
          hist = hist << 8 | (uint32_t)(cd + 1);
          if (cd >= 0) { tok = rtok(run); req = g_req1[tok][0]; }
        } else {
          const unsigned long long m = wait_words(f_l2[i - NSEG], E);
          if (m != run2) { run2 = m; tok = rtok(m); req = g_req2[(tok >> 5) < (rtok(run) >> 5) ? 0 : 1][tok][0]; }
        }
        tok = __shfl_sync(~0u, tok, 0);
        if (tok >= 0) {
          if (cta == 0 && t == 0) TSTAMP(8, i, 0);
          ffn_slice(sb, req, g_y[i], f_y[i][cta], E, t, i < NSEG);
          if (cta == 0 && t == 0) TSTAMP(8, i, 1);
        }
        const int s = i - LAG;
        if (s < 0 || i >= NSEG) continue;
        const int cd = (int)((hist >> (8 * LAG)) & 255) - 1;
        if (cd >= 0 && st == 2) best = 0;
        const int ts = rtok(run) >> 5;
        if ((s & 1) == sq) {
          const int tk = s * 32 + tj;
          unsigned long long wd = (unsigned long long)E << 43;
          if (st == 1 ? s < ts || i < NSEG - 1 : s >= ts) {
            if (st == 2 && cd == tj) wait_eq(&f_hc[s], E);
            wd = token_post<false>(st, tk, st == 2 && cd == tj ? g_x2c[s] : g_x2 + (size_t)tk * 512,
                                   (st == 2 || s < ts ? p.out : g_n) + (size_t)tk * 512, g_req2[st - 1][tk][0], best, wv, wsum, E, lane);
            best = max(best, wd);
            if (st == 1 && s >= ts) open |= 1u << (s >> 1);
          }
          __syncwarp();
          if (lane < 4) st_rel64(&f_w2[st - 1][s][tj][lane], wd);
          __syncwarp();
        }
        if (st == 1) {
          if (i == NSEG - 1 && t == 0 && cta == 0) GSTAMP(1, 0);
#pragma unroll 1
          for (int n = i == NSEG - 1 ? 32 : 2; n > 0 && open; n--) {
            const int s0 = 2 * (__ffs(open) - 1) + sq;
            if (s0 >= ts) break;
            open &= open - 1;
            uint32_t v[8];
            load_row(v, g_n + (size_t)(s0 * 32 + tj) * 512, lane);
            wait_words(f_w2[1][s0][tj], E);
            store_row(p.out + (size_t)(s0 * 32 + tj) * 512, v, lane);
          }
          if (i == NSEG - 1) {
            __syncwarp();
            if (lane == 0) st_rel(&f_cp[sq * 32 + tj], E);
            if (t == 0 && cta == 0) GSTAMP(1, 3);
          }
        }
      }
    } else {
      asm volatile("setmaxnreg.dec.sync.aligned.u32 40;");
      const int tid = fresh_tid(), lane = tid & 31;
      const int t = tid - 384, w = warp - 12;
      for (int i = cta * 128 + t; i < (NSTEP + 1) * 128; i += 4096) ((float4*)&g_y[0][0])[i] = make_float4(0.f, 0.f, 0.f, 0.f);
      bar_sync(3, 128);
      if (t == 0) st_rel(&f_zero[cta], E);
      bar_sync(2, 512);
      if (w == 0) {
        int stage = 0; uint32_t ph = 1;
#pragma unroll 1
        for (int T = 0; T < NSTEP; T++) {
#pragma unroll 1
          for (int k = 0; k < 3; k++) {
            const int st = k == 0 ? 0 : 3 - k, s = st == 0 ? T : T - LAG;
            if (s < 0 || s >= NSEG) continue;
            const uint32_t* fl = f_o[T][kg][st * 4 + (lane & 3)];
            uint32_t ready = 0; int guard = 0;
#pragma unroll 1
            for (int hh = 0; hh < 4; hh++) {
              while (!((ready >> hh) & 1)) {
                ready = __ballot_sync(~0u, ld_rlx(fl) == E);
                if (++guard > (1 << 23)) TRAP();
              }
              fence_async_glob();
              mbar_wait(bars + 64 + 8 * stage, ph);
              e_expect(bars + 8 * stage, OLOAD_);
              e_g2s(sb + A_RING + stage * 8192, g_o[st][s % ORING][kg * 4 + hh], OLOAD_, bars + 8 * stage);
              if (++stage == A_NST) { stage = 0; ph ^= 1; }
            }
          }
          if (cta == 0 && lane == 0) TSTAMP(3, T, 0);
        }
      } else if (w < 3) {
        uint32_t job = 0;
#pragma unroll 1
        for (int T = 0; T < NSTEP; T++) {
#pragma unroll 1
          for (int k = 0; k < 3; k++) {
            const int st = k == 0 ? 0 : 3 - k, s = st == 0 ? T : T - LAG;
            if (s < 0 || s >= NSEG) continue;
            if ((job++ & 1) != w - 1) continue;
            if (s >= PRING) wait_words(st == 0 ? f_h2[s - PRING][lane & 3] : f_w2[st - 1][s - PRING][lane], E);
            mbar_wait(bars + 128 + 8 * (w - 1), ((job - 1) >> 1) & 1);
            if (cta == 0 && st == 0) TSTAMP(7, s, 0);
            e_s2g(g_pp[st][s % PRING] + cta * 8192, sb + A_STG, PST_);
            asm volatile("cp.async.bulk.commit_group;\n cp.async.bulk.wait_group.read 0;" ::: "memory");
            __syncwarp();
            e_arrive(bars + 144);
            if (!HINT_) bulk_wait();
            __syncwarp();
            if (lane < 8) st_rlx(&f_acc[st][s][cta][lane], E);
            __syncwarp();
            if (cta == 0 && st == 0) TSTAMP(7, s, 1);
          }
        }
        bulk_wait();
      }
    }
  } else {
    const int tid = fresh_tid(), lane = tid & 31;
    const int qd = cta - 32;
    input_ln_pair(p.x, qd, warp, lane);
    bar_sync(6, 512);
    if (tid == 0) st_rel(&f_h1[qd], E);
    volatile int* bc = (volatile int*)sm;
    if (warp == 15) {
      unsigned long long run = 0;
      wait_all(&f_zero[lane], E);
      unsigned long long b2[2][2] = {{0, 0}, {0, 0}};
      auto track = [&](int s) {
#pragma unroll
        for (int k = 0; k < 2; k++) {
          const unsigned long long m = warp_max<16>(wait_words(f_w2[k][s][lane], E));
          if (lane == (s & 31)) { if (s < 32) b2[k][0] = m; else b2[k][1] = m; }
        }
      };
#pragma unroll 1
      for (int s = 0; s < NSEG; s++) {
        const int cd = route_step(s, E, lane, run);
        if (cd >= 0 && qd == (s & 1)) {
          uint32_t v[1][8], h[1][8];
          ffn_finish(s, g_req1[s * 32 + cd][0], rscore(run), E, lane, v[0]);
          if (lane == 0) TSTAMP(8, s, 2);
          ln_rows<1>(v, h);
#pragma unroll
          for (int i = 0; i < 8; i++) st_rlx64(&g_hc[s][(i >> 2) * 128 + 4 * lane + (i & 3)], h[0][i], E);
          if (lane == 0) TSTAMP(8, s, 3);
          store_row(g_x2c[s], v[0], lane);
          __syncwarp();
          if (lane == 0) st_rel(&f_hc[s], E);
        }
        if (qd == 2 && s > LAG) track(s - LAG - 1);
      }
      wait_eq(&f_hc[rtok(run) >> 5], E);
      if (lane == 0) *bc = rtok(run);
      bar_sync(7, 288);
      if (qd == 2) {
        uint32_t v[8];
        const int ts = rtok(run) >> 5;
        track(NSEG - LAG - 1);
        run = 0;
#pragma unroll 1
        for (int k = 0; k <= LAG; k++) {
          const int s = NSEG - LAG - 1 + k;
          const unsigned long long m = warp_max<16>(k == 0 ? max(lane < ts ? b2[0][0] : b2[1][0], lane + 32 < ts ? b2[0][1] : b2[1][1])
                                                           : wait_words(f_w2[s < ts ? 0 : 1][s][lane], E));
          const bool lead = m > run;
          if (lead) { run = m; __threadfence(); }
          if (lane < 4) st_rlx64(&f_l2[k][lane], (uint32_t)run, (uint32_t)(run >> 32));
          if (lead) ffn_finish(NSEG + k, g_req2[(rtok(run) >> 5) < ts ? 0 : 1][rtok(run)][0], rscore(run), E, lane, v);
          if (k == 0) { wait_all(&f_cp[lane], E); wait_all(&f_cp[32 + lane], E); }
        }
        if (lane == 0) GSTAMP(1, 1);
        store_row(p.out + (size_t)rtok(run) * 512, v, lane);
        if (lane == 0) GSTAMP(1, 2);
        asm volatile("griddepcontrol.wait;" ::: "memory");
        if (lane == 0) *(volatile uint32_t*)&g_epoch = E;
      }
    } else if (warp < 8) {
      uint32_t wv[8];
      const float wsum = load_wr(wv, p.wr, lane);
      unsigned long long best = 0;
      int ttok = 0;
#pragma unroll 1
      for (int i = 0; i < NSTEP; i++) {
        const bool last = i >= NSEG;
        if (i == NSEG) { bar_sync(7, 288); ttok = *bc; best = 0; }
        const int s = last ? i - LAG : i, st = !last ? 0 : s < (ttok >> 5) ? 1 : 2;
        const int tk = s * 32 + qd * 8 + warp;
        const unsigned long long wd = token_post<true>(st, tk, !last ? p.x + (size_t)tk * 512 : tk == ttok ? g_x2c[s] : g_x2 + (size_t)tk * 512,
                                                 (last ? p.out : g_x2) + (size_t)tk * 512, last ? g_req2[st - 1][tk][0] : g_req1[tk][0], best, wv, wsum, E, lane);
        best = max(best, wd);
        volatile unsigned long long* ws = (volatile unsigned long long*)(sm + 64) + (i & 1) * 8;
        if (lane == 0) ws[warp] = wd;
        bar_sync(5, 256);
        if (warp == 0) {
          if (qd == 0 && lane == 0) TSTAMP(4, i, 1);
          if (!last) { const unsigned long long m = warp_max<4>(ws[lane & 7]); if (lane < 4) st_rel64(&f_h2[s][qd][lane], m); }
          else {
            st_rel64(&f_w2[st - 1][s][qd * 8 + (lane >> 2)][lane & 3], ws[lane >> 2]);
            asm volatile("st.relaxed.gpu.global.u64 [%0], %1;" :: "l"(&f_w2[2 - st][s][qd * 8 + (lane >> 2)][lane & 3]), "l"((unsigned long long)E << 43) : "memory");
          }
          if (qd == 0 && lane == 0) TSTAMP(4, i, 2);
        }
        __syncwarp();
      }
    }
  }
}

}

extern "C" void kernel_launch(void* const* d_in, const int* in_sizes, int n_in, void* d_out, int out_size) {
  (void)in_sizes; (void)n_in; (void)out_size;
  static bool init = false;
  if (!init) {
    cudaFuncSetAttribute(main_kernel, cudaFuncAttributeMaxDynamicSharedMemorySize, M_TOTAL);
    cudaFuncSetAttribute(aux_kernel, cudaFuncAttributeMaxDynamicSharedMemorySize, A_TOTAL);
    init = true;
  }
  Params p;
  p.x = (const bf16*)d_in[0]; p.mem0 = (const bf16*)d_in[1]; p.wq = (const bf16*)d_in[2]; p.wk = (const bf16*)d_in[3];
  p.wv = (const bf16*)d_in[4]; p.wo = (const bf16*)d_in[5]; p.wr = (const bf16*)d_in[8]; p.wg = (const bf16*)d_in[9];
  p.wu = (const bf16*)d_in[10]; p.wd = (const bf16*)d_in[11]; p.out = (bf16*)d_out; p.zero = 0; p.zero2 = 0;
  cudaStream_t st = cudaStreamPerThread;
  main_kernel<<<96, 512, M_TOTAL, st>>>(p);
  cudaLaunchConfig_t cfg = {};
  cfg.gridDim = dim3(36); cfg.blockDim = dim3(512); cfg.dynamicSmemBytes = A_TOTAL; cfg.stream = st;
  cudaLaunchAttribute at[1];
  at[0].id = cudaLaunchAttributeProgrammaticStreamSerialization; at[0].val.programmaticStreamSerializationAllowed = 1;
  cfg.attrs = at; cfg.numAttrs = 1;
  cudaLaunchKernelEx(&cfg, aux_kernel, p);
}
```

```cpp
#include <cuda_runtime.h>
#include <cuda_bf16.h>
#include <stdint.h>

namespace {

typedef __nv_bfloat16 bf16;

constexpr int NSEG = 64;
#define LAG_ 5
constexpr int LAG = LAG_;
constexpr int NSTEP = NSEG + LAG;
constexpr int ORING = 8, PRING = 4;
#define E1_ 10
#define E2_ 0
#define E3_ 10
constexpr int E1 = E1_, E2 = E2_, E3 = E3_, EA = E1 + E2 + E3;
static_assert(EA % 4 == 0 && EA > 0 && EA < 32 && E1 > 0, "early part: whole 64-column chunks");
#define RW_ 176
#define RA_ 136
#define RC_ 24
#define STR2(x) #x
#define STR(x) STR2(x)
#define RED_ 30
#define ARR_ 7
#define PAUSE_ 19
#define PD1_ 4
#define PST2_ 2
#define PGR_ PD1_
#define PVR_ -1
#define SALT_ 0
#define KP1_ 1
#define PRIV_ 1
#define OLOAD_ 8192
#define PST_ 8192
#define ALT_ 1
#define TQ_ 1
#define NOF_ 2
#define EXPQ_ 0
#define XT1_ 8192
#define XT2_ 4096
#define XO_ 8192
#define HINT_ 1
#define HADD_ 2
#define HAND_ 4
#define GO3_ 2
#define NPROBE_ 6
#define TP(i, v) (v)
#define XDLY_ TP(0, 2250)
#define YDLY_ TP(1, 3425)
#define X1_ TP(2, 100)
#define X2_ TP(3, 250)
#define Y1_ TP(4, 150)
#define Y2_ TP(5, 200)
#define HGAP_ TP(6, 50)
#define TGAP_ TP(7, 200)
#define ADLY_ TP(8, 600)
#define ODLY_ TP(9, 2800)
#define LDLY_ TP(10, 3800)
#define LGAP_ 200
#define HDLY_ TP(11, 0)
#define TDLY_ TP(15, 4000)
#define SDLY_ TP(12, 800)
#define AGAP_ 100
#define BOFF_ TP(13, 200)
#define YOFF_ TP(16, 150)
#define CDLY_ TP(17, 300)
#define SLOW0_ TP(18, 400)
#define SLOW1_ TP(19, 300)
#define KDLY_ TP(14, 300)
__device__ uint32_t g_epoch;
__device__ __align__(1024) uint8_t g_h[2][NSEG][32768];
__device__ __align__(128) uint2 g_hc[NSEG][256];
__device__ __align__(128) bf16 g_x2[2048 * 512];
__device__ __align__(128) bf16 g_x2c[NSEG][512];
__device__ __align__(128) uint8_t g_o[3][ORING][32][8192];
__device__ __align__(128) uint8_t g_pp[3][PRING][8 * 32768];
__device__ __align__(128) bf16 g_n[2048 * 512];
__device__ __align__(128) uint8_t g_xch[96 * 16384 + 65536 + 8192];
__device__ __align__(128) bf16 g_req1[2048][2][512];
__device__ __align__(128) bf16 g_req2[2][2048][2][512];
__device__ __align__(128) float g_y[NSTEP + 1][512];
__device__ __align__(128) uint8_t g_tok[96][2][16384];
__device__ uint32_t f_choice[96][2], f_loaded[32];
__device__ uint32_t f_h1[NSEG], f_hc[NSEG];
__device__ __align__(128) unsigned long long f_h2[NSEG][4][4];
__device__ __align__(128) unsigned long long f_w2[2][NSEG][32][4];
__device__ __align__(128) unsigned long long f_l2[LAG + 1][4];
__device__ __align__(128) uint32_t f_o[NSTEP][8][12][8];
__device__ __align__(128) uint32_t f_acc[3][NSEG][32][8], f_y[NSTEP + 1][32][8], f_zero[32], f_cp[64];
__device__ __align__(128) unsigned long long g_sync[2][96][4];

#define TRAP() __trap()
__device__ __forceinline__ uint32_t smem_u32(const void* p) { return (uint32_t)__cvta_generic_to_shared(p); }
__device__ __forceinline__ int fresh_tid() { const int t = threadIdx.x; return __shfl_sync(~0u, t, t & 31); }
__device__ __forceinline__ unsigned long long gtime64() { unsigned long long t; asm volatile("mov.u64 %0, %%globaltimer;" : "=l"(t) :: "memory"); return t; }
__device__ __forceinline__ uint32_t clk() { unsigned long long c; asm volatile("mov.u64 %0, %%clock64;" : "=l"(c) :: "memory"); return (uint32_t)c; }
__device__ __forceinline__ void wait_until(uint32_t t) {
  while ((int)(t - clk()) > 450) __nanosleep(32);
  uint32_t c;
  do { asm volatile("mov.u32 %0, %%clock;" : "=r"(c) :: "memory"); } while ((int)(c - t) < 0);
}
__device__ __forceinline__ void mbar_init(uint32_t bar, uint32_t cnt) { asm volatile("mbarrier.init.shared::cta.b64 [%0], %1;" :: "r"(bar), "r"(cnt) : "memory"); }
__device__ __forceinline__ void mbar_arrive(uint32_t bar) { asm volatile("mbarrier.arrive.shared::cta.b64 _, [%0];" :: "r"(bar) : "memory"); }
__device__ __forceinline__ void mbar_arrive_remote(uint32_t bar) { asm volatile("mbarrier.arrive.relaxed.cluster.shared::cluster.b64 _, [%0];" :: "r"(bar) : "memory"); }
__device__ __forceinline__ void mbar_expect(uint32_t bar, uint32_t bytes) { asm volatile("mbarrier.arrive.expect_tx.shared::cta.b64 _, [%0], %1;" :: "r"(bar), "r"(bytes) : "memory"); }
__device__ __forceinline__ bool mbar_try(uint32_t bar, uint32_t parity) {
  uint32_t ok;
  asm volatile("{.reg .pred p; mbarrier.try_wait.parity.shared::cta.b64 p, [%1], %2; selp.u32 %0, 1, 0, p;}" : "=r"(ok) : "r"(bar), "r"(parity) : "memory");
  return ok;
}
__device__ __forceinline__ bool mbar_test(uint32_t bar, uint32_t parity) {
  uint32_t ok;
  asm volatile("{.reg .pred p; mbarrier.test_wait.parity.shared::cta.b64 p, [%1], %2; selp.u32 %0, 1, 0, p;}" : "=r"(ok) : "r"(bar), "r"(parity) : "memory");
  return ok;
}
__device__ __forceinline__ void mbar_wait(uint32_t bar, uint32_t parity) {
  asm volatile("{\n.reg .pred p;\nWAIT:\nmbarrier.try_wait.parity.shared::cta.b64 p, [%0], %1;\n@!p bra WAIT;\n}" :: "r"(bar), "r"(parity) : "memory");
}
__device__ __forceinline__ uint32_t ld_acq(const uint32_t* p) { uint32_t v; asm volatile("ld.acquire.gpu.global.u32 %0, [%1];" : "=r"(v) : "l"(p) : "memory"); return v; }
__device__ __forceinline__ unsigned long long ld_acq64(const unsigned long long* p) { unsigned long long v; asm volatile("ld.acquire.gpu.global.u64 %0, [%1];" : "=l"(v) : "l"(p) : "memory"); return v; }
__device__ __forceinline__ void st_rel(uint32_t* p, uint32_t v) { asm volatile("st.release.gpu.global.u32 [%0], %1;" :: "l"(p), "r"(v) : "memory"); }
__device__ __forceinline__ void st_rel64(unsigned long long* p, unsigned long long v) { asm volatile("st.release.gpu.global.u64 [%0], %1;" :: "l"(p), "l"(v) : "memory"); }
__device__ __forceinline__ void red_rel(uint32_t* p, uint32_t v) { asm volatile("red.release.gpu.global.add.u32 [%0], %1;" :: "l"(p), "r"(v) : "memory"); }
__device__ __forceinline__ uint32_t ld_rlx(const uint32_t* p) { uint32_t v; asm volatile("ld.relaxed.gpu.global.u32 %0, [%1];" : "=r"(v) : "l"(p) : "memory"); return v; }
__device__ __forceinline__ unsigned long long ld_rlxu64(const unsigned long long* p) { unsigned long long v; asm volatile("ld.relaxed.gpu.global.u64 %0, [%1];" : "=l"(v) : "l"(p) : "memory"); return v; }
__device__ __forceinline__ void st_rlx(uint32_t* p, uint32_t v) { asm volatile("st.relaxed.gpu.global.u32 [%0], %1;" :: "l"(p), "r"(v) : "memory"); }
__device__ __forceinline__ void bulk_wait() { asm volatile("cp.async.bulk.commit_group;\n cp.async.bulk.wait_group 0;" ::: "memory"); }
__device__ __forceinline__ void fence_acq() { asm volatile("fence.acquire.gpu;" ::: "memory"); }
__device__ __forceinline__ void wait_all(const uint32_t* p, uint32_t v, bool acquire = true) {
  int guard = 0;
  while (!__all_sync(~0u, ld_rlx(p) == v)) { __nanosleep(32); if (++guard > (1 << 22)) TRAP(); }
  if (acquire) fence_acq();
}
__device__ __forceinline__ void wait_eq(const uint32_t* p, uint32_t v) {
  int guard = 0;
  while (ld_rlx(p) != v) { __nanosleep(64); if (++guard > (1 << 22)) TRAP(); }
  fence_acq();
}
__device__ __forceinline__ unsigned long long rword(uint32_t E, int tok, float r) {
  uint32_t u = __float_as_uint(r + 0.f);
  u = r != r ? 0u : (u >> 31) ? ~u : u | 0x80000000u;
  return (unsigned long long)(E & 0x1FFFFFu) << 43 | (unsigned long long)u << 11 | (uint32_t)(2047 - tok);
}
__device__ __forceinline__ int rtok(unsigned long long v) { return 2047 - (int)(v & 2047u); }
__device__ __forceinline__ float rscore(unsigned long long v) { const uint32_t u = (uint32_t)(v >> 11); return __uint_as_float((u >> 31) ? u & 0x7fffffffu : ~u); }
__device__ __forceinline__ bool rfresh(unsigned long long v, uint32_t E) { return (uint32_t)(v >> 43) == (E & 0x1FFFFFu); }
template <int TOP> __device__ __forceinline__ unsigned long long warp_max(unsigned long long v) {
#pragma unroll
  for (int o = TOP; o > 0; o >>= 1) { const unsigned long long ov = __shfl_xor_sync(~0u, v, o); v = ov > v ? ov : v; }
  return v;
}
template <int off> __device__ __forceinline__ uint2 ld_rlx64(const void* p) { unsigned long long v; asm volatile("ld.relaxed.gpu.global.b64 %0, [%1+%2];" : "=l"(v) : "l"(p), "n"(off) : "memory"); return make_uint2((uint32_t)v, (uint32_t)(v >> 32)); }
template <int off> __device__ __forceinline__ uint4 ld_rlx128(const void* p) {
  unsigned long long a, b; asm volatile("ld.relaxed.gpu.global.v2.b64 {%0,%1}, [%2+%3];" : "=l"(a), "=l"(b) : "l"(p), "n"(off) : "memory");
  return make_uint4((uint32_t)a, (uint32_t)(a >> 32), (uint32_t)b, (uint32_t)(b >> 32));
}
__device__ __forceinline__ void st_rlx64(void* p, uint32_t lo, uint32_t hi) { asm volatile("{.reg .b64 t; mov.b64 t, {%1,%2}; st.relaxed.gpu.global.b64 [%0], t;}" :: "l"(p), "r"(lo), "r"(hi) : "memory"); }
__device__ __forceinline__ void cp_async16(uint32_t dst, const void* src) { asm volatile("cp.async.cg.shared.global [%0], [%1], 16;" :: "r"(dst), "l"(src) : "memory"); }
__device__ __forceinline__ void cp_async_wait() { asm volatile("cp.async.wait_all;" ::: "memory"); }
__device__ __forceinline__ void fence_async_smem() { asm volatile("fence.proxy.async.shared::cta;" ::: "memory"); }
__device__ __forceinline__ void fence_async_glob() { asm volatile("fence.proxy.async.global;" ::: "memory"); }
__device__ __forceinline__ void fence_async_acq() { asm volatile("fence.proxy.async::generic.acquire.sync_restrict::shared::cluster.cluster;" ::: "memory"); }
__device__ __forceinline__ float ex2(float x) { float y; asm("ex2.approx.ftz.f32 %0, %1;" : "=f"(y) : "f"(x)); return y; }
__device__ __forceinline__ float sqrt_fast(float x) { float y; asm("sqrt.approx.ftz.f32 %0, %1;" : "=f"(y) : "f"(x)); return y; }
__device__ __forceinline__ float rcp(float x) { float y; asm("rcp.approx.ftz.f32 %0, %1;" : "=f"(y) : "f"(x)); return y; }
__device__ __forceinline__ void bar_sync(int id, int n) { asm volatile("bar.sync %0, %1;" :: "r"(id), "r"(n) : "memory"); }
__device__ __forceinline__ bool bar_or(int id, int n, bool v) {
  uint32_t r;
  asm volatile("{.reg .pred p, q; setp.ne.u32 p, %3, 0; barrier.cta.red.or.aligned.pred q, %1, %2, p; selp.u32 %0, 1, 0, q;}" : "=r"(r) : "r"(id), "r"(n), "r"((uint32_t)v) : "memory");
  return r;
}
__device__ __forceinline__ uint32_t mapa(uint32_t a, uint32_t rank) { uint32_t r; asm volatile("mapa.shared::cluster.u32 %0, %1, %2;" : "=r"(r) : "r"(a), "r"(rank)); return r; }
__device__ __forceinline__ void cluster_sync() { asm volatile("barrier.cluster.arrive.release.aligned; barrier.cluster.wait.acquire.aligned;" ::: "memory"); }
__device__ __forceinline__ void st_async32(uint32_t dst, uint32_t v, uint32_t bar) { asm volatile("st.async.shared::cluster.mbarrier::complete_tx::bytes.b32 [%0], %1, [%2];" :: "r"(dst), "r"(v), "r"(bar) : "memory"); }
__device__ __forceinline__ void bulk_g2s(uint32_t dst, const void* src, uint32_t bytes, uint32_t bar) {
  asm volatile("cp.async.bulk.shared::cluster.global.mbarrier::complete_tx::bytes [%0], [%1], %2, [%3];" :: "r"(dst), "l"(src), "r"(bytes), "r"(bar) : "memory");
}
__device__ __forceinline__ void bulk_g2s_mc(uint32_t dst, const void* src, uint32_t bytes, uint32_t bar, uint16_t mask) {
  asm volatile("cp.async.bulk.shared::cluster.global.mbarrier::complete_tx::bytes.multicast::cluster [%0], [%1], %2, [%3], %4;"
               :: "r"(dst), "l"(src), "r"(bytes), "r"(bar), "h"(mask) : "memory");
}
__device__ __forceinline__ void bulk_s2c(uint32_t dst, uint32_t src, uint32_t bytes, uint32_t bar) {
  asm volatile("cp.async.bulk.shared::cluster.shared::cta.mbarrier::complete_tx::bytes [%0], [%1], %2, [%3];" :: "r"(dst), "r"(src), "r"(bytes), "r"(bar) : "memory");
}
__device__ __forceinline__ void bulk_s2g(void* dst, uint32_t src, uint32_t bytes) {
  asm volatile("cp.async.bulk.global.shared::cta.bulk_group [%0], [%1], %2;" :: "l"(dst), "r"(src), "r"(bytes) : "memory");
}
#define ELECT(op) "{.reg .pred p; elect.sync _|p, 0xffffffff; @p " op "}"
__device__ __forceinline__ void e_arrive(uint32_t bar) { asm volatile(ELECT("mbarrier.arrive.shared::cta.b64 _, [%0];") :: "r"(bar) : "memory"); }
__device__ __forceinline__ void e_expect(uint32_t bar, uint32_t bytes) { asm volatile(ELECT("mbarrier.arrive.expect_tx.shared::cta.b64 _, [%0], %1;") :: "r"(bar), "r"(bytes) : "memory"); }
__device__ __forceinline__ void e_g2s(uint32_t dst, const void* src, uint32_t bytes, uint32_t bar) {
  asm volatile(ELECT("cp.async.bulk.shared::cluster.global.mbarrier::complete_tx::bytes [%0], [%1], %2, [%3];") :: "r"(dst), "l"(src), "r"(bytes), "r"(bar) : "memory");
}
__device__ __forceinline__ void e_mc(uint32_t dst, const void* src, uint32_t bytes, uint32_t bar, uint16_t mask) {
  asm volatile(ELECT("cp.async.bulk.shared::cluster.global.mbarrier::complete_tx::bytes.multicast::cluster [%0], [%1], %2, [%3], %4;")
               :: "r"(dst), "l"(src), "r"(bytes), "r"(bar), "h"(mask) : "memory");
}
__device__ __forceinline__ void e_s2g(void* dst, uint32_t src, uint32_t bytes) {
  asm volatile(ELECT("cp.async.bulk.global.shared::cta.bulk_group [%0], [%1], %2;") :: "l"(dst), "r"(src), "r"(bytes) : "memory");
}
__device__ __forceinline__ void e_st_rel(uint32_t* p, uint32_t v) { asm volatile(ELECT("st.release.gpu.global.u32 [%0], %1;") :: "l"(p), "r"(v) : "memory"); }
__device__ __forceinline__ uint32_t clk32() { uint32_t c; asm volatile("mov.u32 %0, %%clock;" : "=r"(c) :: "memory"); return c; }
__device__ __forceinline__ void spin_until(uint32_t t) { while ((int)(clk32() - t) < 0) {} }
__device__ __forceinline__ uint32_t uni(uint32_t v) { return __shfl_sync(~0u, v, 0); }
__device__ __forceinline__ uint32_t pack2(float lo, float hi) { uint32_t r; asm("cvt.rn.bf16x2.f32 %0, %1, %2;" : "=r"(r) : "f"(hi), "f"(lo)); return r; }
__device__ __forceinline__ uint32_t add2(uint32_t a, uint32_t b) { uint32_t r; asm("add.rn.bf16x2 %0, %1, %2;" : "=r"(r) : "r"(a), "r"(b)); return r; }
__device__ __forceinline__ float rbf(float x) { return __bfloat162float(__float2bfloat16_rn(x)); }
__device__ __forceinline__ float blo(uint32_t u) { return __uint_as_float(u << 16); }
__device__ __forceinline__ float bhi(uint32_t u) { return __uint_as_float(u & 0xffff0000u); }
__device__ __forceinline__ uint32_t gentag(uint32_t g) { return (g & 1u) | (g & 2u) << 15; }
__device__ __forceinline__ uint32_t pack2_tag(float lo, float hi, uint32_t tag) {
  const uint32_t u = __byte_perm(__float_as_uint(lo), __float_as_uint(hi), 0x7632);
  return u + ((u ^ tag) & 0x10001u);
}
__device__ __forceinline__ uint32_t xo2(uint32_t a, uint32_t b, uint32_t t) { uint32_t r; asm("lop3.b32 %0, %1, %2, %3, 0x7e;" : "=r"(r) : "r"(a), "r"(b), "r"(t)); return r; }
__device__ __forceinline__ uint32_t or3(uint32_t a, uint32_t b, uint32_t c) { uint32_t r; asm("lop3.b32 %0, %1, %2, %3, 0xfe;" : "=r"(r) : "r"(a), "r"(b), "r"(c)); return r; }
__device__ __forceinline__ void stmatrix4(uint32_t a, uint32_t r0, uint32_t r1, uint32_t r2, uint32_t r3) {
  asm volatile("stmatrix.sync.aligned.m8n8.x4.shared.b16 [%0], {%1,%2,%3,%4};" :: "r"(a), "r"(r0), "r"(r1), "r"(r2), "r"(r3) : "memory");
}
__device__ __forceinline__ void stmatrix4_t(uint32_t a, uint32_t r0, uint32_t r1, uint32_t r2, uint32_t r3) {
  asm volatile("stmatrix.sync.aligned.m8n8.x4.trans.shared.b16 [%0], {%1,%2,%3,%4};" :: "r"(a), "r"(r0), "r"(r1), "r"(r2), "r"(r3) : "memory");
}
__device__ __forceinline__ void ldmatrix4_t(uint32_t* r, uint32_t a) {
  asm volatile("ldmatrix.sync.aligned.m8n8.x4.trans.shared.b16 {%0,%1,%2,%3}, [%4];" : "=r"(r[0]), "=r"(r[1]), "=r"(r[2]), "=r"(r[3]) : "r"(a) : "memory");
}
__device__ __forceinline__ void ldmatrix4(uint32_t* r, uint32_t a) {
  asm volatile("ldmatrix.sync.aligned.m8n8.x4.shared.b16 {%0,%1,%2,%3}, [%4];" : "=r"(r[0]), "=r"(r[1]), "=r"(r[2]), "=r"(r[3]) : "r"(a) : "memory");
}
__device__ __forceinline__ void hmma16(float* c, const uint32_t* a, uint32_t b0, uint32_t b1) {
  asm volatile("mma.sync.aligned.m16n8k16.row.col.f32.bf16.bf16.f32 {%0,%1,%2,%3}, {%4,%5,%6,%7}, {%8,%9}, {%0,%1,%2,%3};"
               : "+f"(c[0]), "+f"(c[1]), "+f"(c[2]), "+f"(c[3]) : "r"(a[0]), "r"(a[1]), "r"(a[2]), "r"(a[3]), "r"(b0), "r"(b1));
}
__device__ __forceinline__ void hmma8(float* c, uint32_t a0, uint32_t a1, uint32_t b0) {
  asm volatile("mma.sync.aligned.m16n8k8.row.col.f32.bf16.bf16.f32 {%0,%1,%2,%3}, {%4,%5}, {%6}, {%0,%1,%2,%3};"
               : "+f"(c[0]), "+f"(c[1]), "+f"(c[2]), "+f"(c[3]) : "r"(a0), "r"(a1), "r"(b0));
}
__device__ __forceinline__ uint4 lds128(uint32_t a) { uint4 v; asm volatile("ld.shared.v4.u32 {%0,%1,%2,%3}, [%4];" : "=r"(v.x), "=r"(v.y), "=r"(v.z), "=r"(v.w) : "r"(a) : "memory"); return v; }
__device__ __forceinline__ void sts128(uint32_t a, uint4 v) { asm volatile("st.shared.v4.u32 [%0], {%1,%2,%3,%4};" :: "r"(a), "r"(v.x), "r"(v.y), "r"(v.z), "r"(v.w) : "memory"); }
__device__ __forceinline__ void sts128f(uint32_t a, float x, float y, float z, float w) { asm volatile("st.shared.v4.f32 [%0], {%1,%2,%3,%4};" :: "r"(a), "f"(x), "f"(y), "f"(z), "f"(w) : "memory"); }
__device__ __forceinline__ void sts64f(uint32_t a, float x, float y) { asm volatile("st.shared.v2.f32 [%0], {%1,%2};" :: "r"(a), "f"(x), "f"(y) : "memory"); }
__device__ __forceinline__ uint32_t lds32(uint32_t a) { uint32_t v; asm volatile("ld.shared.u32 %0, [%1];" : "=r"(v) : "r"(a) : "memory"); return v; }
__device__ __forceinline__ void sts32(uint32_t a, uint32_t v) { asm volatile("st.shared.u32 [%0], %1;" :: "r"(a), "r"(v) : "memory"); }

constexpr uint32_t SBASE = 1024;
__host__ __device__ constexpr uint64_t mkdesc(uint32_t off, uint32_t lbo, uint32_t sbo, uint32_t swz) {
  return (uint64_t)(((SBASE + off) & 0x3FFFF) >> 4) | ((uint64_t)(lbo >> 4) << 16) | ((uint64_t)(sbo >> 4) << 32) | ((uint64_t)swz << 62);
}
__device__ __forceinline__ void wg_fence() { asm volatile("wgmma.fence.sync.aligned;" ::: "memory"); }
__device__ __forceinline__ void wg_commit() { asm volatile("wgmma.commit_group.sync.aligned;" ::: "memory"); }
template <int N> __device__ __forceinline__ void wg_wait() { asm volatile("wgmma.wait_group.sync.aligned %0;" :: "n"(N) : "memory"); }

template <int N> __device__ __forceinline__ void reg_fence(float (&d)[N], int n = N) {
#pragma unroll
  for (int i = 0; i < N; i++) if (i < n) asm volatile("" : "+f"(d[i]) :: "memory");
}
#define F4(b) "+f"(d[b]), "+f"(d[b + 1]), "+f"(d[b + 2]), "+f"(d[b + 3])
#define F8(b) F4(b), F4(b + 4)
#define F16(b) F8(b), F8(b + 8)
#define G4(b) "=f"(d[b]), "=f"(d[b + 1]), "=f"(d[b + 2]), "=f"(d[b + 3])
#define G8(b) G4(b), G4(b + 4)
#define G16(b) G8(b), G8(b + 8)
#define RS_IN "r"(a[0]), "r"(a[1]), "r"(a[2]), "r"(a[3]), "l"(db), "n"(SD), "n"(TB)
#define SS_IN "l"(da), "l"(db), "n"(SD), "n"(TA), "n"(TB)
#define WG_OP(str, out0, out1, in) do { if (SD || KEEP) asm volatile(str : out1 : in); else asm volatile(str : out0 : in); } while (0)
#define O12(X) X##8(0), X##4(8)
#define O20(X) X##16(0), X##4(16)
#define O32(X) X##16(0), X##16(16)
template <int SD, int TB, int KEEP = 0> __device__ __forceinline__ void wgmma_rs24(float* d, const uint32_t* a, uint64_t db) {
  WG_OP("wgmma.mma_async.sync.aligned.m64n24k16.f32.bf16.bf16 {%0,%1,%2,%3,%4,%5,%6,%7,%8,%9,%10,%11}, {%12,%13,%14,%15}, %16, %17, 1, 1, %18;", O12(G), O12(F), RS_IN);
}
template <int SD, int TB, int KEEP = 0> __device__ __forceinline__ void wgmma_rs32(float* d, const uint32_t* a, uint64_t db) {
  WG_OP("wgmma.mma_async.sync.aligned.m64n32k16.f32.bf16.bf16 {%0,%1,%2,%3,%4,%5,%6,%7,%8,%9,%10,%11,%12,%13,%14,%15}, {%16,%17,%18,%19}, %20, %21, 1, 1, %22;", G16(0), F16(0), RS_IN);
}
template <int SD, int TB, int KEEP = 0> __device__ __forceinline__ void wgmma_rs40(float* d, const uint32_t* a, uint64_t db) {
  WG_OP("wgmma.mma_async.sync.aligned.m64n40k16.f32.bf16.bf16 {%0,%1,%2,%3,%4,%5,%6,%7,%8,%9,%10,%11,%12,%13,%14,%15,"
        "%16,%17,%18,%19}, {%20,%21,%22,%23}, %24, %25, 1, 1, %26;", O20(G), O20(F), RS_IN);
}
template <int SD, int TB, int KEEP = 0> __device__ __forceinline__ void wgmma_rs64(float* d, const uint32_t* a, uint64_t db) {
  WG_OP("wgmma.mma_async.sync.aligned.m64n64k16.f32.bf16.bf16 {%0,%1,%2,%3,%4,%5,%6,%7,%8,%9,%10,%11,%12,%13,%14,%15,"
        "%16,%17,%18,%19,%20,%21,%22,%23,%24,%25,%26,%27,%28,%29,%30,%31}, {%32,%33,%34,%35}, %36, %37, 1, 1, %38;", O32(G), O32(F), RS_IN);
}
template <int SD, int TA, int TB, int KEEP = 0> __device__ __forceinline__ void wgmma_ss24(float* d, uint64_t da, uint64_t db) {
  WG_OP("wgmma.mma_async.sync.aligned.m64n24k16.f32.bf16.bf16 {%0,%1,%2,%3,%4,%5,%6,%7,%8,%9,%10,%11}, %12, %13, %14, 1, 1, %15, %16;", O12(G), O12(F), SS_IN);
}
template <int SD, int TA, int TB, int KEEP = 0> __device__ __forceinline__ void wgmma_ss8(float* d, uint64_t da, uint64_t db) {
  WG_OP("wgmma.mma_async.sync.aligned.m64n8k16.f32.bf16.bf16 {%0,%1,%2,%3}, %4, %5, %6, 1, 1, %7, %8;", G4(0), F4(0), SS_IN);
}
__device__ __forceinline__ void bar_arrive(int id, int n) { asm volatile("bar.arrive %0, %1;" :: "r"(id), "r"(n) : "memory"); }
__device__ __forceinline__ uint32_t vis_bits(int pos, int t) {
  uint32_t m = 0;
#pragma unroll
  for (int i = 0; i < 8; i++) m |= (8 * (i / 2 + 1) + 2 * t + (i & 1) <= pos) ? 1u << i : 0u;
  return m;
}

__device__ __forceinline__ unsigned long long wait_words(const unsigned long long* p, uint32_t E) {
  int guard = 0; unsigned long long m;
  while (m = ld_rlxu64(p), !__all_sync(~0u, rfresh(m, E))) { __nanosleep(32); if (++guard > (1 << 22)) TRAP(); }
  fence_acq();
  return m;
}
__device__ __forceinline__ int route_step(int s, uint32_t E, int lane, unsigned long long& run) {
  const unsigned long long m = warp_max<2>(wait_words(f_h2[s][lane & 3], E));
  if (s == 0 || m > run) { run = m; return rtok(m) & 31; }
  return -1;
}

struct Params {
  const bf16 *x, *mem0, *wq, *wk, *wv, *wo, *wr, *wg, *wu, *wd;
  bf16* out;
  uint32_t zero2;
  unsigned long long zero;
};

constexpr uint32_t WSTG_STRIDE = 272;
__device__ __forceinline__ void stage_weights(uint32_t stg, const bf16* src, int ld, int tid, int nthr) {
  for (int i = tid; i < 512 * 16; i += nthr) {
    int k = i >> 4, c = i & 15;
    cp_async16(stg + k * WSTG_STRIDE + c * 16, src + (size_t)k * ld + c * 8);
  }
}
__device__ __forceinline__ void load_frags(uint32_t (*W)[4], uint32_t stg, int wg, int w, int lane) {
  uint32_t a = stg + ((lane >> 4) * 8 + (lane & 7)) * WSTG_STRIDE + (64 * wg + 16 * w + ((lane >> 3) & 1) * 8) * 2;
#pragma unroll
  for (int ks = 0; ks < 32; ks++) ldmatrix4_t(W[ks], a + ks * 16 * WSTG_STRIDE);
}

constexpr uint32_t M_H = 0;
constexpr uint32_t M_MEM = 65536;
constexpr uint32_t M_Q = M_MEM + 24576;
constexpr uint32_t M_K = M_Q + 12288;
constexpr uint32_t M_V = M_K + 12288;
constexpr uint32_t M_OM = M_V + 12288;
constexpr uint32_t M_OST = M_OM + 6144;
constexpr uint32_t M_TST = M_OST + 8192;
constexpr uint32_t M_WO = M_TST + 16384;
constexpr uint32_t M_M0 = M_WO + 49152;
constexpr uint32_t M_PT = M_M0 + 2048;
constexpr uint32_t M_BAR = M_PT + 12288;
constexpr uint32_t M_TOTAL = M_BAR + 384;
static_assert(M_TOTAL <= 232448, "main smem");
static_assert(M_WO >= 512 * WSTG_STRIDE, "staging overlaps Wo");
enum { B_LAND = 0  , B_QK = 3, B_V, B_TOK, B_OM, B_HA, B_HB, B_HAE, B_HBE, B_OST, B_OFREE, B_SYNC,
       B_STG, B_STG1, B_SS, B_TFREE, B_KFREE, B_VFREE, B_FIX  , B_NUM = B_FIX + 8 };
static_assert(B_NUM * 8 <= 256, "barriers");
constexpr uint32_t M_CAND = M_BAR + 256;
constexpr uint32_t M_BASE = M_BAR + 272;
constexpr uint32_t M_ZERO = M_BAR + 280;
constexpr uint32_t M_NEAR = M_BAR + 288;
enum { N_GO1 = 2, N_GO2, N_GO3, N_GO4, N_AG, N_W };

#define GSTAMP(slot, i)
#define TSTAMP(slot, i, k)
#define STAMP(i)
#define ASTAMP(i)
#define WSTAMP(i)
#define CSTAMP(i, v)
#define PIN(x) asm volatile("" : "+r"(x))
#define SCHED(k) asm volatile("{\n.reg .pred p;\nsetp.ne.u32 p, %0, 0;\n@p trap;\n}" :: "r"(zz & (1u << (k))) : "memory")
#define HOLD(k, v) asm volatile("{\n.reg .pred p;\nsetp.ne.u32 p, %0, 0;\n@p st.shared.u32 [%0], %1;\n}" :: "r"(zz & (1u << (k))), "r"(v) : "memory")
#define DRAIN(a) (lds32((a) + zz) & zz)
#define BAR(i) (sb + M_BAR + 8 * (i))

__device__ __forceinline__ int probe(const uint8_t* p, int n) {
  int best = 1 << 30; uint32_t v = 0;
#pragma unroll 1
  for (int r = 0; r < n; r++) {
    uint32_t t0 = clk();
    asm volatile("atom.relaxed.gpu.global.or.b32 %0, [%1], %2;" : "=r"(v) : "l"(p + 3968), "r"(v & 0u) : "memory");
    if (v == 0x7fffffffu) t0++;
    best = min(best, (int)(clk() - t0));
  }
  return best;
}
__device__ __forceinline__ void load_mem0(uint4* u, int k0, int lane, const bf16* mem0) {
#pragma unroll
  for (int i = 0; i < 2; i++) {
    const unsigned short* m = (const unsigned short*)mem0 + k0 + lane + 32 * i;
    u[i] = make_uint4(m[0] | (uint32_t)m[512] << 16, m[1024] | (uint32_t)m[1536] << 16, m[2048] | (uint32_t)m[2560] << 16, m[3072] | (uint32_t)m[3584] << 16);
  }
}

__device__ __forceinline__ void paced_h(uint32_t dst, const uint8_t* src, uint32_t o0, uint32_t o1, uint32_t piece, uint32_t bar, int gap) {
  uint32_t t = clk32();
#pragma unroll 1
  for (uint32_t o = o0; o < o1; o += piece) {
    e_mc(dst + o, src + o, piece, bar, 7);
    spin_until(t += gap);
  }
}

__device__ __forceinline__ void weight_role(const Params& p, const uint32_t sb, const int warp, const int cta, const int C, const uint32_t E,
                                            const uint8_t* const memg) {
  const int tid = fresh_tid(), lane = tid & 31;
  const int wg = warp >> 2, w = warp & 3;
  uint32_t W[32][4];
  cp_async_wait();
  bar_sync(1, 256);
  load_frags(W, sb, wg, w, lane);
  bar_sync(1, 256);
  if (tid < 128) sts128(sb + M_V + 5 * 2048 + tid * 16, make_uint4(0, 0, 0, 0));
  fence_async_smem();
  cluster_sync();
  if (tid == 0 && cta == 0) GSTAMP(0, 1);
  if (tid == 0) TSTAMP(13, cta, 0);

  const uint32_t rba = mapa(sb, C == 2 ? 0 : 2), rbc = mapa(sb, C == 1 ? 0 : 1);
  const uint32_t MYBAR = M_BAR + 8 * (C < 2 ? B_QK : B_V);
  uint32_t qoff = M_Q + C * 12288 + warp * 256 + lane * 4;
  uint32_t toff = sb + warp * 256 + (lane >> 4) * 2048 + (lane & 15) * 16;
  uint32_t rbar = mapa(sb + M_BAR, min(lane, 2));
  uint32_t sv = sb + M_MEM + lane * 32 + ((lane >> 2) & 3) * 8;
  PIN(qoff); PIN(toff); PIN(rbar); PIN(sv);
  const uint32_t gen0 = (E - 1) * (uint32_t)(NSTEP - 1);
  uint32_t fix = 0;
  const bool sig = w == 0 && lane < 3;
  const int pk = PAUSE_ + (cta < 36 ? 0 : cta < 72 ? PD1_ : 2 * PD1_) + (wg ? -PST2_ : PST2_);
  int cand = -1;
  float d[16];
#pragma unroll
  for (int i = 0; i < 16; i++) d[i] = 0.f;
  uint32_t tp[8];
#pragma unroll 1
  for (int T = -1; T < NSTEP; T++) {
    const uint32_t ph = T & 1;
    const uint64_t Z = p.zero << ph;
    const uint32_t zz = p.zero2;
    if (T >= 0) {
      WSTAMP(0);
      const uint64_t db = mkdesc(M_MEM, 128, 256, 0) + Z;
      stmatrix4(toff + M_TST + 8192, tp[0], tp[1], tp[2], tp[3]); stmatrix4(toff + M_TST + 12288, tp[4], tp[5], tp[6], tp[7]);
      if (sig) mbar_arrive_remote(rbar + 8 * B_HBE);
      mbar_wait(BAR(B_LAND), ph);
      WSTAMP(1);
      const uint32_t gt = gentag(gen0 + T);
      auto old = [&](uint32_t a) { return lds32(a) ^ gt; };
      uint32_t bad = 0;
      bool redo = false, ready = false;
      wg_fence();
      wgmma_rs24<0, 1, KP1_>(d, W[0], db);
#pragma unroll
      for (int ks = 1; ks < 32; ks++) {
        if (ks == 2 || ks == 14) bad |= xo2(lds32(sv + (ks == 2 ? 0 : 9) * 1024 + warp * 1024), lds32(sv + (ks == 2 ? 8 : 17) * 1024), gt);
        if (ks == 25) bad |= old(sv + (18 + min(warp, 5)) * 1024);
        if (ks == 6) {
          const uint32_t z5 = DRAIN(toff + M_TST);
          __syncwarp();
          if (lane == 0) mbar_arrive(BAR(B_STG) + z5);
        }
        if (ks == 27) ready = mbar_test(BAR(C < 2 ? B_KFREE : B_VFREE), ph ^ 1) & mbar_test(BAR(B_HA), ph);
        if (ks == RED_) redo = bar_or(N_W, 256, T > 0 && (bad & 0x10001u));
        if (ks == 12 || ks == 24) { mbar_wait(BAR(B_LAND + ks / 12), ph); WSTAMP(6 + ks / 12); wg_fence(); }
        wgmma_rs24<1, 1>(d, W[ks], db + ks * 48);
      }
      wg_commit();
      uint32_t a0 = rba + qoff, a1 = a0 + 128, a2 = rbc + qoff, a3 = a2 + 128, ba = rba + MYBAR, bc = rbc + MYBAR;
      PIN(a0); PIN(a1); PIN(a2); PIN(a3); PIN(ba); PIN(bc);
      if (!ready) {
        mbar_wait(BAR(C < 2 ? B_KFREE : B_VFREE), ph ^ 1);
        if (T < NSTEP - 1) mbar_wait(BAR(B_HA), ph);
      }
      wg_wait<0>(); reg_fence(d);
      if (__builtin_expect(redo, 0)) {
        auto stale = [&]() { return __any_sync(~0u, (old(sv + warp * 3072) | old(sv + warp * 3072 + 1024) | old(sv + warp * 3072 + 2048)) & 0x10001u); };
        auto fetch = [&](int r) {
          e_expect(BAR(B_FIX + warp), 3072);
          e_g2s(sb + M_MEM + warp * 3072, memg + warp * 8192 + ((uni(lds32(sb + M_NEAR + warp * 4)) ^ r) & 1) * 4096, 3072, BAR(B_FIX + warp));
        };
        bool late = stale();
        if (late) fetch(0);
        constexpr uint64_t dc = mkdesc(M_MEM, 128, 256, 0);
#pragma unroll
        for (int ks = 0; ks < 32; ks++) {
          if (ks % 12 == 0) {
            if (ks) { wg_commit(); wg_wait<0>(); reg_fence(d); }
            if (warp / 3 == ks / 12) {
              for (int guard = 0; late; guard++) {
                mbar_wait(BAR(B_FIX + warp), fix); fix ^= 1;
                late = stale();
                if (late) fetch(ALT_ ? guard + 1 : 0);
                if (guard > (1 << 20)) TRAP();
              }
            }
            bar_sync(N_W, 256);
            wg_fence();
          }
          if (ks == 0) wgmma_rs24<0, 1, 1>(d, W[0], dc); else wgmma_rs24<1, 1>(d, W[ks], dc + ks * 48);
        }
        wg_commit();
        wg_wait<0>(); reg_fence(d);
      }
      WSTAMP(2);
      if (T == 0 && tid == 0) TSTAMP(13, cta, 2);
      uint32_t lo[3], hi[3];
#pragma unroll
      for (int j = 0; j < 3; j++) { lo[j] = pack2(d[4 * j], d[4 * j + 1]); hi[j] = pack2(d[4 * j + 2], d[4 * j + 3]); }
      if (__builtin_expect(T == 0, 0)) { sts32(sb + M_M0 + tid * 8, lo[0]); sts32(sb + M_M0 + tid * 8 + 4, hi[0]); }
      if (__builtin_expect(cand >= 0, 0)) {
        if (T == LAG) { lo[1] = lds32(sb + M_M0 + tid * 8); hi[1] = lds32(sb + M_M0 + tid * 8 + 4); }
        if (C < 2) { st_async32(a0 + 5 * 2048, lo[2], ba); st_async32(a1 + 5 * 2048, hi[2], ba); }
        else { sts32(sb + qoff + 5 * 2048, lo[2]); sts32(sb + qoff + 5 * 2048 + 128, hi[2]); }
        lo[2] = lo[1]; hi[2] = hi[1];
      }
      uint32_t z5;
      if (C == 0) {
        sts32(sb + qoff, lo[0]); sts32(sb + qoff + 128, hi[0]); z5 = DRAIN(sb + qoff);
        st_async32(a0, lo[2], ba); st_async32(a1, hi[2], ba); st_async32(a2, lo[1], bc); st_async32(a3, hi[1], bc);
      } else if (C == 1) {
        sts32(sb + qoff, lo[1]); sts32(sb + qoff + 128, hi[1]); z5 = DRAIN(sb + qoff);
        st_async32(a0, lo[2], ba); st_async32(a1, hi[2], ba); st_async32(a2, lo[0], bc); st_async32(a3, hi[0], bc);
      } else {
        sts32(sb + qoff, lo[2]); sts32(sb + qoff + 128, hi[2]); z5 = DRAIN(sb + qoff);
        st_async32(a0, lo[0], ba); st_async32(a1, hi[0], ba); st_async32(a2, lo[1], bc); st_async32(a3, hi[1], bc);
      }
      __syncwarp();
      if (lane == 0) { mbar_arrive(sb + MYBAR + z5); if (w == 3) mbar_arrive(BAR(B_SS)); }
      if (T == NSTEP - 1) break;
    }
    {
      const uint64_t dh = mkdesc(M_H, 16, 1024, 1) + Z;
      static_assert(E2 == 0 && E3 > 0 && PAUSE_ > 0, "config");
      if (T + 2 < NSEG) {
        if (T < 0) mbar_wait(BAR(B_HA), ph);
        WSTAMP(3);
        wg_fence();
        wgmma_rs32<0, 0, 1>(d, W[0], dh);
#pragma unroll
        for (int ks = 1; ks < EA; ks++) {
          if (ks == E1) { wg_commit(); if (T >= 0) bar_sync(N_GO2, 384); wg_fence(); }
          wgmma_rs32<1, 0>(d, W[ks], dh + (ks >> 2) * 256 + (ks & 3) * 2);
        }
        wg_commit();
        mbar_wait(BAR(B_HB), ph);
        wg_wait<0>();
        if (sig) mbar_arrive_remote(rbar + 8 * B_HAE);
        WSTAMP(4);
        if (T >= 0) bar_sync(N_GO3, 384);
        if (wg == 1) bar_sync(N_W, 256);
        wg_fence();
#pragma unroll
        for (int ks = EA; ks < 32; ks++) wgmma_rs32<1, 0>(d, W[ks], dh + (ks >> 2) * 256 + (ks & 3) * 2);
        wg_commit();
        if (wg == 0) bar_arrive(N_W, 256);
        mbar_wait(BAR(B_TFREE), ph ^ 1);
        wg_wait<0>(); reg_fence(d);
      } else {
        bar_sync(N_GO2, 384);
        mbar_wait(BAR(B_HB), ph);
        if (sig) mbar_arrive_remote(rbar + 8 * B_HAE);
        bar_sync(N_GO3, 384);
        mbar_wait(BAR(B_TFREE), ph ^ 1);
      }
#pragma unroll
      for (int i = 0; i < 8; i++) { tp[i] = pack2(d[2 * i], d[2 * i + 1]); PIN(tp[i]); }
      auto staged = [&]() {
        const uint32_t z5 = DRAIN(toff + M_TST);
        __syncwarp();
        if (lane == 0) mbar_arrive(BAR(B_STG1) + z5);
      };
      if (T < 0 || (T + 2 >= LAG && T + 2 < NSTEP)) {
        wg_fence();
        wgmma_rs32<0, 0, 1>(d, W[0], dh + 2048);
        stmatrix4(toff + M_TST, tp[0], tp[1], tp[2], tp[3]); stmatrix4(toff + M_TST + 4096, tp[4], tp[5], tp[6], tp[7]);
#pragma unroll
        for (int ks = 1; ks < 32; ks++) {
          if (ks == 5) staged();
          if (ks >= PAUSE_ - PST2_ && ks <= PAUSE_ + 2 * PD1_ + PST2_ && (ks - PAUSE_ + PST2_) % PGR_ == 0) {
            wg_commit();
            if (T >= 0 && ks == pk) bar_sync(N_GO4, 384);
            wg_fence();
          }
          wgmma_rs32<1, 0>(d, W[ks], dh + 2048 + (ks >> 2) * 256 + (ks & 3) * 2);
        }
        wg_commit();
      } else {
        stmatrix4(toff + M_TST, tp[0], tp[1], tp[2], tp[3]); stmatrix4(toff + M_TST + 4096, tp[4], tp[5], tp[6], tp[7]);
        staged();
        bar_sync(N_GO4, 384);
      }
      if (T >= 0) cand = __shfl_sync(~0u, (int)lds32(sb + M_CAND + ((T + 1) & 3) * 4), 0);
      wg_wait<0>(); reg_fence(d);
      if (T >= 0) WSTAMP(6);
      if (T < 0 && tid == 0) TSTAMP(13, cta, 1);
#pragma unroll
      for (int i = 0; i < 8; i++) tp[i] = pack2(d[2 * i], d[2 * i + 1]);
    }
  }
  cluster_sync();
  if (tid == 0 && cta == 0) GSTAMP(0, 5);
}

__device__ __forceinline__ void attn_role(const Params& p, const uint32_t sb, const int w, const int cta, const int head, const int C, const uint32_t E,
                                          uint8_t* const part, uint8_t* const memg) {
  const int tid = fresh_tid(), lane = tid & 31;
  const int g = lane >> 2, t = lane & 3;
  uint32_t tag = ((E - 1) * (uint32_t)(NSTEP - 1)) & 1;
  uint4 m0[2][2];
  load_mem0(m0[0], w * 64, lane, p.mem0); load_mem0(m0[1], w * 64 + 256, lane, p.mem0);
  cluster_sync();
#pragma unroll
  for (int k = 0; k < 2; k++) {
#pragma unroll 1
    for (int i = 0; i < 6; i++) sts128(sb + M_MEM + (w + 4 * k) * 3072 + lane * 16 + i * 512, make_uint4(0, 0, 0, 0));
    __syncwarp();
#pragma unroll
    for (int i = 0; i < 2; i++) sts128(sb + M_MEM + ((w + 4 * k) * 4 + (lane >> 4) + 2 * i) * 768 + (lane & 15) * 16, m0[k][i]);
  }
  fence_async_smem();
  bar_sync(N_AG, 128);
  if (w == 3 && lane < 3) mbar_arrive(BAR(B_LAND + lane));
  if (lane == 0) {
    if (w == 0) TSTAMP(15, cta, 0);
    sts32(sb + M_PT + w * 4, probe(part + cta * 16384 + w * 4096, NPROBE_ / 2));
    if (w == 0) TSTAMP(15, cta, 1);
  }
  bar_sync(N_AG, 128);
  const uint32_t inear = lds32(sb + M_PT + (w >> 1) * 8 + 4) < lds32(sb + M_PT + (w >> 1) * 8);
  if (lane == 0 && !(w & 1)) st_rlx(&f_choice[cta][w >> 1], (E << 1) | inear);
  if (w == 0) TSTAMP(15, cta, 2);
  uint32_t nb;
  {
    const int i = min(lane >> 1, C < 2 ? 8 : 5);
    const int r = ((i / 3 * 3 + C) * 4 + w) * 3 + i % 3;
    int guard = 0; uint32_t cw;
    while (__any_sync(~0u, ((cw = ld_rlx(&f_choice[r][lane & 1])) >> 1) != (E & 0x7FFFFFFFu))) { if (++guard > (1 << 22)) TRAP(); }
    nb = __ballot_sync(~0u, cw & 1) >> (lane >> 4);
    if (w == 0) TSTAMP(15, cta, 3);
  }
  bar_sync(N_AG, 128);
  const uint32_t pt0 = sb + M_PT + (tid & 127) * 16;
  {
    const uint32_t po = (C * 4 + w) * 49152 + (lane >> 4) * 8192 + ((lane >> 3) & 1) * 2048 + head * 64 + (lane & 7) * 8;
    const uint8_t* in = part + (cta * 16384 + (w >> 1) * 8192 + inear * 4096 + (w & 1) * 2048 + lane * 8);
    const uint8_t* outp = memg + ((cta / 12) * 8192 + (cta % 12) * 256 + w * 64 + (lane >> 4) * 4096 + (lane & 4) * 8 + (lane & 8) * 2 + (lane & 3) * 4);
#pragma unroll
    for (int i = 0; i < 12; i++) {
      const int j = i / 4 * 3 + (i & 3);
      const uint8_t* a = (i & 3) < 3 ? part + (po + i / 4 * 589824 + (i & 3) * 16384 + ((nb >> (2 * j)) & 1) * 4096) : i == 11 ? in : outp;
      asm volatile("st.shared.u64 [%0], %1;" :: "r"(pt0 + (i >> 1) * 2048 + (i & 1) * 8), "l"(a) : "memory");
    }
  }
  const int xd = __shfl_sync(~0u, XDLY_ + (cta < 36 ? 0 : cta < 72 ? X1_ : X2_), 0);
  const uint32_t rba = mapa(sb, C == 2 ? 0 : 2), rbc = mapa(sb, C == 1 ? 0 : 1);
  uint32_t vis = vis_bits(8 + 8 * w + g, t);
  uint32_t ln = lane;
#pragma unroll
  for (int i = 0; i < SALT_; i++) ln += lds32(sb + M_ZERO);
  PIN(vis); PIN(ln);
  if (tid == 256 && C == 0) st_rlx(&f_loaded[head], E);
  uint32_t fa[8][4];
#pragma unroll
  for (int ks = 0; ks < 8; ks++) ldmatrix4_t(fa[ks], sb + M_WO + 32768 + w * 256 + (lane >> 4) * 1024 + (lane & 15) * 16 + ks * 2048);
  if (w == 0) TSTAMP(14, cta, 0);
#pragma unroll 1
  for (int T = 0; T < NSTEP; T++) {
    const uint32_t ph = T & 1;
    const uint32_t zz = uni(lds32(sb + M_ZERO));
    const bool more = T < NSTEP - 1;
    const float sc = 0.08838834764831845f * 1.4426950408889634f;
    tag ^= 1;
    float s[20];
    const uint8_t* in; int cnext = -1; uint32_t tx; bool synced;
    float x[10], tm, ts;
    uint32_t pt[5];
    auto tok_max = [&]() {
      PIN(vis);
      x[0] = s[2]; x[1] = s[3];
#pragma unroll
      for (int i = 0; i < 8; i++) x[2 + i] = (vis >> i & 1) ? s[4 * (i / 2 + 1) + 2 + (i & 1)] : -INFINITY;
      tm = fmaxf(fmaxf(fmaxf(fmaxf(x[0], x[1]), fmaxf(x[2], x[3])), fmaxf(fmaxf(x[4], x[5]), fmaxf(x[6], x[7]))), fmaxf(x[8], x[9]));
      HOLD(7, __float_as_uint(tm));
    };
    auto tok_exp1 = [&]() {
      tm = fmaxf(tm, __shfl_xor_sync(~0u, tm, 1));
      tm = fmaxf(tm, __shfl_xor_sync(~0u, tm, 2));
      const float b = -tm * sc;
#pragma unroll
      for (int i = 0; i < 10; i++) x[i] = fmaf(x[i], sc, b);
      HOLD(10, __float_as_uint(x[9]));
    };
    auto tok_exp2 = [&]() {
#pragma unroll
      for (int i = 0; i < 10; i++) x[i] = ex2(x[i]);
      ts = (((x[0] + x[1]) + (x[2] + x[3])) + ((x[4] + x[5]) + (x[6] + x[7]))) + (x[8] + x[9]);
#pragma unroll
      for (int k = 0; k < 5; k++) pt[k] = pack2(x[2 * k], x[2 * k + 1]);
      HOLD(8, __float_as_uint(ts));
    };
    {
      uint32_t q[8][4];
      auto load_q = [&](uint32_t a, int h) {
#pragma unroll
        for (int k2 = 0; k2 < 4; k2++) {
          uint32_t r[4];
          ldmatrix4_t(r, a + k2 * 512);
          q[2 * k2][h] = r[0]; q[2 * k2][h + 2] = r[1]; q[2 * k2 + 1][h] = r[2]; q[2 * k2 + 1][h + 2] = r[3];
        }
      };
      PIN(ln);
      const uint32_t qa = sb + M_Q + ln * 16;
      const int cand = C == 2 ? (int)uni(lds32(sb + M_CAND + (T & 3) * 4)) : -1;
      mbar_wait(BAR(B_TOK), ph);
      load_q(qa + (1 + w) * 2048, 1);
      mbar_wait(BAR(B_QK), ph);
      ASTAMP(0);
      if (T == 0 && w == 0) TSTAMP(13, cta, 3);
      if (__builtin_expect(cand >= 0, 0)) {
        mbar_wait(BAR(B_V), ph);
        PIN(ln);
        const int e = w * 32 + ln;
#pragma unroll
        for (int i = 0; i < 3; i++) {
          const uint32_t v = lds32(sb + M_Q + i * 12288 + 5 * 2048 + e * 16 + 4);
          asm volatile("st.shared.u16 [%0], %1;" :: "r"(sb + M_Q + i * 12288 + (1 + (cand >> 3)) * 2048 + e * 16 + (cand & 7) * 2), "h"((unsigned short)v) : "memory");
        }
        fence_async_smem();
        bar_sync(N_AG, 128);
        load_q(qa + (1 + w) * 2048, 1);
      }
      load_q(qa, 0);
      if (!(NOF_ & 1)) fence_async_smem();
      constexpr uint64_t dk = mkdesc(M_K, 128, 2048, 0);
      wg_fence();
      wgmma_rs40<0, 1>(s, q[0], dk);
#pragma unroll
      for (int ks = 1; ks < 8; ks++) wgmma_rs40<1, 1>(s, q[ks], dk + ks * 16);
      wg_commit();
    }
    if (more) {
      uint32_t v[5][4];
      PIN(ln);
      const uint32_t va = sb + M_V + w * 512 + ((ln >> 3) & 1) * 128 + (ln >> 4) * 2048 + (ln & 7) * 16;
      const uint32_t ooff = M_OM + w * 1536 + C * 256 + ln * 4;
      mbar_wait(BAR(B_V), ph);
      wg_wait<0>(); reg_fence(s);
      if (ln < 3) mbar_arrive_remote(mapa(BAR(B_KFREE), ln));
      ldmatrix4(v[0], va); ldmatrix4(v[1], va + 256); ldmatrix4(v[2], va + 4096); ldmatrix4(v[3], va + 4096 + 256);
      ldmatrix4(v[4], sb + M_V + 8192 + w * 512 + ln * 16);
      ASTAMP(1);
      float m = fmaxf(fmaxf(fmaxf(fmaxf(s[0], s[1]), fmaxf(s[4], s[5])), fmaxf(fmaxf(s[8], s[9]), fmaxf(s[12], s[13]))), fmaxf(s[16], s[17]));
      m = fmaxf(m, __shfl_xor_sync(~0u, m, 1));
      m = fmaxf(m, __shfl_xor_sync(~0u, m, 2));
      const float b = -m * sc;
      uint32_t pm[5];
#pragma unroll
      for (int j = 0; j < 5; j++) pm[j] = pack2(ex2(fmaf(s[4 * j], sc, b)), ex2(fmaf(s[4 * j + 1], sc, b)));
      float o0[4] = {0.f, 0.f, 0.f, 0.f}, o1[4] = {0.f, 0.f, 0.f, 0.f}, l[4] = {0.f, 0.f, 0.f, 0.f};
      const uint32_t one[4] = {0x3f803f80u, 0x3f803f80u, 0x3f803f80u, 0x3f803f80u};
      hmma16(l, one, pm[0], pm[1]); hmma16(o0, v[0], pm[0], pm[1]); hmma16(o1, v[1], pm[0], pm[1]);
      hmma16(l, one, pm[2], pm[3]); hmma16(o0, v[2], pm[2], pm[3]); hmma16(o1, v[3], pm[2], pm[3]);
      hmma8(l, one[0], one[1], pm[4]); hmma8(o0, v[4][0], v[4][1], pm[4]); hmma8(o1, v[4][2], v[4][3], pm[4]);
      const float r0 = rcp(l[0]), r1 = rcp(l[1]);
      const uint32_t u0 = pack2(o0[0] * r0, o0[1] * r1), u1 = pack2(o0[2] * r0, o0[3] * r1), u2 = pack2(o1[0] * r0, o1[1] * r1), u3 = pack2(o1[2] * r0, o1[3] * r1);
      constexpr uint32_t OB = M_BAR + 8 * B_OM;
      const uint32_t a0 = rba + ooff, a1 = rbc + ooff;
      st_async32(a0, u0, rba + OB); st_async32(a1, u0, rbc + OB);
      st_async32(a0 + 128, u1, rba + OB); st_async32(a1 + 128, u1, rbc + OB);
      st_async32(a0 + 768, u2, rba + OB); st_async32(a1 + 768, u2, rbc + OB);
      st_async32(a0 + 896, u3, rba + OB); st_async32(a1 + 896, u3, rbc + OB);
      bar_arrive(N_GO2, 384);
      sts32(sb + ooff, u0); sts32(sb + ooff + 128, u1); sts32(sb + ooff + 768, u2); sts32(sb + ooff + 896, u3);
      ASTAMP(2);
      uint32_t fb[8][4];
      const uint32_t wa = sb + M_WO + 16384 + w * 256 + (ln >> 4) * 1024 + (ln & 15) * 16 + zz;
      ldmatrix4_t(fb[0], wa);
      SCHED(3);
#pragma unroll
      for (int ks = 1; ks < 8; ks++) {
        ldmatrix4_t(fb[ks], wa + ks * 2048);
        if (ks == ARR_) { __syncwarp(); if (ln == 0) mbar_arrive(BAR(B_OM) + (fb[0][0] & zz)); }
      }
      if (C == 2) cnext = (int)uni(lds32(sb + M_CAND + ((T + 1) & 3) * 4));
      {
        float d[12], e[12];
        constexpr uint64_t ob = mkdesc(M_OM, 128, 256, 0);
        uint8_t* q[3][3];
        auto addr = [&](int i) {
          asm volatile("ld.shared.v2.u64 {%0,%1}, [%2];" : "=l"(q[i][0]), "=l"(q[i][1]) : "r"(pt0 + i * 4096) : "memory");
          if (i < 2) asm volatile("ld.shared.u64 %0, [%1];" : "=l"(q[i][2]) : "r"(pt0 + i * 4096 + 2048) : "memory");
          else asm volatile("ld.shared.v2.u64 {%0,%1}, [%2];" : "=l"(q[i][2]), "=l"(in) : "r"(pt0 + i * 4096 + 2048) : "memory");
        };
        auto put = [&](const float* d, int i) {
          st_rlx64(q[i][0], (pack2(d[0], d[1]) & ~1u) | tag, pack2(d[2], d[3]));
          st_rlx64(q[i][1], (pack2(d[4], d[5]) & ~1u) | tag, pack2(d[6], d[7]));
          st_rlx64(q[i][2], (pack2(d[8], d[9]) & ~1u) | tag, pack2(d[10], d[11]));
        };
        addr(0); addr(1);
        SCHED(6);
        tok_max();
        ASTAMP(3);
        mbar_wait(BAR(B_OM), ph);
        if (!(NOF_ & 2)) fence_async_smem();
        ASTAMP(4);
        constexpr uint64_t w0 = mkdesc(M_WO, 1024, 128, 0);
        float (&f)[12] = d;
        wg_fence();
        wgmma_ss24<0, 1, 1>(d, w0, ob);
#pragma unroll
        for (int ks = 1; ks < 8; ks++) wgmma_ss24<1, 1, 1>(d, w0 + ks * 128, ob + ks * 48);
        wg_commit();
        wgmma_rs24<0, 1>(e, fb[0], ob);
#pragma unroll
        for (int ks = 1; ks < HAND_; ks++) wgmma_rs24<1, 1>(e, fb[ks], ob + ks * 48);
        wg_commit();
        wg_wait<1>(); reg_fence(d);
        put(d, 0);
        addr(2);
        SCHED(4);
        ASTAMP(5);
        wg_fence();
#pragma unroll
        for (int ks = HAND_; ks < 8; ks++) wgmma_rs24<1, 1>(e, fb[ks], ob + ks * 48);
        wg_commit();
        wgmma_rs24<0, 1, 1>(f, fa[0], ob);
#pragma unroll
        for (int ks = 1; ks < HAND_; ks++) wgmma_rs24<1, 1>(f, fa[ks], ob + ks * 48);
        wg_commit();
        wg_wait<1>(); reg_fence(e);
        put(e, 1);
        SCHED(5);
        wg_fence();
#pragma unroll
        for (int ks = HAND_; ks < 8; ks++) wgmma_rs24<1, 1>(f, fa[ks], ob + ks * 48);
        wg_commit();
        if (GO3_ == 0) bar_arrive(N_GO3, 384);
        synced = __all_sync(~0u, mbar_test(BAR(B_SYNC), ph));
        tx = uni(lds32(sb + M_BASE + ph * 4)) + xd;
        wg_wait<0>(); reg_fence(f);
        if (GO3_ == 1) bar_arrive(N_GO3, 384);
        if (C < 2) put(f, 2);
        if (GO3_ == 2) bar_arrive(N_GO3, 384);
        ASTAMP(6);
        if (T == 0 && w == 0) TSTAMP(14, cta, 1);
      }
    } else {
      mbar_wait(BAR(B_V), ph);
      wg_wait<0>(); reg_fence(s);
      tok_max();
    }
    uint2 v[8];
#pragma unroll
    for (int i = 0; i < 8; i++) v[i] = make_uint2(zz, zz);
    auto poll = [&](uint2* v) {
      v[0] = ld_rlx64<0>(in); v[1] = ld_rlx64<256>(in); v[2] = ld_rlx64<512>(in); v[3] = ld_rlx64<768>(in);
      v[4] = ld_rlx64<1024>(in); v[5] = ld_rlx64<1280>(in); v[6] = ld_rlx64<1536>(in); v[7] = ld_rlx64<1792>(in);
    };
    uint8_t* outp;
    asm volatile("ld.shared.u64 %0, [%1];" : "=l"(outp) : "r"(pt0 + 2048 + 8) : "memory");
    const uint32_t itag = gentag((E - 1) * (uint32_t)(NSTEP - 1) + T + 1);
    const bool sum = more && cnext < 0;
    if (more) {
      if (!synced) { mbar_wait(BAR(B_SYNC), ph); tx = uni(lds32(sb + M_BASE + ph * 4)) + xd; }
      ASTAMP(7);
      if (__builtin_expect(cnext >= 0, 0)) {
        const unsigned long long* hp = (const unsigned long long*)&g_hc[T + 1 - LAG][0] + ((cta / 3) * 8 + 2 * w + ((ln >> 2) & 1));
        unsigned long long v0; int guard = 0;
        while (v0 = ld_rlxu64(hp), !__all_sync(~0u, (uint32_t)(v0 >> 32) == E)) { if (++guard > (1 << 22)) TRAP(); }
        st_rlx((uint32_t*)outp, (ln & 3) == 1 ? ((uint32_t)v0 >> ((ln & 8) * 2)) & 0xffffu : (ln & 1) ? 0u : itag);
      } else {
        spin_until(tx);
        ASTAMP(8);
        poll(v);
      }
    }
    auto late = [&](const uint2* v) {
      return __any_sync(~0u, (or3(xo2(v[0].x, v[1].x, tag), xo2(v[2].x, v[3].x, tag), xo2(v[4].x, v[5].x, tag)) | xo2(v[6].x, v[7].x, tag)) & 1u);
    };
    tok_exp1(); tok_exp2();
    auto reduce = [&]() {
      if (sum) {
        ASTAMP(9);
        int guard = 0;
        while (late(v)) {
          if (++guard > (1 << 22)) TRAP();
          poll(v);
        }
#pragma unroll
        for (int i = 0; i < 4; i++) { v[i].x = add2(v[i].x, v[i + 4].x); v[i].y = add2(v[i].y, v[i + 4].y); }
        const bool hi = ln & 8;
        const uint32_t x0 = add2(v[0].x, v[1].x), x1 = add2(v[2].x, v[3].x), y0 = add2(v[0].y, v[1].y), y1 = add2(v[2].y, v[3].y);
        const uint32_t m0 = hi ? y0 : x0, m1 = hi ? y1 : x1;
        const uint32_t n0 = __shfl_xor_sync(~0u, hi ? x0 : y0, 8), n1 = __shfl_xor_sync(~0u, hi ? x1 : y1, 8);
        float k0 = (blo(m0) + blo(m1)) + (blo(n0) + blo(n1)), k1 = (bhi(m0) + bhi(m1)) + (bhi(n0) + bhi(n1));
        k0 += __shfl_xor_sync(~0u, k0, 16); k1 += __shfl_xor_sync(~0u, k1, 16);
        st_rlx((uint32_t*)outp, (ln & 1) ? pack2(k0, k1) : pack2_tag(k0, k1, itag));
        ASTAMP(10);
        if (T == 0 && w == 0) TSTAMP(14, cta, 2);
        CSTAMP(12 + w, (clk() & ~15u) | min(guard + 1, 15));
      }
      if (more) bar_arrive(N_GO4, 384);
    };
    if (PVR_ < 0) reduce();
    {
      PIN(ln);
      const uint32_t oa = sb + M_OST + w * 128 + (ln >> 3) * 512 + (ln & 7) * 16;
      const uint32_t a[3][4] = {{0, pt[0], 0, pt[1]}, {0, pt[2], 0, pt[3]}, {0, pt[4], 0, 0}};
      constexpr uint64_t dv = mkdesc(M_V, 2048, 128, 0);
#pragma unroll 1
      for (int h = 0; h < 2; h++) {
        float o[32];
        const uint64_t dh = dv + (uint64_t)(h * 64);
        wg_fence();
        wgmma_rs64<0, 0>(o, a[0], dh); wgmma_rs64<1, 0>(o, a[1], dh + 256); wgmma_rs64<1, 0>(o, a[2], dh + 512);
        wg_commit();
        if (h == PVR_) reduce();
        if (h == 0) {
          ts += __shfl_xor_sync(~0u, ts, 1);
          ts += __shfl_xor_sync(~0u, ts, 2);
          ts = rcp(ts);
          mbar_wait(BAR(B_OFREE), ph ^ 1);
        }
        wg_wait<0>(); reg_fence(o);
        if (h == 1 && ln < 3) mbar_arrive_remote(mapa(BAR(B_VFREE), ln));
#define OT(i) pack2(o[4 * (i) + 2] * ts, o[4 * (i) + 3] * ts)
        stmatrix4(oa + h * 4096, OT(0), OT(1), OT(2), OT(3));
        stmatrix4(oa + h * 4096 + 2048, OT(4), OT(5), OT(6), OT(7));
      }
      const uint32_t z5 = DRAIN(oa);
      __syncwarp();
      if (ln == 0) mbar_arrive(BAR(B_OST) + z5);
      ASTAMP(11);
    }
  }
}

__global__ void __cluster_dims__(3, 1, 1) __launch_bounds__(512, 1) main_kernel(Params p) {
  extern __shared__ __align__(1024) uint8_t sm[];
  const uint32_t sb = smem_u32(sm);
  if ((sb & 0xFFFFFFu) != SBASE) TRAP();
  asm volatile("griddepcontrol.launch_dependents;");
  const int warp = __shfl_sync(~0u, threadIdx.x >> 5, 0);
  const int cta = blockIdx.x, head = cta / 3, c = cta % 3;
  const uint32_t E = __shfl_sync(~0u, *(volatile uint32_t*)&g_epoch + 1, 0);
  uint8_t* const part = (uint8_t*)(((uintptr_t)g_xch + 8191) & ~(uintptr_t)8191);
  uint8_t* const memg = part + 96 * 16384;

  if (threadIdx.x == 0 && cta == 0) GSTAMP(0, 0);
  if (threadIdx.x < B_NUM) {
    const int i = threadIdx.x;
    const uint32_t cnt = i == B_STG || i == B_STG1 ? 8 : i == B_OST ? 4 : i == B_HAE || i == B_HBE ? 6 : i == B_KFREE || i == B_VFREE ? 12 : i == B_SS ? 2 : i == B_OM ? 5 :
                         i == B_QK ? (c < 2 ? 9 : 1) : i == B_V ? (c < 2 ? 1 : 9) : 1;
    mbar_init(BAR(i), cnt);
    if (i == B_HA || i == B_HB || i == B_STG || i == B_HAE || i == B_HBE || i == B_TFREE)
      asm volatile("mbarrier.arrive.shared::cta.b64 _, [%0], %1;" :: "r"(BAR(i)), "r"(cnt) : "memory");
    asm volatile("fence.mbarrier_init.release.cluster;" ::: "memory");
  }
  if (warp < 8) {
    const int tid = threadIdx.x;
    uint4 wa[6], wb[6];
#pragma unroll
    for (int i = 0; i < 6; i++) {
      const int mi = i >> 1, e = (tid >> 2) + (i & 1) * 64;
      const uint4* src = (const uint4*)(p.wo + (size_t)(head * 128 + e) * 512 + min(3 * mi + c, 7) * 64 + (tid & 3) * 16);
      wa[i] = __ldg(src); wb[i] = __ldg(src + 1);
    }
    stage_weights(sb, (c == 0 ? p.wq : c == 1 ? p.wk : p.wv) + head * 128, 4096, tid, 256);
#pragma unroll
    for (int i = 0; i < 6; i++) {
      const int mi = i >> 1, e = (tid >> 2) + (i & 1) * 64;
      const uint4 a = wa[i], b = wb[i];
      const uint32_t dst = sb + M_WO + mi * 16384 + (e >> 3) * 1024 + (tid & 3) * 256 + (e & 7) * 16;
      sts128(dst, make_uint4(__byte_perm(a.x, a.y, 0x5410), __byte_perm(a.z, a.w, 0x5410), __byte_perm(b.x, b.y, 0x5410), __byte_perm(b.z, b.w, 0x5410)));
      sts128(dst + 128, make_uint4(__byte_perm(a.x, a.y, 0x7632), __byte_perm(a.z, a.w, 0x7632), __byte_perm(b.x, b.y, 0x7632), __byte_perm(b.z, b.w, 0x7632)));
    }
  } else {
    const int i0 = threadIdx.x - 256;
    const uint32_t tag0 = ((E - 1) * (uint32_t)(NSTEP - 1)) & 1;
    for (int i = i0; i < 1024; i += 256) *(uint4*)(part + cta * 16384 + i * 16) = make_uint4(tag0, 0, tag0, 0);
    if (i0 < 16) *(uint32_t*)(memg + i0 * 4096 + 3968) = 0;
    if (i0 < 2) st_rlx(&f_choice[cta][i0], 0);
    if (i0 < 8) st_rlx64(&g_sync[i0 >> 2][cta][i0 & 3], 0, 0);
    __threadfence();
    if (i0 < 12) sts32(sb + M_ZERO + i0 * 4, 0);
    if (i0 < 2) { sts32(sb + M_BASE + i0 * 4, clk32() - 65536); sts32(sb + M_CAND + i0 * 4, (uint32_t)-1); }
  }

  if (warp < 8) {
    asm volatile("setmaxnreg.inc.sync.aligned.u32 " STR(RW_) ";");
    weight_role(p, sb, warp, cta, c, E, memg);
  } else if (warp < 12) {
    if (RA_ < 128) asm volatile("setmaxnreg.dec.sync.aligned.u32 " STR(RA_) ";");
    if (RA_ > 128) asm volatile("setmaxnreg.inc.sync.aligned.u32 " STR(RA_) ";");
    attn_role(p, sb, warp - 8, cta, head, c, E, part, memg);
    cluster_sync();
  } else {
    asm volatile("setmaxnreg.dec.sync.aligned.u32 " STR(RC_) ";");
    const int tid = fresh_tid(), lane = tid & 31;
    const int w = warp - 12;
    cluster_sync();
    if (w != 2) {
      const int tl = min(3 * min(w, 2) + c, 7);
      int near = 0;
      if (lane == 0) { const int t0 = probe(memg + tl * 8192, NPROBE_ / 2); near = probe(memg + tl * 8192 + 4096, NPROBE_ / 2) < t0; }
      near = uni(near);
      if (lane < 3) asm volatile("st.shared::cluster.u32 [%0], %1;" :: "r"(mapa(sb + M_NEAR + tl * 4, lane)), "r"(near) : "memory");
      __syncwarp();
    }
    if (w == 0) {
      uint32_t s0 = c * 8192, s1 = (3 + c) * 8192, s2 = min(6 + c, 7) * 8192;
#pragma unroll 1
      for (int T = 0; T < NSTEP - 1; T++) {
        const uint32_t ph = T & 1;
        mbar_wait(BAR(B_SS), ph);
        const uint32_t cq = clk();
        const uint32_t g0 = (uint32_t)gtime64(); uint32_t g1, ce;
        do { g1 = (uint32_t)gtime64(); ce = clk(); } while (g1 == g0);
        const uint32_t tn = g1 * 8 - (((ce - cq) * 37u) >> 3), id = E * 128u + T;
        if (lane < 4) st_rlx64(&g_sync[ph][cta][lane], tn, id);
        if (lane < 3) mbar_expect(BAR(B_LAND + lane), lane < 2 ? 9216 : 6144);
        if (T == 0) { s0 += uni(lds32(sb + M_NEAR + c * 4)) * 4096; s1 += uni(lds32(sb + M_NEAR + (3 + c) * 4)) * 4096; s2 += uni(lds32(sb + M_NEAR + min(6 + c, 7) * 4)) * 4096; }
        wait_until(cq + SDLY_);
        int guard = 0; unsigned long long v0, v1, v2;
        for (;;) {
          v0 = ld_rlxu64(g_sync[ph][lane]); v1 = ld_rlxu64(g_sync[ph][lane + 32]); v2 = ld_rlxu64(g_sync[ph][lane + 64]);
          if (__all_sync(~0u, (uint32_t)(v0 >> 32) == id && (uint32_t)(v1 >> 32) == id && (uint32_t)(v2 >> 32) == id)) break;
          if (++guard > (1 << 22)) TRAP();
        }
        const int dl = __reduce_max_sync(~0u, max(max((int)((uint32_t)v0 - tn), (int)((uint32_t)v1 - tn)), (int)((uint32_t)v2 - tn)));
        const uint32_t base = uni(cq + ((min(dl, 8 * 4096) * 7) >> 5)) + (T == 0 ? SLOW0_ : T == 1 ? SLOW1_ : 0) +
                              ((int)uni(lds32(sb + M_CAND + (T & 3) * 4)) >= 0 ? CDLY_ : 0) - (T + 2 < NSEG ? 0 : BOFF_);
        if (lane == 0) { sts32(sb + M_BASE + ph * 4, base); mbar_arrive(BAR(B_SYNC)); }
        CSTAMP(0, base); CSTAMP(1, clk());
        const uint32_t ts = base + YDLY_ - (T + 2 >= LAG && T + 2 < NSEG ? 0 : YOFF_);
        uint32_t nr = 0;
        if (PRIV_) nr = __ballot_sync(~0u, lds32(sb + M_NEAR + (lane & 7) * 4) != 0);
        wait_until(ts);
        if (PRIV_ & 1) { for (int k = 0; k < 3; k++) e_g2s(sb + M_MEM + k * 3072, memg + k * 8192 + ((nr >> k) & 1) * 4096, 3072, BAR(B_LAND)); }
        else e_mc(sb + M_MEM + c * 3072, memg + s0, 3072, BAR(B_LAND), 7);
        CSTAMP(2, clk());
        spin_until(ts + Y1_);
        if (PRIV_ & 2) { for (int k = 3; k < 6; k++) e_g2s(sb + M_MEM + k * 3072, memg + k * 8192 + ((nr >> k) & 1) * 4096, 3072, BAR(B_LAND + 1)); }
        else e_mc(sb + M_MEM + (3 + c) * 3072, memg + s1, 3072, BAR(B_LAND + 1), 7);
        CSTAMP(3, clk());
        spin_until(ts + Y2_);
        if (PRIV_ & 4) { for (int k = 6; k < 8; k++) e_g2s(sb + M_MEM + k * 3072, memg + k * 8192 + ((nr >> k) & 1) * 4096, 3072, BAR(B_LAND + 2)); }
        else if (c < 2) e_mc(sb + M_MEM + (6 + c) * 3072, memg + s2, 3072, BAR(B_LAND + 2), 7);
        CSTAMP(4, clk());
      }
    } else if (w == 1) {
#pragma unroll 1
      for (int T = 0; T < NSTEP; T++) {
        const uint32_t ph = T & 1;
        const int s = c == 0 ? T : T - LAG;
        const bool act = s >= 0 && s < NSEG;
        mbar_wait(BAR(B_OST), ph);
        if (cta == 0) TSTAMP(2, T, 0);
        fence_async_smem();
        if (T < NSTEP - 1) wait_until(uni(lds32(sb + M_BASE + ph * 4)) + ODLY_);
        STAMP(22);
        if (act) { e_s2g(g_o[c][s % ORING][head], sb + M_OST, XO_); bulk_wait(); __syncwarp(); }
        e_arrive(BAR(B_OFREE));
        if (cta == 0) TSTAMP(2, T, 1);
        if (act && lane < 8) st_rel(&f_o[T][head >> 2][c * 4 + (head & 3)][lane], E);
        __syncwarp();
        if (cta == 0) TSTAMP(2, T, 2);
      }
    } else if (w == 2) {
      unsigned long long run = 0;
      static_assert(LAG >= 2, "config");
      constexpr uint32_t NA = EA / 4 * 4096;
      e_expect(BAR(B_QK), c < 2 ? 2048 : 4096); e_expect(BAR(B_V), c == 0 ? 10240 : c == 1 ? 2048 : 0);
      e_expect(BAR(B_TOK), c == 0 ? 16384 : 0); e_expect(BAR(B_OM), 4096);
      e_expect(BAR(B_HA), NA); e_expect(BAR(B_HB), 65536 - NA);
      wait_eq(&f_h1[c == 1 ? 0 : 1], E); fence_async_glob();
      {
        const uint32_t o0 = c == 0 ? NA : 0, o1 = c == 2 ? NA : 32768;
        e_mc(sb + M_H + (c == 1 ? 32768 : 0) + o0, g_h[0][c == 1 ? 0 : 1] + o0, o1 - o0, BAR(c == 2 ? B_HA : B_HB), 7);
      }
      TSTAMP(14, cta, 3);
      if (c == 2) wait_eq(&f_h1[2], E);
      mbar_wait(BAR(B_HAE), 1);
      e_expect(BAR(B_HA), NA);
      if (c == 2) { fence_async_glob(); e_mc(sb + M_H, g_h[0][2], NA, BAR(B_HA), 7); }
      int cprev = -1;
#pragma unroll 1
      for (int T = 0; T < NSTEP - 1; T++) {
        const int s1 = T + 2, s2 = T + 2 - LAG;
        const uint32_t ph = T & 1;
        const bool l1 = s1 < NSEG, l2 = s2 >= 0 && s2 < NSEG, la = s1 + 1 < NSEG;
        const bool mine = c == 0 ? l1 : c == 1 ? l2 : la;
        const uint32_t* fl = c != 1 ? &f_h1[min(s1 + (c >> 1), NSEG - 1)] : (const uint32_t*)f_h2[max(s2, 0)][lane & 3] + 1;
        const uint32_t want = E & 0x1FFFFFu, sh = c != 1 ? 0 : 11;
        mbar_wait(BAR(B_HBE), ph ^ 1);
        const bool early = __all_sync(~0u, ((ld_acq(fl) >> sh) & 0x1FFFFFu) == want);
        mbar_wait(BAR(B_LAND + 2), ph);
        STAMP(16);
        e_expect(BAR(B_HB), (l1 ? 32768 - NA : 0) + (l2 ? 32768 : 0));
        if (mine) {
          if (!early) {
            int guard = 0;
            while (!__all_sync(~0u, ((ld_acq(fl) >> sh) & 0x1FFFFFu) == want)) { __nanosleep(32); if (++guard > (1 << 22)) TRAP(); }
          }
          fence_async_glob();
          if (c == 1) { mbar_wait(BAR(B_QK), ph); spin_until(clk32() + HDLY_); }
          if (c < 2) paced_h(sb + M_H + c * 32768, g_h[c][c ? s2 : s1], c ? 0 : NA, 32768, 4096, BAR(B_HB), HGAP_);
        }
        int cd = -1;
        if (l2) { cd = route_step(s2, E, lane, run); if (cta == 0) TSTAMP(5, s2, 0); }
        if (lane == 0) sts32(sb + M_CAND + ((T + 2) & 3) * 4, (uint32_t)cd);
        __syncwarp();
        STAMP(17);
        mbar_wait(BAR(B_HAE), ph);
        e_expect(BAR(B_HA), la ? NA : 0);
        if (c == 2 && la) {
          spin_until(clk32() + ADLY_);
          STAMP(18);
          paced_h(sb + M_H, g_h[0][s1 + 1], 0, NA, 4096, BAR(B_HA), AGAP_);
        }
        mbar_wait(BAR(B_OST), ph);
        e_expect(BAR(B_QK), c < 2 ? 2048 : cprev >= 0 ? 8192 : 4096);
        e_expect(BAR(B_V), c < 2 ? 10240 : 8192);
        e_expect(BAR(B_TOK), 16384);
        e_expect(BAR(B_OM), 4096);
        cprev = cd;
      }
    } else {
      const uint32_t mytok = sb + M_Q + c * 12288 + 2048, tb = BAR(c < 2 ? B_TOK : B_V);
      mbar_wait(BAR(B_STG1), 0);
      fence_async_smem();
      e_s2g(g_tok[cta][1], sb + M_TST, 8192);
#pragma unroll 1
      for (int T = 0; T < NSTEP - 1; T++) {
        const uint32_t ph = T & 1;
        uint8_t* const tok = g_tok[cta][ph ^ 1];
        mbar_wait(BAR(B_STG), ph ^ 1);
        fence_async_smem();
        if (cta == 0 && (T == 0 || T == NSEG || T == NSTEP - 2)) GSTAMP(0, T == 0 ? 2 : T == NSEG ? 3 : 4);
        if (T > 0 && TQ_) mbar_wait(BAR(B_QK), ph);
        STAMP(20);
        uint32_t t = clk32();
        e_s2g(tok + 8192, sb + M_TST + 8192, XT2_);
        spin_until(t + TGAP_);
        e_s2g(tok + 12288, sb + M_TST + 12288, XT2_);
        bulk_wait();
        __syncwarp();
        e_arrive(BAR(B_TFREE));
        if (T == 0) e_mc(mytok, tok + 8192, 8192, tb, 1);
        STAMP(21);
#pragma unroll 1
        for (int k = 0; k < 2; k++) {
          if (k == 1) {
            mbar_wait(BAR(B_STG1), ph ^ 1);
            fence_async_smem();
            t = uni(lds32(sb + M_BASE + ph * 4));
            wait_until(t + TDLY_);
            e_s2g(g_tok[cta][ph], sb + M_TST, XT1_);
          }
          if (k == (c >> 1)) {
            mbar_wait(BAR(c < 2 ? B_KFREE : B_VFREE), ph);
            t = k ? t + LDLY_ : clk32() + KDLY_;
            wait_until(t);
            STAMP(23);
            e_mc(mytok, tok, 8192, tb, 1);
            spin_until(t + LGAP_);
            e_mc(mytok, tok + 8192, 8192, tb, 6);
            STAMP(24);
          }
        }
      }
      bulk_wait();
    }
    __syncwarp();
    cluster_sync();
  }
}

constexpr uint32_t A_RING = 0;
constexpr int A_NST = 6;
constexpr uint32_t A_STG = A_RING + A_NST * 8192;
constexpr uint32_t A_WD = A_STG + 8192;
constexpr uint32_t A_WG = A_WD + 57344;
constexpr uint32_t A_WU = A_WG + 57344;
constexpr uint32_t A_XN = A_WU + 57344;
constexpr uint32_t A_BAR = A_XN + 2048;
constexpr uint32_t A_TOTAL = A_BAR + 256;
static_assert(A_TOTAL <= 232448, "aux smem");

__device__ __forceinline__ uint32_t ptag(int s) { return ((s / PRING) & 1) ^ 1; }
static_assert((NSEG / PRING) % 2 == 0, "tags");
__device__ __forceinline__ void load_row(uint32_t* v, const void* row, int lane) {
  const uint4 a = __ldcg((const uint4*)row + lane), b = __ldcg((const uint4*)row + 32 + lane);
  v[0] = a.x; v[1] = a.y; v[2] = a.z; v[3] = a.w; v[4] = b.x; v[5] = b.y; v[6] = b.z; v[7] = b.w;
}
__device__ __forceinline__ void store_row(void* row, const uint32_t* v, int lane) {
  ((uint4*)row)[lane] = make_uint4(v[0], v[1], v[2], v[3]); ((uint4*)row)[32 + lane] = make_uint4(v[4], v[5], v[6], v[7]);
}
__device__ __forceinline__ void store_img(uint8_t* img, int r, const uint32_t* v, int lane) {
  uint8_t* b = img + (lane >> 3) * 4096 + (r >> 3) * 1024 + (r & 7) * 128 + (((lane ^ r) & 7) << 4);
  *(uint4*)b = make_uint4(v[0], v[1], v[2], v[3]);
  *(uint4*)(b + 16384) = make_uint4(v[4], v[5], v[6], v[7]);
}
template <int NT> __device__ __forceinline__ void ln_rows(const uint32_t (*v)[8], uint32_t (*y)[8]) {
  float c[NT], sm[NT], sq[NT];
#pragma unroll
  for (int k = 0; k < NT; k++) {
    c[k] = blo(__shfl_sync(~0u, v[k][0], 0));
    float s0 = 0.f, s1 = 0.f, q0 = 0.f, q1 = 0.f;
#pragma unroll
    for (int i = 0; i < 8; i++) { const float a = blo(v[k][i]) - c[k], b = bhi(v[k][i]) - c[k]; s0 += a; s1 += b; q0 = fmaf(a, a, q0); q1 = fmaf(b, b, q1); }
    sm[k] = s0 + s1; sq[k] = q0 + q1;
  }
#pragma unroll
  for (int o = 16; o > 0; o >>= 1)
#pragma unroll
    for (int k = 0; k < NT; k++) {
      sm[k] += __shfl_xor_sync(~0u, sm[k], o); sq[k] += __shfl_xor_sync(~0u, sq[k], o);
    }
#pragma unroll
  for (int k = 0; k < NT; k++) {
    const float dm = sm[k] * (1.f / 512.f), var = fmaxf(fmaf(-dm, dm, sq[k] * (1.f / 512.f)), 0.f);
    const float mb = rbf(c[k] + dm), inv = rcp(rbf(sqrt_fast(rbf(rbf(var) + 1e-5f))));
#pragma unroll
    for (int i = 0; i < 8; i++) { const uint32_t a = pack2(blo(v[k][i]) - mb, bhi(v[k][i]) - mb); y[k][i] = pack2(blo(a) * inv, bhi(a) * inv); }
  }
}
__device__ __forceinline__ void input_ln_pair(const bf16* x, int s, int pr, int lane) {
  uint32_t v[2][8], y[2][8];
  load_row(v[0], x + (size_t)(s * 32 + 2 * pr) * 512, lane); load_row(v[1], x + (size_t)(s * 32 + 2 * pr + 1) * 512, lane);
  ln_rows<2>(v, y);
  store_img(g_h[0][s], 2 * pr, y[0], lane); store_img(g_h[0][s], 2 * pr + 1, y[1], lane);
}
__device__ __forceinline__ float load_wr(uint32_t* wv, const bf16* wr, int lane) {
  load_row(wv, wr, lane);
  float wsum = 0.f;
#pragma unroll
  for (int i = 0; i < 8; i++) wsum += blo(wv[i]) + bhi(wv[i]);
#pragma unroll
  for (int o = 16; o > 0; o >>= 1) wsum += __shfl_xor_sync(~0u, wsum, o);
  return wsum;
}

template <bool FAST>
__device__ __forceinline__ unsigned long long token_post(int st, int tk, const bf16* res, bf16* dst, bf16* req, unsigned long long best,
                                                         const uint32_t* wv, float wsum, uint32_t E, int lane) {
  const int s = tk >> 5;
  uint32_t x[8];
  load_row(x, res, lane);
  wait_all(f_acc[st][s][lane], E, false);
  if (tk == s * 32 && st == 0 && lane == 0) TSTAMP(4, s, 0);
  {
    const uint8_t* pp = g_pp[st][s % PRING] + (lane >> 4) * 8192 + (tk & 31) * 256 + (((lane & 15) ^ (tk & 7)) << 4);
    const uint32_t tag = ptag(s);
    uint4 q[8][2];
#define PLD(k, h) q[k][h] = ld_rlx128<(k) * 32768 + (h) * 16384>(pp)
#define PLD8(h) PLD(0, h); PLD(1, h); PLD(2, h); PLD(3, h); PLD(4, h); PLD(5, h); PLD(6, h); PLD(7, h)
#define PBAD(h) __any_sync(~0u, (or3(xo2(q[0][h].x, q[1][h].x, tag), xo2(q[2][h].x, q[3][h].x, tag), xo2(q[4][h].x, q[5][h].x, tag)) | xo2(q[6][h].x, q[7][h].x, tag)) & ~lane & (PST_ == 8192 ? 1u : 0u))
#define PSUM(f, h, m) (((f(q[0][h].m) + f(q[1][h].m)) + (f(q[2][h].m) + f(q[3][h].m))) + ((f(q[4][h].m) + f(q[5][h].m)) + (f(q[6][h].m) + f(q[7][h].m))))
    const uint32_t eye = (lane >> 2) == 2 * (lane & 3) ? 0x3f80u : (lane >> 2) == 2 * (lane & 3) + 1 ? 0x3f800000u : 0u;
    auto padd = [&](int h) {
      if (FAST) {
        float u[4] = {0.f, 0.f, 0.f, 0.f}, v[4] = {0.f, 0.f, 0.f, 0.f};
#pragma unroll
        for (int k = 0; k < 8; k++) { hmma8(u, q[k][h].x, q[k][h].y, eye); hmma8(v, q[k][h].z, q[k][h].w, eye); }
        x[4 * h] = add2(x[4 * h], pack2(u[0], u[1])); x[4 * h + 1] = add2(x[4 * h + 1], pack2(u[2], u[3]));
        x[4 * h + 2] = add2(x[4 * h + 2], pack2(v[0], v[1])); x[4 * h + 3] = add2(x[4 * h + 3], pack2(v[2], v[3]));
      } else {
        x[4 * h] = add2(x[4 * h], pack2(PSUM(blo, h, x), PSUM(bhi, h, x))); x[4 * h + 1] = add2(x[4 * h + 1], pack2(PSUM(blo, h, y), PSUM(bhi, h, y)));
        x[4 * h + 2] = add2(x[4 * h + 2], pack2(PSUM(blo, h, z), PSUM(bhi, h, z))); x[4 * h + 3] = add2(x[4 * h + 3], pack2(PSUM(blo, h, w), PSUM(bhi, h, w)));
      }
    };
    int guard = 0;
    PLD8(0);
    if (FAST) { PLD8(1); }
    while (PBAD(0)) { if (++guard > (1 << 20)) TRAP(); PLD8(0); }
    padd(0);
    if (!FAST) { PLD8(1); }
    while (PBAD(1)) { if (++guard > (1 << 20)) TRAP(); PLD8(1); }
    padd(1);
  }
  const float c = blo(__shfl_sync(~0u, x[0], 0));
  float s0 = 0.f, s1 = 0.f, q0 = 0.f, q1 = 0.f, r0 = 0.f, r1 = 0.f;
#pragma unroll
  for (int i = 0; i < 8; i++) {
    const float a = blo(x[i]) - c, b = bhi(x[i]) - c;
    s0 += a; s1 += b; q0 = fmaf(a, a, q0); q1 = fmaf(b, b, q1); r0 = fmaf(a, blo(wv[i]), r0); r1 = fmaf(b, bhi(wv[i]), r1);
  }
  s0 += s1; q0 += q1; r0 += r1;
#pragma unroll
  for (int o = 16; o > 0; o >>= 1) { s0 += __shfl_xor_sync(~0u, s0, o); q0 += __shfl_xor_sync(~0u, q0, o); r0 += __shfl_xor_sync(~0u, r0, o); }
  const float dm = s0 * (1.f / 512.f), m = c + dm, var = fmaxf(fmaf(-dm, dm, q0 * (1.f / 512.f)), 0.f);
  const float mb = rbf(m), inv = rcp(rbf(sqrt_fast(rbf(rbf(var) + 1e-5f))));
  const uint32_t nmb = pack2(-mb, -mb);
  const unsigned long long wd = rword(E, tk, fmaf(c - mb, wsum, r0) * inv);
  uint32_t xn[8], x2[8];
#pragma unroll
  for (int i = 0; i < 8; i++) { const uint32_t d = add2(x[i], nmb); xn[i] = pack2(blo(d) * inv, bhi(d) * inv); x2[i] = add2(x[i], xn[i]); }
  if (st == 0) {
    const float mb2 = rbf(fmaf(m - mb, inv, m)), inv2 = rcp(rbf(sqrt_fast(rbf(rbf(var * (1.f + inv) * (1.f + inv)) + 1e-5f))));
    const uint32_t nmb2 = pack2(-mb2, -mb2);
    uint32_t h[8];
#pragma unroll
    for (int i = 0; i < 8; i++) { const uint32_t d2 = add2(x2[i], nmb2); h[i] = pack2(blo(d2) * inv2, bhi(d2) * inv2); }
    store_img(g_h[1][s], tk & 31, h, lane);
  }
  store_row(dst, x2, lane);
  if (wd > best && !(EXPQ_ & (st == 0 ? 1 : 2))) { store_row(req, xn, lane); store_row(req + 512, x, lane); }
  return wd;
}

__device__ __forceinline__ void ffn_slice(uint32_t sb, const bf16* xn, float* yacc, uint32_t* flag, uint32_t E, int t, bool urgent) {
  const int w = t >> 5, g = (t >> 2) & 7;
  if (t == 0 && urgent) sts32(sb + A_BAR + 160, 1);
  { const uint2 u = __ldcg((const uint2*)xn + t); asm volatile("st.shared.v2.u32 [%0], {%1,%2};" :: "r"(sb + A_XN + t * 8), "r"(u.x), "r"(u.y) : "memory"); }
  fence_async_smem();
  bar_sync(4, 128);
  float ga[4], ua[4];
  constexpr uint64_t da = mkdesc(A_WG, 896, 128, 0), db = mkdesc(A_XN, 16, 128, 0);
  wg_fence();
  wgmma_ss8<0, 1, 0>(ga, da, db); wgmma_ss8<0, 1, 0>(ua, da + (A_WU - A_WG) / 16, db);
#pragma unroll
  for (int ks = 1; ks < 32; ks++) { wgmma_ss8<1, 1, 0>(ga, da + ks * 112, db + ks * 2); wgmma_ss8<1, 1, 0>(ua, da + (A_WU - A_WG) / 16 + ks * 112, db + ks * 2); }
  wg_commit(); wg_wait<0>(); reg_fence(ga); reg_fence(ua);
  if ((t & 3) == 0) {
#pragma unroll
    for (int h = 0; h < 2; h++) {
      const float gs = rbf(ga[2 * h]), us = rbf(ua[2 * h]);
      const float v = 16 * w + 8 * h < 56 ? rbf(gs * rcp(1.f + __expf(-gs))) * us : 0.f;
      asm volatile("st.shared.u16 [%0], %1;" :: "r"(sb + A_XN + 1280 + (16 * w + 8 * h + g) * 2), "h"((unsigned short)pack2(v, 0.f)) : "memory");
    }
  }
  fence_async_smem();
  bar_sync(4, 128);
#pragma unroll 1
  for (int j = 0; j < 2; j++) {
    float y[4][4];
    const uint64_t dd = mkdesc(A_WD, 8192, 128, 0) + (uint64_t)(j * 256);
    wg_fence();
#pragma unroll
    for (int m = 0; m < 4; m++) {
      wgmma_ss8<0, 1, 0>(y[m], dd + m * 64, mkdesc(A_XN + 1280, 16, 128, 0));
#pragma unroll
      for (int ks = 1; ks < 4; ks++) wgmma_ss8<1, 1, 0>(y[m], dd + m * 64 + ks * 1024, mkdesc(A_XN + 1280 + ks * 32, 16, 128, 0));
    }
    wg_commit(); wg_wait<0>();
#pragma unroll
    for (int m = 0; m < 4; m++) {
      reg_fence(y[m]);
      if ((t & 3) == 0) { float* o = yacc + j * 256 + m * 64 + 16 * w + g; atomicAdd(o, y[m][0]); atomicAdd(o + 8, y[m][2]); }
    }
  }
  bar_sync(4, 128);
  if (t < 8) { sts32(sb + A_BAR + 160, 0); st_rel(flag + t, E); }
  __syncwarp();
}

__device__ __forceinline__ void ffn_finish(int q, const bf16* req, float r, uint32_t E, int lane, uint32_t* v) {
  uint32_t xn[8];
  load_row(xn, req, lane); load_row(v, req + 512, lane);
  const float rs = rbf(1.f / (1.f + __expf(-rbf(r))));
  wait_all(f_y[q][lane], E);
  float4 y[4];
#pragma unroll
  for (int i = 0; i < 4; i++) y[i] = __ldcg((const float4*)g_y[q] + (i >> 1) * 64 + 2 * lane + (i & 1));
#pragma unroll
  for (int i = 0; i < 4; i++) {
    v[2 * i] = add2(v[2 * i], add2(xn[2 * i], pack2(rbf(y[i].x) * rs, rbf(y[i].y) * rs)));
    v[2 * i + 1] = add2(v[2 * i + 1], add2(xn[2 * i + 1], pack2(rbf(y[i].z) * rs, rbf(y[i].w) * rs)));
  }
}
__global__ void __launch_bounds__(512, 1) aux_kernel(Params p) {
  extern __shared__ __align__(1024) uint8_t sm[];
  const uint32_t sb = smem_u32(sm);
  if ((sb & 0xFFFFFFu) != SBASE) TRAP();
  const int warp = __shfl_sync(~0u, threadIdx.x >> 5, 0);
  const int cta = blockIdx.x;
  const uint32_t E = __shfl_sync(~0u, *(volatile uint32_t*)&g_epoch + 1, 0);
  const uint32_t bars = sb + A_BAR;

  if (cta < 32) {
    const int cg = cta & 3, kg = cta >> 2;
    if (threadIdx.x == 0) {
      for (int i = 0; i < A_NST; i++) { mbar_init(bars + 8 * i, 1); mbar_init(bars + 64 + 8 * i, 2); }
      mbar_init(bars + 128, 8); mbar_init(bars + 136, 8); mbar_init(bars + 144, 1);
      sts32(bars + 160, 0);
      asm volatile("fence.mbarrier_init.release.cluster;" ::: "memory");
    }
    if (warp < 8) {
      asm volatile("setmaxnreg.inc.sync.aligned.u32 176;");
      const int tid = fresh_tid(), lane = tid & 31;
      uint32_t W[32][4];
      stage_weights(sb + A_WD, p.wo + (size_t)kg * 512 * 512 + cg * 128, 512, tid, 256);
      cp_async_wait();
      bar_sync(1, 256);
      load_frags(W, sb + A_WD, warp >> 2, warp & 3, lane);
      bar_sync(2, 512);
      const uint32_t so = sb + A_STG + ((lane >> 4) * 8 + (lane & 7)) * 256 + (((warp * 2 + ((lane >> 3) & 1)) ^ (lane & 7)) << 4);
      const uint32_t tm = lane < 4 ? 0x00010001u : 0u;
      int stage = 0; uint32_t ph = 0, job = 0;
#pragma unroll 1
      for (int T = 0; T < NSTEP; T++) {
#pragma unroll 1
        for (int k = 0; k < 3; k++) {
          const int st = k == 0 ? 0 : 3 - k, s = st == 0 ? T : T - LAG;
          if (s < 0 || s >= NSEG) continue;
          float d[16];
#pragma unroll
          for (int hh = 0; hh < 4; hh++) {
            mbar_wait(bars + 8 * stage, ph);
            while (uni(lds32(bars + 160))) __nanosleep(100);
            const uint64_t db = mkdesc(A_RING, 512, 128, 0) + (uint64_t)(stage * 512);
            wg_fence();
            if (hh == 0) wgmma_rs32<0, 0>(d, W[0], db); else wgmma_rs32<1, 0>(d, W[hh * 8], db);
#pragma unroll
            for (int ks = 1; ks < 8; ks++) wgmma_rs32<1, 0>(d, W[hh * 8 + ks], db + ks * 64);
            wg_commit();
            if (hh > 0) { wg_wait<1>(); if ((tid & 127) == 0) mbar_arrive(bars + 64 + 8 * (stage == 0 ? A_NST - 1 : stage - 1)); }
            if (++stage == A_NST) { stage = 0; ph ^= 1; }
          }
          mbar_wait(bars + 144, (job & 1) ^ 1);
          wg_wait<0>(); reg_fence(d);
          if ((tid & 127) == 0) mbar_arrive(bars + 64 + 8 * (stage == 0 ? A_NST - 1 : stage - 1));
          if (cta == 0 && tid == 0) TSTAMP(6, T, k);
          const uint32_t tv = tm * ptag(s);
#define TG(i) ((pack2(d[2 * (i)], d[2 * (i) + 1]) & ~tm) | tv)
          stmatrix4_t(so, TG(0), pack2(d[2], d[3]), TG(2), pack2(d[6], d[7]));
          stmatrix4_t(so + 4096, TG(4), pack2(d[10], d[11]), TG(6), pack2(d[14], d[15]));
          fence_async_smem();
          __syncwarp();
          if (lane == 0) mbar_arrive(bars + 128 + 8 * (job & 1));
          job++;
        }
      }
    } else if (warp < 12) {
      asm volatile("setmaxnreg.dec.sync.aligned.u32 120;");
      const int tid = fresh_tid(), lane = tid & 31;
      const int w = warp - 8, t = tid - 256;
#pragma unroll 1
      for (int s = cta + 4; s < NSEG; s += 32) {
#pragma unroll 1
        for (int pr = w; pr < 16; pr += 4) input_ln_pair(p.x, s, pr, lane);
        bar_sync(4, 128);
        if (t == 0) st_rel(&f_h1[s], E);
      }
      bar_sync(2, 512);
      { int guard = 0; while (ld_rlx(&f_loaded[cta]) != E) { __nanosleep(200); if (++guard > (1 << 22)) TRAP(); } }
#pragma unroll 1
      for (int i = t; i < 512 * 7; i += 128) {
        const int k = i / 7, pc = i % 7;
        cp_async16(sb + A_WG + (k >> 3) * 896 + pc * 128 + (k & 7) * 16, p.wg + (size_t)k * 1792 + cta * 56 + pc * 8);
        cp_async16(sb + A_WU + (k >> 3) * 896 + pc * 128 + (k & 7) * 16, p.wu + (size_t)k * 1792 + cta * 56 + pc * 8);
        cp_async16(sb + A_WD + (i >> 9) * 8192 + (i & 63) * 128 + ((i >> 6) & 7) * 16, p.wd + (size_t)cta * 56 * 512 + i * 8);
      }
      uint32_t wv[8];
      const float wsum = load_wr(wv, p.wr, lane);
      cp_async_wait();
      fence_async_smem();
      wait_all(&f_zero[lane], E);
      bar_sync(4, 128);
      const int tj = (cta * 4 + w) & 31, st = 1 + ((cta >> 3) & 1), sq = cta >> 4;
      unsigned long long run = 0, run2 = 0, best = 0, hist = 0;
      uint32_t open = 0;
#pragma unroll 1
      for (int i = 0; i <= NSTEP; i++) {
        int tok = -1; const bf16* req = nullptr;
        if (i < NSEG) {
          const int cd = (int)uni(route_step(i, E, lane, run));
          run = __shfl_sync(~0u, run, 0);
          hist = hist << 8 | (uint32_t)(cd + 1);
          if (cd >= 0) { tok = rtok(run); req = g_req1[tok][0]; }
        } else {
          const unsigned long long m = wait_words(f_l2[i - NSEG], E);
          if (m != run2) { run2 = m; tok = rtok(m); req = g_req2[(tok >> 5) < (rtok(run) >> 5) ? 0 : 1][tok][0]; }
        }
        tok = __shfl_sync(~0u, tok, 0);
        if (tok >= 0) {
          if (cta == 0 && t == 0) TSTAMP(8, i, 0);
          ffn_slice(sb, req, g_y[i], f_y[i][cta], E, t, i < NSEG);
          if (cta == 0 && t == 0) TSTAMP(8, i, 1);
        }
        const int s = i - LAG;
        if (s < 0 || i >= NSEG) continue;
        const int cd = (int)((hist >> (8 * LAG)) & 255) - 1;
        if (cd >= 0 && st == 2) best = 0;
        const int ts = rtok(run) >> 5;
        if ((s & 1) == sq) {
          const int tk = s * 32 + tj;
          unsigned long long wd = (unsigned long long)E << 43;
          if (st == 1 ? s < ts || i < NSEG - 1 : s >= ts) {
            if (st == 2 && cd == tj) wait_eq(&f_hc[s], E);
            wd = token_post<false>(st, tk, st == 2 && cd == tj ? g_x2c[s] : g_x2 + (size_t)tk * 512,
                                   (st == 2 || s < ts ? p.out : g_n) + (size_t)tk * 512, g_req2[st - 1][tk][0], best, wv, wsum, E, lane);
            best = max(best, wd);
            if (st == 1 && s >= ts) open |= 1u << (s >> 1);
          }
          __syncwarp();
          if (lane < 4) st_rel64(&f_w2[st - 1][s][tj][lane], wd);
          __syncwarp();
        }
        if (st == 1) {
          if (i == NSEG - 1 && t == 0 && cta == 0) GSTAMP(1, 0);
#pragma unroll 1
          for (int n = i == NSEG - 1 ? 32 : 2; n > 0 && open; n--) {
            const int s0 = 2 * (__ffs(open) - 1) + sq;
            if (s0 >= ts) break;
            open &= open - 1;
            uint32_t v[8];
            load_row(v, g_n + (size_t)(s0 * 32 + tj) * 512, lane);
            wait_words(f_w2[1][s0][tj], E);
            store_row(p.out + (size_t)(s0 * 32 + tj) * 512, v, lane);
          }
          if (i == NSEG - 1) {
            __syncwarp();
            if (lane == 0) st_rel(&f_cp[sq * 32 + tj], E);
            if (t == 0 && cta == 0) GSTAMP(1, 3);
          }
        }
      }
    } else {
      asm volatile("setmaxnreg.dec.sync.aligned.u32 40;");
      const int tid = fresh_tid(), lane = tid & 31;
      const int t = tid - 384, w = warp - 12;
      for (int i = cta * 128 + t; i < (NSTEP + 1) * 128; i += 4096) ((float4*)&g_y[0][0])[i] = make_float4(0.f, 0.f, 0.f, 0.f);
      bar_sync(3, 128);
      if (t == 0) st_rel(&f_zero[cta], E);
      bar_sync(2, 512);
      if (w == 0) {
        int stage = 0; uint32_t ph = 1;
#pragma unroll 1
        for (int T = 0; T < NSTEP; T++) {
#pragma unroll 1
          for (int k = 0; k < 3; k++) {
            const int st = k == 0 ? 0 : 3 - k, s = st == 0 ? T : T - LAG;
            if (s < 0 || s >= NSEG) continue;
            const uint32_t* fl = f_o[T][kg][st * 4 + (lane & 3)];
            uint32_t ready = 0; int guard = 0;
#pragma unroll 1
            for (int hh = 0; hh < 4; hh++) {
              while (!((ready >> hh) & 1)) {
                ready = __ballot_sync(~0u, ld_rlx(fl) == E);
                if (++guard > (1 << 23)) TRAP();
              }
              fence_async_glob();
              mbar_wait(bars + 64 + 8 * stage, ph);
              e_expect(bars + 8 * stage, OLOAD_);
              e_g2s(sb + A_RING + stage * 8192, g_o[st][s % ORING][kg * 4 + hh], OLOAD_, bars + 8 * stage);
              if (++stage == A_NST) { stage = 0; ph ^= 1; }
            }
          }
          if (cta == 0 && lane == 0) TSTAMP(3, T, 0);
        }
      } else if (w < 3) {
        uint32_t job = 0;
#pragma unroll 1
        for (int T = 0; T < NSTEP; T++) {
#pragma unroll 1
          for (int k = 0; k < 3; k++) {
            const int st = k == 0 ? 0 : 3 - k, s = st == 0 ? T : T - LAG;
            if (s < 0 || s >= NSEG) continue;
            if ((job++ & 1) != w - 1) continue;
            if (s >= PRING) wait_words(st == 0 ? f_h2[s - PRING][lane & 3] : f_w2[st - 1][s - PRING][lane], E);
            mbar_wait(bars + 128 + 8 * (w - 1), ((job - 1) >> 1) & 1);
            if (cta == 0 && st == 0) TSTAMP(7, s, 0);
            e_s2g(g_pp[st][s % PRING] + cta * 8192, sb + A_STG, PST_);
            asm volatile("cp.async.bulk.commit_group;\n cp.async.bulk.wait_group.read 0;" ::: "memory");
            __syncwarp();
            e_arrive(bars + 144);
            if (!HINT_) bulk_wait();
            __syncwarp();
            if (lane < 8) st_rlx(&f_acc[st][s][cta][lane], E);
            __syncwarp();
            if (cta == 0 && st == 0) TSTAMP(7, s, 1);
          }
        }
        bulk_wait();
      }
    }
  } else {
    const int tid = fresh_tid(), lane = tid & 31;
    const int qd = cta - 32;
    input_ln_pair(p.x, qd, warp, lane);
    bar_sync(6, 512);
    if (tid == 0) st_rel(&f_h1[qd], E);
    volatile int* bc = (volatile int*)sm;
    if (warp == 15) {
      unsigned long long run = 0;
      wait_all(&f_zero[lane], E);
      unsigned long long b2[2][2] = {{0, 0}, {0, 0}};
      auto track = [&](int s) {
#pragma unroll
        for (int k = 0; k < 2; k++) {
          const unsigned long long m = warp_max<16>(wait_words(f_w2[k][s][lane], E));
          if (lane == (s & 31)) { if (s < 32) b2[k][0] = m; else b2[k][1] = m; }
        }
      };
#pragma unroll 1
      for (int s = 0; s < NSEG; s++) {
        const int cd = route_step(s, E, lane, run);
        if (cd >= 0 && qd == (s & 1)) {
          uint32_t v[1][8], h[1][8];
          ffn_finish(s, g_req1[s * 32 + cd][0], rscore(run), E, lane, v[0]);
          if (lane == 0) TSTAMP(8, s, 2);
          ln_rows<1>(v, h);
#pragma unroll
          for (int i = 0; i < 8; i++) st_rlx64(&g_hc[s][(i >> 2) * 128 + 4 * lane + (i & 3)], h[0][i], E);
          if (lane == 0) TSTAMP(8, s, 3);
          store_row(g_x2c[s], v[0], lane);
          __syncwarp();
          if (lane == 0) st_rel(&f_hc[s], E);
        }
        if (qd == 2 && s > LAG) track(s - LAG - 1);
      }
      wait_eq(&f_hc[rtok(run) >> 5], E);
      if (lane == 0) *bc = rtok(run);
      bar_sync(7, 288);
      if (qd == 2) {
        uint32_t v[8];
        const int ts = rtok(run) >> 5;
        track(NSEG - LAG - 1);
        run = 0;
#pragma unroll 1
        for (int k = 0; k <= LAG; k++) {
          const int s = NSEG - LAG - 1 + k;
          const unsigned long long m = warp_max<16>(k == 0 ? max(lane < ts ? b2[0][0] : b2[1][0], lane + 32 < ts ? b2[0][1] : b2[1][1])
                                                           : wait_words(f_w2[s < ts ? 0 : 1][s][lane], E));
          const bool lead = m > run;
          if (lead) { run = m; __threadfence(); }
          if (lane < 4) st_rlx64(&f_l2[k][lane], (uint32_t)run, (uint32_t)(run >> 32));
          if (lead) ffn_finish(NSEG + k, g_req2[(rtok(run) >> 5) < ts ? 0 : 1][rtok(run)][0], rscore(run), E, lane, v);
          if (k == 0) { wait_all(&f_cp[lane], E); wait_all(&f_cp[32 + lane], E); }
        }
        if (lane == 0) GSTAMP(1, 1);
        store_row(p.out + (size_t)rtok(run) * 512, v, lane);
        if (lane == 0) GSTAMP(1, 2);
        asm volatile("griddepcontrol.wait;" ::: "memory");
        if (lane == 0) *(volatile uint32_t*)&g_epoch = E;
      }
    } else if (warp < 8) {
      uint32_t wv[8];
      const float wsum = load_wr(wv, p.wr, lane);
      unsigned long long best = 0;
      int ttok = 0;
#pragma unroll 1
      for (int i = 0; i < NSTEP; i++) {
        const bool last = i >= NSEG;
        if (i == NSEG) { bar_sync(7, 288); ttok = *bc; best = 0; }
        const int s = last ? i - LAG : i, st = !last ? 0 : s < (ttok >> 5) ? 1 : 2;
        const int tk = s * 32 + qd * 8 + warp;
        const unsigned long long wd = token_post<true>(st, tk, !last ? p.x + (size_t)tk * 512 : tk == ttok ? g_x2c[s] : g_x2 + (size_t)tk * 512,
                                                 (last ? p.out : g_x2) + (size_t)tk * 512, last ? g_req2[st - 1][tk][0] : g_req1[tk][0], best, wv, wsum, E, lane);
        best = max(best, wd);
        volatile unsigned long long* ws = (volatile unsigned long long*)(sm + 64) + (i & 1) * 8;
        if (lane == 0) ws[warp] = wd;
        bar_sync(5, 256);
        if (warp == 0) {
          if (qd == 0 && lane == 0) TSTAMP(4, i, 1);
          if (!last) { const unsigned long long m = warp_max<4>(ws[lane & 7]); if (lane < 4) st_rel64(&f_h2[s][qd][lane], m); }
          else {
            st_rel64(&f_w2[st - 1][s][qd * 8 + (lane >> 2)][lane & 3], ws[lane >> 2]);
            asm volatile("st.relaxed.gpu.global.u64 [%0], %1;" :: "l"(&f_w2[2 - st][s][qd * 8 + (lane >> 2)][lane & 3]), "l"((unsigned long long)E << 43) : "memory");
          }
          if (qd == 0 && lane == 0) TSTAMP(4, i, 2);
        }
        __syncwarp();
      }
    }
  }
}

}

extern "C" void kernel_launch(void* const* d_in, const int* in_sizes, int n_in, void* d_out, int out_size) {
  (void)in_sizes; (void)n_in; (void)out_size;
  static bool init = false;
  if (!init) {
    cudaFuncSetAttribute(main_kernel, cudaFuncAttributeMaxDynamicSharedMemorySize, M_TOTAL);
    cudaFuncSetAttribute(aux_kernel, cudaFuncAttributeMaxDynamicSharedMemorySize, A_TOTAL);
    init = true;
  }
  Params p;
  p.x = (const bf16*)d_in[0]; p.mem0 = (const bf16*)d_in[1]; p.wq = (const bf16*)d_in[2]; p.wk = (const bf16*)d_in[3];
  p.wv = (const bf16*)d_in[4]; p.wo = (const bf16*)d_in[5]; p.wr = (const bf16*)d_in[8]; p.wg = (const bf16*)d_in[9];
  p.wu = (const bf16*)d_in[10]; p.wd = (const bf16*)d_in[11]; p.out = (bf16*)d_out; p.zero = 0; p.zero2 = 0;
  cudaStream_t st = cudaStreamPerThread;
  main_kernel<<<96, 512, M_TOTAL, st>>>(p);
  cudaLaunchConfig_t cfg = {};
  cfg.gridDim = dim3(36); cfg.blockDim = dim3(512); cfg.dynamicSmemBytes = A_TOTAL; cfg.stream = st;
  cudaLaunchAttribute at[1];
  at[0].id = cudaLaunchAttributeProgrammaticStreamSerialization; at[0].val.programmaticStreamSerializationAllowed = 1;
  cfg.attrs = at; cfg.numAttrs = 1;
  cudaLaunchKernelEx(&cfg, aux_kernel, p);
}
```

```cpp
#include <cuda_runtime.h>
#include <cuda_bf16.h>
#include <stdint.h>

namespace {

typedef __nv_bfloat16 bf16;

constexpr int NSEG = 64;
#define LAG_ 5
constexpr int LAG = LAG_;
constexpr int NSTEP = NSEG + LAG;
constexpr int ORING = 8, PRING = 4;
#define E1_ 10
#define E2_ 0
#define E3_ 10
constexpr int E1 = E1_, E2 = E2_, E3 = E3_, EA = E1 + E2 + E3;
static_assert(EA % 4 == 0 && EA > 0 && EA < 32 && E1 > 0, "early part: whole 64-column chunks");
#define RW_ 176
#define RA_ 136
#define RC_ 24
#define STR2(x) #x
#define STR(x) STR2(x)
#define RED_ 30
#define ARR_ 7
#define PAUSE_ 19
#define PD1_ 4
#define PST2_ 2
#define PGR_ PD1_
#define PVR_ -1
#define SALT_ 0
#define KP1_ 1
#define PRIV_ 1
#define OLOAD_ 8192
#define PST_ 8192
#define ALT_ 1
#define TQ_ 1
#define NOF_ 2
#define EXPQ_ 0
#define XT1_ 8192
#define XT2_ 4096
#define XO_ 8192
#define HINT_ 1
#define HADD_ 2
#define HAND_ 4
#define GO3_ 2
#define NPROBE_ 6
#define TP(i, v) (v)
#define XDLY_ TP(0, 2250)
#define YDLY_ TP(1, 3400)
#define X1_ TP(2, 100)
#define X2_ TP(3, 250)
#define Y1_ TP(4, 150)
#define Y2_ TP(5, 200)
#define HGAP_ TP(6, 50)
#define TGAP_ TP(7, 200)
#define ADLY_ TP(8, 600)
#define ODLY_ TP(9, 2800)
#define LDLY_ TP(10, 3800)
#define LGAP_ 200
#define HDLY_ TP(11, 0)
#define TDLY_ TP(15, 4050)
#define SDLY_ TP(12, 800)
#define AGAP_ 100
#define BOFF_ TP(13, 200)
#define YOFF_ TP(16, 150)
#define YUP_ TP(20, 40)
#define YDN_ TP(21, 4)
#define CDLY_ TP(17, 300)
#define SLOW0_ TP(18, 400)
#define SLOW1_ TP(19, 300)
#define KDLY_ TP(14, 300)
__device__ uint32_t g_epoch;
__device__ __align__(1024) uint8_t g_h[2][NSEG][32768];
__device__ __align__(128) uint2 g_hc[NSEG][256];
__device__ __align__(128) bf16 g_x2[2048 * 512];
__device__ __align__(128) bf16 g_x2c[NSEG][512];
__device__ __align__(128) uint8_t g_o[3][ORING][32][8192];
__device__ __align__(128) uint8_t g_pp[3][PRING][8 * 32768];
__device__ __align__(128) bf16 g_n[2048 * 512];
__device__ __align__(128) uint8_t g_xch[96 * 16384 + 65536 + 8192];
__device__ __align__(128) bf16 g_req1[2048][2][512];
__device__ __align__(128) bf16 g_req2[2][2048][2][512];
__device__ __align__(128) float g_y[NSTEP + 1][512];
__device__ __align__(128) uint8_t g_tok[96][2][16384];
__device__ uint32_t f_choice[96][2], f_loaded[32];
__device__ uint32_t f_h1[NSEG], f_hc[NSEG];
__device__ __align__(128) unsigned long long f_h2[NSEG][4][4];
__device__ __align__(128) unsigned long long f_w2[2][NSEG][32][4];
__device__ __align__(128) unsigned long long f_l2[LAG + 1][4];
__device__ __align__(128) uint32_t f_o[NSTEP][8][12][8];
__device__ __align__(128) uint32_t f_acc[3][NSEG][32][8], f_y[NSTEP + 1][32][8], f_zero[32], f_cp[64];
__device__ __align__(128) unsigned long long g_sync[2][96][4];

#define TRAP() __trap()
__device__ __forceinline__ uint32_t smem_u32(const void* p) { return (uint32_t)__cvta_generic_to_shared(p); }
__device__ __forceinline__ int fresh_tid() { const int t = threadIdx.x; return __shfl_sync(~0u, t, t & 31); }
__device__ __forceinline__ unsigned long long gtime64() { unsigned long long t; asm volatile("mov.u64 %0, %%globaltimer;" : "=l"(t) :: "memory"); return t; }
__device__ __forceinline__ uint32_t clk() { unsigned long long c; asm volatile("mov.u64 %0, %%clock64;" : "=l"(c) :: "memory"); return (uint32_t)c; }
__device__ __forceinline__ void wait_until(uint32_t t) {
  while ((int)(t - clk()) > 450) __nanosleep(32);
  uint32_t c;
  do { asm volatile("mov.u32 %0, %%clock;" : "=r"(c) :: "memory"); } while ((int)(c - t) < 0);
}
__device__ __forceinline__ void mbar_init(uint32_t bar, uint32_t cnt) { asm volatile("mbarrier.init.shared::cta.b64 [%0], %1;" :: "r"(bar), "r"(cnt) : "memory"); }
__device__ __forceinline__ void mbar_arrive(uint32_t bar) { asm volatile("mbarrier.arrive.shared::cta.b64 _, [%0];" :: "r"(bar) : "memory"); }
__device__ __forceinline__ void mbar_arrive_remote(uint32_t bar) { asm volatile("mbarrier.arrive.relaxed.cluster.shared::cluster.b64 _, [%0];" :: "r"(bar) : "memory"); }
__device__ __forceinline__ void mbar_expect(uint32_t bar, uint32_t bytes) { asm volatile("mbarrier.arrive.expect_tx.shared::cta.b64 _, [%0], %1;" :: "r"(bar), "r"(bytes) : "memory"); }
__device__ __forceinline__ bool mbar_try(uint32_t bar, uint32_t parity) {
  uint32_t ok;
  asm volatile("{.reg .pred p; mbarrier.try_wait.parity.shared::cta.b64 p, [%1], %2; selp.u32 %0, 1, 0, p;}" : "=r"(ok) : "r"(bar), "r"(parity) : "memory");
  return ok;
}
__device__ __forceinline__ bool mbar_test(uint32_t bar, uint32_t parity) {
  uint32_t ok;
  asm volatile("{.reg .pred p; mbarrier.test_wait.parity.shared::cta.b64 p, [%1], %2; selp.u32 %0, 1, 0, p;}" : "=r"(ok) : "r"(bar), "r"(parity) : "memory");
  return ok;
}
__device__ __forceinline__ void mbar_wait(uint32_t bar, uint32_t parity) {
  asm volatile("{\n.reg .pred p;\nWAIT:\nmbarrier.try_wait.parity.shared::cta.b64 p, [%0], %1;\n@!p bra WAIT;\n}" :: "r"(bar), "r"(parity) : "memory");
}
__device__ __forceinline__ uint32_t ld_acq(const uint32_t* p) { uint32_t v; asm volatile("ld.acquire.gpu.global.u32 %0, [%1];" : "=r"(v) : "l"(p) : "memory"); return v; }
__device__ __forceinline__ unsigned long long ld_acq64(const unsigned long long* p) { unsigned long long v; asm volatile("ld.acquire.gpu.global.u64 %0, [%1];" : "=l"(v) : "l"(p) : "memory"); return v; }
__device__ __forceinline__ void st_rel(uint32_t* p, uint32_t v) { asm volatile("st.release.gpu.global.u32 [%0], %1;" :: "l"(p), "r"(v) : "memory"); }
__device__ __forceinline__ void st_rel64(unsigned long long* p, unsigned long long v) { asm volatile("st.release.gpu.global.u64 [%0], %1;" :: "l"(p), "l"(v) : "memory"); }
__device__ __forceinline__ void red_rel(uint32_t* p, uint32_t v) { asm volatile("red.release.gpu.global.add.u32 [%0], %1;" :: "l"(p), "r"(v) : "memory"); }
__device__ __forceinline__ uint32_t ld_rlx(const uint32_t* p) { uint32_t v; asm volatile("ld.relaxed.gpu.global.u32 %0, [%1];" : "=r"(v) : "l"(p) : "memory"); return v; }
__device__ __forceinline__ unsigned long long ld_rlxu64(const unsigned long long* p) { unsigned long long v; asm volatile("ld.relaxed.gpu.global.u64 %0, [%1];" : "=l"(v) : "l"(p) : "memory"); return v; }
__device__ __forceinline__ void st_rlx(uint32_t* p, uint32_t v) { asm volatile("st.relaxed.gpu.global.u32 [%0], %1;" :: "l"(p), "r"(v) : "memory"); }
__device__ __forceinline__ void bulk_wait() { asm volatile("cp.async.bulk.commit_group;\n cp.async.bulk.wait_group 0;" ::: "memory"); }
__device__ __forceinline__ void fence_acq() { asm volatile("fence.acquire.gpu;" ::: "memory"); }
__device__ __forceinline__ void wait_all(const uint32_t* p, uint32_t v, bool acquire = true) {
  int guard = 0;
  while (!__all_sync(~0u, ld_rlx(p) == v)) { __nanosleep(32); if (++guard > (1 << 22)) TRAP(); }
  if (acquire) fence_acq();
}
__device__ __forceinline__ void wait_eq(const uint32_t* p, uint32_t v) {
  int guard = 0;
  while (ld_rlx(p) != v) { __nanosleep(64); if (++guard > (1 << 22)) TRAP(); }
  fence_acq();
}
__device__ __forceinline__ unsigned long long rword(uint32_t E, int tok, float r) {
  uint32_t u = __float_as_uint(r + 0.f);
  u = r != r ? 0u : (u >> 31) ? ~u : u | 0x80000000u;
  return (unsigned long long)(E & 0x1FFFFFu) << 43 | (unsigned long long)u << 11 | (uint32_t)(2047 - tok);
}
__device__ __forceinline__ int rtok(unsigned long long v) { return 2047 - (int)(v & 2047u); }
__device__ __forceinline__ float rscore(unsigned long long v) { const uint32_t u = (uint32_t)(v >> 11); return __uint_as_float((u >> 31) ? u & 0x7fffffffu : ~u); }
__device__ __forceinline__ bool rfresh(unsigned long long v, uint32_t E) { return (uint32_t)(v >> 43) == (E & 0x1FFFFFu); }
template <int TOP> __device__ __forceinline__ unsigned long long warp_max(unsigned long long v) {
#pragma unroll
  for (int o = TOP; o > 0; o >>= 1) { const unsigned long long ov = __shfl_xor_sync(~0u, v, o); v = ov > v ? ov : v; }
  return v;
}
template <int off> __device__ __forceinline__ uint2 ld_rlx64(const void* p) { unsigned long long v; asm volatile("ld.relaxed.gpu.global.b64 %0, [%1+%2];" : "=l"(v) : "l"(p), "n"(off) : "memory"); return make_uint2((uint32_t)v, (uint32_t)(v >> 32)); }
template <int off> __device__ __forceinline__ uint4 ld_rlx128(const void* p) {
  unsigned long long a, b; asm volatile("ld.relaxed.gpu.global.v2.b64 {%0,%1}, [%2+%3];" : "=l"(a), "=l"(b) : "l"(p), "n"(off) : "memory");
  return make_uint4((uint32_t)a, (uint32_t)(a >> 32), (uint32_t)b, (uint32_t)(b >> 32));
}
__device__ __forceinline__ void st_rlx64(void* p, uint32_t lo, uint32_t hi) { asm volatile("{.reg .b64 t; mov.b64 t, {%1,%2}; st.relaxed.gpu.global.b64 [%0], t;}" :: "l"(p), "r"(lo), "r"(hi) : "memory"); }
__device__ __forceinline__ void cp_async16(uint32_t dst, const void* src) { asm volatile("cp.async.cg.shared.global [%0], [%1], 16;" :: "r"(dst), "l"(src) : "memory"); }
__device__ __forceinline__ void cp_async_wait() { asm volatile("cp.async.wait_all;" ::: "memory"); }
__device__ __forceinline__ void fence_async_smem() { asm volatile("fence.proxy.async.shared::cta;" ::: "memory"); }
__device__ __forceinline__ void fence_async_glob() { asm volatile("fence.proxy.async.global;" ::: "memory"); }
__device__ __forceinline__ void fence_async_acq() { asm volatile("fence.proxy.async::generic.acquire.sync_restrict::shared::cluster.cluster;" ::: "memory"); }
__device__ __forceinline__ float ex2(float x) { float y; asm("ex2.approx.ftz.f32 %0, %1;" : "=f"(y) : "f"(x)); return y; }
__device__ __forceinline__ float sqrt_fast(float x) { float y; asm("sqrt.approx.ftz.f32 %0, %1;" : "=f"(y) : "f"(x)); return y; }
__device__ __forceinline__ float rcp(float x) { float y; asm("rcp.approx.ftz.f32 %0, %1;" : "=f"(y) : "f"(x)); return y; }
__device__ __forceinline__ void bar_sync(int id, int n) { asm volatile("bar.sync %0, %1;" :: "r"(id), "r"(n) : "memory"); }
__device__ __forceinline__ bool bar_or(int id, int n, bool v) {
  uint32_t r;
  asm volatile("{.reg .pred p, q; setp.ne.u32 p, %3, 0; barrier.cta.red.or.aligned.pred q, %1, %2, p; selp.u32 %0, 1, 0, q;}" : "=r"(r) : "r"(id), "r"(n), "r"((uint32_t)v) : "memory");
  return r;
}
__device__ __forceinline__ uint32_t mapa(uint32_t a, uint32_t rank) { uint32_t r; asm volatile("mapa.shared::cluster.u32 %0, %1, %2;" : "=r"(r) : "r"(a), "r"(rank)); return r; }
__device__ __forceinline__ void cluster_sync() { asm volatile("barrier.cluster.arrive.release.aligned; barrier.cluster.wait.acquire.aligned;" ::: "memory"); }
__device__ __forceinline__ void st_async32(uint32_t dst, uint32_t v, uint32_t bar) { asm volatile("st.async.shared::cluster.mbarrier::complete_tx::bytes.b32 [%0], %1, [%2];" :: "r"(dst), "r"(v), "r"(bar) : "memory"); }
__device__ __forceinline__ void bulk_g2s(uint32_t dst, const void* src, uint32_t bytes, uint32_t bar) {
  asm volatile("cp.async.bulk.shared::cluster.global.mbarrier::complete_tx::bytes [%0], [%1], %2, [%3];" :: "r"(dst), "l"(src), "r"(bytes), "r"(bar) : "memory");
}
__device__ __forceinline__ void bulk_g2s_mc(uint32_t dst, const void* src, uint32_t bytes, uint32_t bar, uint16_t mask) {
  asm volatile("cp.async.bulk.shared::cluster.global.mbarrier::complete_tx::bytes.multicast::cluster [%0], [%1], %2, [%3], %4;"
               :: "r"(dst), "l"(src), "r"(bytes), "r"(bar), "h"(mask) : "memory");
}
__device__ __forceinline__ void bulk_s2c(uint32_t dst, uint32_t src, uint32_t bytes, uint32_t bar) {
  asm volatile("cp.async.bulk.shared::cluster.shared::cta.mbarrier::complete_tx::bytes [%0], [%1], %2, [%3];" :: "r"(dst), "r"(src), "r"(bytes), "r"(bar) : "memory");
}
__device__ __forceinline__ void bulk_s2g(void* dst, uint32_t src, uint32_t bytes) {
  asm volatile("cp.async.bulk.global.shared::cta.bulk_group [%0], [%1], %2;" :: "l"(dst), "r"(src), "r"(bytes) : "memory");
}
#define ELECT(op) "{.reg .pred p; elect.sync _|p, 0xffffffff; @p " op "}"
__device__ __forceinline__ void e_arrive(uint32_t bar) { asm volatile(ELECT("mbarrier.arrive.shared::cta.b64 _, [%0];") :: "r"(bar) : "memory"); }
__device__ __forceinline__ void e_expect(uint32_t bar, uint32_t bytes) { asm volatile(ELECT("mbarrier.arrive.expect_tx.shared::cta.b64 _, [%0], %1;") :: "r"(bar), "r"(bytes) : "memory"); }
__device__ __forceinline__ void e_g2s(uint32_t dst, const void* src, uint32_t bytes, uint32_t bar) {
  asm volatile(ELECT("cp.async.bulk.shared::cluster.global.mbarrier::complete_tx::bytes [%0], [%1], %2, [%3];") :: "r"(dst), "l"(src), "r"(bytes), "r"(bar) : "memory");
}
__device__ __forceinline__ void e_mc(uint32_t dst, const void* src, uint32_t bytes, uint32_t bar, uint16_t mask) {
  asm volatile(ELECT("cp.async.bulk.shared::cluster.global.mbarrier::complete_tx::bytes.multicast::cluster [%0], [%1], %2, [%3], %4;")
               :: "r"(dst), "l"(src), "r"(bytes), "r"(bar), "h"(mask) : "memory");
}
__device__ __forceinline__ void e_s2g(void* dst, uint32_t src, uint32_t bytes) {
  asm volatile(ELECT("cp.async.bulk.global.shared::cta.bulk_group [%0], [%1], %2;") :: "l"(dst), "r"(src), "r"(bytes) : "memory");
}
__device__ __forceinline__ void e_st_rel(uint32_t* p, uint32_t v) { asm volatile(ELECT("st.release.gpu.global.u32 [%0], %1;") :: "l"(p), "r"(v) : "memory"); }
__device__ __forceinline__ uint32_t clk32() { uint32_t c; asm volatile("mov.u32 %0, %%clock;" : "=r"(c) :: "memory"); return c; }
__device__ __forceinline__ void spin_until(uint32_t t) { while ((int)(clk32() - t) < 0) {} }
__device__ __forceinline__ uint32_t uni(uint32_t v) { return __shfl_sync(~0u, v, 0); }
__device__ __forceinline__ uint32_t pack2(float lo, float hi) { uint32_t r; asm("cvt.rn.bf16x2.f32 %0, %1, %2;" : "=r"(r) : "f"(hi), "f"(lo)); return r; }
__device__ __forceinline__ uint32_t add2(uint32_t a, uint32_t b) { uint32_t r; asm("add.rn.bf16x2 %0, %1, %2;" : "=r"(r) : "r"(a), "r"(b)); return r; }
__device__ __forceinline__ float rbf(float x) { return __bfloat162float(__float2bfloat16_rn(x)); }
__device__ __forceinline__ float blo(uint32_t u) { return __uint_as_float(u << 16); }
__device__ __forceinline__ float bhi(uint32_t u) { return __uint_as_float(u & 0xffff0000u); }
__device__ __forceinline__ uint32_t gentag(uint32_t g) { return (g & 1u) | (g & 2u) << 15; }
__device__ __forceinline__ uint32_t pack2_tag(float lo, float hi, uint32_t tag) {
  const uint32_t u = __byte_perm(__float_as_uint(lo), __float_as_uint(hi), 0x7632);
  return u + ((u ^ tag) & 0x10001u);
}
__device__ __forceinline__ uint32_t xo2(uint32_t a, uint32_t b, uint32_t t) { uint32_t r; asm("lop3.b32 %0, %1, %2, %3, 0x7e;" : "=r"(r) : "r"(a), "r"(b), "r"(t)); return r; }
__device__ __forceinline__ uint32_t or3(uint32_t a, uint32_t b, uint32_t c) { uint32_t r; asm("lop3.b32 %0, %1, %2, %3, 0xfe;" : "=r"(r) : "r"(a), "r"(b), "r"(c)); return r; }
__device__ __forceinline__ void stmatrix4(uint32_t a, uint32_t r0, uint32_t r1, uint32_t r2, uint32_t r3) {
  asm volatile("stmatrix.sync.aligned.m8n8.x4.shared.b16 [%0], {%1,%2,%3,%4};" :: "r"(a), "r"(r0), "r"(r1), "r"(r2), "r"(r3) : "memory");
}
__device__ __forceinline__ void stmatrix4_t(uint32_t a, uint32_t r0, uint32_t r1, uint32_t r2, uint32_t r3) {
  asm volatile("stmatrix.sync.aligned.m8n8.x4.trans.shared.b16 [%0], {%1,%2,%3,%4};" :: "r"(a), "r"(r0), "r"(r1), "r"(r2), "r"(r3) : "memory");
}
__device__ __forceinline__ void ldmatrix4_t(uint32_t* r, uint32_t a) {
  asm volatile("ldmatrix.sync.aligned.m8n8.x4.trans.shared.b16 {%0,%1,%2,%3}, [%4];" : "=r"(r[0]), "=r"(r[1]), "=r"(r[2]), "=r"(r[3]) : "r"(a) : "memory");
}
__device__ __forceinline__ void ldmatrix4(uint32_t* r, uint32_t a) {
  asm volatile("ldmatrix.sync.aligned.m8n8.x4.shared.b16 {%0,%1,%2,%3}, [%4];" : "=r"(r[0]), "=r"(r[1]), "=r"(r[2]), "=r"(r[3]) : "r"(a) : "memory");
}
__device__ __forceinline__ void hmma16(float* c, const uint32_t* a, uint32_t b0, uint32_t b1) {
  asm volatile("mma.sync.aligned.m16n8k16.row.col.f32.bf16.bf16.f32 {%0,%1,%2,%3}, {%4,%5,%6,%7}, {%8,%9}, {%0,%1,%2,%3};"
               : "+f"(c[0]), "+f"(c[1]), "+f"(c[2]), "+f"(c[3]) : "r"(a[0]), "r"(a[1]), "r"(a[2]), "r"(a[3]), "r"(b0), "r"(b1));
}
__device__ __forceinline__ void hmma8(float* c, uint32_t a0, uint32_t a1, uint32_t b0) {
  asm volatile("mma.sync.aligned.m16n8k8.row.col.f32.bf16.bf16.f32 {%0,%1,%2,%3}, {%4,%5}, {%6}, {%0,%1,%2,%3};"
               : "+f"(c[0]), "+f"(c[1]), "+f"(c[2]), "+f"(c[3]) : "r"(a0), "r"(a1), "r"(b0));
}
__device__ __forceinline__ uint4 lds128(uint32_t a) { uint4 v; asm volatile("ld.shared.v4.u32 {%0,%1,%2,%3}, [%4];" : "=r"(v.x), "=r"(v.y), "=r"(v.z), "=r"(v.w) : "r"(a) : "memory"); return v; }
__device__ __forceinline__ void sts128(uint32_t a, uint4 v) { asm volatile("st.shared.v4.u32 [%0], {%1,%2,%3,%4};" :: "r"(a), "r"(v.x), "r"(v.y), "r"(v.z), "r"(v.w) : "memory"); }
__device__ __forceinline__ void sts128f(uint32_t a, float x, float y, float z, float w) { asm volatile("st.shared.v4.f32 [%0], {%1,%2,%3,%4};" :: "r"(a), "f"(x), "f"(y), "f"(z), "f"(w) : "memory"); }
__device__ __forceinline__ void sts64f(uint32_t a, float x, float y) { asm volatile("st.shared.v2.f32 [%0], {%1,%2};" :: "r"(a), "f"(x), "f"(y) : "memory"); }
__device__ __forceinline__ uint32_t lds32(uint32_t a) { uint32_t v; asm volatile("ld.shared.u32 %0, [%1];" : "=r"(v) : "r"(a) : "memory"); return v; }
__device__ __forceinline__ void sts32(uint32_t a, uint32_t v) { asm volatile("st.shared.u32 [%0], %1;" :: "r"(a), "r"(v) : "memory"); }

constexpr uint32_t SBASE = 1024;
__host__ __device__ constexpr uint64_t mkdesc(uint32_t off, uint32_t lbo, uint32_t sbo, uint32_t swz) {
  return (uint64_t)(((SBASE + off) & 0x3FFFF) >> 4) | ((uint64_t)(lbo >> 4) << 16) | ((uint64_t)(sbo >> 4) << 32) | ((uint64_t)swz << 62);
}
__device__ __forceinline__ void wg_fence() { asm volatile("wgmma.fence.sync.aligned;" ::: "memory"); }
__device__ __forceinline__ void wg_commit() { asm volatile("wgmma.commit_group.sync.aligned;" ::: "memory"); }
template <int N> __device__ __forceinline__ void wg_wait() { asm volatile("wgmma.wait_group.sync.aligned %0;" :: "n"(N) : "memory"); }

template <int N> __device__ __forceinline__ void reg_fence(float (&d)[N], int n = N) {
#pragma unroll
  for (int i = 0; i < N; i++) if (i < n) asm volatile("" : "+f"(d[i]) :: "memory");
}
#define F4(b) "+f"(d[b]), "+f"(d[b + 1]), "+f"(d[b + 2]), "+f"(d[b + 3])
#define F8(b) F4(b), F4(b + 4)
#define F16(b) F8(b), F8(b + 8)
#define G4(b) "=f"(d[b]), "=f"(d[b + 1]), "=f"(d[b + 2]), "=f"(d[b + 3])
#define G8(b) G4(b), G4(b + 4)
#define G16(b) G8(b), G8(b + 8)
#define RS_IN "r"(a[0]), "r"(a[1]), "r"(a[2]), "r"(a[3]), "l"(db), "n"(SD), "n"(TB)
#define SS_IN "l"(da), "l"(db), "n"(SD), "n"(TA), "n"(TB)
#define WG_OP(str, out0, out1, in) do { if (SD || KEEP) asm volatile(str : out1 : in); else asm volatile(str : out0 : in); } while (0)
#define O12(X) X##8(0), X##4(8)
#define O20(X) X##16(0), X##4(16)
#define O32(X) X##16(0), X##16(16)
template <int SD, int TB, int KEEP = 0> __device__ __forceinline__ void wgmma_rs24(float* d, const uint32_t* a, uint64_t db) {
  WG_OP("wgmma.mma_async.sync.aligned.m64n24k16.f32.bf16.bf16 {%0,%1,%2,%3,%4,%5,%6,%7,%8,%9,%10,%11}, {%12,%13,%14,%15}, %16, %17, 1, 1, %18;", O12(G), O12(F), RS_IN);
}
template <int SD, int TB, int KEEP = 0> __device__ __forceinline__ void wgmma_rs32(float* d, const uint32_t* a, uint64_t db) {
  WG_OP("wgmma.mma_async.sync.aligned.m64n32k16.f32.bf16.bf16 {%0,%1,%2,%3,%4,%5,%6,%7,%8,%9,%10,%11,%12,%13,%14,%15}, {%16,%17,%18,%19}, %20, %21, 1, 1, %22;", G16(0), F16(0), RS_IN);
}
template <int SD, int TB, int KEEP = 0> __device__ __forceinline__ void wgmma_rs40(float* d, const uint32_t* a, uint64_t db) {
  WG_OP("wgmma.mma_async.sync.aligned.m64n40k16.f32.bf16.bf16 {%0,%1,%2,%3,%4,%5,%6,%7,%8,%9,%10,%11,%12,%13,%14,%15,"
        "%16,%17,%18,%19}, {%20,%21,%22,%23}, %24, %25, 1, 1, %26;", O20(G), O20(F), RS_IN);
}
template <int SD, int TB, int KEEP = 0> __device__ __forceinline__ void wgmma_rs64(float* d, const uint32_t* a, uint64_t db) {
  WG_OP("wgmma.mma_async.sync.aligned.m64n64k16.f32.bf16.bf16 {%0,%1,%2,%3,%4,%5,%6,%7,%8,%9,%10,%11,%12,%13,%14,%15,"
        "%16,%17,%18,%19,%20,%21,%22,%23,%24,%25,%26,%27,%28,%29,%30,%31}, {%32,%33,%34,%35}, %36, %37, 1, 1, %38;", O32(G), O32(F), RS_IN);
}
template <int SD, int TA, int TB, int KEEP = 0> __device__ __forceinline__ void wgmma_ss24(float* d, uint64_t da, uint64_t db) {
  WG_OP("wgmma.mma_async.sync.aligned.m64n24k16.f32.bf16.bf16 {%0,%1,%2,%3,%4,%5,%6,%7,%8,%9,%10,%11}, %12, %13, %14, 1, 1, %15, %16;", O12(G), O12(F), SS_IN);
}
template <int SD, int TA, int TB, int KEEP = 0> __device__ __forceinline__ void wgmma_ss8(float* d, uint64_t da, uint64_t db) {
  WG_OP("wgmma.mma_async.sync.aligned.m64n8k16.f32.bf16.bf16 {%0,%1,%2,%3}, %4, %5, %6, 1, 1, %7, %8;", G4(0), F4(0), SS_IN);
}
__device__ __forceinline__ void bar_arrive(int id, int n) { asm volatile("bar.arrive %0, %1;" :: "r"(id), "r"(n) : "memory"); }
__device__ __forceinline__ uint32_t vis_bits(int pos, int t) {
  uint32_t m = 0;
#pragma unroll
  for (int i = 0; i < 8; i++) m |= (8 * (i / 2 + 1) + 2 * t + (i & 1) <= pos) ? 1u << i : 0u;
  return m;
}

__device__ __forceinline__ unsigned long long wait_words(const unsigned long long* p, uint32_t E) {
  int guard = 0; unsigned long long m;
  while (m = ld_rlxu64(p), !__all_sync(~0u, rfresh(m, E))) { __nanosleep(32); if (++guard > (1 << 22)) TRAP(); }
  fence_acq();
  return m;
}
__device__ __forceinline__ int route_step(int s, uint32_t E, int lane, unsigned long long& run) {
  const unsigned long long m = warp_max<2>(wait_words(f_h2[s][lane & 3], E));
  if (s == 0 || m > run) { run = m; return rtok(m) & 31; }
  return -1;
}

struct Params {
  const bf16 *x, *mem0, *wq, *wk, *wv, *wo, *wr, *wg, *wu, *wd;
  bf16* out;
  uint32_t zero2;
  unsigned long long zero;
};

constexpr uint32_t WSTG_STRIDE = 272;
__device__ __forceinline__ void stage_weights(uint32_t stg, const bf16* src, int ld, int tid, int nthr) {
  for (int i = tid; i < 512 * 16; i += nthr) {
    int k = i >> 4, c = i & 15;
    cp_async16(stg + k * WSTG_STRIDE + c * 16, src + (size_t)k * ld + c * 8);
  }
}
__device__ __forceinline__ void load_frags(uint32_t (*W)[4], uint32_t stg, int wg, int w, int lane) {
  uint32_t a = stg + ((lane >> 4) * 8 + (lane & 7)) * WSTG_STRIDE + (64 * wg + 16 * w + ((lane >> 3) & 1) * 8) * 2;
#pragma unroll
  for (int ks = 0; ks < 32; ks++) ldmatrix4_t(W[ks], a + ks * 16 * WSTG_STRIDE);
}

constexpr uint32_t M_H = 0;
constexpr uint32_t M_MEM = 65536;
constexpr uint32_t M_Q = M_MEM + 24576;
constexpr uint32_t M_K = M_Q + 12288;
constexpr uint32_t M_V = M_K + 12288;
constexpr uint32_t M_OM = M_V + 12288;
constexpr uint32_t M_OST = M_OM + 6144;
constexpr uint32_t M_TST = M_OST + 8192;
constexpr uint32_t M_WO = M_TST + 16384;
constexpr uint32_t M_M0 = M_WO + 49152;
constexpr uint32_t M_PT = M_M0 + 2048;
constexpr uint32_t M_BAR = M_PT + 12288;
constexpr uint32_t M_TOTAL = M_BAR + 384;
static_assert(M_TOTAL <= 232448, "main smem");
static_assert(M_WO >= 512 * WSTG_STRIDE, "staging overlaps Wo");
enum { B_LAND = 0  , B_QK = 3, B_V, B_TOK, B_OM, B_HA, B_HB, B_HAE, B_HBE, B_OST, B_OFREE, B_SYNC,
       B_STG, B_STG1, B_SS, B_TFREE, B_KFREE, B_VFREE, B_FIX  , B_NUM = B_FIX + 8 };
static_assert(B_NUM * 8 <= 256, "barriers");
constexpr uint32_t M_CAND = M_BAR + 256;
constexpr uint32_t M_BASE = M_BAR + 272;
constexpr uint32_t M_ZERO = M_BAR + 280;
constexpr uint32_t M_BAS2 = M_BAR + 328;
constexpr uint32_t M_NEAR = M_BAR + 288;
enum { N_GO1 = 2, N_GO2, N_GO3, N_GO4, N_AG, N_W };

#define GSTAMP(slot, i)
#define TSTAMP(slot, i, k)
#define STAMP(i)
#define ASTAMP(i)
#define WSTAMP(i)
#define CSTAMP(i, v)
#define PIN(x) asm volatile("" : "+r"(x))
#define SCHED(k) asm volatile("{\n.reg .pred p;\nsetp.ne.u32 p, %0, 0;\n@p trap;\n}" :: "r"(zz & (1u << (k))) : "memory")
#define HOLD(k, v) asm volatile("{\n.reg .pred p;\nsetp.ne.u32 p, %0, 0;\n@p st.shared.u32 [%0], %1;\n}" :: "r"(zz & (1u << (k))), "r"(v) : "memory")
#define DRAIN(a) (lds32((a) + zz) & zz)
#define BAR(i) (sb + M_BAR + 8 * (i))

__device__ __forceinline__ int probe(const uint8_t* p, int n) {
  int best = 1 << 30; uint32_t v = 0;
#pragma unroll 1
  for (int r = 0; r < n; r++) {
    uint32_t t0 = clk();
    asm volatile("atom.relaxed.gpu.global.or.b32 %0, [%1], %2;" : "=r"(v) : "l"(p + 3968), "r"(v & 0u) : "memory");
    if (v == 0x7fffffffu) t0++;
    best = min(best, (int)(clk() - t0));
  }
  return best;
}
__device__ __forceinline__ void load_mem0(uint4* u, int k0, int lane, const bf16* mem0) {
#pragma unroll
  for (int i = 0; i < 2; i++) {
    const unsigned short* m = (const unsigned short*)mem0 + k0 + lane + 32 * i;
    u[i] = make_uint4(m[0] | (uint32_t)m[512] << 16, m[1024] | (uint32_t)m[1536] << 16, m[2048] | (uint32_t)m[2560] << 16, m[3072] | (uint32_t)m[3584] << 16);
  }
}

__device__ __forceinline__ void paced_h(uint32_t dst, const uint8_t* src, uint32_t o0, uint32_t o1, uint32_t piece, uint32_t bar, int gap) {
  uint32_t t = clk32();
#pragma unroll 1
  for (uint32_t o = o0; o < o1; o += piece) {
    e_mc(dst + o, src + o, piece, bar, 7);
    spin_until(t += gap);
  }
}

__device__ __forceinline__ void weight_role(const Params& p, const uint32_t sb, const int warp, const int cta, const int C, const uint32_t E,
                                            const uint8_t* const memg) {
  const int tid = fresh_tid(), lane = tid & 31;
  const int wg = warp >> 2, w = warp & 3;
  uint32_t W[32][4];
  cp_async_wait();
  bar_sync(1, 256);
  load_frags(W, sb, wg, w, lane);
  bar_sync(1, 256);
  if (tid < 128) sts128(sb + M_V + 5 * 2048 + tid * 16, make_uint4(0, 0, 0, 0));
  fence_async_smem();
  cluster_sync();
  if (tid == 0 && cta == 0) GSTAMP(0, 1);
  if (tid == 0) TSTAMP(13, cta, 0);

  const uint32_t rba = mapa(sb, C == 2 ? 0 : 2), rbc = mapa(sb, C == 1 ? 0 : 1);
  const uint32_t MYBAR = M_BAR + 8 * (C < 2 ? B_QK : B_V);
  uint32_t qoff = M_Q + C * 12288 + warp * 256 + lane * 4;
  uint32_t toff = sb + warp * 256 + (lane >> 4) * 2048 + (lane & 15) * 16;
  uint32_t rbar = mapa(sb + M_BAR, min(lane, 2));
  uint32_t sv = sb + M_MEM + lane * 32 + ((lane >> 2) & 3) * 8;
  PIN(qoff); PIN(toff); PIN(rbar); PIN(sv);
  const uint32_t gen0 = (E - 1) * (uint32_t)(NSTEP - 1);
  uint32_t fix = 0;
  const bool sig = w == 0 && lane < 3;
  const int pk = PAUSE_ + (cta < 36 ? 0 : cta < 72 ? PD1_ : 2 * PD1_) + (wg ? -PST2_ : PST2_);
  int cand = -1;
  float d[16];
#pragma unroll
  for (int i = 0; i < 16; i++) d[i] = 0.f;
  uint32_t tp[8];
#pragma unroll 1
  for (int T = -1; T < NSTEP; T++) {
    const uint32_t ph = T & 1;
    const uint64_t Z = p.zero << ph;
    const uint32_t zz = p.zero2;
    if (T >= 0) {
      WSTAMP(0);
      const uint64_t db = mkdesc(M_MEM, 128, 256, 0) + Z;
      stmatrix4(toff + M_TST + 8192, tp[0], tp[1], tp[2], tp[3]); stmatrix4(toff + M_TST + 12288, tp[4], tp[5], tp[6], tp[7]);
      if (sig) mbar_arrive_remote(rbar + 8 * B_HBE);
      mbar_wait(BAR(B_LAND), ph);
      WSTAMP(1);
      const uint32_t gt = gentag(gen0 + T);
      auto old = [&](uint32_t a) { return lds32(a) ^ gt; };
      uint32_t bad = 0;
      bool redo = false, ready = false;
      wg_fence();
      wgmma_rs24<0, 1, KP1_>(d, W[0], db);
#pragma unroll
      for (int ks = 1; ks < 32; ks++) {
        if (ks == 2 || ks == 14) bad |= xo2(lds32(sv + (ks == 2 ? 0 : 9) * 1024 + warp * 1024), lds32(sv + (ks == 2 ? 8 : 17) * 1024), gt);
        if (ks == 25) bad |= old(sv + (18 + min(warp, 5)) * 1024);
        if (ks == 6) {
          const uint32_t z5 = DRAIN(toff + M_TST);
          __syncwarp();
          if (lane == 0) mbar_arrive(BAR(B_STG) + z5);
        }
        if (ks == 27) ready = mbar_test(BAR(C < 2 ? B_KFREE : B_VFREE), ph ^ 1) & mbar_test(BAR(B_HA), ph);
        if (ks == RED_) redo = bar_or(N_W, 256, T > 0 && (bad & 0x10001u));
        if (ks == 12 || ks == 24) { mbar_wait(BAR(B_LAND + ks / 12), ph); WSTAMP(6 + ks / 12); wg_fence(); }
        wgmma_rs24<1, 1>(d, W[ks], db + ks * 48);
      }
      wg_commit();
      uint32_t a0 = rba + qoff, a1 = a0 + 128, a2 = rbc + qoff, a3 = a2 + 128, ba = rba + MYBAR, bc = rbc + MYBAR;
      PIN(a0); PIN(a1); PIN(a2); PIN(a3); PIN(ba); PIN(bc);
      if (!ready) {
        mbar_wait(BAR(C < 2 ? B_KFREE : B_VFREE), ph ^ 1);
        if (T < NSTEP - 1) mbar_wait(BAR(B_HA), ph);
      }
      wg_wait<0>(); reg_fence(d);
      if (__builtin_expect(redo, 0)) {
        auto stale = [&]() { return __any_sync(~0u, (old(sv + warp * 3072) | old(sv + warp * 3072 + 1024) | old(sv + warp * 3072 + 2048)) & 0x10001u); };
        auto fetch = [&](int r) {
          e_expect(BAR(B_FIX + warp), 3072);
          e_g2s(sb + M_MEM + warp * 3072, memg + warp * 8192 + ((uni(lds32(sb + M_NEAR + warp * 4)) ^ r) & 1) * 4096, 3072, BAR(B_FIX + warp));
        };
        bool late = stale();
        if (late) fetch(0);
        constexpr uint64_t dc = mkdesc(M_MEM, 128, 256, 0);
#pragma unroll
        for (int ks = 0; ks < 32; ks++) {
          if (ks % 12 == 0) {
            if (ks) { wg_commit(); wg_wait<0>(); reg_fence(d); }
            if (warp / 3 == ks / 12) {
              for (int guard = 0; late; guard++) {
                mbar_wait(BAR(B_FIX + warp), fix); fix ^= 1;
                late = stale();
                if (late) fetch(ALT_ ? guard + 1 : 0);
                if (guard > (1 << 20)) TRAP();
              }
            }
            bar_sync(N_W, 256);
            wg_fence();
          }
          if (ks == 0) wgmma_rs24<0, 1, 1>(d, W[0], dc); else wgmma_rs24<1, 1>(d, W[ks], dc + ks * 48);
        }
        wg_commit();
        wg_wait<0>(); reg_fence(d);
      }
      WSTAMP(2);
      if (T == 0 && tid == 0) TSTAMP(13, cta, 2);
      uint32_t lo[3], hi[3];
#pragma unroll
      for (int j = 0; j < 3; j++) { lo[j] = pack2(d[4 * j], d[4 * j + 1]); hi[j] = pack2(d[4 * j + 2], d[4 * j + 3]); }
      if (__builtin_expect(T == 0, 0)) { sts32(sb + M_M0 + tid * 8, lo[0]); sts32(sb + M_M0 + tid * 8 + 4, hi[0]); }
      if (__builtin_expect(cand >= 0, 0)) {
        if (T == LAG) { lo[1] = lds32(sb + M_M0 + tid * 8); hi[1] = lds32(sb + M_M0 + tid * 8 + 4); }
        if (C < 2) { st_async32(a0 + 5 * 2048, lo[2], ba); st_async32(a1 + 5 * 2048, hi[2], ba); }
        else { sts32(sb + qoff + 5 * 2048, lo[2]); sts32(sb + qoff + 5 * 2048 + 128, hi[2]); }
        lo[2] = lo[1]; hi[2] = hi[1];
      }
      uint32_t z5;
      if (C == 0) {
        sts32(sb + qoff, lo[0]); sts32(sb + qoff + 128, hi[0]); z5 = DRAIN(sb + qoff);
        st_async32(a0, lo[2], ba); st_async32(a1, hi[2], ba); st_async32(a2, lo[1], bc); st_async32(a3, hi[1], bc);
      } else if (C == 1) {
        sts32(sb + qoff, lo[1]); sts32(sb + qoff + 128, hi[1]); z5 = DRAIN(sb + qoff);
        st_async32(a0, lo[2], ba); st_async32(a1, hi[2], ba); st_async32(a2, lo[0], bc); st_async32(a3, hi[0], bc);
      } else {
        sts32(sb + qoff, lo[2]); sts32(sb + qoff + 128, hi[2]); z5 = DRAIN(sb + qoff);
        st_async32(a0, lo[0], ba); st_async32(a1, hi[0], ba); st_async32(a2, lo[1], bc); st_async32(a3, hi[1], bc);
      }
      __syncwarp();
      if (lane == 0) { mbar_arrive(sb + MYBAR + z5); if (w == 3) mbar_arrive(BAR(B_SS)); }
      if (T == NSTEP - 1) break;
    }
    {
      const uint64_t dh = mkdesc(M_H, 16, 1024, 1) + Z;
      static_assert(E2 == 0 && E3 > 0 && PAUSE_ > 0, "config");
      if (T + 2 < NSEG) {
        if (T < 0) mbar_wait(BAR(B_HA), ph);
        WSTAMP(3);
        wg_fence();
        wgmma_rs32<0, 0, 1>(d, W[0], dh);
#pragma unroll
        for (int ks = 1; ks < EA; ks++) {
          if (ks == E1) { wg_commit(); if (T >= 0) bar_sync(N_GO2, 384); wg_fence(); }
          wgmma_rs32<1, 0>(d, W[ks], dh + (ks >> 2) * 256 + (ks & 3) * 2);
        }
        wg_commit();
        mbar_wait(BAR(B_HB), ph);
        wg_wait<0>();
        if (sig) mbar_arrive_remote(rbar + 8 * B_HAE);
        WSTAMP(4);
        if (T >= 0) bar_sync(N_GO3, 384);
        if (wg == 1) bar_sync(N_W, 256);
        wg_fence();
#pragma unroll
        for (int ks = EA; ks < 32; ks++) wgmma_rs32<1, 0>(d, W[ks], dh + (ks >> 2) * 256 + (ks & 3) * 2);
        wg_commit();
        if (wg == 0) bar_arrive(N_W, 256);
        mbar_wait(BAR(B_TFREE), ph ^ 1);
        wg_wait<0>(); reg_fence(d);
      } else {
        bar_sync(N_GO2, 384);
        mbar_wait(BAR(B_HB), ph);
        if (sig) mbar_arrive_remote(rbar + 8 * B_HAE);
        bar_sync(N_GO3, 384);
        mbar_wait(BAR(B_TFREE), ph ^ 1);
      }
#pragma unroll
      for (int i = 0; i < 8; i++) { tp[i] = pack2(d[2 * i], d[2 * i + 1]); PIN(tp[i]); }
      auto staged = [&]() {
        const uint32_t z5 = DRAIN(toff + M_TST);
        __syncwarp();
        if (lane == 0) mbar_arrive(BAR(B_STG1) + z5);
      };
      if (T < 0 || (T + 2 >= LAG && T + 2 < NSTEP)) {
        wg_fence();
        wgmma_rs32<0, 0, 1>(d, W[0], dh + 2048);
        stmatrix4(toff + M_TST, tp[0], tp[1], tp[2], tp[3]); stmatrix4(toff + M_TST + 4096, tp[4], tp[5], tp[6], tp[7]);
#pragma unroll
        for (int ks = 1; ks < 32; ks++) {
          if (ks == 5) staged();
          if (ks >= PAUSE_ - PST2_ && ks <= PAUSE_ + 2 * PD1_ + PST2_ && (ks - PAUSE_ + PST2_) % PGR_ == 0) {
            wg_commit();
            if (T >= 0 && ks == pk) bar_sync(N_GO4, 384);
            wg_fence();
          }
          wgmma_rs32<1, 0>(d, W[ks], dh + 2048 + (ks >> 2) * 256 + (ks & 3) * 2);
        }
        wg_commit();
      } else {
        stmatrix4(toff + M_TST, tp[0], tp[1], tp[2], tp[3]); stmatrix4(toff + M_TST + 4096, tp[4], tp[5], tp[6], tp[7]);
        staged();
        bar_sync(N_GO4, 384);
      }
      if (T >= 0) cand = __shfl_sync(~0u, (int)lds32(sb + M_CAND + ((T + 1) & 3) * 4), 0);
      wg_wait<0>(); reg_fence(d);
      if (T >= 0) WSTAMP(6);
      if (T < 0 && tid == 0) TSTAMP(13, cta, 1);
#pragma unroll
      for (int i = 0; i < 8; i++) tp[i] = pack2(d[2 * i], d[2 * i + 1]);
    }
  }
  cluster_sync();
  if (tid == 0 && cta == 0) GSTAMP(0, 5);
}

__device__ __forceinline__ void attn_role(const Params& p, const uint32_t sb, const int w, const int cta, const int head, const int C, const uint32_t E,
                                          uint8_t* const part, uint8_t* const memg) {
  const int tid = fresh_tid(), lane = tid & 31;
  const int g = lane >> 2, t = lane & 3;
  uint32_t tag = ((E - 1) * (uint32_t)(NSTEP - 1)) & 1;
  uint4 m0[2][2];
  load_mem0(m0[0], w * 64, lane, p.mem0); load_mem0(m0[1], w * 64 + 256, lane, p.mem0);
  cluster_sync();
#pragma unroll
  for (int k = 0; k < 2; k++) {
#pragma unroll 1
    for (int i = 0; i < 6; i++) sts128(sb + M_MEM + (w + 4 * k) * 3072 + lane * 16 + i * 512, make_uint4(0, 0, 0, 0));
    __syncwarp();
#pragma unroll
    for (int i = 0; i < 2; i++) sts128(sb + M_MEM + ((w + 4 * k) * 4 + (lane >> 4) + 2 * i) * 768 + (lane & 15) * 16, m0[k][i]);
  }
  fence_async_smem();
  bar_sync(N_AG, 128);
  if (w == 3 && lane < 3) mbar_arrive(BAR(B_LAND + lane));
  if (lane == 0) {
    if (w == 0) TSTAMP(15, cta, 0);
    sts32(sb + M_PT + w * 4, probe(part + cta * 16384 + w * 4096, NPROBE_ / 2));
    if (w == 0) TSTAMP(15, cta, 1);
  }
  bar_sync(N_AG, 128);
  const uint32_t inear = lds32(sb + M_PT + (w >> 1) * 8 + 4) < lds32(sb + M_PT + (w >> 1) * 8);
  if (lane == 0 && !(w & 1)) st_rlx(&f_choice[cta][w >> 1], (E << 1) | inear);
  if (w == 0) TSTAMP(15, cta, 2);
  uint32_t nb;
  {
    const int i = min(lane >> 1, C < 2 ? 8 : 5);
    const int r = ((i / 3 * 3 + C) * 4 + w) * 3 + i % 3;
    int guard = 0; uint32_t cw;
    while (__any_sync(~0u, ((cw = ld_rlx(&f_choice[r][lane & 1])) >> 1) != (E & 0x7FFFFFFFu))) { if (++guard > (1 << 22)) TRAP(); }
    nb = __ballot_sync(~0u, cw & 1) >> (lane >> 4);
    if (w == 0) TSTAMP(15, cta, 3);
  }
  bar_sync(N_AG, 128);
  const uint32_t pt0 = sb + M_PT + (tid & 127) * 16;
  {
    const uint32_t po = (C * 4 + w) * 49152 + (lane >> 4) * 8192 + ((lane >> 3) & 1) * 2048 + head * 64 + (lane & 7) * 8;
    const uint8_t* in = part + (cta * 16384 + (w >> 1) * 8192 + inear * 4096 + (w & 1) * 2048 + lane * 8);
    const uint8_t* outp = memg + ((cta / 12) * 8192 + (cta % 12) * 256 + w * 64 + (lane >> 4) * 4096 + (lane & 4) * 8 + (lane & 8) * 2 + (lane & 3) * 4);
#pragma unroll
    for (int i = 0; i < 12; i++) {
      const int j = i / 4 * 3 + (i & 3);
      const uint8_t* a = (i & 3) < 3 ? part + (po + i / 4 * 589824 + (i & 3) * 16384 + ((nb >> (2 * j)) & 1) * 4096) : i == 11 ? in : outp;
      asm volatile("st.shared.u64 [%0], %1;" :: "r"(pt0 + (i >> 1) * 2048 + (i & 1) * 8), "l"(a) : "memory");
    }
  }
  const int xd = __shfl_sync(~0u, XDLY_ + (cta < 36 ? 0 : cta < 72 ? X1_ : X2_), 0);
  const uint32_t rba = mapa(sb, C == 2 ? 0 : 2), rbc = mapa(sb, C == 1 ? 0 : 1);
  uint32_t vis = vis_bits(8 + 8 * w + g, t);
  uint32_t ln = lane;
#pragma unroll
  for (int i = 0; i < SALT_; i++) ln += lds32(sb + M_ZERO);
  PIN(vis); PIN(ln);
  if (tid == 256 && C == 0) st_rlx(&f_loaded[head], E);
  uint32_t fa[8][4];
#pragma unroll
  for (int ks = 0; ks < 8; ks++) ldmatrix4_t(fa[ks], sb + M_WO + 32768 + w * 256 + (lane >> 4) * 1024 + (lane & 15) * 16 + ks * 2048);
  if (w == 0) TSTAMP(14, cta, 0);
#pragma unroll 1
  for (int T = 0; T < NSTEP; T++) {
    const uint32_t ph = T & 1;
    const uint32_t zz = uni(lds32(sb + M_ZERO));
    const bool more = T < NSTEP - 1;
    const float sc = 0.08838834764831845f * 1.4426950408889634f;
    tag ^= 1;
    float s[20];
    const uint8_t* in; int cnext = -1; uint32_t tx; bool synced;
    float x[10], tm, ts;
    uint32_t pt[5];
    auto tok_max = [&]() {
      PIN(vis);
      x[0] = s[2]; x[1] = s[3];
#pragma unroll
      for (int i = 0; i < 8; i++) x[2 + i] = (vis >> i & 1) ? s[4 * (i / 2 + 1) + 2 + (i & 1)] : -INFINITY;
      tm = fmaxf(fmaxf(fmaxf(fmaxf(x[0], x[1]), fmaxf(x[2], x[3])), fmaxf(fmaxf(x[4], x[5]), fmaxf(x[6], x[7]))), fmaxf(x[8], x[9]));
      HOLD(7, __float_as_uint(tm));
    };
    auto tok_exp1 = [&]() {
      tm = fmaxf(tm, __shfl_xor_sync(~0u, tm, 1));
      tm = fmaxf(tm, __shfl_xor_sync(~0u, tm, 2));
      const float b = -tm * sc;
#pragma unroll
      for (int i = 0; i < 10; i++) x[i] = fmaf(x[i], sc, b);
      HOLD(10, __float_as_uint(x[9]));
    };
    auto tok_exp2 = [&]() {
#pragma unroll
      for (int i = 0; i < 10; i++) x[i] = ex2(x[i]);
      ts = (((x[0] + x[1]) + (x[2] + x[3])) + ((x[4] + x[5]) + (x[6] + x[7]))) + (x[8] + x[9]);
#pragma unroll
      for (int k = 0; k < 5; k++) pt[k] = pack2(x[2 * k], x[2 * k + 1]);
      HOLD(8, __float_as_uint(ts));
    };
    {
      uint32_t q[8][4];
      auto load_q = [&](uint32_t a, int h) {
#pragma unroll
        for (int k2 = 0; k2 < 4; k2++) {
          uint32_t r[4];
          ldmatrix4_t(r, a + k2 * 512);
          q[2 * k2][h] = r[0]; q[2 * k2][h + 2] = r[1]; q[2 * k2 + 1][h] = r[2]; q[2 * k2 + 1][h + 2] = r[3];
        }
      };
      PIN(ln);
      const uint32_t qa = sb + M_Q + ln * 16;
      const int cand = C == 2 ? (int)uni(lds32(sb + M_CAND + (T & 3) * 4)) : -1;
      mbar_wait(BAR(B_TOK), ph);
      load_q(qa + (1 + w) * 2048, 1);
      mbar_wait(BAR(B_QK), ph);
      ASTAMP(0);
      if (T == 0 && w == 0) TSTAMP(13, cta, 3);
      if (__builtin_expect(cand >= 0, 0)) {
        mbar_wait(BAR(B_V), ph);
        PIN(ln);
        const int e = w * 32 + ln;
#pragma unroll
        for (int i = 0; i < 3; i++) {
          const uint32_t v = lds32(sb + M_Q + i * 12288 + 5 * 2048 + e * 16 + 4);
          asm volatile("st.shared.u16 [%0], %1;" :: "r"(sb + M_Q + i * 12288 + (1 + (cand >> 3)) * 2048 + e * 16 + (cand & 7) * 2), "h"((unsigned short)v) : "memory");
        }
        fence_async_smem();
        bar_sync(N_AG, 128);
        load_q(qa + (1 + w) * 2048, 1);
      }
      load_q(qa, 0);
      if (!(NOF_ & 1)) fence_async_smem();
      constexpr uint64_t dk = mkdesc(M_K, 128, 2048, 0);
      wg_fence();
      wgmma_rs40<0, 1>(s, q[0], dk);
#pragma unroll
      for (int ks = 1; ks < 8; ks++) wgmma_rs40<1, 1>(s, q[ks], dk + ks * 16);
      wg_commit();
    }
    if (more) {
      uint32_t v[5][4];
      PIN(ln);
      const uint32_t va = sb + M_V + w * 512 + ((ln >> 3) & 1) * 128 + (ln >> 4) * 2048 + (ln & 7) * 16;
      const uint32_t ooff = M_OM + w * 1536 + C * 256 + ln * 4;
      mbar_wait(BAR(B_V), ph);
      wg_wait<0>(); reg_fence(s);
      if (ln < 3) mbar_arrive_remote(mapa(BAR(B_KFREE), ln));
      ldmatrix4(v[0], va); ldmatrix4(v[1], va + 256); ldmatrix4(v[2], va + 4096); ldmatrix4(v[3], va + 4096 + 256);
      ldmatrix4(v[4], sb + M_V + 8192 + w * 512 + ln * 16);
      ASTAMP(1);
      float m = fmaxf(fmaxf(fmaxf(fmaxf(s[0], s[1]), fmaxf(s[4], s[5])), fmaxf(fmaxf(s[8], s[9]), fmaxf(s[12], s[13]))), fmaxf(s[16], s[17]));
      m = fmaxf(m, __shfl_xor_sync(~0u, m, 1));
      m = fmaxf(m, __shfl_xor_sync(~0u, m, 2));
      const float b = -m * sc;
      uint32_t pm[5];
#pragma unroll
      for (int j = 0; j < 5; j++) pm[j] = pack2(ex2(fmaf(s[4 * j], sc, b)), ex2(fmaf(s[4 * j + 1], sc, b)));
      float o0[4] = {0.f, 0.f, 0.f, 0.f}, o1[4] = {0.f, 0.f, 0.f, 0.f}, l[4] = {0.f, 0.f, 0.f, 0.f};
      const uint32_t one[4] = {0x3f803f80u, 0x3f803f80u, 0x3f803f80u, 0x3f803f80u};
      hmma16(l, one, pm[0], pm[1]); hmma16(o0, v[0], pm[0], pm[1]); hmma16(o1, v[1], pm[0], pm[1]);
      hmma16(l, one, pm[2], pm[3]); hmma16(o0, v[2], pm[2], pm[3]); hmma16(o1, v[3], pm[2], pm[3]);
      hmma8(l, one[0], one[1], pm[4]); hmma8(o0, v[4][0], v[4][1], pm[4]); hmma8(o1, v[4][2], v[4][3], pm[4]);
      const float r0 = rcp(l[0]), r1 = rcp(l[1]);
      const uint32_t u0 = pack2(o0[0] * r0, o0[1] * r1), u1 = pack2(o0[2] * r0, o0[3] * r1), u2 = pack2(o1[0] * r0, o1[1] * r1), u3 = pack2(o1[2] * r0, o1[3] * r1);
      constexpr uint32_t OB = M_BAR + 8 * B_OM;
      const uint32_t a0 = rba + ooff, a1 = rbc + ooff;
      st_async32(a0, u0, rba + OB); st_async32(a1, u0, rbc + OB);
      st_async32(a0 + 128, u1, rba + OB); st_async32(a1 + 128, u1, rbc + OB);
      st_async32(a0 + 768, u2, rba + OB); st_async32(a1 + 768, u2, rbc + OB);
      st_async32(a0 + 896, u3, rba + OB); st_async32(a1 + 896, u3, rbc + OB);
      bar_arrive(N_GO2, 384);
      sts32(sb + ooff, u0); sts32(sb + ooff + 128, u1); sts32(sb + ooff + 768, u2); sts32(sb + ooff + 896, u3);
      ASTAMP(2);
      uint32_t fb[8][4];
      const uint32_t wa = sb + M_WO + 16384 + w * 256 + (ln >> 4) * 1024 + (ln & 15) * 16 + zz;
      ldmatrix4_t(fb[0], wa);
      SCHED(3);
#pragma unroll
      for (int ks = 1; ks < 8; ks++) {
        ldmatrix4_t(fb[ks], wa + ks * 2048);
        if (ks == ARR_) { __syncwarp(); if (ln == 0) mbar_arrive(BAR(B_OM) + (fb[0][0] & zz)); }
      }
      if (C == 2) cnext = (int)uni(lds32(sb + M_CAND + ((T + 1) & 3) * 4));
      {
        float d[12], e[12];
        constexpr uint64_t ob = mkdesc(M_OM, 128, 256, 0);
        uint8_t* q[3][3];
        auto addr = [&](int i) {
          asm volatile("ld.shared.v2.u64 {%0,%1}, [%2];" : "=l"(q[i][0]), "=l"(q[i][1]) : "r"(pt0 + i * 4096) : "memory");
          if (i < 2) asm volatile("ld.shared.u64 %0, [%1];" : "=l"(q[i][2]) : "r"(pt0 + i * 4096 + 2048) : "memory");
          else asm volatile("ld.shared.v2.u64 {%0,%1}, [%2];" : "=l"(q[i][2]), "=l"(in) : "r"(pt0 + i * 4096 + 2048) : "memory");
        };
        auto put = [&](const float* d, int i) {
          st_rlx64(q[i][0], (pack2(d[0], d[1]) & ~1u) | tag, pack2(d[2], d[3]));
          st_rlx64(q[i][1], (pack2(d[4], d[5]) & ~1u) | tag, pack2(d[6], d[7]));
          st_rlx64(q[i][2], (pack2(d[8], d[9]) & ~1u) | tag, pack2(d[10], d[11]));
        };
        addr(0); addr(1);
        SCHED(6);
        tok_max();
        ASTAMP(3);
        mbar_wait(BAR(B_OM), ph);
        if (!(NOF_ & 2)) fence_async_smem();
        ASTAMP(4);
        constexpr uint64_t w0 = mkdesc(M_WO, 1024, 128, 0);
        float (&f)[12] = d;
        wg_fence();
        wgmma_ss24<0, 1, 1>(d, w0, ob);
#pragma unroll
        for (int ks = 1; ks < 8; ks++) wgmma_ss24<1, 1, 1>(d, w0 + ks * 128, ob + ks * 48);
        wg_commit();
        wgmma_rs24<0, 1>(e, fb[0], ob);
#pragma unroll
        for (int ks = 1; ks < HAND_; ks++) wgmma_rs24<1, 1>(e, fb[ks], ob + ks * 48);
        wg_commit();
        wg_wait<1>(); reg_fence(d);
        put(d, 0);
        addr(2);
        SCHED(4);
        ASTAMP(5);
        wg_fence();
#pragma unroll
        for (int ks = HAND_; ks < 8; ks++) wgmma_rs24<1, 1>(e, fb[ks], ob + ks * 48);
        wg_commit();
        wgmma_rs24<0, 1, 1>(f, fa[0], ob);
#pragma unroll
        for (int ks = 1; ks < HAND_; ks++) wgmma_rs24<1, 1>(f, fa[ks], ob + ks * 48);
        wg_commit();
        wg_wait<1>(); reg_fence(e);
        put(e, 1);
        SCHED(5);
        wg_fence();
#pragma unroll
        for (int ks = HAND_; ks < 8; ks++) wgmma_rs24<1, 1>(f, fa[ks], ob + ks * 48);
        wg_commit();
        if (GO3_ == 0) bar_arrive(N_GO3, 384);
        synced = __all_sync(~0u, mbar_test(BAR(B_SYNC), ph));
        tx = uni(lds32(sb + M_BASE + ph * 4)) + xd;
        wg_wait<0>(); reg_fence(f);
        if (GO3_ == 1) bar_arrive(N_GO3, 384);
        if (C < 2) put(f, 2);
        if (GO3_ == 2) bar_arrive(N_GO3, 384);
        ASTAMP(6);
        if (T == 0 && w == 0) TSTAMP(14, cta, 1);
      }
    } else {
      mbar_wait(BAR(B_V), ph);
      wg_wait<0>(); reg_fence(s);
      tok_max();
    }
    uint2 v[8];
#pragma unroll
    for (int i = 0; i < 8; i++) v[i] = make_uint2(zz, zz);
    auto poll = [&](uint2* v) {
      v[0] = ld_rlx64<0>(in); v[1] = ld_rlx64<256>(in); v[2] = ld_rlx64<512>(in); v[3] = ld_rlx64<768>(in);
      v[4] = ld_rlx64<1024>(in); v[5] = ld_rlx64<1280>(in); v[6] = ld_rlx64<1536>(in); v[7] = ld_rlx64<1792>(in);
    };
    uint8_t* outp;
    asm volatile("ld.shared.u64 %0, [%1];" : "=l"(outp) : "r"(pt0 + 2048 + 8) : "memory");
    const uint32_t itag = gentag((E - 1) * (uint32_t)(NSTEP - 1) + T + 1);
    const bool sum = more && cnext < 0;
    if (more) {
      if (!synced) { mbar_wait(BAR(B_SYNC), ph); tx = uni(lds32(sb + M_BASE + ph * 4)) + xd; }
      ASTAMP(7);
      if (__builtin_expect(cnext >= 0, 0)) {
        const unsigned long long* hp = (const unsigned long long*)&g_hc[T + 1 - LAG][0] + ((cta / 3) * 8 + 2 * w + ((ln >> 2) & 1));
        unsigned long long v0; int guard = 0;
        while (v0 = ld_rlxu64(hp), !__all_sync(~0u, (uint32_t)(v0 >> 32) == E)) { if (++guard > (1 << 22)) TRAP(); }
        st_rlx((uint32_t*)outp, (ln & 3) == 1 ? ((uint32_t)v0 >> ((ln & 8) * 2)) & 0xffffu : (ln & 1) ? 0u : itag);
      } else {
        spin_until(tx);
        ASTAMP(8);
        poll(v);
      }
    }
    auto late = [&](const uint2* v) {
      return __any_sync(~0u, (or3(xo2(v[0].x, v[1].x, tag), xo2(v[2].x, v[3].x, tag), xo2(v[4].x, v[5].x, tag)) | xo2(v[6].x, v[7].x, tag)) & 1u);
    };
    tok_exp1(); tok_exp2();
    auto reduce = [&]() {
      if (sum) {
        ASTAMP(9);
        int guard = 0;
        while (late(v)) {
          if (++guard > (1 << 22)) TRAP();
          poll(v);
        }
#pragma unroll
        for (int i = 0; i < 4; i++) { v[i].x = add2(v[i].x, v[i + 4].x); v[i].y = add2(v[i].y, v[i + 4].y); }
        const bool hi = ln & 8;
        const uint32_t x0 = add2(v[0].x, v[1].x), x1 = add2(v[2].x, v[3].x), y0 = add2(v[0].y, v[1].y), y1 = add2(v[2].y, v[3].y);
        const uint32_t m0 = hi ? y0 : x0, m1 = hi ? y1 : x1;
        const uint32_t n0 = __shfl_xor_sync(~0u, hi ? x0 : y0, 8), n1 = __shfl_xor_sync(~0u, hi ? x1 : y1, 8);
        float k0 = (blo(m0) + blo(m1)) + (blo(n0) + blo(n1)), k1 = (bhi(m0) + bhi(m1)) + (bhi(n0) + bhi(n1));
        k0 += __shfl_xor_sync(~0u, k0, 16); k1 += __shfl_xor_sync(~0u, k1, 16);
        st_rlx((uint32_t*)outp, (ln & 1) ? pack2(k0, k1) : pack2_tag(k0, k1, itag));
        ASTAMP(10);
        if (T == 0 && w == 0) TSTAMP(14, cta, 2);
        CSTAMP(12 + w, (clk() & ~15u) | min(guard + 1, 15));
      }
      if (more) bar_arrive(N_GO4, 384);
    };
    if (PVR_ < 0) reduce();
    {
      PIN(ln);
      const uint32_t oa = sb + M_OST + w * 128 + (ln >> 3) * 512 + (ln & 7) * 16;
      const uint32_t a[3][4] = {{0, pt[0], 0, pt[1]}, {0, pt[2], 0, pt[3]}, {0, pt[4], 0, 0}};
      constexpr uint64_t dv = mkdesc(M_V, 2048, 128, 0);
#pragma unroll 1
      for (int h = 0; h < 2; h++) {
        float o[32];
        const uint64_t dh = dv + (uint64_t)(h * 64);
        wg_fence();
        wgmma_rs64<0, 0>(o, a[0], dh); wgmma_rs64<1, 0>(o, a[1], dh + 256); wgmma_rs64<1, 0>(o, a[2], dh + 512);
        wg_commit();
        if (h == PVR_) reduce();
        if (h == 0) {
          ts += __shfl_xor_sync(~0u, ts, 1);
          ts += __shfl_xor_sync(~0u, ts, 2);
          ts = rcp(ts);
          mbar_wait(BAR(B_OFREE), ph ^ 1);
        }
        wg_wait<0>(); reg_fence(o);
        if (h == 1 && ln < 3) mbar_arrive_remote(mapa(BAR(B_VFREE), ln));
#define OT(i) pack2(o[4 * (i) + 2] * ts, o[4 * (i) + 3] * ts)
        stmatrix4(oa + h * 4096, OT(0), OT(1), OT(2), OT(3));
        stmatrix4(oa + h * 4096 + 2048, OT(4), OT(5), OT(6), OT(7));
      }
      const uint32_t z5 = DRAIN(oa);
      __syncwarp();
      if (ln == 0) mbar_arrive(BAR(B_OST) + z5);
      ASTAMP(11);
    }
  }
}

__global__ void __cluster_dims__(3, 1, 1) __launch_bounds__(512, 1) main_kernel(Params p) {
  extern __shared__ __align__(1024) uint8_t sm[];
  const uint32_t sb = smem_u32(sm);
  if ((sb & 0xFFFFFFu) != SBASE) TRAP();
  asm volatile("griddepcontrol.launch_dependents;");
  const int warp = __shfl_sync(~0u, threadIdx.x >> 5, 0);
  const int cta = blockIdx.x, head = cta / 3, c = cta % 3;
  const uint32_t E = __shfl_sync(~0u, *(volatile uint32_t*)&g_epoch + 1, 0);
  uint8_t* const part = (uint8_t*)(((uintptr_t)g_xch + 8191) & ~(uintptr_t)8191);
  uint8_t* const memg = part + 96 * 16384;

  if (threadIdx.x == 0 && cta == 0) GSTAMP(0, 0);
  if (threadIdx.x < B_NUM) {
    const int i = threadIdx.x;
    const uint32_t cnt = i == B_STG || i == B_STG1 ? 8 : i == B_OST ? 4 : i == B_HAE || i == B_HBE ? 6 : i == B_KFREE || i == B_VFREE ? 12 : i == B_SS ? 2 : i == B_OM ? 5 :
                         i == B_QK ? (c < 2 ? 9 : 1) : i == B_V ? (c < 2 ? 1 : 9) : 1;
    mbar_init(BAR(i), cnt);
    if (i == B_HA || i == B_HB || i == B_STG || i == B_HAE || i == B_HBE || i == B_TFREE)
      asm volatile("mbarrier.arrive.shared::cta.b64 _, [%0], %1;" :: "r"(BAR(i)), "r"(cnt) : "memory");
    asm volatile("fence.mbarrier_init.release.cluster;" ::: "memory");
  }
  if (warp < 8) {
    const int tid = threadIdx.x;
    uint4 wa[6], wb[6];
#pragma unroll
    for (int i = 0; i < 6; i++) {
      const int mi = i >> 1, e = (tid >> 2) + (i & 1) * 64;
      const uint4* src = (const uint4*)(p.wo + (size_t)(head * 128 + e) * 512 + min(3 * mi + c, 7) * 64 + (tid & 3) * 16);
      wa[i] = __ldg(src); wb[i] = __ldg(src + 1);
    }
    stage_weights(sb, (c == 0 ? p.wq : c == 1 ? p.wk : p.wv) + head * 128, 4096, tid, 256);
#pragma unroll
    for (int i = 0; i < 6; i++) {
      const int mi = i >> 1, e = (tid >> 2) + (i & 1) * 64;
      const uint4 a = wa[i], b = wb[i];
      const uint32_t dst = sb + M_WO + mi * 16384 + (e >> 3) * 1024 + (tid & 3) * 256 + (e & 7) * 16;
      sts128(dst, make_uint4(__byte_perm(a.x, a.y, 0x5410), __byte_perm(a.z, a.w, 0x5410), __byte_perm(b.x, b.y, 0x5410), __byte_perm(b.z, b.w, 0x5410)));
      sts128(dst + 128, make_uint4(__byte_perm(a.x, a.y, 0x7632), __byte_perm(a.z, a.w, 0x7632), __byte_perm(b.x, b.y, 0x7632), __byte_perm(b.z, b.w, 0x7632)));
    }
  } else {
    const int i0 = threadIdx.x - 256;
    const uint32_t tag0 = ((E - 1) * (uint32_t)(NSTEP - 1)) & 1;
    for (int i = i0; i < 1024; i += 256) *(uint4*)(part + cta * 16384 + i * 16) = make_uint4(tag0, 0, tag0, 0);
    if (i0 < 16) *(uint32_t*)(memg + i0 * 4096 + 3968) = 0;
    if (i0 < 2) st_rlx(&f_choice[cta][i0], 0);
    if (i0 < 8) st_rlx64(&g_sync[i0 >> 2][cta][i0 & 3], 0, 0);
    __threadfence();
    if (i0 < 12) sts32(sb + M_ZERO + i0 * 4, 0);
    if (i0 < 2) { sts32(sb + M_BASE + i0 * 4, clk32() - 65536); sts32(sb + M_BAS2 + i0 * 4, clk32() - 65536); sts32(sb + M_CAND + i0 * 4, (uint32_t)-1); }
  }

  if (warp < 8) {
    asm volatile("setmaxnreg.inc.sync.aligned.u32 " STR(RW_) ";");
    weight_role(p, sb, warp, cta, c, E, memg);
  } else if (warp < 12) {
    if (RA_ < 128) asm volatile("setmaxnreg.dec.sync.aligned.u32 " STR(RA_) ";");
    if (RA_ > 128) asm volatile("setmaxnreg.inc.sync.aligned.u32 " STR(RA_) ";");
    attn_role(p, sb, warp - 8, cta, head, c, E, part, memg);
    cluster_sync();
  } else {
    asm volatile("setmaxnreg.dec.sync.aligned.u32 " STR(RC_) ";");
    const int tid = fresh_tid(), lane = tid & 31;
    const int w = warp - 12;
    cluster_sync();
    if (w != 2) {
      const int tl = min(3 * min(w, 2) + c, 7);
      int near = 0;
      if (lane == 0) { const int t0 = probe(memg + tl * 8192, NPROBE_ / 2); near = probe(memg + tl * 8192 + 4096, NPROBE_ / 2) < t0; }
      near = uni(near);
      if (lane < 3) asm volatile("st.shared::cluster.u32 [%0], %1;" :: "r"(mapa(sb + M_NEAR + tl * 4, lane)), "r"(near) : "memory");
      __syncwarp();
    }
    if (w == 0) {
      int yadj = 0, dmin = 1 << 20; uint32_t prev = 0; bool cprev = false;
      uint32_t s0 = c * 8192, s1 = (3 + c) * 8192, s2 = min(6 + c, 7) * 8192;
#pragma unroll 1
      for (int T = 0; T < NSTEP - 1; T++) {
        const uint32_t ph = T & 1;
        mbar_wait(BAR(B_SS), ph);
        const uint32_t cq = clk();
        const uint32_t g0 = (uint32_t)gtime64(); uint32_t g1, ce;
        do { g1 = (uint32_t)gtime64(); ce = clk(); } while (g1 == g0);
        const uint32_t tn = g1 * 8 - (((ce - cq) * 37u) >> 3), id = E * 128u + T;
        if (lane < 4) st_rlx64(&g_sync[ph][cta][lane], tn, id);
        if (lane < 3) mbar_expect(BAR(B_LAND + lane), lane < 2 ? 9216 : 6144);
        if (T == 0) { s0 += uni(lds32(sb + M_NEAR + c * 4)) * 4096; s1 += uni(lds32(sb + M_NEAR + (3 + c) * 4)) * 4096; s2 += uni(lds32(sb + M_NEAR + min(6 + c, 7) * 4)) * 4096; }
        wait_until(cq + SDLY_);
        int guard = 0; unsigned long long v0, v1, v2;
        for (;;) {
          v0 = ld_rlxu64(g_sync[ph][lane]); v1 = ld_rlxu64(g_sync[ph][lane + 32]); v2 = ld_rlxu64(g_sync[ph][lane + 64]);
          if (__all_sync(~0u, (uint32_t)(v0 >> 32) == id && (uint32_t)(v1 >> 32) == id && (uint32_t)(v2 >> 32) == id)) break;
          if (++guard > (1 << 22)) TRAP();
        }
        const bool cnd = (int)uni(lds32(sb + M_CAND + (T & 3) * 4)) >= 0;
        const int dl = __reduce_max_sync(~0u, max(max((int)((uint32_t)v0 - tn), (int)((uint32_t)v1 - tn)), (int)((uint32_t)v2 - tn)));
        const uint32_t base = uni(cq + ((min(dl, 8 * 4096) * 7) >> 5)) + (T == 0 ? SLOW0_ : T == 1 ? SLOW1_ : 0) +
                              (cnd ? CDLY_ : 0) - (T + 2 < NSEG ? 0 : BOFF_);
        const int dur = (int)(base - prev);
        if (!cnd && !cprev) {
          yadj = T > 2 && dur > dmin + 700 ? min(yadj + YUP_, 400) : max(yadj - YDN_, 0);
          if (T > 1) dmin = min(dmin + 20, dur);
        }
        prev = base; cprev = cnd;
        if (lane == 0) { sts32(sb + M_BASE + ph * 4, base); sts32(sb + M_BAS2 + ph * 4, base + yadj); mbar_arrive(BAR(B_SYNC)); }
        CSTAMP(0, base); CSTAMP(1, clk());
        const uint32_t ts = base + YDLY_ + yadj - (T + 2 >= LAG && T + 2 < NSEG ? 0 : YOFF_);
        uint32_t nr = 0;
        if (PRIV_) nr = __ballot_sync(~0u, lds32(sb + M_NEAR + (lane & 7) * 4) != 0);
        wait_until(ts);
        if (PRIV_ & 1) { for (int k = 0; k < 3; k++) e_g2s(sb + M_MEM + k * 3072, memg + k * 8192 + ((nr >> k) & 1) * 4096, 3072, BAR(B_LAND)); }
        else e_mc(sb + M_MEM + c * 3072, memg + s0, 3072, BAR(B_LAND), 7);
        CSTAMP(2, clk());
        spin_until(ts + Y1_);
        if (PRIV_ & 2) { for (int k = 3; k < 6; k++) e_g2s(sb + M_MEM + k * 3072, memg + k * 8192 + ((nr >> k) & 1) * 4096, 3072, BAR(B_LAND + 1)); }
        else e_mc(sb + M_MEM + (3 + c) * 3072, memg + s1, 3072, BAR(B_LAND + 1), 7);
        CSTAMP(3, clk());
        spin_until(ts + Y2_);
        if (PRIV_ & 4) { for (int k = 6; k < 8; k++) e_g2s(sb + M_MEM + k * 3072, memg + k * 8192 + ((nr >> k) & 1) * 4096, 3072, BAR(B_LAND + 2)); }
        else if (c < 2) e_mc(sb + M_MEM + (6 + c) * 3072, memg + s2, 3072, BAR(B_LAND + 2), 7);
        CSTAMP(4, clk());
      }
    } else if (w == 1) {
#pragma unroll 1
      for (int T = 0; T < NSTEP; T++) {
        const uint32_t ph = T & 1;
        const int s = c == 0 ? T : T - LAG;
        const bool act = s >= 0 && s < NSEG;
        mbar_wait(BAR(B_OST), ph);
        if (cta == 0) TSTAMP(2, T, 0);
        fence_async_smem();
        if (T < NSTEP - 1) wait_until(uni(lds32(sb + M_BAS2 + ph * 4)) + ODLY_);
        STAMP(22);
        if (act) { e_s2g(g_o[c][s % ORING][head], sb + M_OST, XO_); bulk_wait(); __syncwarp(); }
        e_arrive(BAR(B_OFREE));
        if (cta == 0) TSTAMP(2, T, 1);
        if (act && lane < 8) st_rel(&f_o[T][head >> 2][c * 4 + (head & 3)][lane], E);
        __syncwarp();
        if (cta == 0) TSTAMP(2, T, 2);
      }
    } else if (w == 2) {
      unsigned long long run = 0;
      static_assert(LAG >= 2, "config");
      constexpr uint32_t NA = EA / 4 * 4096;
      e_expect(BAR(B_QK), c < 2 ? 2048 : 4096); e_expect(BAR(B_V), c == 0 ? 10240 : c == 1 ? 2048 : 0);
      e_expect(BAR(B_TOK), c == 0 ? 16384 : 0); e_expect(BAR(B_OM), 4096);
      e_expect(BAR(B_HA), NA); e_expect(BAR(B_HB), 65536 - NA);
      wait_eq(&f_h1[c == 1 ? 0 : 1], E); fence_async_glob();
      {
        const uint32_t o0 = c == 0 ? NA : 0, o1 = c == 2 ? NA : 32768;
        e_mc(sb + M_H + (c == 1 ? 32768 : 0) + o0, g_h[0][c == 1 ? 0 : 1] + o0, o1 - o0, BAR(c == 2 ? B_HA : B_HB), 7);
      }
      TSTAMP(14, cta, 3);
      if (c == 2) wait_eq(&f_h1[2], E);
      mbar_wait(BAR(B_HAE), 1);
      e_expect(BAR(B_HA), NA);
      if (c == 2) { fence_async_glob(); e_mc(sb + M_H, g_h[0][2], NA, BAR(B_HA), 7); }
      int cprev = -1;
#pragma unroll 1
      for (int T = 0; T < NSTEP - 1; T++) {
        const int s1 = T + 2, s2 = T + 2 - LAG;
        const uint32_t ph = T & 1;
        const bool l1 = s1 < NSEG, l2 = s2 >= 0 && s2 < NSEG, la = s1 + 1 < NSEG;
        const bool mine = c == 0 ? l1 : c == 1 ? l2 : la;
        const uint32_t* fl = c != 1 ? &f_h1[min(s1 + (c >> 1), NSEG - 1)] : (const uint32_t*)f_h2[max(s2, 0)][lane & 3] + 1;
        const uint32_t want = E & 0x1FFFFFu, sh = c != 1 ? 0 : 11;
        mbar_wait(BAR(B_HBE), ph ^ 1);
        const bool early = __all_sync(~0u, ((ld_acq(fl) >> sh) & 0x1FFFFFu) == want);
        mbar_wait(BAR(B_LAND + 2), ph);
        STAMP(16);
        e_expect(BAR(B_HB), (l1 ? 32768 - NA : 0) + (l2 ? 32768 : 0));
        if (mine) {
          if (!early) {
            int guard = 0;
            while (!__all_sync(~0u, ((ld_acq(fl) >> sh) & 0x1FFFFFu) == want)) { __nanosleep(32); if (++guard > (1 << 22)) TRAP(); }
          }
          fence_async_glob();
          if (c == 1) { mbar_wait(BAR(B_QK), ph); spin_until(clk32() + HDLY_); }
          if (c < 2) paced_h(sb + M_H + c * 32768, g_h[c][c ? s2 : s1], c ? 0 : NA, 32768, 4096, BAR(B_HB), HGAP_);
        }
        int cd = -1;
        if (l2) { cd = route_step(s2, E, lane, run); if (cta == 0) TSTAMP(5, s2, 0); }
        if (lane == 0) sts32(sb + M_CAND + ((T + 2) & 3) * 4, (uint32_t)cd);
        __syncwarp();
        STAMP(17);
        mbar_wait(BAR(B_HAE), ph);
        e_expect(BAR(B_HA), la ? NA : 0);
        if (c == 2 && la) {
          spin_until(clk32() + ADLY_);
          STAMP(18);
          paced_h(sb + M_H, g_h[0][s1 + 1], 0, NA, 4096, BAR(B_HA), AGAP_);
        }
        mbar_wait(BAR(B_OST), ph);
        e_expect(BAR(B_QK), c < 2 ? 2048 : cprev >= 0 ? 8192 : 4096);
        e_expect(BAR(B_V), c < 2 ? 10240 : 8192);
        e_expect(BAR(B_TOK), 16384);
        e_expect(BAR(B_OM), 4096);
        cprev = cd;
      }
    } else {
      const uint32_t mytok = sb + M_Q + c * 12288 + 2048, tb = BAR(c < 2 ? B_TOK : B_V);
      mbar_wait(BAR(B_STG1), 0);
      fence_async_smem();
      e_s2g(g_tok[cta][1], sb + M_TST, 8192);
#pragma unroll 1
      for (int T = 0; T < NSTEP - 1; T++) {
        const uint32_t ph = T & 1;
        uint8_t* const tok = g_tok[cta][ph ^ 1];
        mbar_wait(BAR(B_STG), ph ^ 1);
        fence_async_smem();
        if (cta == 0 && (T == 0 || T == NSEG || T == NSTEP - 2)) GSTAMP(0, T == 0 ? 2 : T == NSEG ? 3 : 4);
        if (T > 0 && TQ_) mbar_wait(BAR(B_QK), ph);
        STAMP(20);
        uint32_t t = clk32();
        e_s2g(tok + 8192, sb + M_TST + 8192, XT2_);
        spin_until(t + TGAP_);
        e_s2g(tok + 12288, sb + M_TST + 12288, XT2_);
        bulk_wait();
        __syncwarp();
        e_arrive(BAR(B_TFREE));
        if (T == 0) e_mc(mytok, tok + 8192, 8192, tb, 1);
        STAMP(21);
#pragma unroll 1
        for (int k = 0; k < 2; k++) {
          if (k == 1) {
            mbar_wait(BAR(B_STG1), ph ^ 1);
            fence_async_smem();
            t = uni(lds32(sb + M_BAS2 + ph * 4));
            wait_until(t + TDLY_);
            e_s2g(g_tok[cta][ph], sb + M_TST, XT1_);
          }
          if (k == (c >> 1)) {
            mbar_wait(BAR(c < 2 ? B_KFREE : B_VFREE), ph);
            t = k ? t + LDLY_ : clk32() + KDLY_;
            wait_until(t);
            STAMP(23);
            e_mc(mytok, tok, 8192, tb, 1);
            spin_until(t + LGAP_);
            e_mc(mytok, tok + 8192, 8192, tb, 6);
            STAMP(24);
          }
        }
      }
      bulk_wait();
    }
    __syncwarp();
    cluster_sync();
  }
}

constexpr uint32_t A_RING = 0;
constexpr int A_NST = 6;
constexpr uint32_t A_STG = A_RING + A_NST * 8192;
constexpr uint32_t A_WD = A_STG + 8192;
constexpr uint32_t A_WG = A_WD + 57344;
constexpr uint32_t A_WU = A_WG + 57344;
constexpr uint32_t A_XN = A_WU + 57344;
constexpr uint32_t A_BAR = A_XN + 2048;
constexpr uint32_t A_TOTAL = A_BAR + 256;
static_assert(A_TOTAL <= 232448, "aux smem");

__device__ __forceinline__ uint32_t ptag(int s) { return ((s / PRING) & 1) ^ 1; }
static_assert((NSEG / PRING) % 2 == 0, "tags");
__device__ __forceinline__ void load_row(uint32_t* v, const void* row, int lane) {
  const uint4 a = __ldcg((const uint4*)row + lane), b = __ldcg((const uint4*)row + 32 + lane);
  v[0] = a.x; v[1] = a.y; v[2] = a.z; v[3] = a.w; v[4] = b.x; v[5] = b.y; v[6] = b.z; v[7] = b.w;
}
__device__ __forceinline__ void store_row(void* row, const uint32_t* v, int lane) {
  ((uint4*)row)[lane] = make_uint4(v[0], v[1], v[2], v[3]); ((uint4*)row)[32 + lane] = make_uint4(v[4], v[5], v[6], v[7]);
}
__device__ __forceinline__ void store_img(uint8_t* img, int r, const uint32_t* v, int lane) {
  uint8_t* b = img + (lane >> 3) * 4096 + (r >> 3) * 1024 + (r & 7) * 128 + (((lane ^ r) & 7) << 4);
  *(uint4*)b = make_uint4(v[0], v[1], v[2], v[3]);
  *(uint4*)(b + 16384) = make_uint4(v[4], v[5], v[6], v[7]);
}
template <int NT> __device__ __forceinline__ void ln_rows(const uint32_t (*v)[8], uint32_t (*y)[8]) {
  float c[NT], sm[NT], sq[NT];
#pragma unroll
  for (int k = 0; k < NT; k++) {
    c[k] = blo(__shfl_sync(~0u, v[k][0], 0));
    float s0 = 0.f, s1 = 0.f, q0 = 0.f, q1 = 0.f;
#pragma unroll
    for (int i = 0; i < 8; i++) { const float a = blo(v[k][i]) - c[k], b = bhi(v[k][i]) - c[k]; s0 += a; s1 += b; q0 = fmaf(a, a, q0); q1 = fmaf(b, b, q1); }
    sm[k] = s0 + s1; sq[k] = q0 + q1;
  }
#pragma unroll
  for (int o = 16; o > 0; o >>= 1)
#pragma unroll
    for (int k = 0; k < NT; k++) {
      sm[k] += __shfl_xor_sync(~0u, sm[k], o); sq[k] += __shfl_xor_sync(~0u, sq[k], o);
    }
#pragma unroll
  for (int k = 0; k < NT; k++) {
    const float dm = sm[k] * (1.f / 512.f), var = fmaxf(fmaf(-dm, dm, sq[k] * (1.f / 512.f)), 0.f);
    const float mb = rbf(c[k] + dm), inv = rcp(rbf(sqrt_fast(rbf(rbf(var) + 1e-5f))));
#pragma unroll
    for (int i = 0; i < 8; i++) { const uint32_t a = pack2(blo(v[k][i]) - mb, bhi(v[k][i]) - mb); y[k][i] = pack2(blo(a) * inv, bhi(a) * inv); }
  }
}
__device__ __forceinline__ void input_ln_pair(const bf16* x, int s, int pr, int lane) {
  uint32_t v[2][8], y[2][8];
  load_row(v[0], x + (size_t)(s * 32 + 2 * pr) * 512, lane); load_row(v[1], x + (size_t)(s * 32 + 2 * pr + 1) * 512, lane);
  ln_rows<2>(v, y);
  store_img(g_h[0][s], 2 * pr, y[0], lane); store_img(g_h[0][s], 2 * pr + 1, y[1], lane);
}
__device__ __forceinline__ float load_wr(uint32_t* wv, const bf16* wr, int lane) {
  load_row(wv, wr, lane);
  float wsum = 0.f;
#pragma unroll
  for (int i = 0; i < 8; i++) wsum += blo(wv[i]) + bhi(wv[i]);
#pragma unroll
  for (int o = 16; o > 0; o >>= 1) wsum += __shfl_xor_sync(~0u, wsum, o);
  return wsum;
}

template <bool FAST>
__device__ __forceinline__ unsigned long long token_post(int st, int tk, const bf16* res, bf16* dst, bf16* req, unsigned long long best,
                                                         const uint32_t* wv, float wsum, uint32_t E, int lane) {
  const int s = tk >> 5;
  uint32_t x[8];
  load_row(x, res, lane);
  wait_all(f_acc[st][s][lane], E, false);
  if (tk == s * 32 && st == 0 && lane == 0) TSTAMP(4, s, 0);
  {
    const uint8_t* pp = g_pp[st][s % PRING] + (lane >> 4) * 8192 + (tk & 31) * 256 + (((lane & 15) ^ (tk & 7)) << 4);
    const uint32_t tag = ptag(s);
    uint4 q[8][2];
#define PLD(k, h) q[k][h] = ld_rlx128<(k) * 32768 + (h) * 16384>(pp)
#define PLD8(h) PLD(0, h); PLD(1, h); PLD(2, h); PLD(3, h); PLD(4, h); PLD(5, h); PLD(6, h); PLD(7, h)
#define PBAD(h) __any_sync(~0u, (or3(xo2(q[0][h].x, q[1][h].x, tag), xo2(q[2][h].x, q[3][h].x, tag), xo2(q[4][h].x, q[5][h].x, tag)) | xo2(q[6][h].x, q[7][h].x, tag)) & ~lane & (PST_ == 8192 ? 1u : 0u))
#define PSUM(f, h, m) (((f(q[0][h].m) + f(q[1][h].m)) + (f(q[2][h].m) + f(q[3][h].m))) + ((f(q[4][h].m) + f(q[5][h].m)) + (f(q[6][h].m) + f(q[7][h].m))))
    const uint32_t eye = (lane >> 2) == 2 * (lane & 3) ? 0x3f80u : (lane >> 2) == 2 * (lane & 3) + 1 ? 0x3f800000u : 0u;
    auto padd = [&](int h) {
      if (FAST) {
        float u[4] = {0.f, 0.f, 0.f, 0.f}, v[4] = {0.f, 0.f, 0.f, 0.f};
#pragma unroll
        for (int k = 0; k < 8; k++) { hmma8(u, q[k][h].x, q[k][h].y, eye); hmma8(v, q[k][h].z, q[k][h].w, eye); }
        x[4 * h] = add2(x[4 * h], pack2(u[0], u[1])); x[4 * h + 1] = add2(x[4 * h + 1], pack2(u[2], u[3]));
        x[4 * h + 2] = add2(x[4 * h + 2], pack2(v[0], v[1])); x[4 * h + 3] = add2(x[4 * h + 3], pack2(v[2], v[3]));
      } else {
        x[4 * h] = add2(x[4 * h], pack2(PSUM(blo, h, x), PSUM(bhi, h, x))); x[4 * h + 1] = add2(x[4 * h + 1], pack2(PSUM(blo, h, y), PSUM(bhi, h, y)));
        x[4 * h + 2] = add2(x[4 * h + 2], pack2(PSUM(blo, h, z), PSUM(bhi, h, z))); x[4 * h + 3] = add2(x[4 * h + 3], pack2(PSUM(blo, h, w), PSUM(bhi, h, w)));
      }
    };
    int guard = 0;
    PLD8(0);
    if (FAST) { PLD8(1); }
    while (PBAD(0)) { if (++guard > (1 << 20)) TRAP(); PLD8(0); }
    padd(0);
    if (!FAST) { PLD8(1); }
    while (PBAD(1)) { if (++guard > (1 << 20)) TRAP(); PLD8(1); }
    padd(1);
  }
  const float c = blo(__shfl_sync(~0u, x[0], 0));
  float s0 = 0.f, s1 = 0.f, q0 = 0.f, q1 = 0.f, r0 = 0.f, r1 = 0.f;
#pragma unroll
  for (int i = 0; i < 8; i++) {
    const float a = blo(x[i]) - c, b = bhi(x[i]) - c;
    s0 += a; s1 += b; q0 = fmaf(a, a, q0); q1 = fmaf(b, b, q1); r0 = fmaf(a, blo(wv[i]), r0); r1 = fmaf(b, bhi(wv[i]), r1);
  }
  s0 += s1; q0 += q1; r0 += r1;
#pragma unroll
  for (int o = 16; o > 0; o >>= 1) { s0 += __shfl_xor_sync(~0u, s0, o); q0 += __shfl_xor_sync(~0u, q0, o); r0 += __shfl_xor_sync(~0u, r0, o); }
  const float dm = s0 * (1.f / 512.f), m = c + dm, var = fmaxf(fmaf(-dm, dm, q0 * (1.f / 512.f)), 0.f);
  const float mb = rbf(m), inv = rcp(rbf(sqrt_fast(rbf(rbf(var) + 1e-5f))));
  const uint32_t nmb = pack2(-mb, -mb);
  const unsigned long long wd = rword(E, tk, fmaf(c - mb, wsum, r0) * inv);
  uint32_t xn[8], x2[8];
#pragma unroll
  for (int i = 0; i < 8; i++) { const uint32_t d = add2(x[i], nmb); xn[i] = pack2(blo(d) * inv, bhi(d) * inv); x2[i] = add2(x[i], xn[i]); }
  if (st == 0) {
    const float mb2 = rbf(fmaf(m - mb, inv, m)), inv2 = rcp(rbf(sqrt_fast(rbf(rbf(var * (1.f + inv) * (1.f + inv)) + 1e-5f))));
    const uint32_t nmb2 = pack2(-mb2, -mb2);
    uint32_t h[8];
#pragma unroll
    for (int i = 0; i < 8; i++) { const uint32_t d2 = add2(x2[i], nmb2); h[i] = pack2(blo(d2) * inv2, bhi(d2) * inv2); }
    store_img(g_h[1][s], tk & 31, h, lane);
  }
  store_row(dst, x2, lane);
  if (wd > best && !(EXPQ_ & (st == 0 ? 1 : 2))) { store_row(req, xn, lane); store_row(req + 512, x, lane); }
  return wd;
}

__device__ __forceinline__ void ffn_slice(uint32_t sb, const bf16* xn, float* yacc, uint32_t* flag, uint32_t E, int t, bool urgent) {
  const int w = t >> 5, g = (t >> 2) & 7;
  if (t == 0 && urgent) sts32(sb + A_BAR + 160, 1);
  { const uint2 u = __ldcg((const uint2*)xn + t); asm volatile("st.shared.v2.u32 [%0], {%1,%2};" :: "r"(sb + A_XN + t * 8), "r"(u.x), "r"(u.y) : "memory"); }
  fence_async_smem();
  bar_sync(4, 128);
  float ga[4], ua[4];
  constexpr uint64_t da = mkdesc(A_WG, 896, 128, 0), db = mkdesc(A_XN, 16, 128, 0);
  wg_fence();
  wgmma_ss8<0, 1, 0>(ga, da, db); wgmma_ss8<0, 1, 0>(ua, da + (A_WU - A_WG) / 16, db);
#pragma unroll
  for (int ks = 1; ks < 32; ks++) { wgmma_ss8<1, 1, 0>(ga, da + ks * 112, db + ks * 2); wgmma_ss8<1, 1, 0>(ua, da + (A_WU - A_WG) / 16 + ks * 112, db + ks * 2); }
  wg_commit(); wg_wait<0>(); reg_fence(ga); reg_fence(ua);
  if ((t & 3) == 0) {
#pragma unroll
    for (int h = 0; h < 2; h++) {
      const float gs = rbf(ga[2 * h]), us = rbf(ua[2 * h]);
      const float v = 16 * w + 8 * h < 56 ? rbf(gs * rcp(1.f + __expf(-gs))) * us : 0.f;
      asm volatile("st.shared.u16 [%0], %1;" :: "r"(sb + A_XN + 1280 + (16 * w + 8 * h + g) * 2), "h"((unsigned short)pack2(v, 0.f)) : "memory");
    }
  }
  fence_async_smem();
  bar_sync(4, 128);
#pragma unroll 1
  for (int j = 0; j < 2; j++) {
    float y[4][4];
    const uint64_t dd = mkdesc(A_WD, 8192, 128, 0) + (uint64_t)(j * 256);
    wg_fence();
#pragma unroll
    for (int m = 0; m < 4; m++) {
      wgmma_ss8<0, 1, 0>(y[m], dd + m * 64, mkdesc(A_XN + 1280, 16, 128, 0));
#pragma unroll
      for (int ks = 1; ks < 4; ks++) wgmma_ss8<1, 1, 0>(y[m], dd + m * 64 + ks * 1024, mkdesc(A_XN + 1280 + ks * 32, 16, 128, 0));
    }
    wg_commit(); wg_wait<0>();
#pragma unroll
    for (int m = 0; m < 4; m++) {
      reg_fence(y[m]);
      if ((t & 3) == 0) { float* o = yacc + j * 256 + m * 64 + 16 * w + g; atomicAdd(o, y[m][0]); atomicAdd(o + 8, y[m][2]); }
    }
  }
  bar_sync(4, 128);
  if (t < 8) { sts32(sb + A_BAR + 160, 0); st_rel(flag + t, E); }
  __syncwarp();
}

__device__ __forceinline__ void ffn_finish(int q, const bf16* req, float r, uint32_t E, int lane, uint32_t* v) {
  uint32_t xn[8];
  load_row(xn, req, lane); load_row(v, req + 512, lane);
  const float rs = rbf(1.f / (1.f + __expf(-rbf(r))));
  wait_all(f_y[q][lane], E);
  float4 y[4];
#pragma unroll
  for (int i = 0; i < 4; i++) y[i] = __ldcg((const float4*)g_y[q] + (i >> 1) * 64 + 2 * lane + (i & 1));
#pragma unroll
  for (int i = 0; i < 4; i++) {
    v[2 * i] = add2(v[2 * i], add2(xn[2 * i], pack2(rbf(y[i].x) * rs, rbf(y[i].y) * rs)));
    v[2 * i + 1] = add2(v[2 * i + 1], add2(xn[2 * i + 1], pack2(rbf(y[i].z) * rs, rbf(y[i].w) * rs)));
  }
}
__global__ void __launch_bounds__(512, 1) aux_kernel(Params p) {
  extern __shared__ __align__(1024) uint8_t sm[];
  const uint32_t sb = smem_u32(sm);
  if ((sb & 0xFFFFFFu) != SBASE) TRAP();
  const int warp = __shfl_sync(~0u, threadIdx.x >> 5, 0);
  const int cta = blockIdx.x;
  const uint32_t E = __shfl_sync(~0u, *(volatile uint32_t*)&g_epoch + 1, 0);
  const uint32_t bars = sb + A_BAR;

  if (cta < 32) {
    const int cg = cta & 3, kg = cta >> 2;
    if (threadIdx.x == 0) {
      for (int i = 0; i < A_NST; i++) { mbar_init(bars + 8 * i, 1); mbar_init(bars + 64 + 8 * i, 2); }
      mbar_init(bars + 128, 8); mbar_init(bars + 136, 8); mbar_init(bars + 144, 1);
      sts32(bars + 160, 0);
      asm volatile("fence.mbarrier_init.release.cluster;" ::: "memory");
    }
    if (warp < 8) {
      asm volatile("setmaxnreg.inc.sync.aligned.u32 176;");
      const int tid = fresh_tid(), lane = tid & 31;
      uint32_t W[32][4];
      stage_weights(sb + A_WD, p.wo + (size_t)kg * 512 * 512 + cg * 128, 512, tid, 256);
      cp_async_wait();
      bar_sync(1, 256);
      load_frags(W, sb + A_WD, warp >> 2, warp & 3, lane);
      bar_sync(2, 512);
      const uint32_t so = sb + A_STG + ((lane >> 4) * 8 + (lane & 7)) * 256 + (((warp * 2 + ((lane >> 3) & 1)) ^ (lane & 7)) << 4);
      const uint32_t tm = lane < 4 ? 0x00010001u : 0u;
      int stage = 0; uint32_t ph = 0, job = 0;
#pragma unroll 1
      for (int T = 0; T < NSTEP; T++) {
#pragma unroll 1
        for (int k = 0; k < 3; k++) {
          const int st = k == 0 ? 0 : 3 - k, s = st == 0 ? T : T - LAG;
          if (s < 0 || s >= NSEG) continue;
          float d[16];
#pragma unroll
          for (int hh = 0; hh < 4; hh++) {
            mbar_wait(bars + 8 * stage, ph);
            while (uni(lds32(bars + 160))) __nanosleep(100);
            const uint64_t db = mkdesc(A_RING, 512, 128, 0) + (uint64_t)(stage * 512);
            wg_fence();
            if (hh == 0) wgmma_rs32<0, 0>(d, W[0], db); else wgmma_rs32<1, 0>(d, W[hh * 8], db);
#pragma unroll
            for (int ks = 1; ks < 8; ks++) wgmma_rs32<1, 0>(d, W[hh * 8 + ks], db + ks * 64);
            wg_commit();
            if (hh > 0) { wg_wait<1>(); if ((tid & 127) == 0) mbar_arrive(bars + 64 + 8 * (stage == 0 ? A_NST - 1 : stage - 1)); }
            if (++stage == A_NST) { stage = 0; ph ^= 1; }
          }
          mbar_wait(bars + 144, (job & 1) ^ 1);
          wg_wait<0>(); reg_fence(d);
          if ((tid & 127) == 0) mbar_arrive(bars + 64 + 8 * (stage == 0 ? A_NST - 1 : stage - 1));
          if (cta == 0 && tid == 0) TSTAMP(6, T, k);
          const uint32_t tv = tm * ptag(s);
#define TG(i) ((pack2(d[2 * (i)], d[2 * (i) + 1]) & ~tm) | tv)
          stmatrix4_t(so, TG(0), pack2(d[2], d[3]), TG(2), pack2(d[6], d[7]));
          stmatrix4_t(so + 4096, TG(4), pack2(d[10], d[11]), TG(6), pack2(d[14], d[15]));
          fence_async_smem();
          __syncwarp();
          if (lane == 0) mbar_arrive(bars + 128 + 8 * (job & 1));
          job++;
        }
      }
    } else if (warp < 12) {
      asm volatile("setmaxnreg.dec.sync.aligned.u32 120;");
      const int tid = fresh_tid(), lane = tid & 31;
      const int w = warp - 8, t = tid - 256;
#pragma unroll 1
      for (int s = cta + 4; s < NSEG; s += 32) {
#pragma unroll 1
        for (int pr = w; pr < 16; pr += 4) input_ln_pair(p.x, s, pr, lane);
        bar_sync(4, 128);
        if (t == 0) st_rel(&f_h1[s], E);
      }
      bar_sync(2, 512);
      { int guard = 0; while (ld_rlx(&f_loaded[cta]) != E) { __nanosleep(200); if (++guard > (1 << 22)) TRAP(); } }
#pragma unroll 1
      for (int i = t; i < 512 * 7; i += 128) {
        const int k = i / 7, pc = i % 7;
        cp_async16(sb + A_WG + (k >> 3) * 896 + pc * 128 + (k & 7) * 16, p.wg + (size_t)k * 1792 + cta * 56 + pc * 8);
        cp_async16(sb + A_WU + (k >> 3) * 896 + pc * 128 + (k & 7) * 16, p.wu + (size_t)k * 1792 + cta * 56 + pc * 8);
        cp_async16(sb + A_WD + (i >> 9) * 8192 + (i & 63) * 128 + ((i >> 6) & 7) * 16, p.wd + (size_t)cta * 56 * 512 + i * 8);
      }
      uint32_t wv[8];
      const float wsum = load_wr(wv, p.wr, lane);
      cp_async_wait();
      fence_async_smem();
      wait_all(&f_zero[lane], E);
      bar_sync(4, 128);
      const int tj = (cta * 4 + w) & 31, st = 1 + ((cta >> 3) & 1), sq = cta >> 4;
      unsigned long long run = 0, run2 = 0, best = 0, hist = 0;
      uint32_t open = 0;
#pragma unroll 1
      for (int i = 0; i <= NSTEP; i++) {
        int tok = -1; const bf16* req = nullptr;
        if (i < NSEG) {
          const int cd = (int)uni(route_step(i, E, lane, run));
          run = __shfl_sync(~0u, run, 0);
          hist = hist << 8 | (uint32_t)(cd + 1);
          if (cd >= 0) { tok = rtok(run); req = g_req1[tok][0]; }
        } else {
          const unsigned long long m = wait_words(f_l2[i - NSEG], E);
          if (m != run2) { run2 = m; tok = rtok(m); req = g_req2[(tok >> 5) < (rtok(run) >> 5) ? 0 : 1][tok][0]; }
        }
        tok = __shfl_sync(~0u, tok, 0);
        if (tok >= 0) {
          if (cta == 0 && t == 0) TSTAMP(8, i, 0);
          ffn_slice(sb, req, g_y[i], f_y[i][cta], E, t, i < NSEG);
          if (cta == 0 && t == 0) TSTAMP(8, i, 1);
        }
        const int s = i - LAG;
        if (s < 0 || i >= NSEG) continue;
        const int cd = (int)((hist >> (8 * LAG)) & 255) - 1;
        if (cd >= 0 && st == 2) best = 0;
        const int ts = rtok(run) >> 5;
        if ((s & 1) == sq) {
          const int tk = s * 32 + tj;
          unsigned long long wd = (unsigned long long)E << 43;
          if (st == 1 ? s < ts || i < NSEG - 1 : s >= ts) {
            if (st == 2 && cd == tj) wait_eq(&f_hc[s], E);
            wd = token_post<false>(st, tk, st == 2 && cd == tj ? g_x2c[s] : g_x2 + (size_t)tk * 512,
                                   (st == 2 || s < ts ? p.out : g_n) + (size_t)tk * 512, g_req2[st - 1][tk][0], best, wv, wsum, E, lane);
            best = max(best, wd);
            if (st == 1 && s >= ts) open |= 1u << (s >> 1);
          }
          __syncwarp();
          if (lane < 4) st_rel64(&f_w2[st - 1][s][tj][lane], wd);
          __syncwarp();
        }
        if (st == 1) {
          if (i == NSEG - 1 && t == 0 && cta == 0) GSTAMP(1, 0);
#pragma unroll 1
          for (int n = i == NSEG - 1 ? 32 : 2; n > 0 && open; n--) {
            const int s0 = 2 * (__ffs(open) - 1) + sq;
            if (s0 >= ts) break;
            open &= open - 1;
            uint32_t v[8];
            load_row(v, g_n + (size_t)(s0 * 32 + tj) * 512, lane);
            wait_words(f_w2[1][s0][tj], E);
            store_row(p.out + (size_t)(s0 * 32 + tj) * 512, v, lane);
          }
          if (i == NSEG - 1) {
            __syncwarp();
            if (lane == 0) st_rel(&f_cp[sq * 32 + tj], E);
            if (t == 0 && cta == 0) GSTAMP(1, 3);
          }
        }
      }
    } else {
      asm volatile("setmaxnreg.dec.sync.aligned.u32 40;");
      const int tid = fresh_tid(), lane = tid & 31;
      const int t = tid - 384, w = warp - 12;
      for (int i = cta * 128 + t; i < (NSTEP + 1) * 128; i += 4096) ((float4*)&g_y[0][0])[i] = make_float4(0.f, 0.f, 0.f, 0.f);
      bar_sync(3, 128);
      if (t == 0) st_rel(&f_zero[cta], E);
      bar_sync(2, 512);
      if (w == 0) {
        int stage = 0; uint32_t ph = 1;
#pragma unroll 1
        for (int T = 0; T < NSTEP; T++) {
#pragma unroll 1
          for (int k = 0; k < 3; k++) {
            const int st = k == 0 ? 0 : 3 - k, s = st == 0 ? T : T - LAG;
            if (s < 0 || s >= NSEG) continue;
            const uint32_t* fl = f_o[T][kg][st * 4 + (lane & 3)];
            uint32_t ready = 0; int guard = 0;
#pragma unroll 1
            for (int hh = 0; hh < 4; hh++) {
              while (!((ready >> hh) & 1)) {
                ready = __ballot_sync(~0u, ld_rlx(fl) == E);
                if (++guard > (1 << 23)) TRAP();
              }
              fence_async_glob();
              mbar_wait(bars + 64 + 8 * stage, ph);
              e_expect(bars + 8 * stage, OLOAD_);
              e_g2s(sb + A_RING + stage * 8192, g_o[st][s % ORING][kg * 4 + hh], OLOAD_, bars + 8 * stage);
              if (++stage == A_NST) { stage = 0; ph ^= 1; }
            }
          }
          if (cta == 0 && lane == 0) TSTAMP(3, T, 0);
        }
      } else if (w < 3) {
        uint32_t job = 0;
#pragma unroll 1
        for (int T = 0; T < NSTEP; T++) {
#pragma unroll 1
          for (int k = 0; k < 3; k++) {
            const int st = k == 0 ? 0 : 3 - k, s = st == 0 ? T : T - LAG;
            if (s < 0 || s >= NSEG) continue;
            if ((job++ & 1) != w - 1) continue;
            if (s >= PRING) wait_words(st == 0 ? f_h2[s - PRING][lane & 3] : f_w2[st - 1][s - PRING][lane], E);
            mbar_wait(bars + 128 + 8 * (w - 1), ((job - 1) >> 1) & 1);
            if (cta == 0 && st == 0) TSTAMP(7, s, 0);
            e_s2g(g_pp[st][s % PRING] + cta * 8192, sb + A_STG, PST_);
            asm volatile("cp.async.bulk.commit_group;\n cp.async.bulk.wait_group.read 0;" ::: "memory");
            __syncwarp();
            e_arrive(bars + 144);
            if (!HINT_) bulk_wait();
            __syncwarp();
            if (lane < 8) st_rlx(&f_acc[st][s][cta][lane], E);
            __syncwarp();
            if (cta == 0 && st == 0) TSTAMP(7, s, 1);
          }
        }
        bulk_wait();
      }
    }
  } else {
    const int tid = fresh_tid(), lane = tid & 31;
    const int qd = cta - 32;
    input_ln_pair(p.x, qd, warp, lane);
    bar_sync(6, 512);
    if (tid == 0) st_rel(&f_h1[qd], E);
    volatile int* bc = (volatile int*)sm;
    if (warp == 15) {
      unsigned long long run = 0;
      wait_all(&f_zero[lane], E);
      unsigned long long b2[2][2] = {{0, 0}, {0, 0}};
      auto track = [&](int s) {
#pragma unroll
        for (int k = 0; k < 2; k++) {
          const unsigned long long m = warp_max<16>(wait_words(f_w2[k][s][lane], E));
          if (lane == (s & 31)) { if (s < 32) b2[k][0] = m; else b2[k][1] = m; }
        }
      };
#pragma unroll 1
      for (int s = 0; s < NSEG; s++) {
        const int cd = route_step(s, E, lane, run);
        if (cd >= 0 && qd == (s & 1)) {
          uint32_t v[1][8], h[1][8];
          ffn_finish(s, g_req1[s * 32 + cd][0], rscore(run), E, lane, v[0]);
          if (lane == 0) TSTAMP(8, s, 2);
          ln_rows<1>(v, h);
#pragma unroll
          for (int i = 0; i < 8; i++) st_rlx64(&g_hc[s][(i >> 2) * 128 + 4 * lane + (i & 3)], h[0][i], E);
          if (lane == 0) TSTAMP(8, s, 3);
          store_row(g_x2c[s], v[0], lane);
          __syncwarp();
          if (lane == 0) st_rel(&f_hc[s], E);
        }
        if (qd == 2 && s > LAG) track(s - LAG - 1);
      }
      wait_eq(&f_hc[rtok(run) >> 5], E);
      if (lane == 0) *bc = rtok(run);
      bar_sync(7, 288);
      if (qd == 2) {
        uint32_t v[8];
        const int ts = rtok(run) >> 5;
        track(NSEG - LAG - 1);
        run = 0;
#pragma unroll 1
        for (int k = 0; k <= LAG; k++) {
          const int s = NSEG - LAG - 1 + k;
          const unsigned long long m = warp_max<16>(k == 0 ? max(lane < ts ? b2[0][0] : b2[1][0], lane + 32 < ts ? b2[0][1] : b2[1][1])
                                                           : wait_words(f_w2[s < ts ? 0 : 1][s][lane], E));
          const bool lead = m > run;
          if (lead) { run = m; __threadfence(); }
          if (lane < 4) st_rlx64(&f_l2[k][lane], (uint32_t)run, (uint32_t)(run >> 32));
          if (lead) ffn_finish(NSEG + k, g_req2[(rtok(run) >> 5) < ts ? 0 : 1][rtok(run)][0], rscore(run), E, lane, v);
          if (k == 0) { wait_all(&f_cp[lane], E); wait_all(&f_cp[32 + lane], E); }
        }
        if (lane == 0) GSTAMP(1, 1);
        store_row(p.out + (size_t)rtok(run) * 512, v, lane);
        if (lane == 0) GSTAMP(1, 2);
        asm volatile("griddepcontrol.wait;" ::: "memory");
        if (lane == 0) *(volatile uint32_t*)&g_epoch = E;
      }
    } else if (warp < 8) {
      uint32_t wv[8];
      const float wsum = load_wr(wv, p.wr, lane);
      unsigned long long best = 0;
      int ttok = 0;
#pragma unroll 1
      for (int i = 0; i < NSTEP; i++) {
        const bool last = i >= NSEG;
        if (i == NSEG) { bar_sync(7, 288); ttok = *bc; best = 0; }
        const int s = last ? i - LAG : i, st = !last ? 0 : s < (ttok >> 5) ? 1 : 2;
        const int tk = s * 32 + qd * 8 + warp;
        const unsigned long long wd = token_post<true>(st, tk, !last ? p.x + (size_t)tk * 512 : tk == ttok ? g_x2c[s] : g_x2 + (size_t)tk * 512,
                                                 (last ? p.out : g_x2) + (size_t)tk * 512, last ? g_req2[st - 1][tk][0] : g_req1[tk][0], best, wv, wsum, E, lane);
        best = max(best, wd);
        volatile unsigned long long* ws = (volatile unsigned long long*)(sm + 64) + (i & 1) * 8;
        if (lane == 0) ws[warp] = wd;
        bar_sync(5, 256);
        if (warp == 0) {
          if (qd == 0 && lane == 0) TSTAMP(4, i, 1);
          if (!last) { const unsigned long long m = warp_max<4>(ws[lane & 7]); if (lane < 4) st_rel64(&f_h2[s][qd][lane], m); }
          else {
            st_rel64(&f_w2[st - 1][s][qd * 8 + (lane >> 2)][lane & 3], ws[lane >> 2]);
            asm volatile("st.relaxed.gpu.global.u64 [%0], %1;" :: "l"(&f_w2[2 - st][s][qd * 8 + (lane >> 2)][lane & 3]), "l"((unsigned long long)E << 43) : "memory");
          }
          if (qd == 0 && lane == 0) TSTAMP(4, i, 2);
        }
        __syncwarp();
      }
    }
  }
}

}

extern "C" void kernel_launch(void* const* d_in, const int* in_sizes, int n_in, void* d_out, int out_size) {
  (void)in_sizes; (void)n_in; (void)out_size;
  static bool init = false;
  if (!init) {
    cudaFuncSetAttribute(main_kernel, cudaFuncAttributeMaxDynamicSharedMemorySize, M_TOTAL);
    cudaFuncSetAttribute(aux_kernel, cudaFuncAttributeMaxDynamicSharedMemorySize, A_TOTAL);
    init = true;
  }
  Params p;
  p.x = (const bf16*)d_in[0]; p.mem0 = (const bf16*)d_in[1]; p.wq = (const bf16*)d_in[2]; p.wk = (const bf16*)d_in[3];
  p.wv = (const bf16*)d_in[4]; p.wo = (const bf16*)d_in[5]; p.wr = (const bf16*)d_in[8]; p.wg = (const bf16*)d_in[9];
  p.wu = (const bf16*)d_in[10]; p.wd = (const bf16*)d_in[11]; p.out = (bf16*)d_out; p.zero = 0; p.zero2 = 0;
  cudaStream_t st = cudaStreamPerThread;
  main_kernel<<<96, 512, M_TOTAL, st>>>(p);
  cudaLaunchConfig_t cfg = {};
  cfg.gridDim = dim3(36); cfg.blockDim = dim3(512); cfg.dynamicSmemBytes = A_TOTAL; cfg.stream = st;
  cudaLaunchAttribute at[1];
  at[0].id = cudaLaunchAttributeProgrammaticStreamSerialization; at[0].val.programmaticStreamSerializationAllowed = 1;
  cfg.attrs = at; cfg.numAttrs = 1;
  cudaLaunchKernelEx(&cfg, aux_kernel, p);
}
```

```cpp
#include <cuda_runtime.h>
#include <cuda_bf16.h>
#include <stdint.h>

namespace {

typedef __nv_bfloat16 bf16;

constexpr int NSEG = 64;
#define LAG_ 5
constexpr int LAG = LAG_;
constexpr int NSTEP = NSEG + LAG;
constexpr int ORING = 8, PRING = 4;
#define E1_ 10
#define E2_ 0
#define E3_ 10
constexpr int E1 = E1_, E2 = E2_, E3 = E3_, EA = E1 + E2 + E3;
static_assert(EA % 4 == 0 && EA > 0 && EA < 32 && E1 > 0, "early part: whole 64-column chunks");
#define RW_ 176
#define RA_ 136
#define RC_ 24
#define STR2(x) #x
#define STR(x) STR2(x)
#define RED_ 30
#define ARR_ 7
#define PAUSE_ 19
#define PD1_ 4
#define PST2_ 2
#define PGR_ PD1_
#define PVR_ -1
#define SALT_ 0
#define KP1_ 1
#define PRIV_ 1
#define OLOAD_ 8192
#define PST_ 8192
#define ALT_ 1
#define TQ_ 1
#define NOF_ 2
#define EXPQ_ 0
#define XT1_ 8192
#define XT2_ 4096
#define XO_ 8192
#define HINT_ 24
#define HADD_ 2
#define HAND_ 4
#define GO3_ 2
#define NPROBE_ 6
#define TP(i, v) (v)
#define XDLY_ TP(0, 2250)
#define YDLY_ TP(1, 3400)
#define X1_ TP(2, 100)
#define X2_ TP(3, 250)
#define Y1_ TP(4, 150)
#define Y2_ TP(5, 200)
#define HGAP_ TP(6, 50)
#define TGAP_ TP(7, 200)
#define ADLY_ TP(8, 600)
#define ODLY_ TP(9, 2800)
#define LDLY_ TP(10, 3800)
#define LGAP_ 200
#define HDLY_ TP(11, 0)
#define TDLY_ TP(15, 4050)
#define SDLY_ TP(12, 800)
#define AGAP_ 100
#define BOFF_ TP(13, 200)
#define YOFF_ TP(16, 150)
#define YUP_ TP(20, 40)
#define YDN_ TP(21, 4)
#define CDLY_ TP(17, 300)
#define SLOW0_ TP(18, 400)
#define SLOW1_ TP(19, 300)
#define KDLY_ TP(14, 300)
__device__ uint32_t g_epoch;
__device__ __align__(1024) uint8_t g_h[2][NSEG][32768];
__device__ __align__(128) uint2 g_hc[NSEG][256];
__device__ __align__(128) bf16 g_x2[2048 * 512];
__device__ __align__(128) bf16 g_x2c[NSEG][512];
__device__ __align__(128) uint8_t g_o[3][ORING][32][8192];
__device__ __align__(128) uint8_t g_pp[3][PRING][8 * 32768];
__device__ __align__(128) bf16 g_n[2048 * 512];
__device__ __align__(128) uint8_t g_xch[96 * 16384 + 65536 + 8192];
__device__ __align__(128) bf16 g_req1[2048][2][512];
__device__ __align__(128) bf16 g_req2[2][2048][2][512];
__device__ __align__(128) float g_y[NSTEP + 1][512];
__device__ __align__(128) uint8_t g_tok[96][2][16384];
__device__ uint32_t f_choice[96][2], f_loaded[32];
__device__ uint32_t f_h1[NSEG], f_hc[NSEG];
__device__ __align__(128) unsigned long long f_h2[NSEG][4][4];
__device__ __align__(128) unsigned long long f_w2[2][NSEG][32][4];
__device__ __align__(128) unsigned long long f_l2[LAG + 1][4];
__device__ __align__(128) uint32_t f_o[NSTEP][8][12][8];
__device__ __align__(128) uint32_t f_acc[3][NSEG][32][8], f_y[NSTEP + 1][32][8], f_zero[32], f_cp[64];
__device__ __align__(128) unsigned long long g_sync[2][96][4];

#define TRAP() __trap()
__device__ __forceinline__ uint32_t smem_u32(const void* p) { return (uint32_t)__cvta_generic_to_shared(p); }
__device__ __forceinline__ int fresh_tid() { const int t = threadIdx.x; return __shfl_sync(~0u, t, t & 31); }
__device__ __forceinline__ unsigned long long gtime64() { unsigned long long t; asm volatile("mov.u64 %0, %%globaltimer;" : "=l"(t) :: "memory"); return t; }
__device__ __forceinline__ uint32_t clk() { unsigned long long c; asm volatile("mov.u64 %0, %%clock64;" : "=l"(c) :: "memory"); return (uint32_t)c; }
__device__ __forceinline__ void wait_until(uint32_t t) {
  while ((int)(t - clk()) > 450) __nanosleep(32);
  uint32_t c;
  do { asm volatile("mov.u32 %0, %%clock;" : "=r"(c) :: "memory"); } while ((int)(c - t) < 0);
}
__device__ __forceinline__ void mbar_init(uint32_t bar, uint32_t cnt) { asm volatile("mbarrier.init.shared::cta.b64 [%0], %1;" :: "r"(bar), "r"(cnt) : "memory"); }
__device__ __forceinline__ void mbar_arrive(uint32_t bar) { asm volatile("mbarrier.arrive.shared::cta.b64 _, [%0];" :: "r"(bar) : "memory"); }
__device__ __forceinline__ void mbar_arrive_remote(uint32_t bar) { asm volatile("mbarrier.arrive.relaxed.cluster.shared::cluster.b64 _, [%0];" :: "r"(bar) : "memory"); }
__device__ __forceinline__ void mbar_expect(uint32_t bar, uint32_t bytes) { asm volatile("mbarrier.arrive.expect_tx.shared::cta.b64 _, [%0], %1;" :: "r"(bar), "r"(bytes) : "memory"); }
__device__ __forceinline__ bool mbar_try(uint32_t bar, uint32_t parity) {
  uint32_t ok;
  asm volatile("{.reg .pred p; mbarrier.try_wait.parity.shared::cta.b64 p, [%1], %2; selp.u32 %0, 1, 0, p;}" : "=r"(ok) : "r"(bar), "r"(parity) : "memory");
  return ok;
}
__device__ __forceinline__ bool mbar_test(uint32_t bar, uint32_t parity) {
  uint32_t ok;
  asm volatile("{.reg .pred p; mbarrier.test_wait.parity.shared::cta.b64 p, [%1], %2; selp.u32 %0, 1, 0, p;}" : "=r"(ok) : "r"(bar), "r"(parity) : "memory");
  return ok;
}
__device__ __forceinline__ void mbar_wait(uint32_t bar, uint32_t parity) {
  asm volatile("{\n.reg .pred p;\nWAIT:\nmbarrier.try_wait.parity.shared::cta.b64 p, [%0], %1;\n@!p bra WAIT;\n}" :: "r"(bar), "r"(parity) : "memory");
}
__device__ __forceinline__ uint32_t ld_acq(const uint32_t* p) { uint32_t v; asm volatile("ld.acquire.gpu.global.u32 %0, [%1];" : "=r"(v) : "l"(p) : "memory"); return v; }
__device__ __forceinline__ unsigned long long ld_acq64(const unsigned long long* p) { unsigned long long v; asm volatile("ld.acquire.gpu.global.u64 %0, [%1];" : "=l"(v) : "l"(p) : "memory"); return v; }
__device__ __forceinline__ void st_rel(uint32_t* p, uint32_t v) { asm volatile("st.release.gpu.global.u32 [%0], %1;" :: "l"(p), "r"(v) : "memory"); }
__device__ __forceinline__ void st_rel64(unsigned long long* p, unsigned long long v) { asm volatile("st.release.gpu.global.u64 [%0], %1;" :: "l"(p), "l"(v) : "memory"); }
__device__ __forceinline__ void red_rel(uint32_t* p, uint32_t v) { asm volatile("red.release.gpu.global.add.u32 [%0], %1;" :: "l"(p), "r"(v) : "memory"); }
__device__ __forceinline__ uint32_t ld_rlx(const uint32_t* p) { uint32_t v; asm volatile("ld.relaxed.gpu.global.u32 %0, [%1];" : "=r"(v) : "l"(p) : "memory"); return v; }
__device__ __forceinline__ unsigned long long ld_rlxu64(const unsigned long long* p) { unsigned long long v; asm volatile("ld.relaxed.gpu.global.u64 %0, [%1];" : "=l"(v) : "l"(p) : "memory"); return v; }
__device__ __forceinline__ void st_rlx(uint32_t* p, uint32_t v) { asm volatile("st.relaxed.gpu.global.u32 [%0], %1;" :: "l"(p), "r"(v) : "memory"); }
__device__ __forceinline__ void bulk_wait() { asm volatile("cp.async.bulk.commit_group;\n cp.async.bulk.wait_group 0;" ::: "memory"); }
__device__ __forceinline__ void fence_acq() { asm volatile("fence.acquire.gpu;" ::: "memory"); }
__device__ __forceinline__ void wait_all(const uint32_t* p, uint32_t v, bool acquire = true) {
  int guard = 0;
  while (!__all_sync(~0u, ld_rlx(p) == v)) { __nanosleep(32); if (++guard > (1 << 22)) TRAP(); }
  if (acquire) fence_acq();
}
__device__ __forceinline__ void wait_eq(const uint32_t* p, uint32_t v) {
  int guard = 0;
  while (ld_rlx(p) != v) { __nanosleep(64); if (++guard > (1 << 22)) TRAP(); }
  fence_acq();
}
__device__ __forceinline__ unsigned long long rword(uint32_t E, int tok, float r) {
  uint32_t u = __float_as_uint(r + 0.f);
  u = r != r ? 0u : (u >> 31) ? ~u : u | 0x80000000u;
  return (unsigned long long)(E & 0x1FFFFFu) << 43 | (unsigned long long)u << 11 | (uint32_t)(2047 - tok);
}
__device__ __forceinline__ int rtok(unsigned long long v) { return 2047 - (int)(v & 2047u); }
__device__ __forceinline__ float rscore(unsigned long long v) { const uint32_t u = (uint32_t)(v >> 11); return __uint_as_float((u >> 31) ? u & 0x7fffffffu : ~u); }
__device__ __forceinline__ bool rfresh(unsigned long long v, uint32_t E) { return (uint32_t)(v >> 43) == (E & 0x1FFFFFu); }
template <int TOP> __device__ __forceinline__ unsigned long long warp_max(unsigned long long v) {
#pragma unroll
  for (int o = TOP; o > 0; o >>= 1) { const unsigned long long ov = __shfl_xor_sync(~0u, v, o); v = ov > v ? ov : v; }
  return v;
}
template <int off> __device__ __forceinline__ uint2 ld_rlx64(const void* p) { unsigned long long v; asm volatile("ld.relaxed.gpu.global.b64 %0, [%1+%2];" : "=l"(v) : "l"(p), "n"(off) : "memory"); return make_uint2((uint32_t)v, (uint32_t)(v >> 32)); }
template <int off> __device__ __forceinline__ uint4 ld_rlx128(const void* p) {
  unsigned long long a, b; asm volatile("ld.relaxed.gpu.global.v2.b64 {%0,%1}, [%2+%3];" : "=l"(a), "=l"(b) : "l"(p), "n"(off) : "memory");
  return make_uint4((uint32_t)a, (uint32_t)(a >> 32), (uint32_t)b, (uint32_t)(b >> 32));
}
__device__ __forceinline__ void st_rlx64(void* p, uint32_t lo, uint32_t hi) { asm volatile("{.reg .b64 t; mov.b64 t, {%1,%2}; st.relaxed.gpu.global.b64 [%0], t;}" :: "l"(p), "r"(lo), "r"(hi) : "memory"); }
__device__ __forceinline__ void cp_async16(uint32_t dst, const void* src) { asm volatile("cp.async.cg.shared.global [%0], [%1], 16;" :: "r"(dst), "l"(src) : "memory"); }
__device__ __forceinline__ void cp_async_wait() { asm volatile("cp.async.wait_all;" ::: "memory"); }
__device__ __forceinline__ void fence_async_smem() { asm volatile("fence.proxy.async.shared::cta;" ::: "memory"); }
__device__ __forceinline__ void fence_async_glob() { asm volatile("fence.proxy.async.global;" ::: "memory"); }
__device__ __forceinline__ void fence_async_acq() { asm volatile("fence.proxy.async::generic.acquire.sync_restrict::shared::cluster.cluster;" ::: "memory"); }
__device__ __forceinline__ float ex2(float x) { float y; asm("ex2.approx.ftz.f32 %0, %1;" : "=f"(y) : "f"(x)); return y; }
__device__ __forceinline__ float sqrt_fast(float x) { float y; asm("sqrt.approx.ftz.f32 %0, %1;" : "=f"(y) : "f"(x)); return y; }
__device__ __forceinline__ float rcp(float x) { float y; asm("rcp.approx.ftz.f32 %0, %1;" : "=f"(y) : "f"(x)); return y; }
__device__ __forceinline__ void bar_sync(int id, int n) { asm volatile("bar.sync %0, %1;" :: "r"(id), "r"(n) : "memory"); }
__device__ __forceinline__ bool bar_or(int id, int n, bool v) {
  uint32_t r;
  asm volatile("{.reg .pred p, q; setp.ne.u32 p, %3, 0; barrier.cta.red.or.aligned.pred q, %1, %2, p; selp.u32 %0, 1, 0, q;}" : "=r"(r) : "r"(id), "r"(n), "r"((uint32_t)v) : "memory");
  return r;
}
__device__ __forceinline__ uint32_t mapa(uint32_t a, uint32_t rank) { uint32_t r; asm volatile("mapa.shared::cluster.u32 %0, %1, %2;" : "=r"(r) : "r"(a), "r"(rank)); return r; }
__device__ __forceinline__ void cluster_sync() { asm volatile("barrier.cluster.arrive.release.aligned; barrier.cluster.wait.acquire.aligned;" ::: "memory"); }
__device__ __forceinline__ void st_async32(uint32_t dst, uint32_t v, uint32_t bar) { asm volatile("st.async.shared::cluster.mbarrier::complete_tx::bytes.b32 [%0], %1, [%2];" :: "r"(dst), "r"(v), "r"(bar) : "memory"); }
__device__ __forceinline__ void bulk_g2s(uint32_t dst, const void* src, uint32_t bytes, uint32_t bar) {
  asm volatile("cp.async.bulk.shared::cluster.global.mbarrier::complete_tx::bytes [%0], [%1], %2, [%3];" :: "r"(dst), "l"(src), "r"(bytes), "r"(bar) : "memory");
}
__device__ __forceinline__ void bulk_g2s_mc(uint32_t dst, const void* src, uint32_t bytes, uint32_t bar, uint16_t mask) {
  asm volatile("cp.async.bulk.shared::cluster.global.mbarrier::complete_tx::bytes.multicast::cluster [%0], [%1], %2, [%3], %4;"
               :: "r"(dst), "l"(src), "r"(bytes), "r"(bar), "h"(mask) : "memory");
}
__device__ __forceinline__ void bulk_s2c(uint32_t dst, uint32_t src, uint32_t bytes, uint32_t bar) {
  asm volatile("cp.async.bulk.shared::cluster.shared::cta.mbarrier::complete_tx::bytes [%0], [%1], %2, [%3];" :: "r"(dst), "r"(src), "r"(bytes), "r"(bar) : "memory");
}
__device__ __forceinline__ void bulk_s2g(void* dst, uint32_t src, uint32_t bytes) {
  asm volatile("cp.async.bulk.global.shared::cta.bulk_group [%0], [%1], %2;" :: "l"(dst), "r"(src), "r"(bytes) : "memory");
}
#define ELECT(op) "{.reg .pred p; elect.sync _|p, 0xffffffff; @p " op "}"
__device__ __forceinline__ void e_arrive(uint32_t bar) { asm volatile(ELECT("mbarrier.arrive.shared::cta.b64 _, [%0];") :: "r"(bar) : "memory"); }
__device__ __forceinline__ void e_expect(uint32_t bar, uint32_t bytes) { asm volatile(ELECT("mbarrier.arrive.expect_tx.shared::cta.b64 _, [%0], %1;") :: "r"(bar), "r"(bytes) : "memory"); }
__device__ __forceinline__ void e_g2s(uint32_t dst, const void* src, uint32_t bytes, uint32_t bar) {
  asm volatile(ELECT("cp.async.bulk.shared::cluster.global.mbarrier::complete_tx::bytes [%0], [%1], %2, [%3];") :: "r"(dst), "l"(src), "r"(bytes), "r"(bar) : "memory");
}
__device__ __forceinline__ void e_mc(uint32_t dst, const void* src, uint32_t bytes, uint32_t bar, uint16_t mask) {
  asm volatile(ELECT("cp.async.bulk.shared::cluster.global.mbarrier::complete_tx::bytes.multicast::cluster [%0], [%1], %2, [%3], %4;")
               :: "r"(dst), "l"(src), "r"(bytes), "r"(bar), "h"(mask) : "memory");
}
__device__ __forceinline__ void e_s2g(void* dst, uint32_t src, uint32_t bytes) {
  asm volatile(ELECT("cp.async.bulk.global.shared::cta.bulk_group [%0], [%1], %2;") :: "l"(dst), "r"(src), "r"(bytes) : "memory");
}
__device__ __forceinline__ void e_st_rel(uint32_t* p, uint32_t v) { asm volatile(ELECT("st.release.gpu.global.u32 [%0], %1;") :: "l"(p), "r"(v) : "memory"); }
__device__ __forceinline__ uint32_t clk32() { uint32_t c; asm volatile("mov.u32 %0, %%clock;" : "=r"(c) :: "memory"); return c; }
__device__ __forceinline__ void spin_until(uint32_t t) { while ((int)(clk32() - t) < 0) {} }
__device__ __forceinline__ uint32_t uni(uint32_t v) { return __shfl_sync(~0u, v, 0); }
__device__ __forceinline__ uint32_t pack2(float lo, float hi) { uint32_t r; asm("cvt.rn.bf16x2.f32 %0, %1, %2;" : "=r"(r) : "f"(hi), "f"(lo)); return r; }
__device__ __forceinline__ uint32_t add2(uint32_t a, uint32_t b) { uint32_t r; asm("add.rn.bf16x2 %0, %1, %2;" : "=r"(r) : "r"(a), "r"(b)); return r; }
__device__ __forceinline__ float rbf(float x) { return __bfloat162float(__float2bfloat16_rn(x)); }
__device__ __forceinline__ float blo(uint32_t u) { return __uint_as_float(u << 16); }
__device__ __forceinline__ float bhi(uint32_t u) { return __uint_as_float(u & 0xffff0000u); }
__device__ __forceinline__ uint32_t gentag(uint32_t g) { return (g & 1u) | (g & 2u) << 15; }
__device__ __forceinline__ uint32_t pack2_tag(float lo, float hi, uint32_t tag) {
  const uint32_t u = __byte_perm(__float_as_uint(lo), __float_as_uint(hi), 0x7632);
  return u + ((u ^ tag) & 0x10001u);
}
__device__ __forceinline__ uint32_t xo2(uint32_t a, uint32_t b, uint32_t t) { uint32_t r; asm("lop3.b32 %0, %1, %2, %3, 0x7e;" : "=r"(r) : "r"(a), "r"(b), "r"(t)); return r; }
__device__ __forceinline__ uint32_t or3(uint32_t a, uint32_t b, uint32_t c) { uint32_t r; asm("lop3.b32 %0, %1, %2, %3, 0xfe;" : "=r"(r) : "r"(a), "r"(b), "r"(c)); return r; }
__device__ __forceinline__ void stmatrix4(uint32_t a, uint32_t r0, uint32_t r1, uint32_t r2, uint32_t r3) {
  asm volatile("stmatrix.sync.aligned.m8n8.x4.shared.b16 [%0], {%1,%2,%3,%4};" :: "r"(a), "r"(r0), "r"(r1), "r"(r2), "r"(r3) : "memory");
}
__device__ __forceinline__ void stmatrix4_t(uint32_t a, uint32_t r0, uint32_t r1, uint32_t r2, uint32_t r3) {
  asm volatile("stmatrix.sync.aligned.m8n8.x4.trans.shared.b16 [%0], {%1,%2,%3,%4};" :: "r"(a), "r"(r0), "r"(r1), "r"(r2), "r"(r3) : "memory");
}
__device__ __forceinline__ void ldmatrix4_t(uint32_t* r, uint32_t a) {
  asm volatile("ldmatrix.sync.aligned.m8n8.x4.trans.shared.b16 {%0,%1,%2,%3}, [%4];" : "=r"(r[0]), "=r"(r[1]), "=r"(r[2]), "=r"(r[3]) : "r"(a) : "memory");
}
__device__ __forceinline__ void ldmatrix4(uint32_t* r, uint32_t a) {
  asm volatile("ldmatrix.sync.aligned.m8n8.x4.shared.b16 {%0,%1,%2,%3}, [%4];" : "=r"(r[0]), "=r"(r[1]), "=r"(r[2]), "=r"(r[3]) : "r"(a) : "memory");
}
__device__ __forceinline__ void hmma16(float* c, const uint32_t* a, uint32_t b0, uint32_t b1) {
  asm volatile("mma.sync.aligned.m16n8k16.row.col.f32.bf16.bf16.f32 {%0,%1,%2,%3}, {%4,%5,%6,%7}, {%8,%9}, {%0,%1,%2,%3};"
               : "+f"(c[0]), "+f"(c[1]), "+f"(c[2]), "+f"(c[3]) : "r"(a[0]), "r"(a[1]), "r"(a[2]), "r"(a[3]), "r"(b0), "r"(b1));
}
__device__ __forceinline__ void hmma8(float* c, uint32_t a0, uint32_t a1, uint32_t b0) {
  asm volatile("mma.sync.aligned.m16n8k8.row.col.f32.bf16.bf16.f32 {%0,%1,%2,%3}, {%4,%5}, {%6}, {%0,%1,%2,%3};"
               : "+f"(c[0]), "+f"(c[1]), "+f"(c[2]), "+f"(c[3]) : "r"(a0), "r"(a1), "r"(b0));
}
__device__ __forceinline__ uint4 lds128(uint32_t a) { uint4 v; asm volatile("ld.shared.v4.u32 {%0,%1,%2,%3}, [%4];" : "=r"(v.x), "=r"(v.y), "=r"(v.z), "=r"(v.w) : "r"(a) : "memory"); return v; }
__device__ __forceinline__ void sts128(uint32_t a, uint4 v) { asm volatile("st.shared.v4.u32 [%0], {%1,%2,%3,%4};" :: "r"(a), "r"(v.x), "r"(v.y), "r"(v.z), "r"(v.w) : "memory"); }
__device__ __forceinline__ void sts128f(uint32_t a, float x, float y, float z, float w) { asm volatile("st.shared.v4.f32 [%0], {%1,%2,%3,%4};" :: "r"(a), "f"(x), "f"(y), "f"(z), "f"(w) : "memory"); }
__device__ __forceinline__ void sts64f(uint32_t a, float x, float y) { asm volatile("st.shared.v2.f32 [%0], {%1,%2};" :: "r"(a), "f"(x), "f"(y) : "memory"); }
__device__ __forceinline__ uint32_t lds32(uint32_t a) { uint32_t v; asm volatile("ld.shared.u32 %0, [%1];" : "=r"(v) : "r"(a) : "memory"); return v; }
__device__ __forceinline__ void sts32(uint32_t a, uint32_t v) { asm volatile("st.shared.u32 [%0], %1;" :: "r"(a), "r"(v) : "memory"); }

constexpr uint32_t SBASE = 1024;
__host__ __device__ constexpr uint64_t mkdesc(uint32_t off, uint32_t lbo, uint32_t sbo, uint32_t swz) {
  return (uint64_t)(((SBASE + off) & 0x3FFFF) >> 4) | ((uint64_t)(lbo >> 4) << 16) | ((uint64_t)(sbo >> 4) << 32) | ((uint64_t)swz << 62);
}
__device__ __forceinline__ void wg_fence() { asm volatile("wgmma.fence.sync.aligned;" ::: "memory"); }
__device__ __forceinline__ void wg_commit() { asm volatile("wgmma.commit_group.sync.aligned;" ::: "memory"); }
template <int N> __device__ __forceinline__ void wg_wait() { asm volatile("wgmma.wait_group.sync.aligned %0;" :: "n"(N) : "memory"); }

template <int N> __device__ __forceinline__ void reg_fence(float (&d)[N], int n = N) {
#pragma unroll
  for (int i = 0; i < N; i++) if (i < n) asm volatile("" : "+f"(d[i]) :: "memory");
}
#define F4(b) "+f"(d[b]), "+f"(d[b + 1]), "+f"(d[b + 2]), "+f"(d[b + 3])
#define F8(b) F4(b), F4(b + 4)
#define F16(b) F8(b), F8(b + 8)
#define G4(b) "=f"(d[b]), "=f"(d[b + 1]), "=f"(d[b + 2]), "=f"(d[b + 3])
#define G8(b) G4(b), G4(b + 4)
#define G16(b) G8(b), G8(b + 8)
#define RS_IN "r"(a[0]), "r"(a[1]), "r"(a[2]), "r"(a[3]), "l"(db), "n"(SD), "n"(TB)
#define SS_IN "l"(da), "l"(db), "n"(SD), "n"(TA), "n"(TB)
#define WG_OP(str, out0, out1, in) do { if (SD || KEEP) asm volatile(str : out1 : in); else asm volatile(str : out0 : in); } while (0)
#define O12(X) X##8(0), X##4(8)
#define O20(X) X##16(0), X##4(16)
#define O32(X) X##16(0), X##16(16)
template <int SD, int TB, int KEEP = 0> __device__ __forceinline__ void wgmma_rs24(float* d, const uint32_t* a, uint64_t db) {
  WG_OP("wgmma.mma_async.sync.aligned.m64n24k16.f32.bf16.bf16 {%0,%1,%2,%3,%4,%5,%6,%7,%8,%9,%10,%11}, {%12,%13,%14,%15}, %16, %17, 1, 1, %18;", O12(G), O12(F), RS_IN);
}
template <int SD, int TB, int KEEP = 0> __device__ __forceinline__ void wgmma_rs32(float* d, const uint32_t* a, uint64_t db) {
  WG_OP("wgmma.mma_async.sync.aligned.m64n32k16.f32.bf16.bf16 {%0,%1,%2,%3,%4,%5,%6,%7,%8,%9,%10,%11,%12,%13,%14,%15}, {%16,%17,%18,%19}, %20, %21, 1, 1, %22;", G16(0), F16(0), RS_IN);
}
template <int SD, int TB, int KEEP = 0> __device__ __forceinline__ void wgmma_rs40(float* d, const uint32_t* a, uint64_t db) {
  WG_OP("wgmma.mma_async.sync.aligned.m64n40k16.f32.bf16.bf16 {%0,%1,%2,%3,%4,%5,%6,%7,%8,%9,%10,%11,%12,%13,%14,%15,"
        "%16,%17,%18,%19}, {%20,%21,%22,%23}, %24, %25, 1, 1, %26;", O20(G), O20(F), RS_IN);
}
template <int SD, int TB, int KEEP = 0> __device__ __forceinline__ void wgmma_rs64(float* d, const uint32_t* a, uint64_t db) {
  WG_OP("wgmma.mma_async.sync.aligned.m64n64k16.f32.bf16.bf16 {%0,%1,%2,%3,%4,%5,%6,%7,%8,%9,%10,%11,%12,%13,%14,%15,"
        "%16,%17,%18,%19,%20,%21,%22,%23,%24,%25,%26,%27,%28,%29,%30,%31}, {%32,%33,%34,%35}, %36, %37, 1, 1, %38;", O32(G), O32(F), RS_IN);
}
template <int SD, int TA, int TB, int KEEP = 0> __device__ __forceinline__ void wgmma_ss24(float* d, uint64_t da, uint64_t db) {
  WG_OP("wgmma.mma_async.sync.aligned.m64n24k16.f32.bf16.bf16 {%0,%1,%2,%3,%4,%5,%6,%7,%8,%9,%10,%11}, %12, %13, %14, 1, 1, %15, %16;", O12(G), O12(F), SS_IN);
}
template <int SD, int TA, int TB, int KEEP = 0> __device__ __forceinline__ void wgmma_ss8(float* d, uint64_t da, uint64_t db) {
  WG_OP("wgmma.mma_async.sync.aligned.m64n8k16.f32.bf16.bf16 {%0,%1,%2,%3}, %4, %5, %6, 1, 1, %7, %8;", G4(0), F4(0), SS_IN);
}
__device__ __forceinline__ void bar_arrive(int id, int n) { asm volatile("bar.arrive %0, %1;" :: "r"(id), "r"(n) : "memory"); }
__device__ __forceinline__ uint32_t vis_bits(int pos, int t) {
  uint32_t m = 0;
#pragma unroll
  for (int i = 0; i < 8; i++) m |= (8 * (i / 2 + 1) + 2 * t + (i & 1) <= pos) ? 1u << i : 0u;
  return m;
}

__device__ __forceinline__ unsigned long long wait_words(const unsigned long long* p, uint32_t E) {
  int guard = 0; unsigned long long m;
  while (m = ld_rlxu64(p), !__all_sync(~0u, rfresh(m, E))) { __nanosleep(32); if (++guard > (1 << 22)) TRAP(); }
  fence_acq();
  return m;
}
__device__ __forceinline__ int route_step(int s, uint32_t E, int lane, unsigned long long& run) {
  const unsigned long long m = warp_max<2>(wait_words(f_h2[s][lane & 3], E));
  if (s == 0 || m > run) { run = m; return rtok(m) & 31; }
  return -1;
}

struct Params {
  const bf16 *x, *mem0, *wq, *wk, *wv, *wo, *wr, *wg, *wu, *wd;
  bf16* out;
  uint32_t zero2;
  unsigned long long zero;
};

constexpr uint32_t WSTG_STRIDE = 272;
__device__ __forceinline__ void stage_weights(uint32_t stg, const bf16* src, int ld, int tid, int nthr) {
  for (int i = tid; i < 512 * 16; i += nthr) {
    int k = i >> 4, c = i & 15;
    cp_async16(stg + k * WSTG_STRIDE + c * 16, src + (size_t)k * ld + c * 8);
  }
}
__device__ __forceinline__ void load_frags(uint32_t (*W)[4], uint32_t stg, int wg, int w, int lane) {
  uint32_t a = stg + ((lane >> 4) * 8 + (lane & 7)) * WSTG_STRIDE + (64 * wg + 16 * w + ((lane >> 3) & 1) * 8) * 2;
#pragma unroll
  for (int ks = 0; ks < 32; ks++) ldmatrix4_t(W[ks], a + ks * 16 * WSTG_STRIDE);
}

constexpr uint32_t M_H = 0;
constexpr uint32_t M_MEM = 65536;
constexpr uint32_t M_Q = M_MEM + 24576;
constexpr uint32_t M_K = M_Q + 12288;
constexpr uint32_t M_V = M_K + 12288;
constexpr uint32_t M_OM = M_V + 12288;
constexpr uint32_t M_OST = M_OM + 6144;
constexpr uint32_t M_TST = M_OST + 8192;
constexpr uint32_t M_WO = M_TST + 16384;
constexpr uint32_t M_M0 = M_WO + 49152;
constexpr uint32_t M_PT = M_M0 + 2048;
constexpr uint32_t M_BAR = M_PT + 12288;
constexpr uint32_t M_TOTAL = M_BAR + 384;
static_assert(M_TOTAL <= 232448, "main smem");
static_assert(M_WO >= 512 * WSTG_STRIDE, "staging overlaps Wo");
enum { B_LAND = 0  , B_QK = 3, B_V, B_TOK, B_OM, B_HA, B_HB, B_HAE, B_HBE, B_OST, B_OFREE, B_SYNC,
       B_STG, B_STG1, B_SS, B_TFREE, B_KFREE, B_VFREE, B_FIX  , B_NUM = B_FIX + 8 };
static_assert(B_NUM * 8 <= 256, "barriers");
constexpr uint32_t M_CAND = M_BAR + 256;
constexpr uint32_t M_BASE = M_BAR + 272;
constexpr uint32_t M_ZERO = M_BAR + 280;
constexpr uint32_t M_BAS2 = M_BAR + 328;
constexpr uint32_t M_NEAR = M_BAR + 288;
enum { N_GO1 = 2, N_GO2, N_GO3, N_GO4, N_AG, N_W };

#define GSTAMP(slot, i)
#define TSTAMP(slot, i, k)
#define STAMP(i)
#define ASTAMP(i)
#define WSTAMP(i)
#define CSTAMP(i, v)
#define PIN(x) asm volatile("" : "+r"(x))
#define SCHED(k) asm volatile("{\n.reg .pred p;\nsetp.ne.u32 p, %0, 0;\n@p trap;\n}" :: "r"(zz & (1u << (k))) : "memory")
#define HOLD(k, v) asm volatile("{\n.reg .pred p;\nsetp.ne.u32 p, %0, 0;\n@p st.shared.u32 [%0], %1;\n}" :: "r"(zz & (1u << (k))), "r"(v) : "memory")
#define DRAIN(a) (lds32((a) + zz) & zz)
#define BAR(i) (sb + M_BAR + 8 * (i))

__device__ __forceinline__ int probe(const uint8_t* p, int n) {
  int best = 1 << 30; uint32_t v = 0;
#pragma unroll 1
  for (int r = 0; r < n; r++) {
    uint32_t t0 = clk();
    asm volatile("atom.relaxed.gpu.global.or.b32 %0, [%1], %2;" : "=r"(v) : "l"(p + 3968), "r"(v & 0u) : "memory");
    if (v == 0x7fffffffu) t0++;
    best = min(best, (int)(clk() - t0));
  }
  return best;
}
__device__ __forceinline__ void load_mem0(uint4* u, int k0, int lane, const bf16* mem0) {
#pragma unroll
  for (int i = 0; i < 2; i++) {
    const unsigned short* m = (const unsigned short*)mem0 + k0 + lane + 32 * i;
    u[i] = make_uint4(m[0] | (uint32_t)m[512] << 16, m[1024] | (uint32_t)m[1536] << 16, m[2048] | (uint32_t)m[2560] << 16, m[3072] | (uint32_t)m[3584] << 16);
  }
}

__device__ __forceinline__ void paced_h(uint32_t dst, const uint8_t* src, uint32_t o0, uint32_t o1, uint32_t piece, uint32_t bar, int gap) {
  uint32_t t = clk32();
#pragma unroll 1
  for (uint32_t o = o0; o < o1; o += piece) {
    e_mc(dst + o, src + o, piece, bar, 7);
    spin_until(t += gap);
  }
}

__device__ __forceinline__ void weight_role(const Params& p, const uint32_t sb, const int warp, const int cta, const int C, const uint32_t E,
                                            const uint8_t* const memg) {
  const int tid = fresh_tid(), lane = tid & 31;
  const int wg = warp >> 2, w = warp & 3;
  uint32_t W[32][4];
  cp_async_wait();
  bar_sync(1, 256);
  load_frags(W, sb, wg, w, lane);
  bar_sync(1, 256);
  if (tid < 128) sts128(sb + M_V + 5 * 2048 + tid * 16, make_uint4(0, 0, 0, 0));
  fence_async_smem();
  cluster_sync();
  if (tid == 0 && cta == 0) GSTAMP(0, 1);
  if (tid == 0) TSTAMP(13, cta, 0);

  const uint32_t rba = mapa(sb, C == 2 ? 0 : 2), rbc = mapa(sb, C == 1 ? 0 : 1);
  const uint32_t MYBAR = M_BAR + 8 * (C < 2 ? B_QK : B_V);
  uint32_t qoff = M_Q + C * 12288 + warp * 256 + lane * 4;
  uint32_t toff = sb + warp * 256 + (lane >> 4) * 2048 + (lane & 15) * 16;
  uint32_t rbar = mapa(sb + M_BAR, min(lane, 2));
  uint32_t sv = sb + M_MEM + lane * 32 + ((lane >> 2) & 3) * 8;
  PIN(qoff); PIN(toff); PIN(rbar); PIN(sv);
  const uint32_t gen0 = (E - 1) * (uint32_t)(NSTEP - 1);
  uint32_t fix = 0;
  const bool sig = w == 0 && lane < 3;
  const int pk = PAUSE_ + (cta < 36 ? 0 : cta < 72 ? PD1_ : 2 * PD1_) + (wg ? -PST2_ : PST2_);
  int cand = -1;
  float d[16];
#pragma unroll
  for (int i = 0; i < 16; i++) d[i] = 0.f;
  uint32_t tp[8];
#pragma unroll 1
  for (int T = -1; T < NSTEP; T++) {
    const uint32_t ph = T & 1;
    const uint64_t Z = p.zero << ph;
    const uint32_t zz = p.zero2;
    if (T >= 0) {
      WSTAMP(0);
      const uint64_t db = mkdesc(M_MEM, 128, 256, 0) + Z;
      stmatrix4(toff + M_TST + 8192, tp[0], tp[1], tp[2], tp[3]); stmatrix4(toff + M_TST + 12288, tp[4], tp[5], tp[6], tp[7]);
      if (sig) mbar_arrive_remote(rbar + 8 * B_HBE);
      mbar_wait(BAR(B_LAND), ph);
      WSTAMP(1);
      const uint32_t gt = gentag(gen0 + T);
      auto old = [&](uint32_t a) { return lds32(a) ^ gt; };
      uint32_t bad = 0;
      bool redo = false, ready = false;
      wg_fence();
      wgmma_rs24<0, 1, KP1_>(d, W[0], db);
#pragma unroll
      for (int ks = 1; ks < 32; ks++) {
        if (ks == 2 || ks == 14) bad |= xo2(lds32(sv + (ks == 2 ? 0 : 9) * 1024 + warp * 1024), lds32(sv + (ks == 2 ? 8 : 17) * 1024), gt);
        if (ks == 25) bad |= old(sv + (18 + min(warp, 5)) * 1024);
        if (ks == 6) {
          const uint32_t z5 = DRAIN(toff + M_TST);
          __syncwarp();
          if (lane == 0) mbar_arrive(BAR(B_STG) + z5);
        }
        if (ks == 27) ready = mbar_test(BAR(C < 2 ? B_KFREE : B_VFREE), ph ^ 1) & mbar_test(BAR(B_HA), ph);
        if (ks == RED_) redo = bar_or(N_W, 256, T > 0 && (bad & 0x10001u));
        if (ks == 12 || ks == 24) { mbar_wait(BAR(B_LAND + ks / 12), ph); WSTAMP(6 + ks / 12); wg_fence(); }
        wgmma_rs24<1, 1>(d, W[ks], db + ks * 48);
      }
      wg_commit();
      uint32_t a0 = rba + qoff, a1 = a0 + 128, a2 = rbc + qoff, a3 = a2 + 128, ba = rba + MYBAR, bc = rbc + MYBAR;
      PIN(a0); PIN(a1); PIN(a2); PIN(a3); PIN(ba); PIN(bc);
      if (!ready) {
        mbar_wait(BAR(C < 2 ? B_KFREE : B_VFREE), ph ^ 1);
        if (T < NSTEP - 1) mbar_wait(BAR(B_HA), ph);
      }
      wg_wait<0>(); reg_fence(d);
      if (__builtin_expect(redo, 0)) {
        auto stale = [&]() { return __any_sync(~0u, (old(sv + warp * 3072) | old(sv + warp * 3072 + 1024) | old(sv + warp * 3072 + 2048)) & 0x10001u); };
        auto fetch = [&](int r) {
          e_expect(BAR(B_FIX + warp), 3072);
          e_g2s(sb + M_MEM + warp * 3072, memg + warp * 8192 + ((uni(lds32(sb + M_NEAR + warp * 4)) ^ r) & 1) * 4096, 3072, BAR(B_FIX + warp));
        };
        bool late = stale();
        if (late) fetch(0);
        constexpr uint64_t dc = mkdesc(M_MEM, 128, 256, 0);
#pragma unroll
        for (int ks = 0; ks < 32; ks++) {
          if (ks % 12 == 0) {
            if (ks) { wg_commit(); wg_wait<0>(); reg_fence(d); }
            if (warp / 3 == ks / 12) {
              for (int guard = 0; late; guard++) {
                mbar_wait(BAR(B_FIX + warp), fix); fix ^= 1;
                late = stale();
                if (late) fetch(ALT_ ? guard + 1 : 0);
                if (guard > (1 << 20)) TRAP();
              }
            }
            bar_sync(N_W, 256);
            wg_fence();
          }
          if (ks == 0) wgmma_rs24<0, 1, 1>(d, W[0], dc); else wgmma_rs24<1, 1>(d, W[ks], dc + ks * 48);
        }
        wg_commit();
        wg_wait<0>(); reg_fence(d);
      }
      WSTAMP(2);
      if (T == 0 && tid == 0) TSTAMP(13, cta, 2);
      uint32_t lo[3], hi[3];
#pragma unroll
      for (int j = 0; j < 3; j++) { lo[j] = pack2(d[4 * j], d[4 * j + 1]); hi[j] = pack2(d[4 * j + 2], d[4 * j + 3]); }
      if (__builtin_expect(T == 0, 0)) { sts32(sb + M_M0 + tid * 8, lo[0]); sts32(sb + M_M0 + tid * 8 + 4, hi[0]); }
      if (__builtin_expect(cand >= 0, 0)) {
        if (T == LAG) { lo[1] = lds32(sb + M_M0 + tid * 8); hi[1] = lds32(sb + M_M0 + tid * 8 + 4); }
        if (C < 2) { st_async32(a0 + 5 * 2048, lo[2], ba); st_async32(a1 + 5 * 2048, hi[2], ba); }
        else { sts32(sb + qoff + 5 * 2048, lo[2]); sts32(sb + qoff + 5 * 2048 + 128, hi[2]); }
        lo[2] = lo[1]; hi[2] = hi[1];
      }
      uint32_t z5;
      if (C == 0) {
        sts32(sb + qoff, lo[0]); sts32(sb + qoff + 128, hi[0]); z5 = DRAIN(sb + qoff);
        st_async32(a0, lo[2], ba); st_async32(a1, hi[2], ba); st_async32(a2, lo[1], bc); st_async32(a3, hi[1], bc);
      } else if (C == 1) {
        sts32(sb + qoff, lo[1]); sts32(sb + qoff + 128, hi[1]); z5 = DRAIN(sb + qoff);
        st_async32(a0, lo[2], ba); st_async32(a1, hi[2], ba); st_async32(a2, lo[0], bc); st_async32(a3, hi[0], bc);
      } else {
        sts32(sb + qoff, lo[2]); sts32(sb + qoff + 128, hi[2]); z5 = DRAIN(sb + qoff);
        st_async32(a0, lo[0], ba); st_async32(a1, hi[0], ba); st_async32(a2, lo[1], bc); st_async32(a3, hi[1], bc);
      }
      __syncwarp();
      if (lane == 0) { mbar_arrive(sb + MYBAR + z5); if (w == 3) mbar_arrive(BAR(B_SS)); }
      if (T == NSTEP - 1) break;
    }
    {
      const uint64_t dh = mkdesc(M_H, 16, 1024, 1) + Z;
      static_assert(E2 == 0 && E3 > 0 && PAUSE_ > 0, "config");
      if (T + 2 < NSEG) {
        if (T < 0) mbar_wait(BAR(B_HA), ph);
        WSTAMP(3);
        wg_fence();
        wgmma_rs32<0, 0, 1>(d, W[0], dh);
#pragma unroll
        for (int ks = 1; ks < EA; ks++) {
          if (ks == E1) { wg_commit(); if (T >= 0) bar_sync(N_GO2, 384); wg_fence(); }
          wgmma_rs32<1, 0>(d, W[ks], dh + (ks >> 2) * 256 + (ks & 3) * 2);
        }
        wg_commit();
        mbar_wait(BAR(B_HB), ph);
        wg_wait<0>();
        if (sig) mbar_arrive_remote(rbar + 8 * B_HAE);
        WSTAMP(4);
        if (T >= 0) bar_sync(N_GO3, 384);
        if (wg == 1) bar_sync(N_W, 256);
        wg_fence();
#pragma unroll
        for (int ks = EA; ks < 32; ks++) wgmma_rs32<1, 0>(d, W[ks], dh + (ks >> 2) * 256 + (ks & 3) * 2);
        wg_commit();
        if (wg == 0) bar_arrive(N_W, 256);
        mbar_wait(BAR(B_TFREE), ph ^ 1);
        wg_wait<0>(); reg_fence(d);
      } else {
        bar_sync(N_GO2, 384);
        mbar_wait(BAR(B_HB), ph);
        if (sig) mbar_arrive_remote(rbar + 8 * B_HAE);
        bar_sync(N_GO3, 384);
        mbar_wait(BAR(B_TFREE), ph ^ 1);
      }
#pragma unroll
      for (int i = 0; i < 8; i++) { tp[i] = pack2(d[2 * i], d[2 * i + 1]); PIN(tp[i]); }
      auto staged = [&]() {
        const uint32_t z5 = DRAIN(toff + M_TST);
        __syncwarp();
        if (lane == 0) mbar_arrive(BAR(B_STG1) + z5);
      };
      if (T < 0 || (T + 2 >= LAG && T + 2 < NSTEP)) {
        wg_fence();
        wgmma_rs32<0, 0, 1>(d, W[0], dh + 2048);
        stmatrix4(toff + M_TST, tp[0], tp[1], tp[2], tp[3]); stmatrix4(toff + M_TST + 4096, tp[4], tp[5], tp[6], tp[7]);
#pragma unroll
        for (int ks = 1; ks < 32; ks++) {
          if (ks == 5) staged();
          if (ks >= PAUSE_ - PST2_ && ks <= PAUSE_ + 2 * PD1_ + PST2_ && (ks - PAUSE_ + PST2_) % PGR_ == 0) {
            wg_commit();
            if (T >= 0 && ks == pk) bar_sync(N_GO4, 384);
            wg_fence();
          }
          wgmma_rs32<1, 0>(d, W[ks], dh + 2048 + (ks >> 2) * 256 + (ks & 3) * 2);
        }
        wg_commit();
      } else {
        stmatrix4(toff + M_TST, tp[0], tp[1], tp[2], tp[3]); stmatrix4(toff + M_TST + 4096, tp[4], tp[5], tp[6], tp[7]);
        staged();
        bar_sync(N_GO4, 384);
      }
      if (T >= 0) cand = __shfl_sync(~0u, (int)lds32(sb + M_CAND + ((T + 1) & 3) * 4), 0);
      wg_wait<0>(); reg_fence(d);
      if (T >= 0) WSTAMP(6);
      if (T < 0 && tid == 0) TSTAMP(13, cta, 1);
#pragma unroll
      for (int i = 0; i < 8; i++) tp[i] = pack2(d[2 * i], d[2 * i + 1]);
    }
  }
  cluster_sync();
  if (tid == 0 && cta == 0) GSTAMP(0, 5);
}

__device__ __forceinline__ void attn_role(const Params& p, const uint32_t sb, const int w, const int cta, const int head, const int C, const uint32_t E,
                                          uint8_t* const part, uint8_t* const memg) {
  const int tid = fresh_tid(), lane = tid & 31;
  const int g = lane >> 2, t = lane & 3;
  uint32_t tag = ((E - 1) * (uint32_t)(NSTEP - 1)) & 1;
  uint4 m0[2][2];
  load_mem0(m0[0], w * 64, lane, p.mem0); load_mem0(m0[1], w * 64 + 256, lane, p.mem0);
  cluster_sync();
#pragma unroll
  for (int k = 0; k < 2; k++) {
#pragma unroll 1
    for (int i = 0; i < 6; i++) sts128(sb + M_MEM + (w + 4 * k) * 3072 + lane * 16 + i * 512, make_uint4(0, 0, 0, 0));
    __syncwarp();
#pragma unroll
    for (int i = 0; i < 2; i++) sts128(sb + M_MEM + ((w + 4 * k) * 4 + (lane >> 4) + 2 * i) * 768 + (lane & 15) * 16, m0[k][i]);
  }
  fence_async_smem();
  bar_sync(N_AG, 128);
  if (w == 3 && lane < 3) mbar_arrive(BAR(B_LAND + lane));
  if (lane == 0) {
    if (w == 0) TSTAMP(15, cta, 0);
    sts32(sb + M_PT + w * 4, probe(part + cta * 16384 + w * 4096, NPROBE_ / 2));
    if (w == 0) TSTAMP(15, cta, 1);
  }
  bar_sync(N_AG, 128);
  const uint32_t inear = lds32(sb + M_PT + (w >> 1) * 8 + 4) < lds32(sb + M_PT + (w >> 1) * 8);
  if (lane == 0 && !(w & 1)) st_rlx(&f_choice[cta][w >> 1], (E << 1) | inear);
  if (w == 0) TSTAMP(15, cta, 2);
  uint32_t nb;
  {
    const int i = min(lane >> 1, C < 2 ? 8 : 5);
    const int r = ((i / 3 * 3 + C) * 4 + w) * 3 + i % 3;
    int guard = 0; uint32_t cw;
    while (__any_sync(~0u, ((cw = ld_rlx(&f_choice[r][lane & 1])) >> 1) != (E & 0x7FFFFFFFu))) { if (++guard > (1 << 22)) TRAP(); }
    nb = __ballot_sync(~0u, cw & 1) >> (lane >> 4);
    if (w == 0) TSTAMP(15, cta, 3);
  }
  bar_sync(N_AG, 128);
  const uint32_t pt0 = sb + M_PT + (tid & 127) * 16;
  {
    const uint32_t po = (C * 4 + w) * 49152 + (lane >> 4) * 8192 + ((lane >> 3) & 1) * 2048 + head * 64 + (lane & 7) * 8;
    const uint8_t* in = part + (cta * 16384 + (w >> 1) * 8192 + inear * 4096 + (w & 1) * 2048 + lane * 8);
    const uint8_t* outp = memg + ((cta / 12) * 8192 + (cta % 12) * 256 + w * 64 + (lane >> 4) * 4096 + (lane & 4) * 8 + (lane & 8) * 2 + (lane & 3) * 4);
#pragma unroll
    for (int i = 0; i < 12; i++) {
      const int j = i / 4 * 3 + (i & 3);
      const uint8_t* a = (i & 3) < 3 ? part + (po + i / 4 * 589824 + (i & 3) * 16384 + ((nb >> (2 * j)) & 1) * 4096) : i == 11 ? in : outp;
      asm volatile("st.shared.u64 [%0], %1;" :: "r"(pt0 + (i >> 1) * 2048 + (i & 1) * 8), "l"(a) : "memory");
    }
  }
  const int xd = __shfl_sync(~0u, XDLY_ + (cta < 36 ? 0 : cta < 72 ? X1_ : X2_), 0);
  const uint32_t rba = mapa(sb, C == 2 ? 0 : 2), rbc = mapa(sb, C == 1 ? 0 : 1);
  uint32_t vis = vis_bits(8 + 8 * w + g, t);
  uint32_t ln = lane;
#pragma unroll
  for (int i = 0; i < SALT_; i++) ln += lds32(sb + M_ZERO);
  PIN(vis); PIN(ln);
  if (tid == 256 && C == 0) st_rlx(&f_loaded[head], E);
  uint32_t fa[8][4];
#pragma unroll
  for (int ks = 0; ks < 8; ks++) ldmatrix4_t(fa[ks], sb + M_WO + 32768 + w * 256 + (lane >> 4) * 1024 + (lane & 15) * 16 + ks * 2048);
  if (w == 0) TSTAMP(14, cta, 0);
#pragma unroll 1
  for (int T = 0; T < NSTEP; T++) {
    const uint32_t ph = T & 1;
    const uint32_t zz = uni(lds32(sb + M_ZERO));
    const bool more = T < NSTEP - 1;
    const float sc = 0.08838834764831845f * 1.4426950408889634f;
    tag ^= 1;
    float s[20];
    const uint8_t* in; int cnext = -1; uint32_t tx; bool synced;
    float x[10], tm, ts;
    uint32_t pt[5];
    auto tok_max = [&]() {
      PIN(vis);
      x[0] = s[2]; x[1] = s[3];
#pragma unroll
      for (int i = 0; i < 8; i++) x[2 + i] = (vis >> i & 1) ? s[4 * (i / 2 + 1) + 2 + (i & 1)] : -INFINITY;
      tm = fmaxf(fmaxf(fmaxf(fmaxf(x[0], x[1]), fmaxf(x[2], x[3])), fmaxf(fmaxf(x[4], x[5]), fmaxf(x[6], x[7]))), fmaxf(x[8], x[9]));
      HOLD(7, __float_as_uint(tm));
    };
    auto tok_exp1 = [&]() {
      tm = fmaxf(tm, __shfl_xor_sync(~0u, tm, 1));
      tm = fmaxf(tm, __shfl_xor_sync(~0u, tm, 2));
      const float b = -tm * sc;
#pragma unroll
      for (int i = 0; i < 10; i++) x[i] = fmaf(x[i], sc, b);
      HOLD(10, __float_as_uint(x[9]));
    };
    auto tok_exp2 = [&]() {
#pragma unroll
      for (int i = 0; i < 10; i++) x[i] = ex2(x[i]);
      ts = (((x[0] + x[1]) + (x[2] + x[3])) + ((x[4] + x[5]) + (x[6] + x[7]))) + (x[8] + x[9]);
#pragma unroll
      for (int k = 0; k < 5; k++) pt[k] = pack2(x[2 * k], x[2 * k + 1]);
      HOLD(8, __float_as_uint(ts));
    };
    {
      uint32_t q[8][4];
      auto load_q = [&](uint32_t a, int h) {
#pragma unroll
        for (int k2 = 0; k2 < 4; k2++) {
          uint32_t r[4];
          ldmatrix4_t(r, a + k2 * 512);
          q[2 * k2][h] = r[0]; q[2 * k2][h + 2] = r[1]; q[2 * k2 + 1][h] = r[2]; q[2 * k2 + 1][h + 2] = r[3];
        }
      };
      PIN(ln);
      const uint32_t qa = sb + M_Q + ln * 16;
      const int cand = C == 2 ? (int)uni(lds32(sb + M_CAND + (T & 3) * 4)) : -1;
      mbar_wait(BAR(B_TOK), ph);
      load_q(qa + (1 + w) * 2048, 1);
      mbar_wait(BAR(B_QK), ph);
      ASTAMP(0);
      if (T == 0 && w == 0) TSTAMP(13, cta, 3);
      if (__builtin_expect(cand >= 0, 0)) {
        mbar_wait(BAR(B_V), ph);
        PIN(ln);
        const int e = w * 32 + ln;
#pragma unroll
        for (int i = 0; i < 3; i++) {
          const uint32_t v = lds32(sb + M_Q + i * 12288 + 5 * 2048 + e * 16 + 4);
          asm volatile("st.shared.u16 [%0], %1;" :: "r"(sb + M_Q + i * 12288 + (1 + (cand >> 3)) * 2048 + e * 16 + (cand & 7) * 2), "h"((unsigned short)v) : "memory");
        }
        fence_async_smem();
        bar_sync(N_AG, 128);
        load_q(qa + (1 + w) * 2048, 1);
      }
      load_q(qa, 0);
      if (!(NOF_ & 1)) fence_async_smem();
      constexpr uint64_t dk = mkdesc(M_K, 128, 2048, 0);
      wg_fence();
      wgmma_rs40<0, 1>(s, q[0], dk);
#pragma unroll
      for (int ks = 1; ks < 8; ks++) wgmma_rs40<1, 1>(s, q[ks], dk + ks * 16);
      wg_commit();
    }
    if (more) {
      uint32_t v[5][4];
      PIN(ln);
      const uint32_t va = sb + M_V + w * 512 + ((ln >> 3) & 1) * 128 + (ln >> 4) * 2048 + (ln & 7) * 16;
      const uint32_t ooff = M_OM + w * 1536 + C * 256 + ln * 4;
      mbar_wait(BAR(B_V), ph);
      wg_wait<0>(); reg_fence(s);
      if (ln < 3) mbar_arrive_remote(mapa(BAR(B_KFREE), ln));
      ldmatrix4(v[0], va); ldmatrix4(v[1], va + 256); ldmatrix4(v[2], va + 4096); ldmatrix4(v[3], va + 4096 + 256);
      ldmatrix4(v[4], sb + M_V + 8192 + w * 512 + ln * 16);
      ASTAMP(1);
      float m = fmaxf(fmaxf(fmaxf(fmaxf(s[0], s[1]), fmaxf(s[4], s[5])), fmaxf(fmaxf(s[8], s[9]), fmaxf(s[12], s[13]))), fmaxf(s[16], s[17]));
      m = fmaxf(m, __shfl_xor_sync(~0u, m, 1));
      m = fmaxf(m, __shfl_xor_sync(~0u, m, 2));
      const float b = -m * sc;
      uint32_t pm[5];
#pragma unroll
      for (int j = 0; j < 5; j++) pm[j] = pack2(ex2(fmaf(s[4 * j], sc, b)), ex2(fmaf(s[4 * j + 1], sc, b)));
      float o0[4] = {0.f, 0.f, 0.f, 0.f}, o1[4] = {0.f, 0.f, 0.f, 0.f}, l[4] = {0.f, 0.f, 0.f, 0.f};
      const uint32_t one[4] = {0x3f803f80u, 0x3f803f80u, 0x3f803f80u, 0x3f803f80u};
      hmma16(l, one, pm[0], pm[1]); hmma16(o0, v[0], pm[0], pm[1]); hmma16(o1, v[1], pm[0], pm[1]);
      hmma16(l, one, pm[2], pm[3]); hmma16(o0, v[2], pm[2], pm[3]); hmma16(o1, v[3], pm[2], pm[3]);
      hmma8(l, one[0], one[1], pm[4]); hmma8(o0, v[4][0], v[4][1], pm[4]); hmma8(o1, v[4][2], v[4][3], pm[4]);
      const float r0 = rcp(l[0]), r1 = rcp(l[1]);
      const uint32_t u0 = pack2(o0[0] * r0, o0[1] * r1), u1 = pack2(o0[2] * r0, o0[3] * r1), u2 = pack2(o1[0] * r0, o1[1] * r1), u3 = pack2(o1[2] * r0, o1[3] * r1);
      constexpr uint32_t OB = M_BAR + 8 * B_OM;
      const uint32_t a0 = rba + ooff, a1 = rbc + ooff;
      st_async32(a0, u0, rba + OB); st_async32(a1, u0, rbc + OB);
      st_async32(a0 + 128, u1, rba + OB); st_async32(a1 + 128, u1, rbc + OB);
      st_async32(a0 + 768, u2, rba + OB); st_async32(a1 + 768, u2, rbc + OB);
      st_async32(a0 + 896, u3, rba + OB); st_async32(a1 + 896, u3, rbc + OB);
      bar_arrive(N_GO2, 384);
      sts32(sb + ooff, u0); sts32(sb + ooff + 128, u1); sts32(sb + ooff + 768, u2); sts32(sb + ooff + 896, u3);
      ASTAMP(2);
      uint32_t fb[8][4];
      const uint32_t wa = sb + M_WO + 16384 + w * 256 + (ln >> 4) * 1024 + (ln & 15) * 16 + zz;
      ldmatrix4_t(fb[0], wa);
      SCHED(3);
#pragma unroll
      for (int ks = 1; ks < 8; ks++) {
        ldmatrix4_t(fb[ks], wa + ks * 2048);
        if (ks == ARR_) { __syncwarp(); if (ln == 0) mbar_arrive(BAR(B_OM) + (fb[0][0] & zz)); }
      }
      if (C == 2) cnext = (int)uni(lds32(sb + M_CAND + ((T + 1) & 3) * 4));
      {
        float d[12], e[12];
        constexpr uint64_t ob = mkdesc(M_OM, 128, 256, 0);
        uint8_t* q[3][3];
        auto addr = [&](int i) {
          asm volatile("ld.shared.v2.u64 {%0,%1}, [%2];" : "=l"(q[i][0]), "=l"(q[i][1]) : "r"(pt0 + i * 4096) : "memory");
          if (i < 2) asm volatile("ld.shared.u64 %0, [%1];" : "=l"(q[i][2]) : "r"(pt0 + i * 4096 + 2048) : "memory");
          else asm volatile("ld.shared.v2.u64 {%0,%1}, [%2];" : "=l"(q[i][2]), "=l"(in) : "r"(pt0 + i * 4096 + 2048) : "memory");
        };
        auto put = [&](const float* d, int i) {
          st_rlx64(q[i][0], (pack2(d[0], d[1]) & ~1u) | tag, pack2(d[2], d[3]));
          st_rlx64(q[i][1], (pack2(d[4], d[5]) & ~1u) | tag, pack2(d[6], d[7]));
          st_rlx64(q[i][2], (pack2(d[8], d[9]) & ~1u) | tag, pack2(d[10], d[11]));
        };
        addr(0); addr(1);
        SCHED(6);
        tok_max();
        ASTAMP(3);
        mbar_wait(BAR(B_OM), ph);
        if (!(NOF_ & 2)) fence_async_smem();
        ASTAMP(4);
        constexpr uint64_t w0 = mkdesc(M_WO, 1024, 128, 0);
        float (&f)[12] = d;
        wg_fence();
        wgmma_ss24<0, 1, 1>(d, w0, ob);
#pragma unroll
        for (int ks = 1; ks < 8; ks++) wgmma_ss24<1, 1, 1>(d, w0 + ks * 128, ob + ks * 48);
        wg_commit();
        wgmma_rs24<0, 1>(e, fb[0], ob);
#pragma unroll
        for (int ks = 1; ks < HAND_; ks++) wgmma_rs24<1, 1>(e, fb[ks], ob + ks * 48);
        wg_commit();
        wg_wait<1>(); reg_fence(d);
        put(d, 0);
        addr(2);
        SCHED(4);
        ASTAMP(5);
        wg_fence();
#pragma unroll
        for (int ks = HAND_; ks < 8; ks++) wgmma_rs24<1, 1>(e, fb[ks], ob + ks * 48);
        wg_commit();
        wgmma_rs24<0, 1, 1>(f, fa[0], ob);
#pragma unroll
        for (int ks = 1; ks < HAND_; ks++) wgmma_rs24<1, 1>(f, fa[ks], ob + ks * 48);
        wg_commit();
        wg_wait<1>(); reg_fence(e);
        put(e, 1);
        SCHED(5);
        wg_fence();
#pragma unroll
        for (int ks = HAND_; ks < 8; ks++) wgmma_rs24<1, 1>(f, fa[ks], ob + ks * 48);
        wg_commit();
        if (GO3_ == 0) bar_arrive(N_GO3, 384);
        synced = __all_sync(~0u, mbar_test(BAR(B_SYNC), ph));
        tx = uni(lds32(sb + M_BASE + ph * 4)) + xd;
        wg_wait<0>(); reg_fence(f);
        if (GO3_ == 1) bar_arrive(N_GO3, 384);
        if (C < 2) put(f, 2);
        if (GO3_ == 2) bar_arrive(N_GO3, 384);
        ASTAMP(6);
        if (T == 0 && w == 0) TSTAMP(14, cta, 1);
      }
    } else {
      mbar_wait(BAR(B_V), ph);
      wg_wait<0>(); reg_fence(s);
      tok_max();
    }
    uint2 v[8];
#pragma unroll
    for (int i = 0; i < 8; i++) v[i] = make_uint2(zz, zz);
    auto poll = [&](uint2* v) {
      v[0] = ld_rlx64<0>(in); v[1] = ld_rlx64<256>(in); v[2] = ld_rlx64<512>(in); v[3] = ld_rlx64<768>(in);
      v[4] = ld_rlx64<1024>(in); v[5] = ld_rlx64<1280>(in); v[6] = ld_rlx64<1536>(in); v[7] = ld_rlx64<1792>(in);
    };
    uint8_t* outp;
    asm volatile("ld.shared.u64 %0, [%1];" : "=l"(outp) : "r"(pt0 + 2048 + 8) : "memory");
    const uint32_t itag = gentag((E - 1) * (uint32_t)(NSTEP - 1) + T + 1);
    const bool sum = more && cnext < 0;
    if (more) {
      if (!synced) { mbar_wait(BAR(B_SYNC), ph); tx = uni(lds32(sb + M_BASE + ph * 4)) + xd; }
      ASTAMP(7);
      if (__builtin_expect(cnext >= 0, 0)) {
        const unsigned long long* hp = (const unsigned long long*)&g_hc[T + 1 - LAG][0] + ((cta / 3) * 8 + 2 * w + ((ln >> 2) & 1));
        unsigned long long v0; int guard = 0;
        while (v0 = ld_rlxu64(hp), !__all_sync(~0u, (uint32_t)(v0 >> 32) == E)) { if (++guard > (1 << 22)) TRAP(); }
        st_rlx((uint32_t*)outp, (ln & 3) == 1 ? ((uint32_t)v0 >> ((ln & 8) * 2)) & 0xffffu : (ln & 1) ? 0u : itag);
      } else {
        spin_until(tx);
        ASTAMP(8);
        poll(v);
      }
    }
    auto late = [&](const uint2* v) {
      return __any_sync(~0u, (or3(xo2(v[0].x, v[1].x, tag), xo2(v[2].x, v[3].x, tag), xo2(v[4].x, v[5].x, tag)) | xo2(v[6].x, v[7].x, tag)) & 1u);
    };
    tok_exp1(); tok_exp2();
    auto reduce = [&]() {
      if (sum) {
        ASTAMP(9);
        int guard = 0;
        while (late(v)) {
          if (++guard > (1 << 22)) TRAP();
          poll(v);
        }
#pragma unroll
        for (int i = 0; i < 4; i++) { v[i].x = add2(v[i].x, v[i + 4].x); v[i].y = add2(v[i].y, v[i + 4].y); }
        const bool hi = ln & 8;
        const uint32_t x0 = add2(v[0].x, v[1].x), x1 = add2(v[2].x, v[3].x), y0 = add2(v[0].y, v[1].y), y1 = add2(v[2].y, v[3].y);
        const uint32_t m0 = hi ? y0 : x0, m1 = hi ? y1 : x1;
        const uint32_t n0 = __shfl_xor_sync(~0u, hi ? x0 : y0, 8), n1 = __shfl_xor_sync(~0u, hi ? x1 : y1, 8);
        float k0 = (blo(m0) + blo(m1)) + (blo(n0) + blo(n1)), k1 = (bhi(m0) + bhi(m1)) + (bhi(n0) + bhi(n1));
        k0 += __shfl_xor_sync(~0u, k0, 16); k1 += __shfl_xor_sync(~0u, k1, 16);
        st_rlx((uint32_t*)outp, (ln & 1) ? pack2(k0, k1) : pack2_tag(k0, k1, itag));
        ASTAMP(10);
        if (T == 0 && w == 0) TSTAMP(14, cta, 2);
        CSTAMP(12 + w, (clk() & ~15u) | min(guard + 1, 15));
      }
      if (more) bar_arrive(N_GO4, 384);
    };
    if (PVR_ < 0) reduce();
    {
      PIN(ln);
      const uint32_t oa = sb + M_OST + w * 128 + (ln >> 3) * 512 + (ln & 7) * 16;
      const uint32_t a[3][4] = {{0, pt[0], 0, pt[1]}, {0, pt[2], 0, pt[3]}, {0, pt[4], 0, 0}};
      constexpr uint64_t dv = mkdesc(M_V, 2048, 128, 0);
#pragma unroll 1
      for (int h = 0; h < 2; h++) {
        float o[32];
        const uint64_t dh = dv + (uint64_t)(h * 64);
        wg_fence();
        wgmma_rs64<0, 0>(o, a[0], dh); wgmma_rs64<1, 0>(o, a[1], dh + 256); wgmma_rs64<1, 0>(o, a[2], dh + 512);
        wg_commit();
        if (h == PVR_) reduce();
        if (h == 0) {
          ts += __shfl_xor_sync(~0u, ts, 1);
          ts += __shfl_xor_sync(~0u, ts, 2);
          ts = rcp(ts);
          mbar_wait(BAR(B_OFREE), ph ^ 1);
        }
        wg_wait<0>(); reg_fence(o);
        if (h == 1 && ln < 3) mbar_arrive_remote(mapa(BAR(B_VFREE), ln));
#define OT(i) pack2(o[4 * (i) + 2] * ts, o[4 * (i) + 3] * ts)
        stmatrix4(oa + h * 4096, OT(0), OT(1), OT(2), OT(3));
        stmatrix4(oa + h * 4096 + 2048, OT(4), OT(5), OT(6), OT(7));
      }
      const uint32_t z5 = DRAIN(oa);
      __syncwarp();
      if (ln == 0) mbar_arrive(BAR(B_OST) + z5);
      ASTAMP(11);
    }
  }
}

__global__ void __cluster_dims__(3, 1, 1) __launch_bounds__(512, 1) main_kernel(Params p) {
  extern __shared__ __align__(1024) uint8_t sm[];
  const uint32_t sb = smem_u32(sm);
  if ((sb & 0xFFFFFFu) != SBASE) TRAP();
  asm volatile("griddepcontrol.launch_dependents;");
  const int warp = __shfl_sync(~0u, threadIdx.x >> 5, 0);
  const int cta = blockIdx.x, head = cta / 3, c = cta % 3;
  const uint32_t E = __shfl_sync(~0u, *(volatile uint32_t*)&g_epoch + 1, 0);
  uint8_t* const part = (uint8_t*)(((uintptr_t)g_xch + 8191) & ~(uintptr_t)8191);
  uint8_t* const memg = part + 96 * 16384;

  if (threadIdx.x == 0 && cta == 0) GSTAMP(0, 0);
  if (threadIdx.x < B_NUM) {
    const int i = threadIdx.x;
    const uint32_t cnt = i == B_STG || i == B_STG1 ? 8 : i == B_OST ? 4 : i == B_HAE || i == B_HBE ? 6 : i == B_KFREE || i == B_VFREE ? 12 : i == B_SS ? 2 : i == B_OM ? 5 :
                         i == B_QK ? (c < 2 ? 9 : 1) : i == B_V ? (c < 2 ? 1 : 9) : 1;
    mbar_init(BAR(i), cnt);
    if (i == B_HA || i == B_HB || i == B_STG || i == B_HAE || i == B_HBE || i == B_TFREE)
      asm volatile("mbarrier.arrive.shared::cta.b64 _, [%0], %1;" :: "r"(BAR(i)), "r"(cnt) : "memory");
    asm volatile("fence.mbarrier_init.release.cluster;" ::: "memory");
  }
  if (warp < 8) {
    const int tid = threadIdx.x;
    uint4 wa[6], wb[6];
#pragma unroll
    for (int i = 0; i < 6; i++) {
      const int mi = i >> 1, e = (tid >> 2) + (i & 1) * 64;
      const uint4* src = (const uint4*)(p.wo + (size_t)(head * 128 + e) * 512 + min(3 * mi + c, 7) * 64 + (tid & 3) * 16);
      wa[i] = __ldg(src); wb[i] = __ldg(src + 1);
    }
    stage_weights(sb, (c == 0 ? p.wq : c == 1 ? p.wk : p.wv) + head * 128, 4096, tid, 256);
#pragma unroll
    for (int i = 0; i < 6; i++) {
      const int mi = i >> 1, e = (tid >> 2) + (i & 1) * 64;
      const uint4 a = wa[i], b = wb[i];
      const uint32_t dst = sb + M_WO + mi * 16384 + (e >> 3) * 1024 + (tid & 3) * 256 + (e & 7) * 16;
      sts128(dst, make_uint4(__byte_perm(a.x, a.y, 0x5410), __byte_perm(a.z, a.w, 0x5410), __byte_perm(b.x, b.y, 0x5410), __byte_perm(b.z, b.w, 0x5410)));
      sts128(dst + 128, make_uint4(__byte_perm(a.x, a.y, 0x7632), __byte_perm(a.z, a.w, 0x7632), __byte_perm(b.x, b.y, 0x7632), __byte_perm(b.z, b.w, 0x7632)));
    }
  } else {
    const int i0 = threadIdx.x - 256;
    const uint32_t tag0 = ((E - 1) * (uint32_t)(NSTEP - 1)) & 1;
    for (int i = i0; i < 1024; i += 256) *(uint4*)(part + cta * 16384 + i * 16) = make_uint4(tag0, 0, tag0, 0);
    if (i0 < 16) *(uint32_t*)(memg + i0 * 4096 + 3968) = 0;
    if (i0 < 2) st_rlx(&f_choice[cta][i0], 0);
    if (i0 < 8) st_rlx64(&g_sync[i0 >> 2][cta][i0 & 3], 0, 0);
    __threadfence();
    if (i0 < 12) sts32(sb + M_ZERO + i0 * 4, 0);
    if (i0 < 2) { sts32(sb + M_BASE + i0 * 4, clk32() - 65536); sts32(sb + M_BAS2 + i0 * 4, clk32() - 65536); sts32(sb + M_CAND + i0 * 4, (uint32_t)-1); }
  }

  if (warp < 8) {
    asm volatile("setmaxnreg.inc.sync.aligned.u32 " STR(RW_) ";");
    weight_role(p, sb, warp, cta, c, E, memg);
  } else if (warp < 12) {
    if (RA_ < 128) asm volatile("setmaxnreg.dec.sync.aligned.u32 " STR(RA_) ";");
    if (RA_ > 128) asm volatile("setmaxnreg.inc.sync.aligned.u32 " STR(RA_) ";");
    attn_role(p, sb, warp - 8, cta, head, c, E, part, memg);
    cluster_sync();
  } else {
    asm volatile("setmaxnreg.dec.sync.aligned.u32 " STR(RC_) ";");
    const int tid = fresh_tid(), lane = tid & 31;
    const int w = warp - 12;
    cluster_sync();
    if (w != 2) {
      const int tl = min(3 * min(w, 2) + c, 7);
      int near = 0;
      if (lane == 0) { const int t0 = probe(memg + tl * 8192, NPROBE_ / 2); near = probe(memg + tl * 8192 + 4096, NPROBE_ / 2) < t0; }
      near = uni(near);
      if (lane < 3) asm volatile("st.shared::cluster.u32 [%0], %1;" :: "r"(mapa(sb + M_NEAR + tl * 4, lane)), "r"(near) : "memory");
      __syncwarp();
    }
    if (w == 0) {
      int yadj = 0, dmin = 1 << 20; uint32_t prev = 0; bool cprev = false;
      uint32_t s0 = c * 8192, s1 = (3 + c) * 8192, s2 = min(6 + c, 7) * 8192;
#pragma unroll 1
      for (int T = 0; T < NSTEP - 1; T++) {
        const uint32_t ph = T & 1;
        mbar_wait(BAR(B_SS), ph);
        const uint32_t cq = clk();
        const uint32_t g0 = (uint32_t)gtime64(); uint32_t g1, ce;
        do { g1 = (uint32_t)gtime64(); ce = clk(); } while (g1 == g0);
        const uint32_t tn = g1 * 8 - (((ce - cq) * 37u) >> 3), id = E * 128u + T;
        if (lane < 4) st_rlx64(&g_sync[ph][cta][lane], tn, id);
        if (lane < 3) mbar_expect(BAR(B_LAND + lane), lane < 2 ? 9216 : 6144);
        if (T == 0) { s0 += uni(lds32(sb + M_NEAR + c * 4)) * 4096; s1 += uni(lds32(sb + M_NEAR + (3 + c) * 4)) * 4096; s2 += uni(lds32(sb + M_NEAR + min(6 + c, 7) * 4)) * 4096; }
        wait_until(cq + SDLY_);
        int guard = 0; unsigned long long v0, v1, v2;
        for (;;) {
          v0 = ld_rlxu64(g_sync[ph][lane]); v1 = ld_rlxu64(g_sync[ph][lane + 32]); v2 = ld_rlxu64(g_sync[ph][lane + 64]);
          if (__all_sync(~0u, (uint32_t)(v0 >> 32) == id && (uint32_t)(v1 >> 32) == id && (uint32_t)(v2 >> 32) == id)) break;
          if (++guard > (1 << 22)) TRAP();
        }
        const bool cnd = (int)uni(lds32(sb + M_CAND + (T & 3) * 4)) >= 0;
        const int dl = __reduce_max_sync(~0u, max(max((int)((uint32_t)v0 - tn), (int)((uint32_t)v1 - tn)), (int)((uint32_t)v2 - tn)));
        const uint32_t base = uni(cq + ((min(dl, 8 * 4096) * 7) >> 5)) + (T == 0 ? SLOW0_ : T == 1 ? SLOW1_ : 0) +
                              (cnd ? CDLY_ : 0) - (T + 2 < NSEG ? 0 : BOFF_);
        const int dur = (int)(base - prev);
        if (!cnd && !cprev) {
          yadj = T > 2 && dur > dmin + 700 ? min(yadj + YUP_, 400) : max(yadj - YDN_, 0);
          if (T > 1) dmin = min(dmin + 20, dur);
        }
        prev = base; cprev = cnd;
        if (lane == 0) { sts32(sb + M_BASE + ph * 4, base); sts32(sb + M_BAS2 + ph * 4, base + yadj); mbar_arrive(BAR(B_SYNC)); }
        CSTAMP(0, base); CSTAMP(1, clk());
        const uint32_t ts = base + YDLY_ + yadj - (T + 2 >= LAG && T + 2 < NSEG ? 0 : YOFF_);
        uint32_t nr = 0;
        if (PRIV_) nr = __ballot_sync(~0u, lds32(sb + M_NEAR + (lane & 7) * 4) != 0);
        wait_until(ts);
        if (PRIV_ & 1) { for (int k = 0; k < 3; k++) e_g2s(sb + M_MEM + k * 3072, memg + k * 8192 + ((nr >> k) & 1) * 4096, 3072, BAR(B_LAND)); }
        else e_mc(sb + M_MEM + c * 3072, memg + s0, 3072, BAR(B_LAND), 7);
        CSTAMP(2, clk());
        spin_until(ts + Y1_);
        if (PRIV_ & 2) { for (int k = 3; k < 6; k++) e_g2s(sb + M_MEM + k * 3072, memg + k * 8192 + ((nr >> k) & 1) * 4096, 3072, BAR(B_LAND + 1)); }
        else e_mc(sb + M_MEM + (3 + c) * 3072, memg + s1, 3072, BAR(B_LAND + 1), 7);
        CSTAMP(3, clk());
        spin_until(ts + Y2_);
        if (PRIV_ & 4) { for (int k = 6; k < 8; k++) e_g2s(sb + M_MEM + k * 3072, memg + k * 8192 + ((nr >> k) & 1) * 4096, 3072, BAR(B_LAND + 2)); }
        else if (c < 2) e_mc(sb + M_MEM + (6 + c) * 3072, memg + s2, 3072, BAR(B_LAND + 2), 7);
        CSTAMP(4, clk());
      }
    } else if (w == 1) {
#pragma unroll 1
      for (int T = 0; T < NSTEP; T++) {
        const uint32_t ph = T & 1;
        const int s = c == 0 ? T : T - LAG;
        const bool act = s >= 0 && s < NSEG;
        mbar_wait(BAR(B_OST), ph);
        if (cta == 0) TSTAMP(2, T, 0);
        fence_async_smem();
        if (T < NSTEP - 1) wait_until(uni(lds32(sb + M_BAS2 + ph * 4)) + ODLY_);
        STAMP(22);
        if (act) { e_s2g(g_o[c][s % ORING][head], sb + M_OST, XO_); bulk_wait(); __syncwarp(); }
        e_arrive(BAR(B_OFREE));
        if (cta == 0) TSTAMP(2, T, 1);
        if (act && lane < 8) st_rel(&f_o[T][head >> 2][c * 4 + (head & 3)][lane], E);
        __syncwarp();
        if (cta == 0) TSTAMP(2, T, 2);
      }
    } else if (w == 2) {
      unsigned long long run = 0;
      static_assert(LAG >= 2, "config");
      constexpr uint32_t NA = EA / 4 * 4096;
      e_expect(BAR(B_QK), c < 2 ? 2048 : 4096); e_expect(BAR(B_V), c == 0 ? 10240 : c == 1 ? 2048 : 0);
      e_expect(BAR(B_TOK), c == 0 ? 16384 : 0); e_expect(BAR(B_OM), 4096);
      e_expect(BAR(B_HA), NA); e_expect(BAR(B_HB), 65536 - NA);
      wait_eq(&f_h1[c == 1 ? 0 : 1], E); fence_async_glob();
      {
        const uint32_t o0 = c == 0 ? NA : 0, o1 = c == 2 ? NA : 32768;
        e_mc(sb + M_H + (c == 1 ? 32768 : 0) + o0, g_h[0][c == 1 ? 0 : 1] + o0, o1 - o0, BAR(c == 2 ? B_HA : B_HB), 7);
      }
      TSTAMP(14, cta, 3);
      if (c == 2) wait_eq(&f_h1[2], E);
      mbar_wait(BAR(B_HAE), 1);
      e_expect(BAR(B_HA), NA);
      if (c == 2) { fence_async_glob(); e_mc(sb + M_H, g_h[0][2], NA, BAR(B_HA), 7); }
      int cprev = -1;
#pragma unroll 1
      for (int T = 0; T < NSTEP - 1; T++) {
        const int s1 = T + 2, s2 = T + 2 - LAG;
        const uint32_t ph = T & 1;
        const bool l1 = s1 < NSEG, l2 = s2 >= 0 && s2 < NSEG, la = s1 + 1 < NSEG;
        const bool mine = c == 0 ? l1 : c == 1 ? l2 : la;
        const uint32_t* fl = c != 1 ? &f_h1[min(s1 + (c >> 1), NSEG - 1)] : (const uint32_t*)f_h2[max(s2, 0)][lane & 3] + 1;
        const uint32_t want = E & 0x1FFFFFu, sh = c != 1 ? 0 : 11;
        mbar_wait(BAR(B_HBE), ph ^ 1);
        const bool early = __all_sync(~0u, ((ld_acq(fl) >> sh) & 0x1FFFFFu) == want);
        mbar_wait(BAR(B_LAND + 2), ph);
        STAMP(16);
        e_expect(BAR(B_HB), (l1 ? 32768 - NA : 0) + (l2 ? 32768 : 0));
        if (mine) {
          if (!early) {
            int guard = 0;
            while (!__all_sync(~0u, ((ld_acq(fl) >> sh) & 0x1FFFFFu) == want)) { __nanosleep(32); if (++guard > (1 << 22)) TRAP(); }
          }
          fence_async_glob();
          if (c == 1) { mbar_wait(BAR(B_QK), ph); spin_until(clk32() + HDLY_); }
          if (c < 2) paced_h(sb + M_H + c * 32768, g_h[c][c ? s2 : s1], c ? 0 : NA, 32768, 4096, BAR(B_HB), HGAP_);
        }
        int cd = -1;
        if (l2) { cd = route_step(s2, E, lane, run); if (cta == 0) TSTAMP(5, s2, 0); }
        if (lane == 0) sts32(sb + M_CAND + ((T + 2) & 3) * 4, (uint32_t)cd);
        __syncwarp();
        STAMP(17);
        mbar_wait(BAR(B_HAE), ph);
        e_expect(BAR(B_HA), la ? NA : 0);
        if (c == 2 && la) {
          spin_until(clk32() + ADLY_);
          STAMP(18);
          paced_h(sb + M_H, g_h[0][s1 + 1], 0, NA, 4096, BAR(B_HA), AGAP_);
        }
        mbar_wait(BAR(B_OST), ph);
        e_expect(BAR(B_QK), c < 2 ? 2048 : cprev >= 0 ? 8192 : 4096);
        e_expect(BAR(B_V), c < 2 ? 10240 : 8192);
        e_expect(BAR(B_TOK), 16384);
        e_expect(BAR(B_OM), 4096);
        cprev = cd;
      }
    } else {
      const uint32_t mytok = sb + M_Q + c * 12288 + 2048, tb = BAR(c < 2 ? B_TOK : B_V);
      mbar_wait(BAR(B_STG1), 0);
      fence_async_smem();
      e_s2g(g_tok[cta][1], sb + M_TST, 8192);
#pragma unroll 1
      for (int T = 0; T < NSTEP - 1; T++) {
        const uint32_t ph = T & 1;
        uint8_t* const tok = g_tok[cta][ph ^ 1];
        mbar_wait(BAR(B_STG), ph ^ 1);
        fence_async_smem();
        if (cta == 0 && (T == 0 || T == NSEG || T == NSTEP - 2)) GSTAMP(0, T == 0 ? 2 : T == NSEG ? 3 : 4);
        if (T > 0 && TQ_) mbar_wait(BAR(B_QK), ph);
        STAMP(20);
        uint32_t t = clk32();
        e_s2g(tok + 8192, sb + M_TST + 8192, XT2_);
        spin_until(t + TGAP_);
        e_s2g(tok + 12288, sb + M_TST + 12288, XT2_);
        bulk_wait();
        __syncwarp();
        e_arrive(BAR(B_TFREE));
        if (T == 0) e_mc(mytok, tok + 8192, 8192, tb, 1);
        STAMP(21);
#pragma unroll 1
        for (int k = 0; k < 2; k++) {
          if (k == 1) {
            mbar_wait(BAR(B_STG1), ph ^ 1);
            fence_async_smem();
            t = uni(lds32(sb + M_BAS2 + ph * 4));
            wait_until(t + TDLY_);
            e_s2g(g_tok[cta][ph], sb + M_TST, XT1_);
          }
          if (k == (c >> 1)) {
            mbar_wait(BAR(c < 2 ? B_KFREE : B_VFREE), ph);
            t = k ? t + LDLY_ : clk32() + KDLY_;
            wait_until(t);
            STAMP(23);
            e_mc(mytok, tok, 8192, tb, 1);
            spin_until(t + LGAP_);
            e_mc(mytok, tok + 8192, 8192, tb, 6);
            STAMP(24);
          }
        }
      }
      bulk_wait();
    }
    __syncwarp();
    cluster_sync();
  }
}

constexpr uint32_t A_RING = 0;
constexpr int A_NST = 6;
constexpr uint32_t A_STG = A_RING + A_NST * 8192;
constexpr uint32_t A_WD = A_STG + 8192;
constexpr uint32_t A_WG = A_WD + 57344;
constexpr uint32_t A_WU = A_WG + 57344;
constexpr uint32_t A_XN = A_WU + 57344;
constexpr uint32_t A_BAR = A_XN + 2048;
constexpr uint32_t A_TOTAL = A_BAR + 256;
static_assert(A_TOTAL <= 232448, "aux smem");

__device__ __forceinline__ uint32_t ptag(int s) { return ((s / PRING) & 1) ^ 1; }
static_assert((NSEG / PRING) % 2 == 0, "tags");
__device__ __forceinline__ void load_row(uint32_t* v, const void* row, int lane) {
  const uint4 a = __ldcg((const uint4*)row + lane), b = __ldcg((const uint4*)row + 32 + lane);
  v[0] = a.x; v[1] = a.y; v[2] = a.z; v[3] = a.w; v[4] = b.x; v[5] = b.y; v[6] = b.z; v[7] = b.w;
}
__device__ __forceinline__ void store_row(void* row, const uint32_t* v, int lane) {
  ((uint4*)row)[lane] = make_uint4(v[0], v[1], v[2], v[3]); ((uint4*)row)[32 + lane] = make_uint4(v[4], v[5], v[6], v[7]);
}
__device__ __forceinline__ void store_img(uint8_t* img, int r, const uint32_t* v, int lane) {
  uint8_t* b = img + (lane >> 3) * 4096 + (r >> 3) * 1024 + (r & 7) * 128 + (((lane ^ r) & 7) << 4);
  *(uint4*)b = make_uint4(v[0], v[1], v[2], v[3]);
  *(uint4*)(b + 16384) = make_uint4(v[4], v[5], v[6], v[7]);
}
template <int NT> __device__ __forceinline__ void ln_rows(const uint32_t (*v)[8], uint32_t (*y)[8]) {
  float c[NT], sm[NT], sq[NT];
#pragma unroll
  for (int k = 0; k < NT; k++) {
    c[k] = blo(__shfl_sync(~0u, v[k][0], 0));
    float s0 = 0.f, s1 = 0.f, q0 = 0.f, q1 = 0.f;
#pragma unroll
    for (int i = 0; i < 8; i++) { const float a = blo(v[k][i]) - c[k], b = bhi(v[k][i]) - c[k]; s0 += a; s1 += b; q0 = fmaf(a, a, q0); q1 = fmaf(b, b, q1); }
    sm[k] = s0 + s1; sq[k] = q0 + q1;
  }
#pragma unroll
  for (int o = 16; o > 0; o >>= 1)
#pragma unroll
    for (int k = 0; k < NT; k++) {
      sm[k] += __shfl_xor_sync(~0u, sm[k], o); sq[k] += __shfl_xor_sync(~0u, sq[k], o);
    }
#pragma unroll
  for (int k = 0; k < NT; k++) {
    const float dm = sm[k] * (1.f / 512.f), var = fmaxf(fmaf(-dm, dm, sq[k] * (1.f / 512.f)), 0.f);
    const float mb = rbf(c[k] + dm), inv = rcp(rbf(sqrt_fast(rbf(rbf(var) + 1e-5f))));
#pragma unroll
    for (int i = 0; i < 8; i++) { const uint32_t a = pack2(blo(v[k][i]) - mb, bhi(v[k][i]) - mb); y[k][i] = pack2(blo(a) * inv, bhi(a) * inv); }
  }
}
__device__ __forceinline__ void input_ln_pair(const bf16* x, int s, int pr, int lane) {
  uint32_t v[2][8], y[2][8];
  load_row(v[0], x + (size_t)(s * 32 + 2 * pr) * 512, lane); load_row(v[1], x + (size_t)(s * 32 + 2 * pr + 1) * 512, lane);
  ln_rows<2>(v, y);
  store_img(g_h[0][s], 2 * pr, y[0], lane); store_img(g_h[0][s], 2 * pr + 1, y[1], lane);
}
__device__ __forceinline__ float load_wr(uint32_t* wv, const bf16* wr, int lane) {
  load_row(wv, wr, lane);
  float wsum = 0.f;
#pragma unroll
  for (int i = 0; i < 8; i++) wsum += blo(wv[i]) + bhi(wv[i]);
#pragma unroll
  for (int o = 16; o > 0; o >>= 1) wsum += __shfl_xor_sync(~0u, wsum, o);
  return wsum;
}

template <bool FAST>
__device__ __forceinline__ unsigned long long token_post(int st, int tk, const bf16* res, bf16* dst, bf16* req, unsigned long long best,
                                                         const uint32_t* wv, float wsum, uint32_t E, int lane) {
  const int s = tk >> 5;
  uint32_t x[8];
  load_row(x, res, lane);
  {
    int guard = 0;
    while (__popc(__ballot_sync(~0u, ld_rlx(f_acc[st][s][lane]) == E)) < (FAST ? HINT_ : 32)) { __nanosleep(FAST ? 20 : 100); if (++guard > (1 << 22)) TRAP(); }
  }
  if (tk == s * 32 && st == 0 && lane == 0) TSTAMP(4, s, 0);
  {
    const uint8_t* pp = g_pp[st][s % PRING] + (lane >> 4) * 8192 + (tk & 31) * 256 + (((lane & 15) ^ (tk & 7)) << 4);
    const uint32_t tag = ptag(s);
    uint4 q[8][2];
#define PLD(k, h) q[k][h] = ld_rlx128<(k) * 32768 + (h) * 16384>(pp)
#define PLD8(h) PLD(0, h); PLD(1, h); PLD(2, h); PLD(3, h); PLD(4, h); PLD(5, h); PLD(6, h); PLD(7, h)
#define PBAD(h) __any_sync(~0u, (or3(xo2(q[0][h].x, q[1][h].x, tag), xo2(q[2][h].x, q[3][h].x, tag), xo2(q[4][h].x, q[5][h].x, tag)) | xo2(q[6][h].x, q[7][h].x, tag)) & ~lane & (PST_ == 8192 ? 1u : 0u))
#define PSUM(f, h, m) (((f(q[0][h].m) + f(q[1][h].m)) + (f(q[2][h].m) + f(q[3][h].m))) + ((f(q[4][h].m) + f(q[5][h].m)) + (f(q[6][h].m) + f(q[7][h].m))))
    const uint32_t eye = (lane >> 2) == 2 * (lane & 3) ? 0x3f80u : (lane >> 2) == 2 * (lane & 3) + 1 ? 0x3f800000u : 0u;
    auto padd = [&](int h) {
      if (FAST) {
        float u[4] = {0.f, 0.f, 0.f, 0.f}, v[4] = {0.f, 0.f, 0.f, 0.f};
#pragma unroll
        for (int k = 0; k < 8; k++) { hmma8(u, q[k][h].x, q[k][h].y, eye); hmma8(v, q[k][h].z, q[k][h].w, eye); }
        x[4 * h] = add2(x[4 * h], pack2(u[0], u[1])); x[4 * h + 1] = add2(x[4 * h + 1], pack2(u[2], u[3]));
        x[4 * h + 2] = add2(x[4 * h + 2], pack2(v[0], v[1])); x[4 * h + 3] = add2(x[4 * h + 3], pack2(v[2], v[3]));
      } else {
        x[4 * h] = add2(x[4 * h], pack2(PSUM(blo, h, x), PSUM(bhi, h, x))); x[4 * h + 1] = add2(x[4 * h + 1], pack2(PSUM(blo, h, y), PSUM(bhi, h, y)));
        x[4 * h + 2] = add2(x[4 * h + 2], pack2(PSUM(blo, h, z), PSUM(bhi, h, z))); x[4 * h + 3] = add2(x[4 * h + 3], pack2(PSUM(blo, h, w), PSUM(bhi, h, w)));
      }
    };
    int guard = 0;
    PLD8(0);
    if (FAST) { PLD8(1); }
    while (PBAD(0)) { if (++guard > (1 << 20)) TRAP(); PLD8(0); }
    padd(0);
    if (!FAST) { PLD8(1); }
    while (PBAD(1)) { if (++guard > (1 << 20)) TRAP(); PLD8(1); }
    padd(1);
  }
  const float c = blo(__shfl_sync(~0u, x[0], 0));
  float s0 = 0.f, s1 = 0.f, q0 = 0.f, q1 = 0.f, r0 = 0.f, r1 = 0.f;
#pragma unroll
  for (int i = 0; i < 8; i++) {
    const float a = blo(x[i]) - c, b = bhi(x[i]) - c;
    s0 += a; s1 += b; q0 = fmaf(a, a, q0); q1 = fmaf(b, b, q1); r0 = fmaf(a, blo(wv[i]), r0); r1 = fmaf(b, bhi(wv[i]), r1);
  }
  s0 += s1; q0 += q1; r0 += r1;
#pragma unroll
  for (int o = 16; o > 0; o >>= 1) { s0 += __shfl_xor_sync(~0u, s0, o); q0 += __shfl_xor_sync(~0u, q0, o); r0 += __shfl_xor_sync(~0u, r0, o); }
  const float dm = s0 * (1.f / 512.f), m = c + dm, var = fmaxf(fmaf(-dm, dm, q0 * (1.f / 512.f)), 0.f);
  const float mb = rbf(m), inv = rcp(rbf(sqrt_fast(rbf(rbf(var) + 1e-5f))));
  const uint32_t nmb = pack2(-mb, -mb);
  const unsigned long long wd = rword(E, tk, fmaf(c - mb, wsum, r0) * inv);
  uint32_t xn[8], x2[8];
#pragma unroll
  for (int i = 0; i < 8; i++) { const uint32_t d = add2(x[i], nmb); xn[i] = pack2(blo(d) * inv, bhi(d) * inv); x2[i] = add2(x[i], xn[i]); }
  if (st == 0) {
    const float mb2 = rbf(fmaf(m - mb, inv, m)), inv2 = rcp(rbf(sqrt_fast(rbf(rbf(var * (1.f + inv) * (1.f + inv)) + 1e-5f))));
    const uint32_t nmb2 = pack2(-mb2, -mb2);
    uint32_t h[8];
#pragma unroll
    for (int i = 0; i < 8; i++) { const uint32_t d2 = add2(x2[i], nmb2); h[i] = pack2(blo(d2) * inv2, bhi(d2) * inv2); }
    store_img(g_h[1][s], tk & 31, h, lane);
  }
  store_row(dst, x2, lane);
  if (wd > best && !(EXPQ_ & (st == 0 ? 1 : 2))) { store_row(req, xn, lane); store_row(req + 512, x, lane); }
  return wd;
}

__device__ __forceinline__ void ffn_slice(uint32_t sb, const bf16* xn, float* yacc, uint32_t* flag, uint32_t E, int t, bool urgent) {
  const int w = t >> 5, g = (t >> 2) & 7;
  if (t == 0 && urgent) sts32(sb + A_BAR + 160, 1);
  { const uint2 u = __ldcg((const uint2*)xn + t); asm volatile("st.shared.v2.u32 [%0], {%1,%2};" :: "r"(sb + A_XN + t * 8), "r"(u.x), "r"(u.y) : "memory"); }
  fence_async_smem();
  bar_sync(4, 128);
  float ga[4], ua[4];
  constexpr uint64_t da = mkdesc(A_WG, 896, 128, 0), db = mkdesc(A_XN, 16, 128, 0);
  wg_fence();
  wgmma_ss8<0, 1, 0>(ga, da, db); wgmma_ss8<0, 1, 0>(ua, da + (A_WU - A_WG) / 16, db);
#pragma unroll
  for (int ks = 1; ks < 32; ks++) { wgmma_ss8<1, 1, 0>(ga, da + ks * 112, db + ks * 2); wgmma_ss8<1, 1, 0>(ua, da + (A_WU - A_WG) / 16 + ks * 112, db + ks * 2); }
  wg_commit(); wg_wait<0>(); reg_fence(ga); reg_fence(ua);
  if ((t & 3) == 0) {
#pragma unroll
    for (int h = 0; h < 2; h++) {
      const float gs = rbf(ga[2 * h]), us = rbf(ua[2 * h]);
      const float v = 16 * w + 8 * h < 56 ? rbf(gs * rcp(1.f + __expf(-gs))) * us : 0.f;
      asm volatile("st.shared.u16 [%0], %1;" :: "r"(sb + A_XN + 1280 + (16 * w + 8 * h + g) * 2), "h"((unsigned short)pack2(v, 0.f)) : "memory");
    }
  }
  fence_async_smem();
  bar_sync(4, 128);
#pragma unroll 1
  for (int j = 0; j < 2; j++) {
    float y[4][4];
    const uint64_t dd = mkdesc(A_WD, 8192, 128, 0) + (uint64_t)(j * 256);
    wg_fence();
#pragma unroll
    for (int m = 0; m < 4; m++) {
      wgmma_ss8<0, 1, 0>(y[m], dd + m * 64, mkdesc(A_XN + 1280, 16, 128, 0));
#pragma unroll
      for (int ks = 1; ks < 4; ks++) wgmma_ss8<1, 1, 0>(y[m], dd + m * 64 + ks * 1024, mkdesc(A_XN + 1280 + ks * 32, 16, 128, 0));
    }
    wg_commit(); wg_wait<0>();
#pragma unroll
    for (int m = 0; m < 4; m++) {
      reg_fence(y[m]);
      if ((t & 3) == 0) { float* o = yacc + j * 256 + m * 64 + 16 * w + g; atomicAdd(o, y[m][0]); atomicAdd(o + 8, y[m][2]); }
    }
  }
  bar_sync(4, 128);
  if (t < 8) { sts32(sb + A_BAR + 160, 0); st_rel(flag + t, E); }
  __syncwarp();
}

__device__ __forceinline__ void ffn_finish(int q, const bf16* req, float r, uint32_t E, int lane, uint32_t* v) {
  uint32_t xn[8];
  load_row(xn, req, lane); load_row(v, req + 512, lane);
  const float rs = rbf(1.f / (1.f + __expf(-rbf(r))));
  wait_all(f_y[q][lane], E);
  float4 y[4];
#pragma unroll
  for (int i = 0; i < 4; i++) y[i] = __ldcg((const float4*)g_y[q] + (i >> 1) * 64 + 2 * lane + (i & 1));
#pragma unroll
  for (int i = 0; i < 4; i++) {
    v[2 * i] = add2(v[2 * i], add2(xn[2 * i], pack2(rbf(y[i].x) * rs, rbf(y[i].y) * rs)));
    v[2 * i + 1] = add2(v[2 * i + 1], add2(xn[2 * i + 1], pack2(rbf(y[i].z) * rs, rbf(y[i].w) * rs)));
  }
}
__global__ void __launch_bounds__(512, 1) aux_kernel(Params p) {
  extern __shared__ __align__(1024) uint8_t sm[];
  const uint32_t sb = smem_u32(sm);
  if ((sb & 0xFFFFFFu) != SBASE) TRAP();
  const int warp = __shfl_sync(~0u, threadIdx.x >> 5, 0);
  const int cta = blockIdx.x;
  const uint32_t E = __shfl_sync(~0u, *(volatile uint32_t*)&g_epoch + 1, 0);
  const uint32_t bars = sb + A_BAR;

  if (cta < 32) {
    const int cg = cta & 3, kg = cta >> 2;
    if (threadIdx.x == 0) {
      for (int i = 0; i < A_NST; i++) { mbar_init(bars + 8 * i, 1); mbar_init(bars + 64 + 8 * i, 2); }
      mbar_init(bars + 128, 8); mbar_init(bars + 136, 8); mbar_init(bars + 144, 1);
      sts32(bars + 160, 0);
      asm volatile("fence.mbarrier_init.release.cluster;" ::: "memory");
    }
    if (warp < 8) {
      asm volatile("setmaxnreg.inc.sync.aligned.u32 176;");
      const int tid = fresh_tid(), lane = tid & 31;
      uint32_t W[32][4];
      stage_weights(sb + A_WD, p.wo + (size_t)kg * 512 * 512 + cg * 128, 512, tid, 256);
      cp_async_wait();
      bar_sync(1, 256);
      load_frags(W, sb + A_WD, warp >> 2, warp & 3, lane);
      bar_sync(2, 512);
      const uint32_t so = sb + A_STG + ((lane >> 4) * 8 + (lane & 7)) * 256 + (((warp * 2 + ((lane >> 3) & 1)) ^ (lane & 7)) << 4);
      const uint32_t tm = lane < 4 ? 0x00010001u : 0u;
      int stage = 0; uint32_t ph = 0, job = 0;
#pragma unroll 1
      for (int T = 0; T < NSTEP; T++) {
#pragma unroll 1
        for (int k = 0; k < 3; k++) {
          const int st = k == 0 ? 0 : 3 - k, s = st == 0 ? T : T - LAG;
          if (s < 0 || s >= NSEG) continue;
          float d[16];
#pragma unroll
          for (int hh = 0; hh < 4; hh++) {
            mbar_wait(bars + 8 * stage, ph);
            while (uni(lds32(bars + 160))) __nanosleep(100);
            const uint64_t db = mkdesc(A_RING, 512, 128, 0) + (uint64_t)(stage * 512);
            wg_fence();
            if (hh == 0) wgmma_rs32<0, 0>(d, W[0], db); else wgmma_rs32<1, 0>(d, W[hh * 8], db);
#pragma unroll
            for (int ks = 1; ks < 8; ks++) wgmma_rs32<1, 0>(d, W[hh * 8 + ks], db + ks * 64);
            wg_commit();
            if (hh > 0) { wg_wait<1>(); if ((tid & 127) == 0) mbar_arrive(bars + 64 + 8 * (stage == 0 ? A_NST - 1 : stage - 1)); }
            if (++stage == A_NST) { stage = 0; ph ^= 1; }
          }
          mbar_wait(bars + 144, (job & 1) ^ 1);
          wg_wait<0>(); reg_fence(d);
          if ((tid & 127) == 0) mbar_arrive(bars + 64 + 8 * (stage == 0 ? A_NST - 1 : stage - 1));
          if (cta == 0 && tid == 0) TSTAMP(6, T, k);
          const uint32_t tv = tm * ptag(s);
#define TG(i) ((pack2(d[2 * (i)], d[2 * (i) + 1]) & ~tm) | tv)
          stmatrix4_t(so, TG(0), pack2(d[2], d[3]), TG(2), pack2(d[6], d[7]));
          stmatrix4_t(so + 4096, TG(4), pack2(d[10], d[11]), TG(6), pack2(d[14], d[15]));
          fence_async_smem();
          __syncwarp();
          if (lane == 0) mbar_arrive(bars + 128 + 8 * (job & 1));
          job++;
        }
      }
    } else if (warp < 12) {
      asm volatile("setmaxnreg.dec.sync.aligned.u32 120;");
      const int tid = fresh_tid(), lane = tid & 31;
      const int w = warp - 8, t = tid - 256;
#pragma unroll 1
      for (int s = cta + 4; s < NSEG; s += 32) {
#pragma unroll 1
        for (int pr = w; pr < 16; pr += 4) input_ln_pair(p.x, s, pr, lane);
        bar_sync(4, 128);
        if (t == 0) st_rel(&f_h1[s], E);
      }
      bar_sync(2, 512);
      { int guard = 0; while (ld_rlx(&f_loaded[cta]) != E) { __nanosleep(200); if (++guard > (1 << 22)) TRAP(); } }
#pragma unroll 1
      for (int i = t; i < 512 * 7; i += 128) {
        const int k = i / 7, pc = i % 7;
        cp_async16(sb + A_WG + (k >> 3) * 896 + pc * 128 + (k & 7) * 16, p.wg + (size_t)k * 1792 + cta * 56 + pc * 8);
        cp_async16(sb + A_WU + (k >> 3) * 896 + pc * 128 + (k & 7) * 16, p.wu + (size_t)k * 1792 + cta * 56 + pc * 8);
        cp_async16(sb + A_WD + (i >> 9) * 8192 + (i & 63) * 128 + ((i >> 6) & 7) * 16, p.wd + (size_t)cta * 56 * 512 + i * 8);
      }
      uint32_t wv[8];
      const float wsum = load_wr(wv, p.wr, lane);
      cp_async_wait();
      fence_async_smem();
      wait_all(&f_zero[lane], E);
      bar_sync(4, 128);
      const int tj = (cta * 4 + w) & 31, st = 1 + ((cta >> 3) & 1), sq = cta >> 4;
      unsigned long long run = 0, run2 = 0, best = 0, hist = 0;
      uint32_t open = 0;
#pragma unroll 1
      for (int i = 0; i <= NSTEP; i++) {
        int tok = -1; const bf16* req = nullptr;
        if (i < NSEG) {
          const int cd = (int)uni(route_step(i, E, lane, run));
          run = __shfl_sync(~0u, run, 0);
          hist = hist << 8 | (uint32_t)(cd + 1);
          if (cd >= 0) { tok = rtok(run); req = g_req1[tok][0]; }
        } else {
          const unsigned long long m = wait_words(f_l2[i - NSEG], E);
          const unsigned long long n = ld_rlxu64(f_l2[min(i - NSEG + 1 + (lane & 7), LAG)]);
          const bool over = bar_or(4, 128, rfresh(n, E) && n != m);
          if (m != run2 && !over) { run2 = m; tok = rtok(m); req = g_req2[(tok >> 5) < (rtok(run) >> 5) ? 0 : 1][tok][0]; }
        }
        tok = __shfl_sync(~0u, tok, 0);
        if (tok >= 0) {
          if (cta == 0 && t == 0) TSTAMP(8, i, 0);
          ffn_slice(sb, req, g_y[i], f_y[i][cta], E, t, i < NSEG);
          if (cta == 0 && t == 0) TSTAMP(8, i, 1);
        }
        const int s = i - LAG;
        if (s < 0 || i >= NSEG) continue;
        const int cd = (int)((hist >> (8 * LAG)) & 255) - 1;
        if (cd >= 0 && st == 2) best = 0;
        const int ts = rtok(run) >> 5;
        if ((s & 1) == sq) {
          const int tk = s * 32 + tj;
          unsigned long long wd = (unsigned long long)E << 43;
          if (st == 1 ? s < ts || i < NSEG - 1 : s >= ts) {
            if (st == 2 && cd == tj) wait_eq(&f_hc[s], E);
            wd = token_post<false>(st, tk, st == 2 && cd == tj ? g_x2c[s] : g_x2 + (size_t)tk * 512,
                                   (st == 2 || s < ts ? p.out : g_n) + (size_t)tk * 512, g_req2[st - 1][tk][0], best, wv, wsum, E, lane);
            best = max(best, wd);
            if (st == 1 && s >= ts) open |= 1u << (s >> 1);
          }
          __syncwarp();
          if (lane < 4) st_rel64(&f_w2[st - 1][s][tj][lane], wd);
          __syncwarp();
        }
        if (st == 1) {
          if (i == NSEG - 1 && t == 0 && cta == 0) GSTAMP(1, 0);
#pragma unroll 1
          for (int n = i == NSEG - 1 ? 32 : 2; n > 0 && open; n--) {
            const int s0 = 2 * (__ffs(open) - 1) + sq;
            if (s0 >= ts) break;
            open &= open - 1;
            uint32_t v[8];
            load_row(v, g_n + (size_t)(s0 * 32 + tj) * 512, lane);
            wait_words(f_w2[1][s0][tj], E);
            store_row(p.out + (size_t)(s0 * 32 + tj) * 512, v, lane);
          }
          if (i == NSEG - 1) {
            __syncwarp();
            if (lane == 0) st_rel(&f_cp[sq * 32 + tj], E);
            if (t == 0 && cta == 0) GSTAMP(1, 3);
          }
        }
      }
    } else {
      asm volatile("setmaxnreg.dec.sync.aligned.u32 40;");
      const int tid = fresh_tid(), lane = tid & 31;
      const int t = tid - 384, w = warp - 12;
      for (int i = cta * 128 + t; i < (NSTEP + 1) * 128; i += 4096) ((float4*)&g_y[0][0])[i] = make_float4(0.f, 0.f, 0.f, 0.f);
      bar_sync(3, 128);
      if (t == 0) st_rel(&f_zero[cta], E);
      bar_sync(2, 512);
      if (w == 0) {
        int stage = 0; uint32_t ph = 1;
#pragma unroll 1
        for (int T = 0; T < NSTEP; T++) {
#pragma unroll 1
          for (int k = 0; k < 3; k++) {
            const int st = k == 0 ? 0 : 3 - k, s = st == 0 ? T : T - LAG;
            if (s < 0 || s >= NSEG) continue;
            const uint32_t* fl = f_o[T][kg][st * 4 + (lane & 3)];
            uint32_t ready = 0; int guard = 0;
#pragma unroll 1
            for (int hh = 0; hh < 4; hh++) {
              while (!((ready >> hh) & 1)) {
                ready = __ballot_sync(~0u, ld_rlx(fl) == E);
                if (++guard > (1 << 23)) TRAP();
              }
              fence_async_glob();
              mbar_wait(bars + 64 + 8 * stage, ph);
              e_expect(bars + 8 * stage, OLOAD_);
              e_g2s(sb + A_RING + stage * 8192, g_o[st][s % ORING][kg * 4 + hh], OLOAD_, bars + 8 * stage);
              if (++stage == A_NST) { stage = 0; ph ^= 1; }
            }
          }
          if (cta == 0 && lane == 0) TSTAMP(3, T, 0);
        }
      } else if (w < 3) {
        uint32_t job = 0;
#pragma unroll 1
        for (int T = 0; T < NSTEP; T++) {
#pragma unroll 1
          for (int k = 0; k < 3; k++) {
            const int st = k == 0 ? 0 : 3 - k, s = st == 0 ? T : T - LAG;
            if (s < 0 || s >= NSEG) continue;
            if ((job++ & 1) != w - 1) continue;
            if (s >= PRING) wait_words(st == 0 ? f_h2[s - PRING][lane & 3] : f_w2[st - 1][s - PRING][lane], E);
            mbar_wait(bars + 128 + 8 * (w - 1), ((job - 1) >> 1) & 1);
            if (cta == 0 && st == 0) TSTAMP(7, s, 0);
            e_s2g(g_pp[st][s % PRING] + cta * 8192, sb + A_STG, PST_);
            if (lane < 8) st_rlx(&f_acc[st][s][cta][lane], E);
            asm volatile("cp.async.bulk.commit_group;\n cp.async.bulk.wait_group.read 0;" ::: "memory");
            __syncwarp();
            e_arrive(bars + 144);
            __syncwarp();
            if (cta == 0 && st == 0) TSTAMP(7, s, 1);
          }
        }
        bulk_wait();
      }
    }
  } else {
    const int tid = fresh_tid(), lane = tid & 31;
    const int qd = cta - 32;
    input_ln_pair(p.x, qd, warp, lane);
    bar_sync(6, 512);
    if (tid == 0) st_rel(&f_h1[qd], E);
    volatile int* bc = (volatile int*)sm;
    if (warp == 15) {
      unsigned long long run = 0;
      wait_all(&f_zero[lane], E);
      unsigned long long b2[2][2] = {{0, 0}, {0, 0}};
      auto track = [&](int s) {
#pragma unroll
        for (int k = 0; k < 2; k++) {
          const unsigned long long m = warp_max<16>(wait_words(f_w2[k][s][lane], E));
          if (lane == (s & 31)) { if (s < 32) b2[k][0] = m; else b2[k][1] = m; }
        }
      };
#pragma unroll 1
      for (int s = 0; s < NSEG; s++) {
        const int cd = route_step(s, E, lane, run);
        if (cd >= 0 && qd == (s & 1)) {
          uint32_t v[1][8], h[1][8];
          ffn_finish(s, g_req1[s * 32 + cd][0], rscore(run), E, lane, v[0]);
          if (lane == 0) TSTAMP(8, s, 2);
          ln_rows<1>(v, h);
#pragma unroll
          for (int i = 0; i < 8; i++) st_rlx64(&g_hc[s][(i >> 2) * 128 + 4 * lane + (i & 3)], h[0][i], E);
          if (lane == 0) TSTAMP(8, s, 3);
          store_row(g_x2c[s], v[0], lane);
          __syncwarp();
          if (lane == 0) st_rel(&f_hc[s], E);
        }
        if (qd == 2 && s > LAG) track(s - LAG - 1);
      }
      wait_eq(&f_hc[rtok(run) >> 5], E);
      if (lane == 0) *bc = rtok(run);
      bar_sync(7, 288);
      if (qd == 2) {
        uint32_t v[8];
        const int ts = rtok(run) >> 5;
        track(NSEG - LAG - 1);
        run = 0;
        int kl = 0;
#pragma unroll 1
        for (int k = 0; k <= LAG; k++) {
          const int s = NSEG - LAG - 1 + k;
          const unsigned long long m = warp_max<16>(k == 0 ? max(lane < ts ? b2[0][0] : b2[1][0], lane + 32 < ts ? b2[0][1] : b2[1][1])
                                                           : wait_words(f_w2[s < ts ? 0 : 1][s][lane], E));
          const bool lead = m > run;
          if (lead) { run = m; __threadfence(); }
          if (lane < 4) st_rlx64(&f_l2[k][lane], (uint32_t)run, (uint32_t)(run >> 32));
          if (lead) kl = k;
          if (k == LAG - 1) { wait_all(&f_cp[lane], E); wait_all(&f_cp[32 + lane], E); }
          if (k == LAG - 1 || (k == LAG && lead)) ffn_finish(NSEG + kl, g_req2[(rtok(run) >> 5) < ts ? 0 : 1][rtok(run)][0], rscore(run), E, lane, v);
        }
        if (lane == 0) GSTAMP(1, 1);
        store_row(p.out + (size_t)rtok(run) * 512, v, lane);
        if (lane == 0) GSTAMP(1, 2);
        asm volatile("griddepcontrol.wait;" ::: "memory");
        if (lane == 0) *(volatile uint32_t*)&g_epoch = E;
      }
    } else if (warp < 8) {
      uint32_t wv[8];
      const float wsum = load_wr(wv, p.wr, lane);
      unsigned long long best = 0;
      int ttok = 0;
#pragma unroll 1
      for (int i = 0; i < NSTEP; i++) {
        const bool last = i >= NSEG;
        if (i == NSEG) { bar_sync(7, 288); ttok = *bc; best = 0; }
        const int s = last ? i - LAG : i, st = !last ? 0 : s < (ttok >> 5) ? 1 : 2;
        const int tk = s * 32 + qd * 8 + warp;
        const unsigned long long wd = token_post<true>(st, tk, !last ? p.x + (size_t)tk * 512 : tk == ttok ? g_x2c[s] : g_x2 + (size_t)tk * 512,
                                                 (last ? p.out : g_x2) + (size_t)tk * 512, last ? g_req2[st - 1][tk][0] : g_req1[tk][0], best, wv, wsum, E, lane);
        best = max(best, wd);
        volatile unsigned long long* ws = (volatile unsigned long long*)(sm + 64) + (i & 1) * 8;
        if (lane == 0) ws[warp] = wd;
        bar_sync(5, 256);
        if (warp == 0) {
          if (qd == 0 && lane == 0) TSTAMP(4, i, 1);
          if (!last) { const unsigned long long m = warp_max<4>(ws[lane & 7]); if (lane < 4) st_rel64(&f_h2[s][qd][lane], m); }
          else {
            st_rel64(&f_w2[st - 1][s][qd * 8 + (lane >> 2)][lane & 3], ws[lane >> 2]);
            asm volatile("st.relaxed.gpu.global.u64 [%0], %1;" :: "l"(&f_w2[2 - st][s][qd * 8 + (lane >> 2)][lane & 3]), "l"((unsigned long long)E << 43) : "memory");
          }
          if (qd == 0 && lane == 0) TSTAMP(4, i, 2);
        }
        __syncwarp();
      }
    }
  }
}

}

extern "C" void kernel_launch(void* const* d_in, const int* in_sizes, int n_in, void* d_out, int out_size) {
  (void)in_sizes; (void)n_in; (void)out_size;
  static bool init = false;
  if (!init) {
    cudaFuncSetAttribute(main_kernel, cudaFuncAttributeMaxDynamicSharedMemorySize, M_TOTAL);
    cudaFuncSetAttribute(aux_kernel, cudaFuncAttributeMaxDynamicSharedMemorySize, A_TOTAL);
    init = true;
  }
  Params p;
  p.x = (const bf16*)d_in[0]; p.mem0 = (const bf16*)d_in[1]; p.wq = (const bf16*)d_in[2]; p.wk = (const bf16*)d_in[3];
  p.wv = (const bf16*)d_in[4]; p.wo = (const bf16*)d_in[5]; p.wr = (const bf16*)d_in[8]; p.wg = (const bf16*)d_in[9];
  p.wu = (const bf16*)d_in[10]; p.wd = (const bf16*)d_in[11]; p.out = (bf16*)d_out; p.zero = 0; p.zero2 = 0;
  cudaStream_t st = cudaStreamPerThread;
  main_kernel<<<96, 512, M_TOTAL, st>>>(p);
  cudaLaunchConfig_t cfg = {};
  cfg.gridDim = dim3(36); cfg.blockDim = dim3(512); cfg.dynamicSmemBytes = A_TOTAL; cfg.stream = st;
  cudaLaunchAttribute at[1];
  at[0].id = cudaLaunchAttributeProgrammaticStreamSerialization; at[0].val.programmaticStreamSerializationAllowed = 1;
  cfg.attrs = at; cfg.numAttrs = 1;
  cudaLaunchKernelEx(&cfg, aux_kernel, p);
}
```

```cpp
#include <cuda_runtime.h>
#include <cuda_bf16.h>
#include <stdint.h>

namespace {

typedef __nv_bfloat16 bf16;

constexpr int NSEG = 64;
#define LAG_ 5
constexpr int LAG = LAG_;
constexpr int NSTEP = NSEG + LAG;
constexpr int ORING = 8, PRING = 4;
static_assert(LAG < 8, "rings");
#define E1_ 10
#define E2_ 0
#define E3_ 10
constexpr int E1 = E1_, E2 = E2_, E3 = E3_, EA = E1 + E2 + E3;
static_assert(EA % 4 == 0 && EA > 0 && EA < 32 && E1 > 0, "early part: whole 64-column chunks");
#define RW_ 176
#define RA_ 136
#define RC_ 24
#define STR2(x) #x
#define STR(x) STR2(x)
#define RED_ 30
#define ARR_ 7
#define PAUSE_ 19
#define PD1_ 4
#define PST2_ 2
#define PGR_ PD1_
#define PVR_ -1
#define SALT_ 0
#define KP1_ 1
#define PRIV_ 1
#define OLOAD_ 8192
#define PST_ 8192
#define ALT_ 1
#define TQ_ 1
#define NOF_ 2
#define EXPQ_ 0
#define XT1_ 8192
#define XT2_ 4096
#define XO_ 8192
#define HINT_ 24
#define HADD_ 2
#define HAND_ 4
#define GO3_ 2
#define NPROBE_ 6
#define TP(i, v) (v)
#define XDLY_ TP(0, 2250)
#define YDLY_ TP(1, 3425)
#define X1_ TP(2, 100)
#define X2_ TP(3, 250)
#define Y1_ TP(4, 150)
#define Y2_ TP(5, 200)
#define HGAP_ TP(6, 50)
#define TGAP_ TP(7, 200)
#define ADLY_ TP(8, 600)
#define ODLY_ TP(9, 2800)
#define LDLY_ TP(10, 3800)
#define LGAP_ 200
#define HDLY_ TP(11, 0)
#define TDLY_ TP(15, 4075)
#define SDLY_ TP(12, 800)
#define AGAP_ 100
#define BOFF_ TP(13, 200)
#define YOFF_ TP(16, 150)
#define YUP_ TP(20, 40)
#define YDN_ TP(21, 4)
#define CDLY_ TP(17, 300)
#define SLOW0_ TP(18, 400)
#define SLOW1_ TP(19, 300)
#define KDLY_ TP(14, 300)
__device__ uint32_t g_epoch;
__device__ __align__(1024) uint8_t g_h[2][NSEG][32768];
__device__ __align__(128) uint2 g_hc[NSEG][256];
__device__ __align__(128) bf16 g_x2[2048 * 512];
__device__ __align__(128) bf16 g_x2c[NSEG][512];
__device__ __align__(128) uint8_t g_o[3][ORING][32][8192];
__device__ __align__(128) uint8_t g_pp[3][PRING][8 * 32768];
__device__ __align__(128) bf16 g_n[2048 * 512];
__device__ __align__(128) uint8_t g_xch[96 * 16384 + 65536 + 8192];
__device__ __align__(128) bf16 g_req1[2048][2][512];
__device__ __align__(128) bf16 g_req2[2][2048][2][512];
__device__ __align__(128) float g_y[8][32][512];
__device__ __align__(128) uint8_t g_tok[96][2][16384];
__device__ uint32_t f_choice[96][2], f_loaded[32];
__device__ uint32_t f_h1[NSEG], f_hc[NSEG];
__device__ __align__(128) unsigned long long f_h2[NSEG][4][4];
__device__ __align__(128) unsigned long long f_w2[2][NSEG][32][4];
__device__ __align__(128) unsigned long long f_l2[LAG + 1][4];
__device__ __align__(128) uint32_t f_o[NSTEP][8][12][8];
__device__ __align__(128) uint32_t f_acc[3][NSEG][32][8], f_y[NSTEP + 1][32][8], f_cp[64];
__device__ __align__(128) unsigned long long g_sync[2][96][4];

#define TRAP() __trap()
__device__ __forceinline__ uint32_t smem_u32(const void* p) { return (uint32_t)__cvta_generic_to_shared(p); }
__device__ __forceinline__ int fresh_tid() { const int t = threadIdx.x; return __shfl_sync(~0u, t, t & 31); }
__device__ __forceinline__ unsigned long long gtime64() { unsigned long long t; asm volatile("mov.u64 %0, %%globaltimer;" : "=l"(t) :: "memory"); return t; }
__device__ __forceinline__ uint32_t clk() { unsigned long long c; asm volatile("mov.u64 %0, %%clock64;" : "=l"(c) :: "memory"); return (uint32_t)c; }
__device__ __forceinline__ void wait_until(uint32_t t) {
  while ((int)(t - clk()) > 450) __nanosleep(32);
  uint32_t c;
  do { asm volatile("mov.u32 %0, %%clock;" : "=r"(c) :: "memory"); } while ((int)(c - t) < 0);
}
__device__ __forceinline__ void mbar_init(uint32_t bar, uint32_t cnt) { asm volatile("mbarrier.init.shared::cta.b64 [%0], %1;" :: "r"(bar), "r"(cnt) : "memory"); }
__device__ __forceinline__ void mbar_arrive(uint32_t bar) { asm volatile("mbarrier.arrive.shared::cta.b64 _, [%0];" :: "r"(bar) : "memory"); }
__device__ __forceinline__ void mbar_arrive_remote(uint32_t bar) { asm volatile("mbarrier.arrive.relaxed.cluster.shared::cluster.b64 _, [%0];" :: "r"(bar) : "memory"); }
__device__ __forceinline__ void mbar_expect(uint32_t bar, uint32_t bytes) { asm volatile("mbarrier.arrive.expect_tx.shared::cta.b64 _, [%0], %1;" :: "r"(bar), "r"(bytes) : "memory"); }
__device__ __forceinline__ bool mbar_try(uint32_t bar, uint32_t parity) {
  uint32_t ok;
  asm volatile("{.reg .pred p; mbarrier.try_wait.parity.shared::cta.b64 p, [%1], %2; selp.u32 %0, 1, 0, p;}" : "=r"(ok) : "r"(bar), "r"(parity) : "memory");
  return ok;
}
__device__ __forceinline__ bool mbar_test(uint32_t bar, uint32_t parity) {
  uint32_t ok;
  asm volatile("{.reg .pred p; mbarrier.test_wait.parity.shared::cta.b64 p, [%1], %2; selp.u32 %0, 1, 0, p;}" : "=r"(ok) : "r"(bar), "r"(parity) : "memory");
  return ok;
}
__device__ __forceinline__ void mbar_wait(uint32_t bar, uint32_t parity) {
  asm volatile("{\n.reg .pred p;\nWAIT:\nmbarrier.try_wait.parity.shared::cta.b64 p, [%0], %1;\n@!p bra WAIT;\n}" :: "r"(bar), "r"(parity) : "memory");
}
__device__ __forceinline__ uint32_t ld_acq(const uint32_t* p) { uint32_t v; asm volatile("ld.acquire.gpu.global.u32 %0, [%1];" : "=r"(v) : "l"(p) : "memory"); return v; }
__device__ __forceinline__ unsigned long long ld_acq64(const unsigned long long* p) { unsigned long long v; asm volatile("ld.acquire.gpu.global.u64 %0, [%1];" : "=l"(v) : "l"(p) : "memory"); return v; }
__device__ __forceinline__ void st_rel(uint32_t* p, uint32_t v) { asm volatile("st.release.gpu.global.u32 [%0], %1;" :: "l"(p), "r"(v) : "memory"); }
__device__ __forceinline__ void st_rel64(unsigned long long* p, unsigned long long v) { asm volatile("st.release.gpu.global.u64 [%0], %1;" :: "l"(p), "l"(v) : "memory"); }
__device__ __forceinline__ void red_rel(uint32_t* p, uint32_t v) { asm volatile("red.release.gpu.global.add.u32 [%0], %1;" :: "l"(p), "r"(v) : "memory"); }
__device__ __forceinline__ uint32_t ld_rlx(const uint32_t* p) { uint32_t v; asm volatile("ld.relaxed.gpu.global.u32 %0, [%1];" : "=r"(v) : "l"(p) : "memory"); return v; }
__device__ __forceinline__ unsigned long long ld_rlxu64(const unsigned long long* p) { unsigned long long v; asm volatile("ld.relaxed.gpu.global.u64 %0, [%1];" : "=l"(v) : "l"(p) : "memory"); return v; }
__device__ __forceinline__ void st_rlx(uint32_t* p, uint32_t v) { asm volatile("st.relaxed.gpu.global.u32 [%0], %1;" :: "l"(p), "r"(v) : "memory"); }
__device__ __forceinline__ void bulk_wait() { asm volatile("cp.async.bulk.commit_group;\n cp.async.bulk.wait_group 0;" ::: "memory"); }
__device__ __forceinline__ void fence_acq() { asm volatile("fence.acquire.gpu;" ::: "memory"); }
__device__ __forceinline__ void wait_all(const uint32_t* p, uint32_t v, bool acquire = true) {
  int guard = 0;
  while (!__all_sync(~0u, ld_rlx(p) == v)) { __nanosleep(32); if (++guard > (1 << 22)) TRAP(); }
  if (acquire) fence_acq();
}
__device__ __forceinline__ void wait_eq(const uint32_t* p, uint32_t v) {
  int guard = 0;
  while (ld_rlx(p) != v) { __nanosleep(64); if (++guard > (1 << 22)) TRAP(); }
  fence_acq();
}
__device__ __forceinline__ unsigned long long rword(uint32_t E, int tok, float r) {
  uint32_t u = __float_as_uint(r + 0.f);
  u = r != r ? 0u : (u >> 31) ? ~u : u | 0x80000000u;
  return (unsigned long long)(E & 0x1FFFFFu) << 43 | (unsigned long long)u << 11 | (uint32_t)(2047 - tok);
}
__device__ __forceinline__ int rtok(unsigned long long v) { return 2047 - (int)(v & 2047u); }
__device__ __forceinline__ float rscore(unsigned long long v) { const uint32_t u = (uint32_t)(v >> 11); return __uint_as_float((u >> 31) ? u & 0x7fffffffu : ~u); }
__device__ __forceinline__ bool rfresh(unsigned long long v, uint32_t E) { return (uint32_t)(v >> 43) == (E & 0x1FFFFFu); }
template <int TOP> __device__ __forceinline__ unsigned long long warp_max(unsigned long long v) {
#pragma unroll
  for (int o = TOP; o > 0; o >>= 1) { const unsigned long long ov = __shfl_xor_sync(~0u, v, o); v = ov > v ? ov : v; }
  return v;
}
template <int off> __device__ __forceinline__ uint2 ld_rlx64(const void* p) { unsigned long long v; asm volatile("ld.relaxed.gpu.global.b64 %0, [%1+%2];" : "=l"(v) : "l"(p), "n"(off) : "memory"); return make_uint2((uint32_t)v, (uint32_t)(v >> 32)); }
template <int off> __device__ __forceinline__ uint4 ld_rlx128(const void* p) {
  unsigned long long a, b; asm volatile("ld.relaxed.gpu.global.v2.b64 {%0,%1}, [%2+%3];" : "=l"(a), "=l"(b) : "l"(p), "n"(off) : "memory");
  return make_uint4((uint32_t)a, (uint32_t)(a >> 32), (uint32_t)b, (uint32_t)(b >> 32));
}
__device__ __forceinline__ void st_rlx64(void* p, uint32_t lo, uint32_t hi) { asm volatile("{.reg .b64 t; mov.b64 t, {%1,%2}; st.relaxed.gpu.global.b64 [%0], t;}" :: "l"(p), "r"(lo), "r"(hi) : "memory"); }
__device__ __forceinline__ void cp_async16(uint32_t dst, const void* src) { asm volatile("cp.async.cg.shared.global [%0], [%1], 16;" :: "r"(dst), "l"(src) : "memory"); }
__device__ __forceinline__ void cp_async_wait() { asm volatile("cp.async.wait_all;" ::: "memory"); }
__device__ __forceinline__ void fence_async_smem() { asm volatile("fence.proxy.async.shared::cta;" ::: "memory"); }
__device__ __forceinline__ void fence_async_glob() { asm volatile("fence.proxy.async.global;" ::: "memory"); }
__device__ __forceinline__ void fence_async_acq() { asm volatile("fence.proxy.async::generic.acquire.sync_restrict::shared::cluster.cluster;" ::: "memory"); }
__device__ __forceinline__ float ex2(float x) { float y; asm("ex2.approx.ftz.f32 %0, %1;" : "=f"(y) : "f"(x)); return y; }
__device__ __forceinline__ float sqrt_fast(float x) { float y; asm("sqrt.approx.ftz.f32 %0, %1;" : "=f"(y) : "f"(x)); return y; }
__device__ __forceinline__ float rcp(float x) { float y; asm("rcp.approx.ftz.f32 %0, %1;" : "=f"(y) : "f"(x)); return y; }
__device__ __forceinline__ void bar_sync(int id, int n) { asm volatile("bar.sync %0, %1;" :: "r"(id), "r"(n) : "memory"); }
__device__ __forceinline__ bool bar_or(int id, int n, bool v) {
  uint32_t r;
  asm volatile("{.reg .pred p, q; setp.ne.u32 p, %3, 0; barrier.cta.red.or.aligned.pred q, %1, %2, p; selp.u32 %0, 1, 0, q;}" : "=r"(r) : "r"(id), "r"(n), "r"((uint32_t)v) : "memory");
  return r;
}
__device__ __forceinline__ uint32_t mapa(uint32_t a, uint32_t rank) { uint32_t r; asm volatile("mapa.shared::cluster.u32 %0, %1, %2;" : "=r"(r) : "r"(a), "r"(rank)); return r; }
__device__ __forceinline__ void cluster_sync() { asm volatile("barrier.cluster.arrive.release.aligned; barrier.cluster.wait.acquire.aligned;" ::: "memory"); }
__device__ __forceinline__ void st_async32(uint32_t dst, uint32_t v, uint32_t bar) { asm volatile("st.async.shared::cluster.mbarrier::complete_tx::bytes.b32 [%0], %1, [%2];" :: "r"(dst), "r"(v), "r"(bar) : "memory"); }
__device__ __forceinline__ void bulk_g2s(uint32_t dst, const void* src, uint32_t bytes, uint32_t bar) {
  asm volatile("cp.async.bulk.shared::cluster.global.mbarrier::complete_tx::bytes [%0], [%1], %2, [%3];" :: "r"(dst), "l"(src), "r"(bytes), "r"(bar) : "memory");
}
__device__ __forceinline__ void bulk_g2s_mc(uint32_t dst, const void* src, uint32_t bytes, uint32_t bar, uint16_t mask) {
  asm volatile("cp.async.bulk.shared::cluster.global.mbarrier::complete_tx::bytes.multicast::cluster [%0], [%1], %2, [%3], %4;"
               :: "r"(dst), "l"(src), "r"(bytes), "r"(bar), "h"(mask) : "memory");
}
__device__ __forceinline__ void bulk_s2c(uint32_t dst, uint32_t src, uint32_t bytes, uint32_t bar) {
  asm volatile("cp.async.bulk.shared::cluster.shared::cta.mbarrier::complete_tx::bytes [%0], [%1], %2, [%3];" :: "r"(dst), "r"(src), "r"(bytes), "r"(bar) : "memory");
}
__device__ __forceinline__ void bulk_s2g(void* dst, uint32_t src, uint32_t bytes) {
  asm volatile("cp.async.bulk.global.shared::cta.bulk_group [%0], [%1], %2;" :: "l"(dst), "r"(src), "r"(bytes) : "memory");
}
#define ELECT(op) "{.reg .pred p; elect.sync _|p, 0xffffffff; @p " op "}"
__device__ __forceinline__ void e_arrive(uint32_t bar) { asm volatile(ELECT("mbarrier.arrive.shared::cta.b64 _, [%0];") :: "r"(bar) : "memory"); }
__device__ __forceinline__ void e_expect(uint32_t bar, uint32_t bytes) { asm volatile(ELECT("mbarrier.arrive.expect_tx.shared::cta.b64 _, [%0], %1;") :: "r"(bar), "r"(bytes) : "memory"); }
__device__ __forceinline__ void e_g2s(uint32_t dst, const void* src, uint32_t bytes, uint32_t bar) {
  asm volatile(ELECT("cp.async.bulk.shared::cluster.global.mbarrier::complete_tx::bytes [%0], [%1], %2, [%3];") :: "r"(dst), "l"(src), "r"(bytes), "r"(bar) : "memory");
}
__device__ __forceinline__ void e_mc(uint32_t dst, const void* src, uint32_t bytes, uint32_t bar, uint16_t mask) {
  asm volatile(ELECT("cp.async.bulk.shared::cluster.global.mbarrier::complete_tx::bytes.multicast::cluster [%0], [%1], %2, [%3], %4;")
               :: "r"(dst), "l"(src), "r"(bytes), "r"(bar), "h"(mask) : "memory");
}
__device__ __forceinline__ void e_s2g(void* dst, uint32_t src, uint32_t bytes) {
  asm volatile(ELECT("cp.async.bulk.global.shared::cta.bulk_group [%0], [%1], %2;") :: "l"(dst), "r"(src), "r"(bytes) : "memory");
}
__device__ __forceinline__ void e_st_rel(uint32_t* p, uint32_t v) { asm volatile(ELECT("st.release.gpu.global.u32 [%0], %1;") :: "l"(p), "r"(v) : "memory"); }
__device__ __forceinline__ uint32_t clk32() { uint32_t c; asm volatile("mov.u32 %0, %%clock;" : "=r"(c) :: "memory"); return c; }
__device__ __forceinline__ void spin_until(uint32_t t) { while ((int)(clk32() - t) < 0) {} }
__device__ __forceinline__ uint32_t uni(uint32_t v) { return __shfl_sync(~0u, v, 0); }
__device__ __forceinline__ uint32_t pack2(float lo, float hi) { uint32_t r; asm("cvt.rn.bf16x2.f32 %0, %1, %2;" : "=r"(r) : "f"(hi), "f"(lo)); return r; }
__device__ __forceinline__ uint32_t add2(uint32_t a, uint32_t b) { uint32_t r; asm("add.rn.bf16x2 %0, %1, %2;" : "=r"(r) : "r"(a), "r"(b)); return r; }
__device__ __forceinline__ float rbf(float x) { return __bfloat162float(__float2bfloat16_rn(x)); }
__device__ __forceinline__ float blo(uint32_t u) { return __uint_as_float(u << 16); }
__device__ __forceinline__ float bhi(uint32_t u) { return __uint_as_float(u & 0xffff0000u); }
__device__ __forceinline__ uint32_t gentag(uint32_t g) { return (g & 1u) | (g & 2u) << 15; }
__device__ __forceinline__ uint32_t pack2_tag(float lo, float hi, uint32_t tag) {
  const uint32_t u = __byte_perm(__float_as_uint(lo), __float_as_uint(hi), 0x7632);
  return u + ((u ^ tag) & 0x10001u);
}
__device__ __forceinline__ uint32_t xo2(uint32_t a, uint32_t b, uint32_t t) { uint32_t r; asm("lop3.b32 %0, %1, %2, %3, 0x7e;" : "=r"(r) : "r"(a), "r"(b), "r"(t)); return r; }
__device__ __forceinline__ uint32_t or3(uint32_t a, uint32_t b, uint32_t c) { uint32_t r; asm("lop3.b32 %0, %1, %2, %3, 0xfe;" : "=r"(r) : "r"(a), "r"(b), "r"(c)); return r; }
__device__ __forceinline__ void stmatrix4(uint32_t a, uint32_t r0, uint32_t r1, uint32_t r2, uint32_t r3) {
  asm volatile("stmatrix.sync.aligned.m8n8.x4.shared.b16 [%0], {%1,%2,%3,%4};" :: "r"(a), "r"(r0), "r"(r1), "r"(r2), "r"(r3) : "memory");
}
__device__ __forceinline__ void stmatrix4_t(uint32_t a, uint32_t r0, uint32_t r1, uint32_t r2, uint32_t r3) {
  asm volatile("stmatrix.sync.aligned.m8n8.x4.trans.shared.b16 [%0], {%1,%2,%3,%4};" :: "r"(a), "r"(r0), "r"(r1), "r"(r2), "r"(r3) : "memory");
}
__device__ __forceinline__ void ldmatrix4_t(uint32_t* r, uint32_t a) {
  asm volatile("ldmatrix.sync.aligned.m8n8.x4.trans.shared.b16 {%0,%1,%2,%3}, [%4];" : "=r"(r[0]), "=r"(r[1]), "=r"(r[2]), "=r"(r[3]) : "r"(a) : "memory");
}
__device__ __forceinline__ void ldmatrix4(uint32_t* r, uint32_t a) {
  asm volatile("ldmatrix.sync.aligned.m8n8.x4.shared.b16 {%0,%1,%2,%3}, [%4];" : "=r"(r[0]), "=r"(r[1]), "=r"(r[2]), "=r"(r[3]) : "r"(a) : "memory");
}
__device__ __forceinline__ void hmma16(float* c, const uint32_t* a, uint32_t b0, uint32_t b1) {
  asm volatile("mma.sync.aligned.m16n8k16.row.col.f32.bf16.bf16.f32 {%0,%1,%2,%3}, {%4,%5,%6,%7}, {%8,%9}, {%0,%1,%2,%3};"
               : "+f"(c[0]), "+f"(c[1]), "+f"(c[2]), "+f"(c[3]) : "r"(a[0]), "r"(a[1]), "r"(a[2]), "r"(a[3]), "r"(b0), "r"(b1));
}
__device__ __forceinline__ void hmma8(float* c, uint32_t a0, uint32_t a1, uint32_t b0) {
  asm volatile("mma.sync.aligned.m16n8k8.row.col.f32.bf16.bf16.f32 {%0,%1,%2,%3}, {%4,%5}, {%6}, {%0,%1,%2,%3};"
               : "+f"(c[0]), "+f"(c[1]), "+f"(c[2]), "+f"(c[3]) : "r"(a0), "r"(a1), "r"(b0));
}
__device__ __forceinline__ uint4 lds128(uint32_t a) { uint4 v; asm volatile("ld.shared.v4.u32 {%0,%1,%2,%3}, [%4];" : "=r"(v.x), "=r"(v.y), "=r"(v.z), "=r"(v.w) : "r"(a) : "memory"); return v; }
__device__ __forceinline__ void sts128(uint32_t a, uint4 v) { asm volatile("st.shared.v4.u32 [%0], {%1,%2,%3,%4};" :: "r"(a), "r"(v.x), "r"(v.y), "r"(v.z), "r"(v.w) : "memory"); }
__device__ __forceinline__ void sts128f(uint32_t a, float x, float y, float z, float w) { asm volatile("st.shared.v4.f32 [%0], {%1,%2,%3,%4};" :: "r"(a), "f"(x), "f"(y), "f"(z), "f"(w) : "memory"); }
__device__ __forceinline__ void sts64f(uint32_t a, float x, float y) { asm volatile("st.shared.v2.f32 [%0], {%1,%2};" :: "r"(a), "f"(x), "f"(y) : "memory"); }
__device__ __forceinline__ uint32_t lds32(uint32_t a) { uint32_t v; asm volatile("ld.shared.u32 %0, [%1];" : "=r"(v) : "r"(a) : "memory"); return v; }
__device__ __forceinline__ void sts32(uint32_t a, uint32_t v) { asm volatile("st.shared.u32 [%0], %1;" :: "r"(a), "r"(v) : "memory"); }

constexpr uint32_t SBASE = 1024;
__host__ __device__ constexpr uint64_t mkdesc(uint32_t off, uint32_t lbo, uint32_t sbo, uint32_t swz) {
  return (uint64_t)(((SBASE + off) & 0x3FFFF) >> 4) | ((uint64_t)(lbo >> 4) << 16) | ((uint64_t)(sbo >> 4) << 32) | ((uint64_t)swz << 62);
}
__device__ __forceinline__ void wg_fence() { asm volatile("wgmma.fence.sync.aligned;" ::: "memory"); }
__device__ __forceinline__ void wg_commit() { asm volatile("wgmma.commit_group.sync.aligned;" ::: "memory"); }
template <int N> __device__ __forceinline__ void wg_wait() { asm volatile("wgmma.wait_group.sync.aligned %0;" :: "n"(N) : "memory"); }

template <int N> __device__ __forceinline__ void reg_fence(float (&d)[N], int n = N) {
#pragma unroll
  for (int i = 0; i < N; i++) if (i < n) asm volatile("" : "+f"(d[i]) :: "memory");
}
#define F4(b) "+f"(d[b]), "+f"(d[b + 1]), "+f"(d[b + 2]), "+f"(d[b + 3])
#define F8(b) F4(b), F4(b + 4)
#define F16(b) F8(b), F8(b + 8)
#define G4(b) "=f"(d[b]), "=f"(d[b + 1]), "=f"(d[b + 2]), "=f"(d[b + 3])
#define G8(b) G4(b), G4(b + 4)
#define G16(b) G8(b), G8(b + 8)
#define RS_IN "r"(a[0]), "r"(a[1]), "r"(a[2]), "r"(a[3]), "l"(db), "n"(SD), "n"(TB)
#define SS_IN "l"(da), "l"(db), "n"(SD), "n"(TA), "n"(TB)
#define WG_OP(str, out0, out1, in) do { if (SD || KEEP) asm volatile(str : out1 : in); else asm volatile(str : out0 : in); } while (0)
#define O12(X) X##8(0), X##4(8)
#define O20(X) X##16(0), X##4(16)
#define O32(X) X##16(0), X##16(16)
template <int SD, int TB, int KEEP = 0> __device__ __forceinline__ void wgmma_rs24(float* d, const uint32_t* a, uint64_t db) {
  WG_OP("wgmma.mma_async.sync.aligned.m64n24k16.f32.bf16.bf16 {%0,%1,%2,%3,%4,%5,%6,%7,%8,%9,%10,%11}, {%12,%13,%14,%15}, %16, %17, 1, 1, %18;", O12(G), O12(F), RS_IN);
}
template <int SD, int TB, int KEEP = 0> __device__ __forceinline__ void wgmma_rs32(float* d, const uint32_t* a, uint64_t db) {
  WG_OP("wgmma.mma_async.sync.aligned.m64n32k16.f32.bf16.bf16 {%0,%1,%2,%3,%4,%5,%6,%7,%8,%9,%10,%11,%12,%13,%14,%15}, {%16,%17,%18,%19}, %20, %21, 1, 1, %22;", G16(0), F16(0), RS_IN);
}
template <int SD, int TB, int KEEP = 0> __device__ __forceinline__ void wgmma_rs40(float* d, const uint32_t* a, uint64_t db) {
  WG_OP("wgmma.mma_async.sync.aligned.m64n40k16.f32.bf16.bf16 {%0,%1,%2,%3,%4,%5,%6,%7,%8,%9,%10,%11,%12,%13,%14,%15,"
        "%16,%17,%18,%19}, {%20,%21,%22,%23}, %24, %25, 1, 1, %26;", O20(G), O20(F), RS_IN);
}
template <int SD, int TB, int KEEP = 0> __device__ __forceinline__ void wgmma_rs64(float* d, const uint32_t* a, uint64_t db) {
  WG_OP("wgmma.mma_async.sync.aligned.m64n64k16.f32.bf16.bf16 {%0,%1,%2,%3,%4,%5,%6,%7,%8,%9,%10,%11,%12,%13,%14,%15,"
        "%16,%17,%18,%19,%20,%21,%22,%23,%24,%25,%26,%27,%28,%29,%30,%31}, {%32,%33,%34,%35}, %36, %37, 1, 1, %38;", O32(G), O32(F), RS_IN);
}
template <int SD, int TA, int TB, int KEEP = 0> __device__ __forceinline__ void wgmma_ss24(float* d, uint64_t da, uint64_t db) {
  WG_OP("wgmma.mma_async.sync.aligned.m64n24k16.f32.bf16.bf16 {%0,%1,%2,%3,%4,%5,%6,%7,%8,%9,%10,%11}, %12, %13, %14, 1, 1, %15, %16;", O12(G), O12(F), SS_IN);
}
template <int SD, int TA, int TB, int KEEP = 0> __device__ __forceinline__ void wgmma_ss8(float* d, uint64_t da, uint64_t db) {
  WG_OP("wgmma.mma_async.sync.aligned.m64n8k16.f32.bf16.bf16 {%0,%1,%2,%3}, %4, %5, %6, 1, 1, %7, %8;", G4(0), F4(0), SS_IN);
}
__device__ __forceinline__ void bar_arrive(int id, int n) { asm volatile("bar.arrive %0, %1;" :: "r"(id), "r"(n) : "memory"); }
__device__ __forceinline__ uint32_t vis_bits(int pos, int t) {
  uint32_t m = 0;
#pragma unroll
  for (int i = 0; i < 8; i++) m |= (8 * (i / 2 + 1) + 2 * t + (i & 1) <= pos) ? 1u << i : 0u;
  return m;
}

__device__ __forceinline__ unsigned long long wait_words(const unsigned long long* p, uint32_t E) {
  int guard = 0; unsigned long long m;
  while (m = ld_rlxu64(p), !__all_sync(~0u, rfresh(m, E))) { __nanosleep(20); if (++guard > (1 << 22)) TRAP(); }
  fence_acq();
  return m;
}
__device__ __forceinline__ int route_step(int s, uint32_t E, int lane, unsigned long long& run) {
  const unsigned long long m = warp_max<2>(wait_words(f_h2[s][lane & 3], E));
  if (s == 0 || m > run) { run = m; return rtok(m) & 31; }
  return -1;
}

struct Params {
  const bf16 *x, *mem0, *wq, *wk, *wv, *wo, *wr, *wg, *wu, *wd;
  bf16* out;
  uint32_t zero2;
  unsigned long long zero;
};

constexpr uint32_t WSTG_STRIDE = 272;
__device__ __forceinline__ void stage_weights(uint32_t stg, const bf16* src, int ld, int tid, int nthr) {
  for (int i = tid; i < 512 * 16; i += nthr) {
    int k = i >> 4, c = i & 15;
    cp_async16(stg + k * WSTG_STRIDE + c * 16, src + (size_t)k * ld + c * 8);
  }
}
__device__ __forceinline__ void load_frags(uint32_t (*W)[4], uint32_t stg, int wg, int w, int lane) {
  uint32_t a = stg + ((lane >> 4) * 8 + (lane & 7)) * WSTG_STRIDE + (64 * wg + 16 * w + ((lane >> 3) & 1) * 8) * 2;
#pragma unroll
  for (int ks = 0; ks < 32; ks++) ldmatrix4_t(W[ks], a + ks * 16 * WSTG_STRIDE);
}

constexpr uint32_t M_H = 0;
constexpr uint32_t M_MEM = 65536;
constexpr uint32_t M_Q = M_MEM + 24576;
constexpr uint32_t M_K = M_Q + 12288;
constexpr uint32_t M_V = M_K + 12288;
constexpr uint32_t M_OM = M_V + 12288;
constexpr uint32_t M_OST = M_OM + 6144;
constexpr uint32_t M_TST = M_OST + 8192;
constexpr uint32_t M_WO = M_TST + 16384;
constexpr uint32_t M_M0 = M_WO + 49152;
constexpr uint32_t M_PT = M_M0 + 2048;
constexpr uint32_t M_BAR = M_PT + 12288;
constexpr uint32_t M_TOTAL = M_BAR + 384;
static_assert(M_TOTAL <= 232448, "main smem");
static_assert(M_WO >= 512 * WSTG_STRIDE, "staging overlaps Wo");
enum { B_LAND = 0  , B_QK = 3, B_V, B_TOK, B_OM, B_HA, B_HB, B_HAE, B_HBE, B_OST, B_OFREE, B_SYNC,
       B_STG, B_STG1, B_SS, B_TFREE, B_KFREE, B_VFREE, B_FIX  , B_NUM = B_FIX + 8 };
static_assert(B_NUM * 8 <= 256, "barriers");
constexpr uint32_t M_CAND = M_BAR + 256;
constexpr uint32_t M_BASE = M_BAR + 272;
constexpr uint32_t M_ZERO = M_BAR + 280;
constexpr uint32_t M_BAS2 = M_BAR + 328;
constexpr uint32_t M_NEAR = M_BAR + 288;
enum { N_GO1 = 2, N_GO2, N_GO3, N_GO4, N_AG, N_W };

#define GSTAMP(slot, i)
#define TSTAMP(slot, i, k)
#define STAMP(i)
#define ASTAMP(i)
#define WSTAMP(i)
#define CSTAMP(i, v)
#define PIN(x) asm volatile("" : "+r"(x))
#define SCHED(k) asm volatile("{\n.reg .pred p;\nsetp.ne.u32 p, %0, 0;\n@p trap;\n}" :: "r"(zz & (1u << (k))) : "memory")
#define HOLD(k, v) asm volatile("{\n.reg .pred p;\nsetp.ne.u32 p, %0, 0;\n@p st.shared.u32 [%0], %1;\n}" :: "r"(zz & (1u << (k))), "r"(v) : "memory")
#define DRAIN(a) (lds32((a) + zz) & zz)
#define BAR(i) (sb + M_BAR + 8 * (i))

__device__ __forceinline__ int probe(const uint8_t* p, int n) {
  int best = 1 << 30; uint32_t v = 0;
#pragma unroll 1
  for (int r = 0; r < n; r++) {
    uint32_t t0 = clk();
    asm volatile("atom.relaxed.gpu.global.or.b32 %0, [%1], %2;" : "=r"(v) : "l"(p + 3968), "r"(v & 0u) : "memory");
    if (v == 0x7fffffffu) t0++;
    best = min(best, (int)(clk() - t0));
  }
  return best;
}
__device__ __forceinline__ void load_mem0(uint4* u, int k0, int lane, const bf16* mem0) {
#pragma unroll
  for (int i = 0; i < 2; i++) {
    const unsigned short* m = (const unsigned short*)mem0 + k0 + lane + 32 * i;
    u[i] = make_uint4(m[0] | (uint32_t)m[512] << 16, m[1024] | (uint32_t)m[1536] << 16, m[2048] | (uint32_t)m[2560] << 16, m[3072] | (uint32_t)m[3584] << 16);
  }
}

__device__ __forceinline__ void paced_h(uint32_t dst, const uint8_t* src, uint32_t o0, uint32_t o1, uint32_t piece, uint32_t bar, int gap) {
  uint32_t t = clk32();
#pragma unroll 1
  for (uint32_t o = o0; o < o1; o += piece) {
    e_mc(dst + o, src + o, piece, bar, 7);
    spin_until(t += gap);
  }
}

__device__ __forceinline__ void weight_role(const Params& p, const uint32_t sb, const int warp, const int cta, const int C, const uint32_t E,
                                            const uint8_t* const memg) {
  const int tid = fresh_tid(), lane = tid & 31;
  const int wg = warp >> 2, w = warp & 3;
  uint32_t W[32][4];
  cp_async_wait();
  bar_sync(1, 256);
  load_frags(W, sb, wg, w, lane);
  bar_sync(1, 256);
  if (tid < 128) sts128(sb + M_V + 5 * 2048 + tid * 16, make_uint4(0, 0, 0, 0));
  fence_async_smem();
  cluster_sync();
  if (tid == 0 && cta == 0) GSTAMP(0, 1);
  if (tid == 0) TSTAMP(13, cta, 0);

  const uint32_t rba = mapa(sb, C == 2 ? 0 : 2), rbc = mapa(sb, C == 1 ? 0 : 1);
  const uint32_t MYBAR = M_BAR + 8 * (C < 2 ? B_QK : B_V);
  uint32_t qoff = M_Q + C * 12288 + warp * 256 + lane * 4;
  uint32_t toff = sb + warp * 256 + (lane >> 4) * 2048 + (lane & 15) * 16;
  uint32_t rbar = mapa(sb + M_BAR, min(lane, 2));
  uint32_t sv = sb + M_MEM + lane * 32 + ((lane >> 2) & 3) * 8;
  PIN(qoff); PIN(toff); PIN(rbar); PIN(sv);
  const uint32_t gen0 = (E - 1) * (uint32_t)(NSTEP - 1);
  uint32_t fix = 0;
  const bool sig = w == 0 && lane < 3;
  const int pk = PAUSE_ + (cta < 36 ? 0 : cta < 72 ? PD1_ : 2 * PD1_) + (wg ? -PST2_ : PST2_);
  int cand = -1;
  float d[16];
#pragma unroll
  for (int i = 0; i < 16; i++) d[i] = 0.f;
  uint32_t tp[8];
#pragma unroll 1
  for (int T = -1; T < NSTEP; T++) {
    const uint32_t ph = T & 1;
    const uint64_t Z = p.zero << ph;
    const uint32_t zz = p.zero2;
    if (T >= 0) {
      WSTAMP(0);
      const uint64_t db = mkdesc(M_MEM, 128, 256, 0) + Z;
      stmatrix4(toff + M_TST + 8192, tp[0], tp[1], tp[2], tp[3]); stmatrix4(toff + M_TST + 12288, tp[4], tp[5], tp[6], tp[7]);
      if (sig) mbar_arrive_remote(rbar + 8 * B_HBE);
      mbar_wait(BAR(B_LAND), ph);
      WSTAMP(1);
      const uint32_t gt = gentag(gen0 + T);
      auto old = [&](uint32_t a) { return lds32(a) ^ gt; };
      uint32_t bad = 0;
      bool redo = false, ready = false;
      wg_fence();
      wgmma_rs24<0, 1, KP1_>(d, W[0], db);
#pragma unroll
      for (int ks = 1; ks < 32; ks++) {
        if (ks == 2 || ks == 14) bad |= xo2(lds32(sv + (ks == 2 ? 0 : 9) * 1024 + warp * 1024), lds32(sv + (ks == 2 ? 8 : 17) * 1024), gt);
        if (ks == 25) bad |= old(sv + (18 + min(warp, 5)) * 1024);
        if (ks == 6) {
          const uint32_t z5 = DRAIN(toff + M_TST);
          __syncwarp();
          if (lane == 0) mbar_arrive(BAR(B_STG) + z5);
        }
        if (ks == 27) ready = mbar_test(BAR(C < 2 ? B_KFREE : B_VFREE), ph ^ 1) & mbar_test(BAR(B_HA), ph);
        if (ks == RED_) redo = bar_or(N_W, 256, T > 0 && (bad & 0x10001u));
        if (ks == 12 || ks == 24) { mbar_wait(BAR(B_LAND + ks / 12), ph); WSTAMP(6 + ks / 12); wg_fence(); }
        wgmma_rs24<1, 1>(d, W[ks], db + ks * 48);
      }
      wg_commit();
      uint32_t a0 = rba + qoff, a1 = a0 + 128, a2 = rbc + qoff, a3 = a2 + 128, ba = rba + MYBAR, bc = rbc + MYBAR;
      PIN(a0); PIN(a1); PIN(a2); PIN(a3); PIN(ba); PIN(bc);
      if (!ready) {
        mbar_wait(BAR(C < 2 ? B_KFREE : B_VFREE), ph ^ 1);
        if (T < NSTEP - 1) mbar_wait(BAR(B_HA), ph);
      }
      wg_wait<0>(); reg_fence(d);
      if (__builtin_expect(redo, 0)) {
        auto stale = [&]() { return __any_sync(~0u, (old(sv + warp * 3072) | old(sv + warp * 3072 + 1024) | old(sv + warp * 3072 + 2048)) & 0x10001u); };
        auto fetch = [&](int r) {
          e_expect(BAR(B_FIX + warp), 3072);
          e_g2s(sb + M_MEM + warp * 3072, memg + warp * 8192 + ((uni(lds32(sb + M_NEAR + warp * 4)) ^ r) & 1) * 4096, 3072, BAR(B_FIX + warp));
        };
        bool late = stale();
        if (late) fetch(0);
        constexpr uint64_t dc = mkdesc(M_MEM, 128, 256, 0);
#pragma unroll
        for (int ks = 0; ks < 32; ks++) {
          if (ks % 12 == 0) {
            if (ks) { wg_commit(); wg_wait<0>(); reg_fence(d); }
            if (warp / 3 == ks / 12) {
              for (int guard = 0; late; guard++) {
                mbar_wait(BAR(B_FIX + warp), fix); fix ^= 1;
                late = stale();
                if (late) fetch(ALT_ ? guard + 1 : 0);
                if (guard > (1 << 20)) TRAP();
              }
            }
            bar_sync(N_W, 256);
            wg_fence();
          }
          if (ks == 0) wgmma_rs24<0, 1, 1>(d, W[0], dc); else wgmma_rs24<1, 1>(d, W[ks], dc + ks * 48);
        }
        wg_commit();
        wg_wait<0>(); reg_fence(d);
      }
      WSTAMP(2);
      if (T == 0 && tid == 0) TSTAMP(13, cta, 2);
      uint32_t lo[3], hi[3];
#pragma unroll
      for (int j = 0; j < 3; j++) { lo[j] = pack2(d[4 * j], d[4 * j + 1]); hi[j] = pack2(d[4 * j + 2], d[4 * j + 3]); }
      if (__builtin_expect(T == 0, 0)) { sts32(sb + M_M0 + tid * 8, lo[0]); sts32(sb + M_M0 + tid * 8 + 4, hi[0]); }
      if (__builtin_expect(cand >= 0, 0)) {
        if (T == LAG) { lo[1] = lds32(sb + M_M0 + tid * 8); hi[1] = lds32(sb + M_M0 + tid * 8 + 4); }
        if (C < 2) { st_async32(a0 + 5 * 2048, lo[2], ba); st_async32(a1 + 5 * 2048, hi[2], ba); }
        else { sts32(sb + qoff + 5 * 2048, lo[2]); sts32(sb + qoff + 5 * 2048 + 128, hi[2]); }
        lo[2] = lo[1]; hi[2] = hi[1];
      }
      uint32_t z5;
      if (C == 0) {
        sts32(sb + qoff, lo[0]); sts32(sb + qoff + 128, hi[0]); z5 = DRAIN(sb + qoff);
        st_async32(a0, lo[2], ba); st_async32(a1, hi[2], ba); st_async32(a2, lo[1], bc); st_async32(a3, hi[1], bc);
      } else if (C == 1) {
        sts32(sb + qoff, lo[1]); sts32(sb + qoff + 128, hi[1]); z5 = DRAIN(sb + qoff);
        st_async32(a0, lo[2], ba); st_async32(a1, hi[2], ba); st_async32(a2, lo[0], bc); st_async32(a3, hi[0], bc);
      } else {
        sts32(sb + qoff, lo[2]); sts32(sb + qoff + 128, hi[2]); z5 = DRAIN(sb + qoff);
        st_async32(a0, lo[0], ba); st_async32(a1, hi[0], ba); st_async32(a2, lo[1], bc); st_async32(a3, hi[1], bc);
      }
      __syncwarp();
      if (lane == 0) { mbar_arrive(sb + MYBAR + z5); if (w == 3) mbar_arrive(BAR(B_SS)); }
      if (T == NSTEP - 1) break;
    }
    {
      const uint64_t dh = mkdesc(M_H, 16, 1024, 1) + Z;
      static_assert(E2 == 0 && E3 > 0 && PAUSE_ > 0, "config");
      if (T + 2 < NSEG) {
        if (T < 0) mbar_wait(BAR(B_HA), ph);
        WSTAMP(3);
        wg_fence();
        wgmma_rs32<0, 0, 1>(d, W[0], dh);
#pragma unroll
        for (int ks = 1; ks < EA; ks++) {
          if (ks == E1) { wg_commit(); if (T >= 0) bar_sync(N_GO2, 384); wg_fence(); }
          wgmma_rs32<1, 0>(d, W[ks], dh + (ks >> 2) * 256 + (ks & 3) * 2);
        }
        wg_commit();
        mbar_wait(BAR(B_HB), ph);
        wg_wait<0>();
        if (sig) mbar_arrive_remote(rbar + 8 * B_HAE);
        WSTAMP(4);
        if (T >= 0) bar_sync(N_GO3, 384);
        if (wg == 1) bar_sync(N_W, 256);
        wg_fence();
#pragma unroll
        for (int ks = EA; ks < 32; ks++) wgmma_rs32<1, 0>(d, W[ks], dh + (ks >> 2) * 256 + (ks & 3) * 2);
        wg_commit();
        if (wg == 0) bar_arrive(N_W, 256);
        mbar_wait(BAR(B_TFREE), ph ^ 1);
        wg_wait<0>(); reg_fence(d);
      } else {
        bar_sync(N_GO2, 384);
        mbar_wait(BAR(B_HB), ph);
        if (sig) mbar_arrive_remote(rbar + 8 * B_HAE);
        bar_sync(N_GO3, 384);
        mbar_wait(BAR(B_TFREE), ph ^ 1);
      }
#pragma unroll
      for (int i = 0; i < 8; i++) { tp[i] = pack2(d[2 * i], d[2 * i + 1]); PIN(tp[i]); }
      auto staged = [&]() {
        const uint32_t z5 = DRAIN(toff + M_TST);
        __syncwarp();
        if (lane == 0) mbar_arrive(BAR(B_STG1) + z5);
      };
      if (T < 0 || (T + 2 >= LAG && T + 2 < NSTEP)) {
        wg_fence();
        wgmma_rs32<0, 0, 1>(d, W[0], dh + 2048);
        stmatrix4(toff + M_TST, tp[0], tp[1], tp[2], tp[3]); stmatrix4(toff + M_TST + 4096, tp[4], tp[5], tp[6], tp[7]);
#pragma unroll
        for (int ks = 1; ks < 32; ks++) {
          if (ks == 5) staged();
          if (ks >= PAUSE_ - PST2_ && ks <= PAUSE_ + 2 * PD1_ + PST2_ && (ks - PAUSE_ + PST2_) % PGR_ == 0) {
            wg_commit();
            if (T >= 0 && ks == pk) bar_sync(N_GO4, 384);
            wg_fence();
          }
          wgmma_rs32<1, 0>(d, W[ks], dh + 2048 + (ks >> 2) * 256 + (ks & 3) * 2);
        }
        wg_commit();
      } else {
        stmatrix4(toff + M_TST, tp[0], tp[1], tp[2], tp[3]); stmatrix4(toff + M_TST + 4096, tp[4], tp[5], tp[6], tp[7]);
        staged();
        bar_sync(N_GO4, 384);
      }
      if (T >= 0) cand = __shfl_sync(~0u, (int)lds32(sb + M_CAND + ((T + 1) & 3) * 4), 0);
      wg_wait<0>(); reg_fence(d);
      if (T >= 0) WSTAMP(6);
      if (T < 0 && tid == 0) TSTAMP(13, cta, 1);
#pragma unroll
      for (int i = 0; i < 8; i++) tp[i] = pack2(d[2 * i], d[2 * i + 1]);
    }
  }
  cluster_sync();
  if (tid == 0 && cta == 0) GSTAMP(0, 5);
}

__device__ __forceinline__ void attn_role(const Params& p, const uint32_t sb, const int w, const int cta, const int head, const int C, const uint32_t E,
                                          uint8_t* const part, uint8_t* const memg) {
  const int tid = fresh_tid(), lane = tid & 31;
  const int g = lane >> 2, t = lane & 3;
  uint32_t tag = ((E - 1) * (uint32_t)(NSTEP - 1)) & 1;
  uint4 m0[2][2];
  load_mem0(m0[0], w * 64, lane, p.mem0); load_mem0(m0[1], w * 64 + 256, lane, p.mem0);
  cluster_sync();
#pragma unroll
  for (int k = 0; k < 2; k++) {
#pragma unroll 1
    for (int i = 0; i < 6; i++) sts128(sb + M_MEM + (w + 4 * k) * 3072 + lane * 16 + i * 512, make_uint4(0, 0, 0, 0));
    __syncwarp();
#pragma unroll
    for (int i = 0; i < 2; i++) sts128(sb + M_MEM + ((w + 4 * k) * 4 + (lane >> 4) + 2 * i) * 768 + (lane & 15) * 16, m0[k][i]);
  }
  fence_async_smem();
  bar_sync(N_AG, 128);
  if (w == 3 && lane < 3) mbar_arrive(BAR(B_LAND + lane));
  if (lane == 0) {
    if (w == 0) TSTAMP(15, cta, 0);
    sts32(sb + M_PT + w * 4, probe(part + cta * 16384 + w * 4096, NPROBE_ / 2));
    if (w == 0) TSTAMP(15, cta, 1);
  }
  bar_sync(N_AG, 128);
  const uint32_t inear = lds32(sb + M_PT + (w >> 1) * 8 + 4) < lds32(sb + M_PT + (w >> 1) * 8);
  if (lane == 0 && !(w & 1)) st_rlx(&f_choice[cta][w >> 1], (E << 1) | inear);
  if (w == 0) TSTAMP(15, cta, 2);
  uint32_t nb;
  {
    const int i = min(lane >> 1, C < 2 ? 8 : 5);
    const int r = ((i / 3 * 3 + C) * 4 + w) * 3 + i % 3;
    int guard = 0; uint32_t cw;
    while (__any_sync(~0u, ((cw = ld_rlx(&f_choice[r][lane & 1])) >> 1) != (E & 0x7FFFFFFFu))) { if (++guard > (1 << 22)) TRAP(); }
    nb = __ballot_sync(~0u, cw & 1) >> (lane >> 4);
    if (w == 0) TSTAMP(15, cta, 3);
  }
  bar_sync(N_AG, 128);
  const uint32_t pt0 = sb + M_PT + (tid & 127) * 16;
  {
    const uint32_t po = (C * 4 + w) * 49152 + (lane >> 4) * 8192 + ((lane >> 3) & 1) * 2048 + head * 64 + (lane & 7) * 8;
    const uint8_t* in = part + (cta * 16384 + (w >> 1) * 8192 + inear * 4096 + (w & 1) * 2048 + lane * 8);
    const uint8_t* outp = memg + ((cta / 12) * 8192 + (cta % 12) * 256 + w * 64 + (lane >> 4) * 4096 + (lane & 4) * 8 + (lane & 8) * 2 + (lane & 3) * 4);
#pragma unroll
    for (int i = 0; i < 12; i++) {
      const int j = i / 4 * 3 + (i & 3);
      const uint8_t* a = (i & 3) < 3 ? part + (po + i / 4 * 589824 + (i & 3) * 16384 + ((nb >> (2 * j)) & 1) * 4096) : i == 11 ? in : outp;
      asm volatile("st.shared.u64 [%0], %1;" :: "r"(pt0 + (i >> 1) * 2048 + (i & 1) * 8), "l"(a) : "memory");
    }
  }
  const int xd = __shfl_sync(~0u, XDLY_ + (cta < 36 ? 0 : cta < 72 ? X1_ : X2_), 0);
  const uint32_t rba = mapa(sb, C == 2 ? 0 : 2), rbc = mapa(sb, C == 1 ? 0 : 1);
  uint32_t vis = vis_bits(8 + 8 * w + g, t);
  uint32_t ln = lane;
#pragma unroll
  for (int i = 0; i < SALT_; i++) ln += lds32(sb + M_ZERO);
  PIN(vis); PIN(ln);
  if (tid == 256 && C == 0) st_rlx(&f_loaded[head], E);
  uint32_t fa[8][4];
#pragma unroll
  for (int ks = 0; ks < 8; ks++) ldmatrix4_t(fa[ks], sb + M_WO + 32768 + w * 256 + (lane >> 4) * 1024 + (lane & 15) * 16 + ks * 2048);
  if (w == 0) TSTAMP(14, cta, 0);
#pragma unroll 1
  for (int T = 0; T < NSTEP; T++) {
    const uint32_t ph = T & 1;
    const uint32_t zz = uni(lds32(sb + M_ZERO));
    const bool more = T < NSTEP - 1;
    const float sc = 0.08838834764831845f * 1.4426950408889634f;
    tag ^= 1;
    float s[20];
    const uint8_t* in; int cnext = -1; uint32_t tx; bool synced;
    float x[10], tm, ts;
    uint32_t pt[5];
    auto tok_max = [&]() {
      PIN(vis);
      x[0] = s[2]; x[1] = s[3];
#pragma unroll
      for (int i = 0; i < 8; i++) x[2 + i] = (vis >> i & 1) ? s[4 * (i / 2 + 1) + 2 + (i & 1)] : -INFINITY;
      tm = fmaxf(fmaxf(fmaxf(fmaxf(x[0], x[1]), fmaxf(x[2], x[3])), fmaxf(fmaxf(x[4], x[5]), fmaxf(x[6], x[7]))), fmaxf(x[8], x[9]));
      HOLD(7, __float_as_uint(tm));
    };
    auto tok_exp1 = [&]() {
      tm = fmaxf(tm, __shfl_xor_sync(~0u, tm, 1));
      tm = fmaxf(tm, __shfl_xor_sync(~0u, tm, 2));
      const float b = -tm * sc;
#pragma unroll
      for (int i = 0; i < 10; i++) x[i] = fmaf(x[i], sc, b);
      HOLD(10, __float_as_uint(x[9]));
    };
    auto tok_exp2 = [&]() {
#pragma unroll
      for (int i = 0; i < 10; i++) x[i] = ex2(x[i]);
      ts = (((x[0] + x[1]) + (x[2] + x[3])) + ((x[4] + x[5]) + (x[6] + x[7]))) + (x[8] + x[9]);
#pragma unroll
      for (int k = 0; k < 5; k++) pt[k] = pack2(x[2 * k], x[2 * k + 1]);
      HOLD(8, __float_as_uint(ts));
    };
    {
      uint32_t q[8][4];
      auto load_q = [&](uint32_t a, int h) {
#pragma unroll
        for (int k2 = 0; k2 < 4; k2++) {
          uint32_t r[4];
          ldmatrix4_t(r, a + k2 * 512);
          q[2 * k2][h] = r[0]; q[2 * k2][h + 2] = r[1]; q[2 * k2 + 1][h] = r[2]; q[2 * k2 + 1][h + 2] = r[3];
        }
      };
      PIN(ln);
      const uint32_t qa = sb + M_Q + ln * 16;
      const int cand = C == 2 ? (int)uni(lds32(sb + M_CAND + (T & 3) * 4)) : -1;
      mbar_wait(BAR(B_TOK), ph);
      load_q(qa + (1 + w) * 2048, 1);
      mbar_wait(BAR(B_QK), ph);
      ASTAMP(0);
      if (T == 0 && w == 0) TSTAMP(13, cta, 3);
      if (__builtin_expect(cand >= 0, 0)) {
        mbar_wait(BAR(B_V), ph);
        PIN(ln);
        const int e = w * 32 + ln;
#pragma unroll
        for (int i = 0; i < 3; i++) {
          const uint32_t v = lds32(sb + M_Q + i * 12288 + 5 * 2048 + e * 16 + 4);
          asm volatile("st.shared.u16 [%0], %1;" :: "r"(sb + M_Q + i * 12288 + (1 + (cand >> 3)) * 2048 + e * 16 + (cand & 7) * 2), "h"((unsigned short)v) : "memory");
        }
        fence_async_smem();
        bar_sync(N_AG, 128);
        load_q(qa + (1 + w) * 2048, 1);
      }
      load_q(qa, 0);
      if (!(NOF_ & 1)) fence_async_smem();
      constexpr uint64_t dk = mkdesc(M_K, 128, 2048, 0);
      wg_fence();
      wgmma_rs40<0, 1>(s, q[0], dk);
#pragma unroll
      for (int ks = 1; ks < 8; ks++) wgmma_rs40<1, 1>(s, q[ks], dk + ks * 16);
      wg_commit();
    }
    if (more) {
      uint32_t v[5][4];
      PIN(ln);
      const uint32_t va = sb + M_V + w * 512 + ((ln >> 3) & 1) * 128 + (ln >> 4) * 2048 + (ln & 7) * 16;
      const uint32_t ooff = M_OM + w * 1536 + C * 256 + ln * 4;
      mbar_wait(BAR(B_V), ph);
      wg_wait<0>(); reg_fence(s);
      if (ln < 3) mbar_arrive_remote(mapa(BAR(B_KFREE), ln));
      ldmatrix4(v[0], va); ldmatrix4(v[1], va + 256); ldmatrix4(v[2], va + 4096); ldmatrix4(v[3], va + 4096 + 256);
      ldmatrix4(v[4], sb + M_V + 8192 + w * 512 + ln * 16);
      ASTAMP(1);
      float m = fmaxf(fmaxf(fmaxf(fmaxf(s[0], s[1]), fmaxf(s[4], s[5])), fmaxf(fmaxf(s[8], s[9]), fmaxf(s[12], s[13]))), fmaxf(s[16], s[17]));
      m = fmaxf(m, __shfl_xor_sync(~0u, m, 1));
      m = fmaxf(m, __shfl_xor_sync(~0u, m, 2));
      const float b = -m * sc;
      uint32_t pm[5];
#pragma unroll
      for (int j = 0; j < 5; j++) pm[j] = pack2(ex2(fmaf(s[4 * j], sc, b)), ex2(fmaf(s[4 * j + 1], sc, b)));
      float o0[4] = {0.f, 0.f, 0.f, 0.f}, o1[4] = {0.f, 0.f, 0.f, 0.f}, l[4] = {0.f, 0.f, 0.f, 0.f};
      const uint32_t one[4] = {0x3f803f80u, 0x3f803f80u, 0x3f803f80u, 0x3f803f80u};
      hmma16(l, one, pm[0], pm[1]); hmma16(o0, v[0], pm[0], pm[1]); hmma16(o1, v[1], pm[0], pm[1]);
      hmma16(l, one, pm[2], pm[3]); hmma16(o0, v[2], pm[2], pm[3]); hmma16(o1, v[3], pm[2], pm[3]);
      hmma8(l, one[0], one[1], pm[4]); hmma8(o0, v[4][0], v[4][1], pm[4]); hmma8(o1, v[4][2], v[4][3], pm[4]);
      const float r0 = rcp(l[0]), r1 = rcp(l[1]);
      const uint32_t u0 = pack2(o0[0] * r0, o0[1] * r1), u1 = pack2(o0[2] * r0, o0[3] * r1), u2 = pack2(o1[0] * r0, o1[1] * r1), u3 = pack2(o1[2] * r0, o1[3] * r1);
      constexpr uint32_t OB = M_BAR + 8 * B_OM;
      const uint32_t a0 = rba + ooff, a1 = rbc + ooff;
      st_async32(a0, u0, rba + OB); st_async32(a1, u0, rbc + OB);
      st_async32(a0 + 128, u1, rba + OB); st_async32(a1 + 128, u1, rbc + OB);
      st_async32(a0 + 768, u2, rba + OB); st_async32(a1 + 768, u2, rbc + OB);
      st_async32(a0 + 896, u3, rba + OB); st_async32(a1 + 896, u3, rbc + OB);
      bar_arrive(N_GO2, 384);
      sts32(sb + ooff, u0); sts32(sb + ooff + 128, u1); sts32(sb + ooff + 768, u2); sts32(sb + ooff + 896, u3);
      ASTAMP(2);
      uint32_t fb[8][4];
      const uint32_t wa = sb + M_WO + 16384 + w * 256 + (ln >> 4) * 1024 + (ln & 15) * 16 + zz;
      ldmatrix4_t(fb[0], wa);
      SCHED(3);
#pragma unroll
      for (int ks = 1; ks < 8; ks++) {
        ldmatrix4_t(fb[ks], wa + ks * 2048);
        if (ks == ARR_) { __syncwarp(); if (ln == 0) mbar_arrive(BAR(B_OM) + (fb[0][0] & zz)); }
      }
      if (C == 2) cnext = (int)uni(lds32(sb + M_CAND + ((T + 1) & 3) * 4));
      {
        float d[12], e[12];
        constexpr uint64_t ob = mkdesc(M_OM, 128, 256, 0);
        uint8_t* q[3][3];
        auto addr = [&](int i) {
          asm volatile("ld.shared.v2.u64 {%0,%1}, [%2];" : "=l"(q[i][0]), "=l"(q[i][1]) : "r"(pt0 + i * 4096) : "memory");
          if (i < 2) asm volatile("ld.shared.u64 %0, [%1];" : "=l"(q[i][2]) : "r"(pt0 + i * 4096 + 2048) : "memory");
          else asm volatile("ld.shared.v2.u64 {%0,%1}, [%2];" : "=l"(q[i][2]), "=l"(in) : "r"(pt0 + i * 4096 + 2048) : "memory");
        };
        auto put = [&](const float* d, int i) {
          st_rlx64(q[i][0], (pack2(d[0], d[1]) & ~1u) | tag, pack2(d[2], d[3]));
          st_rlx64(q[i][1], (pack2(d[4], d[5]) & ~1u) | tag, pack2(d[6], d[7]));
          st_rlx64(q[i][2], (pack2(d[8], d[9]) & ~1u) | tag, pack2(d[10], d[11]));
        };
        addr(0); addr(1);
        SCHED(6);
        tok_max();
        ASTAMP(3);
        mbar_wait(BAR(B_OM), ph);
        if (!(NOF_ & 2)) fence_async_smem();
        ASTAMP(4);
        constexpr uint64_t w0 = mkdesc(M_WO, 1024, 128, 0);
        float (&f)[12] = d;
        wg_fence();
        wgmma_ss24<0, 1, 1>(d, w0, ob);
#pragma unroll
        for (int ks = 1; ks < 8; ks++) wgmma_ss24<1, 1, 1>(d, w0 + ks * 128, ob + ks * 48);
        wg_commit();
        wgmma_rs24<0, 1>(e, fb[0], ob);
#pragma unroll
        for (int ks = 1; ks < HAND_; ks++) wgmma_rs24<1, 1>(e, fb[ks], ob + ks * 48);
        wg_commit();
        wg_wait<1>(); reg_fence(d);
        put(d, 0);
        addr(2);
        SCHED(4);
        ASTAMP(5);
        wg_fence();
#pragma unroll
        for (int ks = HAND_; ks < 8; ks++) wgmma_rs24<1, 1>(e, fb[ks], ob + ks * 48);
        wg_commit();
        wgmma_rs24<0, 1, 1>(f, fa[0], ob);
#pragma unroll
        for (int ks = 1; ks < HAND_; ks++) wgmma_rs24<1, 1>(f, fa[ks], ob + ks * 48);
        wg_commit();
        wg_wait<1>(); reg_fence(e);
        put(e, 1);
        SCHED(5);
        wg_fence();
#pragma unroll
        for (int ks = HAND_; ks < 8; ks++) wgmma_rs24<1, 1>(f, fa[ks], ob + ks * 48);
        wg_commit();
        if (GO3_ == 0) bar_arrive(N_GO3, 384);
        synced = __all_sync(~0u, mbar_test(BAR(B_SYNC), ph));
        tx = uni(lds32(sb + M_BASE + ph * 4)) + xd;
        wg_wait<0>(); reg_fence(f);
        if (GO3_ == 1) bar_arrive(N_GO3, 384);
        if (C < 2) put(f, 2);
        if (GO3_ == 2) bar_arrive(N_GO3, 384);
        ASTAMP(6);
        if (T == 0 && w == 0) TSTAMP(14, cta, 1);
      }
    } else {
      mbar_wait(BAR(B_V), ph);
      wg_wait<0>(); reg_fence(s);
      tok_max();
    }
    uint2 v[8];
#pragma unroll
    for (int i = 0; i < 8; i++) v[i] = make_uint2(zz, zz);
    auto poll = [&](uint2* v) {
      v[0] = ld_rlx64<0>(in); v[1] = ld_rlx64<256>(in); v[2] = ld_rlx64<512>(in); v[3] = ld_rlx64<768>(in);
      v[4] = ld_rlx64<1024>(in); v[5] = ld_rlx64<1280>(in); v[6] = ld_rlx64<1536>(in); v[7] = ld_rlx64<1792>(in);
    };
    uint8_t* outp;
    asm volatile("ld.shared.u64 %0, [%1];" : "=l"(outp) : "r"(pt0 + 2048 + 8) : "memory");
    const uint32_t itag = gentag((E - 1) * (uint32_t)(NSTEP - 1) + T + 1);
    const bool sum = more && cnext < 0;
    if (more) {
      if (!synced) { mbar_wait(BAR(B_SYNC), ph); tx = uni(lds32(sb + M_BASE + ph * 4)) + xd; }
      ASTAMP(7);
      if (__builtin_expect(cnext >= 0, 0)) {
        const unsigned long long* hp = (const unsigned long long*)&g_hc[T + 1 - LAG][0] + ((cta / 3) * 8 + 2 * w + ((ln >> 2) & 1));
        unsigned long long v0; int guard = 0;
        while (v0 = ld_rlxu64(hp), !__all_sync(~0u, (uint32_t)(v0 >> 32) == E)) { if (++guard > (1 << 22)) TRAP(); }
        st_rlx((uint32_t*)outp, (ln & 3) == 1 ? ((uint32_t)v0 >> ((ln & 8) * 2)) & 0xffffu : (ln & 1) ? 0u : itag);
      } else {
        spin_until(tx);
        ASTAMP(8);
        poll(v);
      }
    }
    auto late = [&](const uint2* v) {
      return __any_sync(~0u, (or3(xo2(v[0].x, v[1].x, tag), xo2(v[2].x, v[3].x, tag), xo2(v[4].x, v[5].x, tag)) | xo2(v[6].x, v[7].x, tag)) & 1u);
    };
    tok_exp1(); tok_exp2();
    auto reduce = [&]() {
      if (sum) {
        ASTAMP(9);
        int guard = 0;
        while (late(v)) {
          if (++guard > (1 << 22)) TRAP();
          poll(v);
        }
#pragma unroll
        for (int i = 0; i < 4; i++) { v[i].x = add2(v[i].x, v[i + 4].x); v[i].y = add2(v[i].y, v[i + 4].y); }
        const bool hi = ln & 8;
        const uint32_t x0 = add2(v[0].x, v[1].x), x1 = add2(v[2].x, v[3].x), y0 = add2(v[0].y, v[1].y), y1 = add2(v[2].y, v[3].y);
        const uint32_t m0 = hi ? y0 : x0, m1 = hi ? y1 : x1;
        const uint32_t n0 = __shfl_xor_sync(~0u, hi ? x0 : y0, 8), n1 = __shfl_xor_sync(~0u, hi ? x1 : y1, 8);
        float k0 = (blo(m0) + blo(m1)) + (blo(n0) + blo(n1)), k1 = (bhi(m0) + bhi(m1)) + (bhi(n0) + bhi(n1));
        k0 += __shfl_xor_sync(~0u, k0, 16); k1 += __shfl_xor_sync(~0u, k1, 16);
        st_rlx((uint32_t*)outp, (ln & 1) ? pack2(k0, k1) : pack2_tag(k0, k1, itag));
        ASTAMP(10);
        if (T == 0 && w == 0) TSTAMP(14, cta, 2);
        CSTAMP(12 + w, (clk() & ~15u) | min(guard + 1, 15));
      }
      if (more) bar_arrive(N_GO4, 384);
    };
    if (PVR_ < 0) reduce();
    {
      PIN(ln);
      const uint32_t oa = sb + M_OST + w * 128 + (ln >> 3) * 512 + (ln & 7) * 16;
      const uint32_t a[3][4] = {{0, pt[0], 0, pt[1]}, {0, pt[2], 0, pt[3]}, {0, pt[4], 0, 0}};
      constexpr uint64_t dv = mkdesc(M_V, 2048, 128, 0);
#pragma unroll 1
      for (int h = 0; h < 2; h++) {
        float o[32];
        const uint64_t dh = dv + (uint64_t)(h * 64);
        wg_fence();
        wgmma_rs64<0, 0>(o, a[0], dh); wgmma_rs64<1, 0>(o, a[1], dh + 256); wgmma_rs64<1, 0>(o, a[2], dh + 512);
        wg_commit();
        if (h == PVR_) reduce();
        if (h == 0) {
          ts += __shfl_xor_sync(~0u, ts, 1);
          ts += __shfl_xor_sync(~0u, ts, 2);
          ts = rcp(ts);
          mbar_wait(BAR(B_OFREE), ph ^ 1);
        }
        wg_wait<0>(); reg_fence(o);
        if (h == 1 && ln < 3) mbar_arrive_remote(mapa(BAR(B_VFREE), ln));
#define OT(i) pack2(o[4 * (i) + 2] * ts, o[4 * (i) + 3] * ts)
        stmatrix4(oa + h * 4096, OT(0), OT(1), OT(2), OT(3));
        stmatrix4(oa + h * 4096 + 2048, OT(4), OT(5), OT(6), OT(7));
      }
      const uint32_t z5 = DRAIN(oa);
      __syncwarp();
      if (ln == 0) mbar_arrive(BAR(B_OST) + z5);
      ASTAMP(11);
    }
  }
}

__global__ void __cluster_dims__(3, 1, 1) __launch_bounds__(512, 1) main_kernel(Params p) {
  extern __shared__ __align__(1024) uint8_t sm[];
  const uint32_t sb = smem_u32(sm);
  if ((sb & 0xFFFFFFu) != SBASE) TRAP();
  asm volatile("griddepcontrol.launch_dependents;");
  const int warp = __shfl_sync(~0u, threadIdx.x >> 5, 0);
  const int cta = blockIdx.x, head = cta / 3, c = cta % 3;
  const uint32_t E = __shfl_sync(~0u, *(volatile uint32_t*)&g_epoch + 1, 0);
  uint8_t* const part = (uint8_t*)(((uintptr_t)g_xch + 8191) & ~(uintptr_t)8191);
  uint8_t* const memg = part + 96 * 16384;

  if (threadIdx.x == 0 && cta == 0) GSTAMP(0, 0);
  if (threadIdx.x < B_NUM) {
    const int i = threadIdx.x;
    const uint32_t cnt = i == B_STG || i == B_STG1 ? 8 : i == B_OST ? 4 : i == B_HAE || i == B_HBE ? 6 : i == B_KFREE || i == B_VFREE ? 12 : i == B_SS ? 2 : i == B_OM ? 5 :
                         i == B_QK ? (c < 2 ? 9 : 1) : i == B_V ? (c < 2 ? 1 : 9) : 1;
    mbar_init(BAR(i), cnt);
    if (i == B_HA || i == B_HB || i == B_STG || i == B_HAE || i == B_HBE || i == B_TFREE)
      asm volatile("mbarrier.arrive.shared::cta.b64 _, [%0], %1;" :: "r"(BAR(i)), "r"(cnt) : "memory");
    asm volatile("fence.mbarrier_init.release.cluster;" ::: "memory");
  }
  if (warp < 8) {
    const int tid = threadIdx.x;
    uint4 wa[6], wb[6];
#pragma unroll
    for (int i = 0; i < 6; i++) {
      const int mi = i >> 1, e = (tid >> 2) + (i & 1) * 64;
      const uint4* src = (const uint4*)(p.wo + (size_t)(head * 128 + e) * 512 + min(3 * mi + c, 7) * 64 + (tid & 3) * 16);
      wa[i] = __ldg(src); wb[i] = __ldg(src + 1);
    }
    stage_weights(sb, (c == 0 ? p.wq : c == 1 ? p.wk : p.wv) + head * 128, 4096, tid, 256);
#pragma unroll
    for (int i = 0; i < 6; i++) {
      const int mi = i >> 1, e = (tid >> 2) + (i & 1) * 64;
      const uint4 a = wa[i], b = wb[i];
      const uint32_t dst = sb + M_WO + mi * 16384 + (e >> 3) * 1024 + (tid & 3) * 256 + (e & 7) * 16;
      sts128(dst, make_uint4(__byte_perm(a.x, a.y, 0x5410), __byte_perm(a.z, a.w, 0x5410), __byte_perm(b.x, b.y, 0x5410), __byte_perm(b.z, b.w, 0x5410)));
      sts128(dst + 128, make_uint4(__byte_perm(a.x, a.y, 0x7632), __byte_perm(a.z, a.w, 0x7632), __byte_perm(b.x, b.y, 0x7632), __byte_perm(b.z, b.w, 0x7632)));
    }
  } else {
    const int i0 = threadIdx.x - 256;
    const uint32_t tag0 = ((E - 1) * (uint32_t)(NSTEP - 1)) & 1;
    for (int i = i0; i < 1024; i += 256) *(uint4*)(part + cta * 16384 + i * 16) = make_uint4(tag0, 0, tag0, 0);
    if (i0 < 16) *(uint32_t*)(memg + i0 * 4096 + 3968) = 0;
    if (i0 < 2) st_rlx(&f_choice[cta][i0], 0);
    if (i0 < 8) st_rlx64(&g_sync[i0 >> 2][cta][i0 & 3], 0, 0);
    __threadfence();
    if (i0 < 12) sts32(sb + M_ZERO + i0 * 4, 0);
    if (i0 < 2) { sts32(sb + M_BASE + i0 * 4, clk32() - 65536); sts32(sb + M_BAS2 + i0 * 4, clk32() - 65536); sts32(sb + M_CAND + i0 * 4, (uint32_t)-1); }
  }

  if (warp < 8) {
    asm volatile("setmaxnreg.inc.sync.aligned.u32 " STR(RW_) ";");
    weight_role(p, sb, warp, cta, c, E, memg);
  } else if (warp < 12) {
    if (RA_ < 128) asm volatile("setmaxnreg.dec.sync.aligned.u32 " STR(RA_) ";");
    if (RA_ > 128) asm volatile("setmaxnreg.inc.sync.aligned.u32 " STR(RA_) ";");
    attn_role(p, sb, warp - 8, cta, head, c, E, part, memg);
    cluster_sync();
  } else {
    asm volatile("setmaxnreg.dec.sync.aligned.u32 " STR(RC_) ";");
    const int tid = fresh_tid(), lane = tid & 31;
    const int w = warp - 12;
    cluster_sync();
    if (w != 2) {
      const int tl = min(3 * min(w, 2) + c, 7);
      int near = 0;
      if (lane == 0) { const int t0 = probe(memg + tl * 8192, NPROBE_ / 2); near = probe(memg + tl * 8192 + 4096, NPROBE_ / 2) < t0; }
      near = uni(near);
      if (lane < 3) asm volatile("st.shared::cluster.u32 [%0], %1;" :: "r"(mapa(sb + M_NEAR + tl * 4, lane)), "r"(near) : "memory");
      __syncwarp();
    }
    if (w == 0) {
      int yadj = 0, dmin = 1 << 20; uint32_t prev = 0; bool cprev = false;
      uint32_t s0 = c * 8192, s1 = (3 + c) * 8192, s2 = min(6 + c, 7) * 8192;
#pragma unroll 1
      for (int T = 0; T < NSTEP - 1; T++) {
        const uint32_t ph = T & 1;
        mbar_wait(BAR(B_SS), ph);
        const uint32_t cq = clk();
        const uint32_t g0 = (uint32_t)gtime64(); uint32_t g1, ce;
        do { g1 = (uint32_t)gtime64(); ce = clk(); } while (g1 == g0);
        const uint32_t tn = g1 * 8 - (((ce - cq) * 37u) >> 3), id = E * 128u + T;
        if (lane < 4) st_rlx64(&g_sync[ph][cta][lane], tn, id);
        if (lane < 3) mbar_expect(BAR(B_LAND + lane), lane < 2 ? 9216 : 6144);
        if (T == 0) { s0 += uni(lds32(sb + M_NEAR + c * 4)) * 4096; s1 += uni(lds32(sb + M_NEAR + (3 + c) * 4)) * 4096; s2 += uni(lds32(sb + M_NEAR + min(6 + c, 7) * 4)) * 4096; }
        wait_until(cq + SDLY_);
        int guard = 0; unsigned long long v0, v1, v2;
        for (;;) {
          v0 = ld_rlxu64(g_sync[ph][lane]); v1 = ld_rlxu64(g_sync[ph][lane + 32]); v2 = ld_rlxu64(g_sync[ph][lane + 64]);
          if (__all_sync(~0u, (uint32_t)(v0 >> 32) == id && (uint32_t)(v1 >> 32) == id && (uint32_t)(v2 >> 32) == id)) break;
          if (++guard > (1 << 22)) TRAP();
        }
        const bool cnd = (int)uni(lds32(sb + M_CAND + (T & 3) * 4)) >= 0;
        const int dl = __reduce_max_sync(~0u, max(max((int)((uint32_t)v0 - tn), (int)((uint32_t)v1 - tn)), (int)((uint32_t)v2 - tn)));
        const uint32_t base = uni(cq + ((min(dl, 8 * 4096) * 7) >> 5)) + (T == 0 ? SLOW0_ : T == 1 ? SLOW1_ : 0) +
                              (cnd ? CDLY_ : 0) - (T + 2 < NSEG ? 0 : BOFF_);
        const int dur = (int)(base - prev);
        if (!cnd && !cprev) {
          yadj = T > 2 && dur > dmin + 700 ? min(yadj + YUP_, 400) : max(yadj - YDN_, 0);
          if (T > 1) dmin = min(dmin + 20, dur);
        }
        prev = base; cprev = cnd;
        if (lane == 0) { sts32(sb + M_BASE + ph * 4, base); sts32(sb + M_BAS2 + ph * 4, base + yadj); mbar_arrive(BAR(B_SYNC)); }
        CSTAMP(0, base); CSTAMP(1, clk());
        const uint32_t ts = base + YDLY_ + yadj - (T + 2 >= LAG && T + 2 < NSEG ? 0 : YOFF_);
        uint32_t nr = 0;
        if (PRIV_) nr = __ballot_sync(~0u, lds32(sb + M_NEAR + (lane & 7) * 4) != 0);
        wait_until(ts);
        if (PRIV_ & 1) { for (int k = 0; k < 3; k++) e_g2s(sb + M_MEM + k * 3072, memg + k * 8192 + ((nr >> k) & 1) * 4096, 3072, BAR(B_LAND)); }
        else e_mc(sb + M_MEM + c * 3072, memg + s0, 3072, BAR(B_LAND), 7);
        CSTAMP(2, clk());
        spin_until(ts + Y1_);
        if (PRIV_ & 2) { for (int k = 3; k < 6; k++) e_g2s(sb + M_MEM + k * 3072, memg + k * 8192 + ((nr >> k) & 1) * 4096, 3072, BAR(B_LAND + 1)); }
        else e_mc(sb + M_MEM + (3 + c) * 3072, memg + s1, 3072, BAR(B_LAND + 1), 7);
        CSTAMP(3, clk());
        spin_until(ts + Y2_);
        if (PRIV_ & 4) { for (int k = 6; k < 8; k++) e_g2s(sb + M_MEM + k * 3072, memg + k * 8192 + ((nr >> k) & 1) * 4096, 3072, BAR(B_LAND + 2)); }
        else if (c < 2) e_mc(sb + M_MEM + (6 + c) * 3072, memg + s2, 3072, BAR(B_LAND + 2), 7);
        CSTAMP(4, clk());
      }
    } else if (w == 1) {
#pragma unroll 1
      for (int T = 0; T < NSTEP; T++) {
        const uint32_t ph = T & 1;
        const int s = c == 0 ? T : T - LAG;
        const bool act = s >= 0 && s < NSEG;
        mbar_wait(BAR(B_OST), ph);
        if (cta == 0) TSTAMP(2, T, 0);
        fence_async_smem();
        if (T < NSTEP - 1) wait_until(uni(lds32(sb + M_BAS2 + ph * 4)) + ODLY_);
        STAMP(22);
        if (act) { e_s2g(g_o[c][s % ORING][head], sb + M_OST, XO_); bulk_wait(); __syncwarp(); }
        e_arrive(BAR(B_OFREE));
        if (cta == 0) TSTAMP(2, T, 1);
        if (act && lane < 8) st_rel(&f_o[T][head >> 2][c * 4 + (head & 3)][lane], E);
        __syncwarp();
        if (cta == 0) TSTAMP(2, T, 2);
      }
    } else if (w == 2) {
      unsigned long long run = 0;
      static_assert(LAG >= 2, "config");
      constexpr uint32_t NA = EA / 4 * 4096;
      e_expect(BAR(B_QK), c < 2 ? 2048 : 4096); e_expect(BAR(B_V), c == 0 ? 10240 : c == 1 ? 2048 : 0);
      e_expect(BAR(B_TOK), c == 0 ? 16384 : 0); e_expect(BAR(B_OM), 4096);
      e_expect(BAR(B_HA), NA); e_expect(BAR(B_HB), 65536 - NA);
      wait_eq(&f_h1[c == 1 ? 0 : 1], E); fence_async_glob();
      {
        const uint32_t o0 = c == 0 ? NA : 0, o1 = c == 2 ? NA : 32768;
        e_mc(sb + M_H + (c == 1 ? 32768 : 0) + o0, g_h[0][c == 1 ? 0 : 1] + o0, o1 - o0, BAR(c == 2 ? B_HA : B_HB), 7);
      }
      TSTAMP(14, cta, 3);
      if (c == 2) wait_eq(&f_h1[2], E);
      mbar_wait(BAR(B_HAE), 1);
      e_expect(BAR(B_HA), NA);
      if (c == 2) { fence_async_glob(); e_mc(sb + M_H, g_h[0][2], NA, BAR(B_HA), 7); }
      int cprev = -1;
#pragma unroll 1
      for (int T = 0; T < NSTEP - 1; T++) {
        const int s1 = T + 2, s2 = T + 2 - LAG;
        const uint32_t ph = T & 1;
        const bool l1 = s1 < NSEG, l2 = s2 >= 0 && s2 < NSEG, la = s1 + 1 < NSEG;
        const bool mine = c == 0 ? l1 : c == 1 ? l2 : la;
        const uint32_t* fl = c != 1 ? &f_h1[min(s1 + (c >> 1), NSEG - 1)] : (const uint32_t*)f_h2[max(s2, 0)][lane & 3] + 1;
        const uint32_t want = E & 0x1FFFFFu, sh = c != 1 ? 0 : 11;
        mbar_wait(BAR(B_HBE), ph ^ 1);
        const bool early = __all_sync(~0u, ((ld_acq(fl) >> sh) & 0x1FFFFFu) == want);
        mbar_wait(BAR(B_LAND + 2), ph);
        STAMP(16);
        e_expect(BAR(B_HB), (l1 ? 32768 - NA : 0) + (l2 ? 32768 : 0));
        if (mine) {
          if (!early) {
            int guard = 0;
            while (!__all_sync(~0u, ((ld_acq(fl) >> sh) & 0x1FFFFFu) == want)) { __nanosleep(32); if (++guard > (1 << 22)) TRAP(); }
          }
          fence_async_glob();
          if (c == 1) { mbar_wait(BAR(B_QK), ph); spin_until(clk32() + HDLY_); }
          if (c < 2) paced_h(sb + M_H + c * 32768, g_h[c][c ? s2 : s1], c ? 0 : NA, 32768, 4096, BAR(B_HB), HGAP_);
        }
        int cd = -1;
        if (l2) { cd = route_step(s2, E, lane, run); if (cta == 0) TSTAMP(5, s2, 0); }
        if (lane == 0) sts32(sb + M_CAND + ((T + 2) & 3) * 4, (uint32_t)cd);
        __syncwarp();
        STAMP(17);
        mbar_wait(BAR(B_HAE), ph);
        e_expect(BAR(B_HA), la ? NA : 0);
        if (c == 2 && la) {
          spin_until(clk32() + ADLY_);
          STAMP(18);
          paced_h(sb + M_H, g_h[0][s1 + 1], 0, NA, 4096, BAR(B_HA), AGAP_);
        }
        mbar_wait(BAR(B_OST), ph);
        e_expect(BAR(B_QK), c < 2 ? 2048 : cprev >= 0 ? 8192 : 4096);
        e_expect(BAR(B_V), c < 2 ? 10240 : 8192);
        e_expect(BAR(B_TOK), 16384);
        e_expect(BAR(B_OM), 4096);
        cprev = cd;
      }
    } else {
      const uint32_t mytok = sb + M_Q + c * 12288 + 2048, tb = BAR(c < 2 ? B_TOK : B_V);
      mbar_wait(BAR(B_STG1), 0);
      fence_async_smem();
      e_s2g(g_tok[cta][1], sb + M_TST, 8192);
#pragma unroll 1
      for (int T = 0; T < NSTEP - 1; T++) {
        const uint32_t ph = T & 1;
        uint8_t* const tok = g_tok[cta][ph ^ 1];
        mbar_wait(BAR(B_STG), ph ^ 1);
        fence_async_smem();
        if (cta == 0 && (T == 0 || T == NSEG || T == NSTEP - 2)) GSTAMP(0, T == 0 ? 2 : T == NSEG ? 3 : 4);
        if (T > 0 && TQ_) mbar_wait(BAR(B_QK), ph);
        STAMP(20);
        uint32_t t = clk32();
        e_s2g(tok + 8192, sb + M_TST + 8192, XT2_);
        spin_until(t + TGAP_);
        e_s2g(tok + 12288, sb + M_TST + 12288, XT2_);
        bulk_wait();
        __syncwarp();
        e_arrive(BAR(B_TFREE));
        if (T == 0) e_mc(mytok, tok + 8192, 8192, tb, 1);
        STAMP(21);
#pragma unroll 1
        for (int k = 0; k < 2; k++) {
          if (k == 1) {
            mbar_wait(BAR(B_STG1), ph ^ 1);
            fence_async_smem();
            t = uni(lds32(sb + M_BAS2 + ph * 4));
            wait_until(t + TDLY_);
            e_s2g(g_tok[cta][ph], sb + M_TST, XT1_);
          }
          if (k == (c >> 1)) {
            mbar_wait(BAR(c < 2 ? B_KFREE : B_VFREE), ph);
            t = k ? t + LDLY_ : clk32() + KDLY_;
            wait_until(t);
            STAMP(23);
            e_mc(mytok, tok, 8192, tb, 1);
            spin_until(t + LGAP_);
            e_mc(mytok, tok + 8192, 8192, tb, 6);
            STAMP(24);
          }
        }
      }
      bulk_wait();
    }
    __syncwarp();
    cluster_sync();
  }
}

constexpr uint32_t A_RING = 0;
constexpr int A_NST = 6;
constexpr uint32_t A_STG = A_RING + A_NST * 8192;
constexpr uint32_t A_WD = A_STG + 8192;
constexpr uint32_t A_WG = A_WD + 57344;
constexpr uint32_t A_WU = A_WG + 57344;
constexpr uint32_t A_XN = A_WU + 57344;
constexpr uint32_t A_BAR = A_XN + 2048;
constexpr uint32_t A_TOTAL = A_BAR + 256;
static_assert(A_TOTAL <= 232448, "aux smem");

__device__ __forceinline__ uint32_t ptag(int s) { return ((s / PRING) & 1) ^ 1; }
static_assert((NSEG / PRING) % 2 == 0, "tags");
__device__ __forceinline__ void load_row(uint32_t* v, const void* row, int lane) {
  const uint4 a = __ldcg((const uint4*)row + lane), b = __ldcg((const uint4*)row + 32 + lane);
  v[0] = a.x; v[1] = a.y; v[2] = a.z; v[3] = a.w; v[4] = b.x; v[5] = b.y; v[6] = b.z; v[7] = b.w;
}
__device__ __forceinline__ void store_row(void* row, const uint32_t* v, int lane) {
  ((uint4*)row)[lane] = make_uint4(v[0], v[1], v[2], v[3]); ((uint4*)row)[32 + lane] = make_uint4(v[4], v[5], v[6], v[7]);
}
__device__ __forceinline__ void store_img(uint8_t* img, int r, const uint32_t* v, int lane) {
  uint8_t* b = img + (lane >> 3) * 4096 + (r >> 3) * 1024 + (r & 7) * 128 + (((lane ^ r) & 7) << 4);
  *(uint4*)b = make_uint4(v[0], v[1], v[2], v[3]);
  *(uint4*)(b + 16384) = make_uint4(v[4], v[5], v[6], v[7]);
}
template <int NT> __device__ __forceinline__ void ln_rows(const uint32_t (*v)[8], uint32_t (*y)[8]) {
  float c[NT], sm[NT], sq[NT];
#pragma unroll
  for (int k = 0; k < NT; k++) {
    c[k] = blo(__shfl_sync(~0u, v[k][0], 0));
    float s0 = 0.f, s1 = 0.f, q0 = 0.f, q1 = 0.f;
#pragma unroll
    for (int i = 0; i < 8; i++) { const float a = blo(v[k][i]) - c[k], b = bhi(v[k][i]) - c[k]; s0 += a; s1 += b; q0 = fmaf(a, a, q0); q1 = fmaf(b, b, q1); }
    sm[k] = s0 + s1; sq[k] = q0 + q1;
  }
#pragma unroll
  for (int o = 16; o > 0; o >>= 1)
#pragma unroll
    for (int k = 0; k < NT; k++) {
      sm[k] += __shfl_xor_sync(~0u, sm[k], o); sq[k] += __shfl_xor_sync(~0u, sq[k], o);
    }
#pragma unroll
  for (int k = 0; k < NT; k++) {
    const float dm = sm[k] * (1.f / 512.f), var = fmaxf(fmaf(-dm, dm, sq[k] * (1.f / 512.f)), 0.f);
    const float mb = rbf(c[k] + dm), inv = rcp(rbf(sqrt_fast(rbf(rbf(var) + 1e-5f))));
#pragma unroll
    for (int i = 0; i < 8; i++) { const uint32_t a = pack2(blo(v[k][i]) - mb, bhi(v[k][i]) - mb); y[k][i] = pack2(blo(a) * inv, bhi(a) * inv); }
  }
}
__device__ __forceinline__ void input_ln_pair(const bf16* x, int s, int pr, int lane) {
  uint32_t v[2][8], y[2][8];
  load_row(v[0], x + (size_t)(s * 32 + 2 * pr) * 512, lane); load_row(v[1], x + (size_t)(s * 32 + 2 * pr + 1) * 512, lane);
  ln_rows<2>(v, y);
  store_img(g_h[0][s], 2 * pr, y[0], lane); store_img(g_h[0][s], 2 * pr + 1, y[1], lane);
}
__device__ __forceinline__ float load_wr(uint32_t* wv, const bf16* wr, int lane) {
  load_row(wv, wr, lane);
  float wsum = 0.f;
#pragma unroll
  for (int i = 0; i < 8; i++) wsum += blo(wv[i]) + bhi(wv[i]);
#pragma unroll
  for (int o = 16; o > 0; o >>= 1) wsum += __shfl_xor_sync(~0u, wsum, o);
  return wsum;
}

template <bool FAST>
__device__ __forceinline__ unsigned long long token_post(int st, int tk, const bf16* res, bf16* dst, bf16* req, unsigned long long best,
                                                         const uint32_t* wv, float wsum, uint32_t E, int lane) {
  const int s = tk >> 5;
  uint32_t x[8];
  load_row(x, res, lane);
  {
    int guard = 0;
    while (__popc(__ballot_sync(~0u, ld_rlx(f_acc[st][s][lane]) == E)) < (FAST ? HINT_ : 32)) { __nanosleep(FAST ? 20 : 100); if (++guard > (1 << 22)) TRAP(); }
  }
  if (tk == s * 32 && st == 0 && lane == 0) TSTAMP(4, s, 0);
  {
    const uint8_t* pp = g_pp[st][s % PRING] + (lane >> 4) * 8192 + (tk & 31) * 256 + (((lane & 15) ^ (tk & 7)) << 4);
    const uint32_t tag = ptag(s);
    uint4 q[8][2];
#define PLD(k, h) q[k][h] = ld_rlx128<(k) * 32768 + (h) * 16384>(pp)
#define PLD8(h) PLD(0, h); PLD(1, h); PLD(2, h); PLD(3, h); PLD(4, h); PLD(5, h); PLD(6, h); PLD(7, h)
#define PBAD(h) __any_sync(~0u, (or3(xo2(q[0][h].x, q[1][h].x, tag), xo2(q[2][h].x, q[3][h].x, tag), xo2(q[4][h].x, q[5][h].x, tag)) | xo2(q[6][h].x, q[7][h].x, tag)) & ~lane & (PST_ == 8192 ? 1u : 0u))
#define PSUM(f, h, m) (((f(q[0][h].m) + f(q[1][h].m)) + (f(q[2][h].m) + f(q[3][h].m))) + ((f(q[4][h].m) + f(q[5][h].m)) + (f(q[6][h].m) + f(q[7][h].m))))
    const uint32_t eye = (lane >> 2) == 2 * (lane & 3) ? 0x3f80u : (lane >> 2) == 2 * (lane & 3) + 1 ? 0x3f800000u : 0u;
    auto padd = [&](int h) {
      if (FAST) {
        float u[4] = {0.f, 0.f, 0.f, 0.f}, v[4] = {0.f, 0.f, 0.f, 0.f};
#pragma unroll
        for (int k = 0; k < 8; k++) { hmma8(u, q[k][h].x, q[k][h].y, eye); hmma8(v, q[k][h].z, q[k][h].w, eye); }
        x[4 * h] = add2(x[4 * h], pack2(u[0], u[1])); x[4 * h + 1] = add2(x[4 * h + 1], pack2(u[2], u[3]));
        x[4 * h + 2] = add2(x[4 * h + 2], pack2(v[0], v[1])); x[4 * h + 3] = add2(x[4 * h + 3], pack2(v[2], v[3]));
      } else {
        x[4 * h] = add2(x[4 * h], pack2(PSUM(blo, h, x), PSUM(bhi, h, x))); x[4 * h + 1] = add2(x[4 * h + 1], pack2(PSUM(blo, h, y), PSUM(bhi, h, y)));
        x[4 * h + 2] = add2(x[4 * h + 2], pack2(PSUM(blo, h, z), PSUM(bhi, h, z))); x[4 * h + 3] = add2(x[4 * h + 3], pack2(PSUM(blo, h, w), PSUM(bhi, h, w)));
      }
    };
    int guard = 0;
    PLD8(0);
    if (FAST) { PLD8(1); }
    while (PBAD(0)) { if (++guard > (1 << 20)) TRAP(); PLD8(0); }
    padd(0);
    if (!FAST) { PLD8(1); }
    while (PBAD(1)) { if (++guard > (1 << 20)) TRAP(); PLD8(1); }
    padd(1);
  }
  const float c = blo(__shfl_sync(~0u, x[0], 0));
  float s0 = 0.f, s1 = 0.f, q0 = 0.f, q1 = 0.f, r0 = 0.f, r1 = 0.f;
#pragma unroll
  for (int i = 0; i < 8; i++) {
    const float a = blo(x[i]) - c, b = bhi(x[i]) - c;
    s0 += a; s1 += b; q0 = fmaf(a, a, q0); q1 = fmaf(b, b, q1); r0 = fmaf(a, blo(wv[i]), r0); r1 = fmaf(b, bhi(wv[i]), r1);
  }
  s0 += s1; q0 += q1; r0 += r1;
#pragma unroll
  for (int o = 16; o > 0; o >>= 1) { s0 += __shfl_xor_sync(~0u, s0, o); q0 += __shfl_xor_sync(~0u, q0, o); r0 += __shfl_xor_sync(~0u, r0, o); }
  const float dm = s0 * (1.f / 512.f), m = c + dm, var = fmaxf(fmaf(-dm, dm, q0 * (1.f / 512.f)), 0.f);
  const float mb = rbf(m), inv = rcp(rbf(sqrt_fast(rbf(rbf(var) + 1e-5f))));
  const uint32_t nmb = pack2(-mb, -mb);
  const unsigned long long wd = rword(E, tk, fmaf(c - mb, wsum, r0) * inv);
  uint32_t xn[8], x2[8];
#pragma unroll
  for (int i = 0; i < 8; i++) { const uint32_t d = add2(x[i], nmb); xn[i] = pack2(blo(d) * inv, bhi(d) * inv); x2[i] = add2(x[i], xn[i]); }
  if (st == 0) {
    const float mb2 = rbf(fmaf(m - mb, inv, m)), inv2 = rcp(rbf(sqrt_fast(rbf(rbf(var * (1.f + inv) * (1.f + inv)) + 1e-5f))));
    const uint32_t nmb2 = pack2(-mb2, -mb2);
    uint32_t h[8];
#pragma unroll
    for (int i = 0; i < 8; i++) { const uint32_t d2 = add2(x2[i], nmb2); h[i] = pack2(blo(d2) * inv2, bhi(d2) * inv2); }
    store_img(g_h[1][s], tk & 31, h, lane);
  }
  store_row(dst, x2, lane);
  if (wd > best && !(EXPQ_ & (st == 0 ? 1 : 2))) { store_row(req, xn, lane); store_row(req + 512, x, lane); }
  return wd;
}

__device__ __forceinline__ void ffn_slice(uint32_t sb, const bf16* xn, float* yacc, uint32_t* flag, uint32_t E, int t, bool urgent) {
  const int w = t >> 5, g = (t >> 2) & 7;
  if (t == 0 && urgent) sts32(sb + A_BAR + 160, 1);
  { const uint2 u = __ldcg((const uint2*)xn + t); asm volatile("st.shared.v2.u32 [%0], {%1,%2};" :: "r"(sb + A_XN + t * 8), "r"(u.x), "r"(u.y) : "memory"); }
  fence_async_smem();
  bar_sync(4, 128);
  float ga[4], ua[4];
  constexpr uint64_t da = mkdesc(A_WG, 896, 128, 0), db = mkdesc(A_XN, 16, 128, 0);
  wg_fence();
  wgmma_ss8<0, 1, 0>(ga, da, db); wgmma_ss8<0, 1, 0>(ua, da + (A_WU - A_WG) / 16, db);
#pragma unroll
  for (int ks = 1; ks < 32; ks++) { wgmma_ss8<1, 1, 0>(ga, da + ks * 112, db + ks * 2); wgmma_ss8<1, 1, 0>(ua, da + (A_WU - A_WG) / 16 + ks * 112, db + ks * 2); }
  wg_commit(); wg_wait<0>(); reg_fence(ga); reg_fence(ua);
  if ((t & 3) == 0) {
#pragma unroll
    for (int h = 0; h < 2; h++) {
      const float gs = rbf(ga[2 * h]), us = rbf(ua[2 * h]);
      const float v = 16 * w + 8 * h < 56 ? rbf(gs * rcp(1.f + __expf(-gs))) * us : 0.f;
      asm volatile("st.shared.u16 [%0], %1;" :: "r"(sb + A_XN + 1280 + (16 * w + 8 * h + g) * 2), "h"((unsigned short)pack2(v, 0.f)) : "memory");
    }
  }
  fence_async_smem();
  bar_sync(4, 128);
#pragma unroll 1
  for (int j = 0; j < 2; j++) {
    float y[4][4];
    const uint64_t dd = mkdesc(A_WD, 8192, 128, 0) + (uint64_t)(j * 256);
    wg_fence();
#pragma unroll
    for (int m = 0; m < 4; m++) {
      wgmma_ss8<0, 1, 0>(y[m], dd + m * 64, mkdesc(A_XN + 1280, 16, 128, 0));
#pragma unroll
      for (int ks = 1; ks < 4; ks++) wgmma_ss8<1, 1, 0>(y[m], dd + m * 64 + ks * 1024, mkdesc(A_XN + 1280 + ks * 32, 16, 128, 0));
    }
    wg_commit(); wg_wait<0>();
#pragma unroll
    for (int m = 0; m < 4; m++) {
      reg_fence(y[m]);
      if ((t & 3) == 0) { float* o = yacc + j * 256 + m * 64 + 16 * w + g; o[0] = y[m][0]; o[8] = y[m][2]; }
    }
  }
  bar_sync(4, 128);
  if (t < 8) { sts32(sb + A_BAR + 160, 0); st_rel(flag + t, E); }
  __syncwarp();
}

__device__ __forceinline__ void ffn_gather(uint32_t sb, int q, int j, uint32_t E, int lane) {
  wait_all(f_y[q][4 * j + (lane & 3)], E);
  float4 y[4][4];
#pragma unroll
  for (int k = 0; k < 4; k++)
#pragma unroll
    for (int i = 0; i < 4; i++) y[k][i] = __ldcg((const float4*)g_y[q & 7][4 * j + k] + i * 32 + lane);
#pragma unroll
  for (int i = 0; i < 4; i++)
    sts128f(sb + 1024 + j * 2048 + i * 512 + lane * 16, (y[0][i].x + y[1][i].x) + (y[2][i].x + y[3][i].x), (y[0][i].y + y[1][i].y) + (y[2][i].y + y[3][i].y),
            (y[0][i].z + y[1][i].z) + (y[2][i].z + y[3][i].z), (y[0][i].w + y[1][i].w) + (y[2][i].w + y[3][i].w));
  bar_sync(9, 256);
}
__device__ __forceinline__ void ffn_finish(uint32_t sb, int q, const bf16* req, float r, uint32_t E, int lane, uint32_t* v) {
  if (lane == 0) sts32(sb + 16, q);
  bar_sync(8, 256);
  uint32_t xn[8];
  load_row(xn, req, lane); load_row(v, req + 512, lane);
  const float rs = rbf(1.f / (1.f + __expf(-rbf(r))));
  ffn_gather(sb, q, 7, E, lane);
#pragma unroll
  for (int i = 0; i < 4; i++) {
    float y[4] = {0.f, 0.f, 0.f, 0.f};
#pragma unroll
    for (int j = 0; j < 8; j++) {
      const uint4 u = lds128(sb + 1024 + j * 2048 + (i >> 1) * 1024 + lane * 32 + (i & 1) * 16);
      y[0] += __uint_as_float(u.x); y[1] += __uint_as_float(u.y); y[2] += __uint_as_float(u.z); y[3] += __uint_as_float(u.w);
    }
    v[2 * i] = add2(v[2 * i], add2(xn[2 * i], pack2(rbf(y[0]) * rs, rbf(y[1]) * rs)));
    v[2 * i + 1] = add2(v[2 * i + 1], add2(xn[2 * i + 1], pack2(rbf(y[2]) * rs, rbf(y[3]) * rs)));
  }
}

__global__ void __launch_bounds__(512, 1) aux_kernel(Params p) {
  extern __shared__ __align__(1024) uint8_t sm[];
  const uint32_t sb = smem_u32(sm);
  if ((sb & 0xFFFFFFu) != SBASE) TRAP();
  const int warp = __shfl_sync(~0u, threadIdx.x >> 5, 0);
  const int cta = blockIdx.x;
  const uint32_t E = __shfl_sync(~0u, *(volatile uint32_t*)&g_epoch + 1, 0);
  const uint32_t bars = sb + A_BAR;

  if (cta < 32) {
    const int cg = cta & 3, kg = cta >> 2;
    if (threadIdx.x == 0) {
      for (int i = 0; i < A_NST; i++) { mbar_init(bars + 8 * i, 1); mbar_init(bars + 64 + 8 * i, 2); }
      mbar_init(bars + 128, 8); mbar_init(bars + 136, 8); mbar_init(bars + 144, 1);
      sts32(bars + 160, 0);
      asm volatile("fence.mbarrier_init.release.cluster;" ::: "memory");
    }
    if (warp < 8) {
      asm volatile("setmaxnreg.inc.sync.aligned.u32 176;");
      const int tid = fresh_tid(), lane = tid & 31;
      uint32_t W[32][4];
      stage_weights(sb + A_WD, p.wo + (size_t)kg * 512 * 512 + cg * 128, 512, tid, 256);
      cp_async_wait();
      bar_sync(1, 256);
      load_frags(W, sb + A_WD, warp >> 2, warp & 3, lane);
      bar_sync(2, 512);
      const uint32_t so = sb + A_STG + ((lane >> 4) * 8 + (lane & 7)) * 256 + (((warp * 2 + ((lane >> 3) & 1)) ^ (lane & 7)) << 4);
      const uint32_t tm = lane < 4 ? 0x00010001u : 0u;
      int stage = 0; uint32_t ph = 0, job = 0;
#pragma unroll 1
      for (int T = 0; T < NSTEP; T++) {
#pragma unroll 1
        for (int k = 0; k < 3; k++) {
          const int st = k == 0 ? 0 : 3 - k, s = st == 0 ? T : T - LAG;
          if (s < 0 || s >= NSEG) continue;
          float d[16];
#pragma unroll
          for (int hh = 0; hh < 4; hh++) {
            mbar_wait(bars + 8 * stage, ph);
            while (uni(lds32(bars + 160))) __nanosleep(100);
            const uint64_t db = mkdesc(A_RING, 512, 128, 0) + (uint64_t)(stage * 512);
            wg_fence();
            if (hh == 0) wgmma_rs32<0, 0>(d, W[0], db); else wgmma_rs32<1, 0>(d, W[hh * 8], db);
#pragma unroll
            for (int ks = 1; ks < 8; ks++) wgmma_rs32<1, 0>(d, W[hh * 8 + ks], db + ks * 64);
            wg_commit();
            if (hh > 0) { wg_wait<1>(); if ((tid & 127) == 0) mbar_arrive(bars + 64 + 8 * (stage == 0 ? A_NST - 1 : stage - 1)); }
            if (++stage == A_NST) { stage = 0; ph ^= 1; }
          }
          mbar_wait(bars + 144, (job & 1) ^ 1);
          wg_wait<0>(); reg_fence(d);
          if ((tid & 127) == 0) mbar_arrive(bars + 64 + 8 * (stage == 0 ? A_NST - 1 : stage - 1));
          if (cta == 0 && tid == 0) TSTAMP(6, T, k);
          const uint32_t tv = tm * ptag(s);
#define TG(i) ((pack2(d[2 * (i)], d[2 * (i) + 1]) & ~tm) | tv)
          stmatrix4_t(so, TG(0), pack2(d[2], d[3]), TG(2), pack2(d[6], d[7]));
          stmatrix4_t(so + 4096, TG(4), pack2(d[10], d[11]), TG(6), pack2(d[14], d[15]));
          fence_async_smem();
          __syncwarp();
          if (lane == 0) mbar_arrive(bars + 128 + 8 * (job & 1));
          job++;
        }
      }
    } else if (warp < 12) {
      asm volatile("setmaxnreg.dec.sync.aligned.u32 120;");
      const int tid = fresh_tid(), lane = tid & 31;
      const int w = warp - 8, t = tid - 256;
#pragma unroll 1
      for (int s = cta + 4; s < NSEG; s += 32) {
#pragma unroll 1
        for (int pr = w; pr < 16; pr += 4) input_ln_pair(p.x, s, pr, lane);
        bar_sync(4, 128);
        if (t == 0) st_rel(&f_h1[s], E);
      }
      bar_sync(2, 512);
      { int guard = 0; while (ld_rlx(&f_loaded[cta]) != E) { __nanosleep(200); if (++guard > (1 << 22)) TRAP(); } }
#pragma unroll 1
      for (int i = t; i < 512 * 7; i += 128) {
        const int k = i / 7, pc = i % 7;
        cp_async16(sb + A_WG + (k >> 3) * 896 + pc * 128 + (k & 7) * 16, p.wg + (size_t)k * 1792 + cta * 56 + pc * 8);
        cp_async16(sb + A_WU + (k >> 3) * 896 + pc * 128 + (k & 7) * 16, p.wu + (size_t)k * 1792 + cta * 56 + pc * 8);
        cp_async16(sb + A_WD + (i >> 9) * 8192 + (i & 63) * 128 + ((i >> 6) & 7) * 16, p.wd + (size_t)cta * 56 * 512 + i * 8);
      }
      uint32_t wv[8];
      const float wsum = load_wr(wv, p.wr, lane);
      cp_async_wait();
      fence_async_smem();
      bar_sync(4, 128);
      const int tj = (cta * 4 + w) & 31, st = 1 + ((cta >> 3) & 1), sq = cta >> 4;
      unsigned long long run = 0, run2 = 0, best = 0, hist = 0;
      uint32_t open = 0;
#pragma unroll 1
      for (int i = 0; i <= NSTEP; i++) {
        int tok = -1; const bf16* req = nullptr;
        if (i < NSEG) {
          const int cd = (int)uni(route_step(i, E, lane, run));
          run = __shfl_sync(~0u, run, 0);
          hist = hist << 8 | (uint32_t)(cd + 1);
          if (cd >= 0) { tok = rtok(run); req = g_req1[tok][0]; }
        } else {
          const unsigned long long m = wait_words(f_l2[i - NSEG], E);
          const unsigned long long n = ld_rlxu64(f_l2[min(i - NSEG + 1 + (lane & 7), LAG)]);
          const bool over = bar_or(4, 128, rfresh(n, E) && n != m);
          if (m != run2 && !over) { run2 = m; tok = rtok(m); req = g_req2[(tok >> 5) < (rtok(run) >> 5) ? 0 : 1][tok][0]; }
        }
        tok = __shfl_sync(~0u, tok, 0);
        if (tok >= 0) {
          if (cta == 0 && t == 0) TSTAMP(8, i, 0);
          ffn_slice(sb, req, g_y[i & 7][cta], f_y[i][cta], E, t, i < NSEG);
          if (cta == 0 && t == 0) TSTAMP(8, i, 1);
        }
        const int s = i - LAG;
        if (s < 0 || i >= NSEG) continue;
        const int cd = (int)((hist >> (8 * LAG)) & 255) - 1;
        if (cd >= 0 && st == 2) best = 0;
        const int ts = rtok(run) >> 5;
        if ((s & 1) == sq) {
          const int tk = s * 32 + tj;
          unsigned long long wd = (unsigned long long)E << 43;
          if (st == 1 ? s < ts || i < NSEG - 1 : s >= ts) {
            if (st == 2 && cd == tj) wait_eq(&f_hc[s], E);
            wd = token_post<false>(st, tk, st == 2 && cd == tj ? g_x2c[s] : g_x2 + (size_t)tk * 512,
                                   (st == 2 || s < ts ? p.out : g_n) + (size_t)tk * 512, g_req2[st - 1][tk][0], best, wv, wsum, E, lane);
            best = max(best, wd);
            if (st == 1 && s >= ts) open |= 1u << (s >> 1);
          }
          __syncwarp();
          if (lane < 4) st_rel64(&f_w2[st - 1][s][tj][lane], wd);
          __syncwarp();
        }
        if (st == 1) {
          if (i == NSEG - 1 && t == 0 && cta == 0) GSTAMP(1, 0);
#pragma unroll 1
          for (int n = i == NSEG - 1 ? 32 : 2; n > 0 && open; n--) {
            const int s0 = 2 * (__ffs(open) - 1) + sq;
            if (s0 >= ts) break;
            open &= open - 1;
            uint32_t v[8];
            load_row(v, g_n + (size_t)(s0 * 32 + tj) * 512, lane);
            wait_words(f_w2[1][s0][tj], E);
            store_row(p.out + (size_t)(s0 * 32 + tj) * 512, v, lane);
          }
          if (i == NSEG - 1) {
            __syncwarp();
            if (lane == 0) st_rel(&f_cp[sq * 32 + tj], E);
            if (t == 0 && cta == 0) GSTAMP(1, 3);
          }
        }
      }
    } else {
      asm volatile("setmaxnreg.dec.sync.aligned.u32 40;");
      const int tid = fresh_tid(), lane = tid & 31;
      const int w = warp - 12;
      bar_sync(2, 512);
      if (w == 0) {
        int stage = 0; uint32_t ph = 1;
#pragma unroll 1
        for (int T = 0; T < NSTEP; T++) {
#pragma unroll 1
          for (int k = 0; k < 3; k++) {
            const int st = k == 0 ? 0 : 3 - k, s = st == 0 ? T : T - LAG;
            if (s < 0 || s >= NSEG) continue;
            const uint32_t* fl = f_o[T][kg][st * 4 + (lane & 3)];
            uint32_t ready = 0; int guard = 0;
#pragma unroll 1
            for (int hh = 0; hh < 4; hh++) {
              while (!((ready >> hh) & 1)) {
                ready = __ballot_sync(~0u, ld_rlx(fl) == E);
                if (++guard > (1 << 23)) TRAP();
              }
              fence_async_glob();
              mbar_wait(bars + 64 + 8 * stage, ph);
              e_expect(bars + 8 * stage, OLOAD_);
              e_g2s(sb + A_RING + stage * 8192, g_o[st][s % ORING][kg * 4 + hh], OLOAD_, bars + 8 * stage);
              if (++stage == A_NST) { stage = 0; ph ^= 1; }
            }
          }
          if (cta == 0 && lane == 0) TSTAMP(3, T, 0);
        }
      } else if (w < 3) {
        uint32_t job = 0;
#pragma unroll 1
        for (int T = 0; T < NSTEP; T++) {
#pragma unroll 1
          for (int k = 0; k < 3; k++) {
            const int st = k == 0 ? 0 : 3 - k, s = st == 0 ? T : T - LAG;
            if (s < 0 || s >= NSEG) continue;
            if ((job++ & 1) != w - 1) continue;
            if (s >= PRING) wait_words(st == 0 ? f_h2[s - PRING][lane & 3] : f_w2[st - 1][s - PRING][lane], E);
            mbar_wait(bars + 128 + 8 * (w - 1), ((job - 1) >> 1) & 1);
            if (cta == 0 && st == 0) TSTAMP(7, s, 0);
            e_s2g(g_pp[st][s % PRING] + cta * 8192, sb + A_STG, PST_);
            if (lane < 8) st_rlx(&f_acc[st][s][cta][lane], E);
            asm volatile("cp.async.bulk.commit_group;\n cp.async.bulk.wait_group.read 0;" ::: "memory");
            __syncwarp();
            e_arrive(bars + 144);
            __syncwarp();
            if (cta == 0 && st == 0) TSTAMP(7, s, 1);
          }
        }
        bulk_wait();
      }
    }
  } else {
    const int tid = fresh_tid(), lane = tid & 31;
    const int qd = cta - 32;
    input_ln_pair(p.x, qd, warp, lane);
    bar_sync(6, 512);
    if (tid == 0) st_rel(&f_h1[qd], E);
    volatile int* bc = (volatile int*)sm;
    if (warp == 15) {
      unsigned long long run = 0;
      unsigned long long b2[2][2] = {{0, 0}, {0, 0}};
      auto track = [&](int s) {
#pragma unroll
        for (int k = 0; k < 2; k++) {
          const unsigned long long m = warp_max<16>(wait_words(f_w2[k][s][lane], E));
          if (lane == (s & 31)) { if (s < 32) b2[k][0] = m; else b2[k][1] = m; }
        }
      };
#pragma unroll 1
      for (int s = 0; s < NSEG; s++) {
        const int cd = route_step(s, E, lane, run);
        if (cd >= 0 && qd == (s & 1)) {
          uint32_t v[1][8], h[1][8];
          ffn_finish(sb, s, g_req1[s * 32 + cd][0], rscore(run), E, lane, v[0]);
          if (lane == 0) TSTAMP(8, s, 2);
          ln_rows<1>(v, h);
#pragma unroll
          for (int i = 0; i < 8; i++) st_rlx64(&g_hc[s][(i >> 2) * 128 + 4 * lane + (i & 3)], h[0][i], E);
          if (lane == 0) TSTAMP(8, s, 3);
          store_row(g_x2c[s], v[0], lane);
          __syncwarp();
          if (lane == 0) st_rel(&f_hc[s], E);
        }
        if (qd == 2 && s > LAG) track(s - LAG - 1);
      }
      wait_eq(&f_hc[rtok(run) >> 5], E);
      if (lane == 0) *bc = rtok(run);
      bar_sync(7, 288);
      if (qd == 2) {
        uint32_t v[8];
        const int ts = rtok(run) >> 5;
        track(NSEG - LAG - 1);
        run = 0;
        int kl = 0;
#pragma unroll 1
        for (int k = 0; k <= LAG; k++) {
          const int s = NSEG - LAG - 1 + k;
          const unsigned long long m = warp_max<16>(k == 0 ? max(lane < ts ? b2[0][0] : b2[1][0], lane + 32 < ts ? b2[0][1] : b2[1][1])
                                                           : wait_words(f_w2[s < ts ? 0 : 1][s][lane], E));
          const bool lead = m > run;
          if (lead) { run = m; __threadfence(); }
          if (lane < 4) st_rlx64(&f_l2[k][lane], (uint32_t)run, (uint32_t)(run >> 32));
          if (lead) kl = k;
          if (k == LAG - 1) { wait_all(&f_cp[lane], E); wait_all(&f_cp[32 + lane], E); }
          if (k == LAG - 1 || (k == LAG && lead)) ffn_finish(sb, NSEG + kl, g_req2[(rtok(run) >> 5) < ts ? 0 : 1][rtok(run)][0], rscore(run), E, lane, v);
        }
        if (lane == 0) GSTAMP(1, 1);
        store_row(p.out + (size_t)rtok(run) * 512, v, lane);
        if (lane == 0) GSTAMP(1, 2);
      }
      if (lane == 0) sts32(sb + 16, (uint32_t)-1);
      bar_sync(8, 256);
      if (qd == 2) {
        asm volatile("griddepcontrol.wait;" ::: "memory");
        if (lane == 0) *(volatile uint32_t*)&g_epoch = E;
      }
    } else if (warp >= 8) {
#pragma unroll 1
      for (;;) {
        bar_sync(8, 256);
        const int q = (int)uni(lds32(sb + 16));
        if (q < 0) break;
        ffn_gather(sb, q, warp - 8, E, lane);
      }
    } else {
      uint32_t wv[8];
      const float wsum = load_wr(wv, p.wr, lane);
      unsigned long long best = 0;
      int ttok = 0;
#pragma unroll 1
      for (int i = 0; i < NSTEP; i++) {
        const bool last = i >= NSEG;
        if (i == NSEG) { bar_sync(7, 288); ttok = *bc; best = 0; }
        const int s = last ? i - LAG : i, st = !last ? 0 : s < (ttok >> 5) ? 1 : 2;
        const int tk = s * 32 + qd * 8 + warp;
        const unsigned long long wd = token_post<true>(st, tk, !last ? p.x + (size_t)tk * 512 : tk == ttok ? g_x2c[s] : g_x2 + (size_t)tk * 512,
                                                 (last ? p.out : g_x2) + (size_t)tk * 512, last ? g_req2[st - 1][tk][0] : g_req1[tk][0], best, wv, wsum, E, lane);
        best = max(best, wd);
        volatile unsigned long long* ws = (volatile unsigned long long*)(sm + 64) + (i & 1) * 8;
        if (lane == 0) ws[warp] = wd;
        bar_sync(5, 256);
        if (warp == 0) {
          if (qd == 0 && lane == 0) TSTAMP(4, i, 1);
          if (!last) { const unsigned long long m = warp_max<4>(ws[lane & 7]); if (lane < 4) st_rel64(&f_h2[s][qd][lane], m); }
          else {
            st_rel64(&f_w2[st - 1][s][qd * 8 + (lane >> 2)][lane & 3], ws[lane >> 2]);
            asm volatile("st.relaxed.gpu.global.u64 [%0], %1;" :: "l"(&f_w2[2 - st][s][qd * 8 + (lane >> 2)][lane & 3]), "l"((unsigned long long)E << 43) : "memory");
          }
          if (qd == 0 && lane == 0) TSTAMP(4, i, 2);
        }
        __syncwarp();
      }
    }
  }
}

}

extern "C" void kernel_launch(void* const* d_in, const int* in_sizes, int n_in, void* d_out, int out_size) {
  (void)in_sizes; (void)n_in; (void)out_size;
  static bool init = false;
  if (!init) {
    cudaFuncSetAttribute(main_kernel, cudaFuncAttributeMaxDynamicSharedMemorySize, M_TOTAL);
    cudaFuncSetAttribute(aux_kernel, cudaFuncAttributeMaxDynamicSharedMemorySize, A_TOTAL);
    init = true;
  }
  Params p;
  p.x = (const bf16*)d_in[0]; p.mem0 = (const bf16*)d_in[1]; p.wq = (const bf16*)d_in[2]; p.wk = (const bf16*)d_in[3];
  p.wv = (const bf16*)d_in[4]; p.wo = (const bf16*)d_in[5]; p.wr = (const bf16*)d_in[8]; p.wg = (const bf16*)d_in[9];
  p.wu = (const bf16*)d_in[10]; p.wd = (const bf16*)d_in[11]; p.out = (bf16*)d_out; p.zero = 0; p.zero2 = 0;
  cudaStream_t st = cudaStreamPerThread;
  main_kernel<<<96, 512, M_TOTAL, st>>>(p);
  cudaLaunchConfig_t cfg = {};
  cfg.gridDim = dim3(36); cfg.blockDim = dim3(512); cfg.dynamicSmemBytes = A_TOTAL; cfg.stream = st;
  cudaLaunchAttribute at[1];
  at[0].id = cudaLaunchAttributeProgrammaticStreamSerialization; at[0].val.programmaticStreamSerializationAllowed = 1;
  cfg.attrs = at; cfg.numAttrs = 1;
  cudaLaunchKernelEx(&cfg, aux_kernel, p);
}
```

```cpp
#include <cuda_runtime.h>
#include <cuda_bf16.h>
#include <stdint.h>

namespace {

typedef __nv_bfloat16 bf16;

constexpr int NSEG = 64;
#define LAG_ 5
constexpr int LAG = LAG_;
constexpr int NSTEP = NSEG + LAG;
constexpr int ORING = 8, PRING = 4;
static_assert(LAG < 8, "rings");
#define E1_ 10
#define E2_ 0
#define E3_ 10
constexpr int E1 = E1_, E2 = E2_, E3 = E3_, EA = E1 + E2 + E3;
static_assert(EA % 4 == 0 && EA > 0 && EA < 32 && E1 > 0, "early part: whole 64-column chunks");
#define RW_ 176
#define RA_ 136
#define RC_ 24
#define STR2(x) #x
#define STR(x) STR2(x)
#define RED_ 30
#define ARR_ 7
#define PAUSE_ 13
#define PAUS2_ 29
#define PST2_ 2
#define PVR_ -1
#define SALT_ 0
#define KP1_ 1
#define OLOAD_ 8192
#define PST_ 8192
#define ALT_ 1
#define TQ_ 1
#define NOF_ 2
#define EXPQ_ 0
#define SPC_ 4096
#define HINT_ 24
#define HADD_ 2
#define HAND_ 4
#define REMAP_ 1
#define NPROBE_ 6
#define TP(i, v) (v)
#define XDLY_ TP(0, 2100)
#define YDLY_ TP(1, 3350)
#define X1_ TP(2, 100)
#define X2_ TP(3, 300)
#define Y1_ TP(4, 250)
#define Y2_ TP(5, 450)
#define HGAP_ TP(6, 50)
#define TGAP_ TP(7, 100)
#define ADLY_ TP(8, 600)
#define ODLY_ TP(9, 2800)
#define LDLY_ TP(10, 3800)
#define HDLY_ TP(11, 0)
#define TDLY_ TP(15, 4025)
#define SDLY_ TP(12, 800)
#define AGAP_ 100
#define BOFF_ TP(13, 200)
#define YOFF_ TP(16, 150)
#define YUP_ TP(20, 40)
#define YDN_ TP(21, 4)
#define T1GAP_ TP(22, 100)
#define OGAP_ TP(23, 100)
#define CDLY_ TP(17, 300)
#define SLOW0_ TP(18, 400)
#define SLOW1_ TP(19, 300)
#define KDLY_ TP(14, 300)
__device__ uint32_t g_epoch;
__device__ __align__(1024) uint8_t g_h[2][NSEG][32768];
__device__ __align__(128) uint2 g_hc[NSEG][256];
__device__ __align__(128) bf16 g_x2[2048 * 512];
__device__ __align__(128) bf16 g_x2c[NSEG][512];
__device__ __align__(128) uint8_t g_o[3][ORING][32][8192];
__device__ __align__(128) uint8_t g_pp[3][PRING][8 * 32768];
__device__ __align__(128) bf16 g_n[2048 * 512];
__device__ __align__(128) uint8_t g_xch[96 * 16384 + 65536 + 8192];
__device__ __align__(128) bf16 g_req1[2048][2][512];
__device__ __align__(128) bf16 g_req2[2][2048][2][512];
__device__ __align__(128) float g_y[8][32][512];
__device__ __align__(128) uint8_t g_tok[96][2][16384];
__device__ uint32_t f_choice[96][2], f_loaded[32];
__device__ uint32_t f_h1[NSEG], f_hc[NSEG];
__device__ __align__(128) unsigned long long f_h2[NSEG][4][4];
__device__ __align__(128) unsigned long long f_w2[2][NSEG][32][4];
__device__ __align__(128) unsigned long long f_l2[LAG + 1][4];
__device__ __align__(128) uint32_t f_o[NSTEP][8][12][8];
__device__ __align__(128) uint32_t f_acc[3][NSEG][32][8], f_y[NSTEP + 1][32][8], f_cp[64];
__device__ __align__(128) unsigned long long g_sync[2][96][4];

#define TRAP() __trap()
__device__ __forceinline__ uint32_t smem_u32(const void* p) { return (uint32_t)__cvta_generic_to_shared(p); }
__device__ __forceinline__ int fresh_tid() { const int t = threadIdx.x; return __shfl_sync(~0u, t, t & 31); }
__device__ __forceinline__ unsigned long long gtime64() { unsigned long long t; asm volatile("mov.u64 %0, %%globaltimer;" : "=l"(t) :: "memory"); return t; }
__device__ __forceinline__ uint32_t clk() { unsigned long long c; asm volatile("mov.u64 %0, %%clock64;" : "=l"(c) :: "memory"); return (uint32_t)c; }
__device__ __forceinline__ void wait_until(uint32_t t) {
  while ((int)(t - clk()) > 450) __nanosleep(32);
  uint32_t c;
  do { asm volatile("mov.u32 %0, %%clock;" : "=r"(c) :: "memory"); } while ((int)(c - t) < 0);
}
__device__ __forceinline__ void mbar_init(uint32_t bar, uint32_t cnt) { asm volatile("mbarrier.init.shared::cta.b64 [%0], %1;" :: "r"(bar), "r"(cnt) : "memory"); }
__device__ __forceinline__ void mbar_arrive(uint32_t bar) { asm volatile("mbarrier.arrive.shared::cta.b64 _, [%0];" :: "r"(bar) : "memory"); }
__device__ __forceinline__ void mbar_arrive_remote(uint32_t bar) { asm volatile("mbarrier.arrive.relaxed.cluster.shared::cluster.b64 _, [%0];" :: "r"(bar) : "memory"); }
__device__ __forceinline__ void mbar_expect(uint32_t bar, uint32_t bytes) { asm volatile("mbarrier.arrive.expect_tx.shared::cta.b64 _, [%0], %1;" :: "r"(bar), "r"(bytes) : "memory"); }
__device__ __forceinline__ bool mbar_try(uint32_t bar, uint32_t parity) {
  uint32_t ok;
  asm volatile("{.reg .pred p; mbarrier.try_wait.parity.shared::cta.b64 p, [%1], %2; selp.u32 %0, 1, 0, p;}" : "=r"(ok) : "r"(bar), "r"(parity) : "memory");
  return ok;
}
__device__ __forceinline__ bool mbar_test(uint32_t bar, uint32_t parity) {
  uint32_t ok;
  asm volatile("{.reg .pred p; mbarrier.test_wait.parity.shared::cta.b64 p, [%1], %2; selp.u32 %0, 1, 0, p;}" : "=r"(ok) : "r"(bar), "r"(parity) : "memory");
  return ok;
}
__device__ __forceinline__ void mbar_wait(uint32_t bar, uint32_t parity) {
  asm volatile("{\n.reg .pred p;\nWAIT:\nmbarrier.try_wait.parity.shared::cta.b64 p, [%0], %1;\n@!p bra WAIT;\n}" :: "r"(bar), "r"(parity) : "memory");
}
__device__ __forceinline__ uint32_t ld_acq(const uint32_t* p) { uint32_t v; asm volatile("ld.acquire.gpu.global.u32 %0, [%1];" : "=r"(v) : "l"(p) : "memory"); return v; }
__device__ __forceinline__ unsigned long long ld_acq64(const unsigned long long* p) { unsigned long long v; asm volatile("ld.acquire.gpu.global.u64 %0, [%1];" : "=l"(v) : "l"(p) : "memory"); return v; }
__device__ __forceinline__ void st_rel(uint32_t* p, uint32_t v) { asm volatile("st.release.gpu.global.u32 [%0], %1;" :: "l"(p), "r"(v) : "memory"); }
__device__ __forceinline__ void st_rel64(unsigned long long* p, unsigned long long v) { asm volatile("st.release.gpu.global.u64 [%0], %1;" :: "l"(p), "l"(v) : "memory"); }
__device__ __forceinline__ void red_rel(uint32_t* p, uint32_t v) { asm volatile("red.release.gpu.global.add.u32 [%0], %1;" :: "l"(p), "r"(v) : "memory"); }
__device__ __forceinline__ uint32_t ld_rlx(const uint32_t* p) { uint32_t v; asm volatile("ld.relaxed.gpu.global.u32 %0, [%1];" : "=r"(v) : "l"(p) : "memory"); return v; }
__device__ __forceinline__ unsigned long long ld_rlxu64(const unsigned long long* p) { unsigned long long v; asm volatile("ld.relaxed.gpu.global.u64 %0, [%1];" : "=l"(v) : "l"(p) : "memory"); return v; }
__device__ __forceinline__ void st_rlx(uint32_t* p, uint32_t v) { asm volatile("st.relaxed.gpu.global.u32 [%0], %1;" :: "l"(p), "r"(v) : "memory"); }
__device__ __forceinline__ void bulk_wait() { asm volatile("cp.async.bulk.commit_group;\n cp.async.bulk.wait_group 0;" ::: "memory"); }
__device__ __forceinline__ void fence_acq() { asm volatile("fence.acquire.gpu;" ::: "memory"); }
__device__ __forceinline__ void wait_all(const uint32_t* p, uint32_t v, bool acquire = true) {
  int guard = 0;
  while (!__all_sync(~0u, ld_rlx(p) == v)) { __nanosleep(32); if (++guard > (1 << 22)) TRAP(); }
  if (acquire) fence_acq();
}
__device__ __forceinline__ void wait_eq(const uint32_t* p, uint32_t v) {
  int guard = 0;
  while (ld_rlx(p) != v) { __nanosleep(64); if (++guard > (1 << 22)) TRAP(); }
  fence_acq();
}
__device__ __forceinline__ unsigned long long rword(uint32_t E, int tok, float r) {
  uint32_t u = __float_as_uint(r + 0.f);
  u = r != r ? 0u : (u >> 31) ? ~u : u | 0x80000000u;
  return (unsigned long long)(E & 0x1FFFFFu) << 43 | (unsigned long long)u << 11 | (uint32_t)(2047 - tok);
}
__device__ __forceinline__ int rtok(unsigned long long v) { return 2047 - (int)(v & 2047u); }
__device__ __forceinline__ float rscore(unsigned long long v) { const uint32_t u = (uint32_t)(v >> 11); return __uint_as_float((u >> 31) ? u & 0x7fffffffu : ~u); }
__device__ __forceinline__ bool rfresh(unsigned long long v, uint32_t E) { return (uint32_t)(v >> 43) == (E & 0x1FFFFFu); }
template <int TOP> __device__ __forceinline__ unsigned long long warp_max(unsigned long long v) {
#pragma unroll
  for (int o = TOP; o > 0; o >>= 1) { const unsigned long long ov = __shfl_xor_sync(~0u, v, o); v = ov > v ? ov : v; }
  return v;
}
template <int off> __device__ __forceinline__ uint2 ld_rlx64(const void* p) { unsigned long long v; asm volatile("ld.relaxed.gpu.global.b64 %0, [%1+%2];" : "=l"(v) : "l"(p), "n"(off) : "memory"); return make_uint2((uint32_t)v, (uint32_t)(v >> 32)); }
template <int off> __device__ __forceinline__ uint4 ld_rlx128(const void* p) {
  unsigned long long a, b; asm volatile("ld.relaxed.gpu.global.v2.b64 {%0,%1}, [%2+%3];" : "=l"(a), "=l"(b) : "l"(p), "n"(off) : "memory");
  return make_uint4((uint32_t)a, (uint32_t)(a >> 32), (uint32_t)b, (uint32_t)(b >> 32));
}
__device__ __forceinline__ void st_rlx64(void* p, uint32_t lo, uint32_t hi) { asm volatile("{.reg .b64 t; mov.b64 t, {%1,%2}; st.relaxed.gpu.global.b64 [%0], t;}" :: "l"(p), "r"(lo), "r"(hi) : "memory"); }
__device__ __forceinline__ void cp_async16(uint32_t dst, const void* src) { asm volatile("cp.async.cg.shared.global [%0], [%1], 16;" :: "r"(dst), "l"(src) : "memory"); }
__device__ __forceinline__ void cp_async_wait() { asm volatile("cp.async.wait_all;" ::: "memory"); }
__device__ __forceinline__ void fence_async_smem() { asm volatile("fence.proxy.async.shared::cta;" ::: "memory"); }
__device__ __forceinline__ void fence_async_glob() { asm volatile("fence.proxy.async.global;" ::: "memory"); }
__device__ __forceinline__ void fence_async_acq() { asm volatile("fence.proxy.async::generic.acquire.sync_restrict::shared::cluster.cluster;" ::: "memory"); }
__device__ __forceinline__ float ex2(float x) { float y; asm("ex2.approx.ftz.f32 %0, %1;" : "=f"(y) : "f"(x)); return y; }
__device__ __forceinline__ float sqrt_fast(float x) { float y; asm("sqrt.approx.ftz.f32 %0, %1;" : "=f"(y) : "f"(x)); return y; }
__device__ __forceinline__ float rcp(float x) { float y; asm("rcp.approx.ftz.f32 %0, %1;" : "=f"(y) : "f"(x)); return y; }
__device__ __forceinline__ void bar_sync(int id, int n) { asm volatile("bar.sync %0, %1;" :: "r"(id), "r"(n) : "memory"); }
__device__ __forceinline__ bool bar_or(int id, int n, bool v) {
  uint32_t r;
  asm volatile("{.reg .pred p, q; setp.ne.u32 p, %3, 0; barrier.cta.red.or.aligned.pred q, %1, %2, p; selp.u32 %0, 1, 0, q;}" : "=r"(r) : "r"(id), "r"(n), "r"((uint32_t)v) : "memory");
  return r;
}
__device__ __forceinline__ uint32_t mapa(uint32_t a, uint32_t rank) { uint32_t r; asm volatile("mapa.shared::cluster.u32 %0, %1, %2;" : "=r"(r) : "r"(a), "r"(rank)); return r; }
__device__ __forceinline__ void cluster_sync() { asm volatile("barrier.cluster.arrive.release.aligned; barrier.cluster.wait.acquire.aligned;" ::: "memory"); }
__device__ __forceinline__ void st_async32(uint32_t dst, uint32_t v, uint32_t bar) { asm volatile("st.async.shared::cluster.mbarrier::complete_tx::bytes.b32 [%0], %1, [%2];" :: "r"(dst), "r"(v), "r"(bar) : "memory"); }
__device__ __forceinline__ void bulk_g2s(uint32_t dst, const void* src, uint32_t bytes, uint32_t bar) {
  asm volatile("cp.async.bulk.shared::cluster.global.mbarrier::complete_tx::bytes [%0], [%1], %2, [%3];" :: "r"(dst), "l"(src), "r"(bytes), "r"(bar) : "memory");
}
__device__ __forceinline__ void bulk_g2s_mc(uint32_t dst, const void* src, uint32_t bytes, uint32_t bar, uint16_t mask) {
  asm volatile("cp.async.bulk.shared::cluster.global.mbarrier::complete_tx::bytes.multicast::cluster [%0], [%1], %2, [%3], %4;"
               :: "r"(dst), "l"(src), "r"(bytes), "r"(bar), "h"(mask) : "memory");
}
__device__ __forceinline__ void bulk_s2c(uint32_t dst, uint32_t src, uint32_t bytes, uint32_t bar) {
  asm volatile("cp.async.bulk.shared::cluster.shared::cta.mbarrier::complete_tx::bytes [%0], [%1], %2, [%3];" :: "r"(dst), "r"(src), "r"(bytes), "r"(bar) : "memory");
}
__device__ __forceinline__ void bulk_s2g(void* dst, uint32_t src, uint32_t bytes) {
  asm volatile("cp.async.bulk.global.shared::cta.bulk_group [%0], [%1], %2;" :: "l"(dst), "r"(src), "r"(bytes) : "memory");
}
#define ELECT(op) "{.reg .pred p; elect.sync _|p, 0xffffffff; @p " op "}"
__device__ __forceinline__ void e_arrive(uint32_t bar) { asm volatile(ELECT("mbarrier.arrive.shared::cta.b64 _, [%0];") :: "r"(bar) : "memory"); }
__device__ __forceinline__ void e_expect(uint32_t bar, uint32_t bytes) { asm volatile(ELECT("mbarrier.arrive.expect_tx.shared::cta.b64 _, [%0], %1;") :: "r"(bar), "r"(bytes) : "memory"); }
__device__ __forceinline__ void e_g2s(uint32_t dst, const void* src, uint32_t bytes, uint32_t bar) {
  asm volatile(ELECT("cp.async.bulk.shared::cluster.global.mbarrier::complete_tx::bytes [%0], [%1], %2, [%3];") :: "r"(dst), "l"(src), "r"(bytes), "r"(bar) : "memory");
}
__device__ __forceinline__ void e_mc(uint32_t dst, const void* src, uint32_t bytes, uint32_t bar, uint16_t mask) {
  asm volatile(ELECT("cp.async.bulk.shared::cluster.global.mbarrier::complete_tx::bytes.multicast::cluster [%0], [%1], %2, [%3], %4;")
               :: "r"(dst), "l"(src), "r"(bytes), "r"(bar), "h"(mask) : "memory");
}
__device__ __forceinline__ void e_s2g(void* dst, uint32_t src, uint32_t bytes) {
  asm volatile(ELECT("cp.async.bulk.global.shared::cta.bulk_group [%0], [%1], %2;") :: "l"(dst), "r"(src), "r"(bytes) : "memory");
}
__device__ __forceinline__ void e_st_rel(uint32_t* p, uint32_t v) { asm volatile(ELECT("st.release.gpu.global.u32 [%0], %1;") :: "l"(p), "r"(v) : "memory"); }
__device__ __forceinline__ uint32_t clk32() { uint32_t c; asm volatile("mov.u32 %0, %%clock;" : "=r"(c) :: "memory"); return c; }
__device__ __forceinline__ void spin_until(uint32_t t) { while ((int)(clk32() - t) < 0) {} }
__device__ __forceinline__ uint32_t uni(uint32_t v) { return __shfl_sync(~0u, v, 0); }
__device__ __forceinline__ uint32_t pack2(float lo, float hi) { uint32_t r; asm("cvt.rn.bf16x2.f32 %0, %1, %2;" : "=r"(r) : "f"(hi), "f"(lo)); return r; }
__device__ __forceinline__ uint32_t add2(uint32_t a, uint32_t b) { uint32_t r; asm("add.rn.bf16x2 %0, %1, %2;" : "=r"(r) : "r"(a), "r"(b)); return r; }
__device__ __forceinline__ float rbf(float x) { return __bfloat162float(__float2bfloat16_rn(x)); }
__device__ __forceinline__ float blo(uint32_t u) { return __uint_as_float(u << 16); }
__device__ __forceinline__ float bhi(uint32_t u) { return __uint_as_float(u & 0xffff0000u); }
__device__ __forceinline__ uint32_t gentag(uint32_t g) { return (g & 1u) | (g & 2u) << 15; }
__device__ __forceinline__ uint32_t pack2_tag(float lo, float hi, uint32_t tag) {
  const uint32_t u = __byte_perm(__float_as_uint(lo), __float_as_uint(hi), 0x7632);
  return u + ((u ^ tag) & 0x10001u);
}
__device__ __forceinline__ uint32_t xo2(uint32_t a, uint32_t b, uint32_t t) { uint32_t r; asm("lop3.b32 %0, %1, %2, %3, 0x7e;" : "=r"(r) : "r"(a), "r"(b), "r"(t)); return r; }
__device__ __forceinline__ uint32_t or3(uint32_t a, uint32_t b, uint32_t c) { uint32_t r; asm("lop3.b32 %0, %1, %2, %3, 0xfe;" : "=r"(r) : "r"(a), "r"(b), "r"(c)); return r; }
__device__ __forceinline__ void stmatrix4(uint32_t a, uint32_t r0, uint32_t r1, uint32_t r2, uint32_t r3) {
  asm volatile("stmatrix.sync.aligned.m8n8.x4.shared.b16 [%0], {%1,%2,%3,%4};" :: "r"(a), "r"(r0), "r"(r1), "r"(r2), "r"(r3) : "memory");
}
__device__ __forceinline__ void stmatrix4_t(uint32_t a, uint32_t r0, uint32_t r1, uint32_t r2, uint32_t r3) {
  asm volatile("stmatrix.sync.aligned.m8n8.x4.trans.shared.b16 [%0], {%1,%2,%3,%4};" :: "r"(a), "r"(r0), "r"(r1), "r"(r2), "r"(r3) : "memory");
}
__device__ __forceinline__ void ldmatrix4_t(uint32_t* r, uint32_t a) {
  asm volatile("ldmatrix.sync.aligned.m8n8.x4.trans.shared.b16 {%0,%1,%2,%3}, [%4];" : "=r"(r[0]), "=r"(r[1]), "=r"(r[2]), "=r"(r[3]) : "r"(a) : "memory");
}
__device__ __forceinline__ void ldmatrix4(uint32_t* r, uint32_t a) {
  asm volatile("ldmatrix.sync.aligned.m8n8.x4.shared.b16 {%0,%1,%2,%3}, [%4];" : "=r"(r[0]), "=r"(r[1]), "=r"(r[2]), "=r"(r[3]) : "r"(a) : "memory");
}
__device__ __forceinline__ void hmma16(float* c, const uint32_t* a, uint32_t b0, uint32_t b1) {
  asm volatile("mma.sync.aligned.m16n8k16.row.col.f32.bf16.bf16.f32 {%0,%1,%2,%3}, {%4,%5,%6,%7}, {%8,%9}, {%0,%1,%2,%3};"
               : "+f"(c[0]), "+f"(c[1]), "+f"(c[2]), "+f"(c[3]) : "r"(a[0]), "r"(a[1]), "r"(a[2]), "r"(a[3]), "r"(b0), "r"(b1));
}
__device__ __forceinline__ void hmma8(float* c, uint32_t a0, uint32_t a1, uint32_t b0) {
  asm volatile("mma.sync.aligned.m16n8k8.row.col.f32.bf16.bf16.f32 {%0,%1,%2,%3}, {%4,%5}, {%6}, {%0,%1,%2,%3};"
               : "+f"(c[0]), "+f"(c[1]), "+f"(c[2]), "+f"(c[3]) : "r"(a0), "r"(a1), "r"(b0));
}
__device__ __forceinline__ uint4 lds128(uint32_t a) { uint4 v; asm volatile("ld.shared.v4.u32 {%0,%1,%2,%3}, [%4];" : "=r"(v.x), "=r"(v.y), "=r"(v.z), "=r"(v.w) : "r"(a) : "memory"); return v; }
__device__ __forceinline__ void sts128(uint32_t a, uint4 v) { asm volatile("st.shared.v4.u32 [%0], {%1,%2,%3,%4};" :: "r"(a), "r"(v.x), "r"(v.y), "r"(v.z), "r"(v.w) : "memory"); }
__device__ __forceinline__ void sts128f(uint32_t a, float x, float y, float z, float w) { asm volatile("st.shared.v4.f32 [%0], {%1,%2,%3,%4};" :: "r"(a), "f"(x), "f"(y), "f"(z), "f"(w) : "memory"); }
__device__ __forceinline__ void sts64f(uint32_t a, float x, float y) { asm volatile("st.shared.v2.f32 [%0], {%1,%2};" :: "r"(a), "f"(x), "f"(y) : "memory"); }
__device__ __forceinline__ uint32_t lds32(uint32_t a) { uint32_t v; asm volatile("ld.shared.u32 %0, [%1];" : "=r"(v) : "r"(a) : "memory"); return v; }
__device__ __forceinline__ void sts32(uint32_t a, uint32_t v) { asm volatile("st.shared.u32 [%0], %1;" :: "r"(a), "r"(v) : "memory"); }

constexpr uint32_t SBASE = 1024;
__host__ __device__ constexpr uint64_t mkdesc(uint32_t off, uint32_t lbo, uint32_t sbo, uint32_t swz) {
  return (uint64_t)(((SBASE + off) & 0x3FFFF) >> 4) | ((uint64_t)(lbo >> 4) << 16) | ((uint64_t)(sbo >> 4) << 32) | ((uint64_t)swz << 62);
}
__device__ __forceinline__ void wg_fence() { asm volatile("wgmma.fence.sync.aligned;" ::: "memory"); }
__device__ __forceinline__ void wg_commit() { asm volatile("wgmma.commit_group.sync.aligned;" ::: "memory"); }
template <int N> __device__ __forceinline__ void wg_wait() { asm volatile("wgmma.wait_group.sync.aligned %0;" :: "n"(N) : "memory"); }

template <int N> __device__ __forceinline__ void reg_fence(float (&d)[N], int n = N) {
#pragma unroll
  for (int i = 0; i < N; i++) if (i < n) asm volatile("" : "+f"(d[i]) :: "memory");
}
#define F4(b) "+f"(d[b]), "+f"(d[b + 1]), "+f"(d[b + 2]), "+f"(d[b + 3])
#define F8(b) F4(b), F4(b + 4)
#define F16(b) F8(b), F8(b + 8)
#define G4(b) "=f"(d[b]), "=f"(d[b + 1]), "=f"(d[b + 2]), "=f"(d[b + 3])
#define G8(b) G4(b), G4(b + 4)
#define G16(b) G8(b), G8(b + 8)
#define RS_IN "r"(a[0]), "r"(a[1]), "r"(a[2]), "r"(a[3]), "l"(db), "n"(SD), "n"(TB)
#define SS_IN "l"(da), "l"(db), "n"(SD), "n"(TA), "n"(TB)
#define WG_OP(str, out0, out1, in) do { if (SD || KEEP) asm volatile(str : out1 : in); else asm volatile(str : out0 : in); } while (0)
#define O12(X) X##8(0), X##4(8)
#define O20(X) X##16(0), X##4(16)
#define O32(X) X##16(0), X##16(16)
template <int SD, int TB, int KEEP = 0> __device__ __forceinline__ void wgmma_rs24(float* d, const uint32_t* a, uint64_t db) {
  WG_OP("wgmma.mma_async.sync.aligned.m64n24k16.f32.bf16.bf16 {%0,%1,%2,%3,%4,%5,%6,%7,%8,%9,%10,%11}, {%12,%13,%14,%15}, %16, %17, 1, 1, %18;", O12(G), O12(F), RS_IN);
}
template <int SD, int TB, int KEEP = 0> __device__ __forceinline__ void wgmma_rs32(float* d, const uint32_t* a, uint64_t db) {
  WG_OP("wgmma.mma_async.sync.aligned.m64n32k16.f32.bf16.bf16 {%0,%1,%2,%3,%4,%5,%6,%7,%8,%9,%10,%11,%12,%13,%14,%15}, {%16,%17,%18,%19}, %20, %21, 1, 1, %22;", G16(0), F16(0), RS_IN);
}
template <int SD, int TB, int KEEP = 0> __device__ __forceinline__ void wgmma_rs40(float* d, const uint32_t* a, uint64_t db) {
  WG_OP("wgmma.mma_async.sync.aligned.m64n40k16.f32.bf16.bf16 {%0,%1,%2,%3,%4,%5,%6,%7,%8,%9,%10,%11,%12,%13,%14,%15,"
        "%16,%17,%18,%19}, {%20,%21,%22,%23}, %24, %25, 1, 1, %26;", O20(G), O20(F), RS_IN);
}
template <int SD, int TB, int KEEP = 0> __device__ __forceinline__ void wgmma_rs64(float* d, const uint32_t* a, uint64_t db) {
  WG_OP("wgmma.mma_async.sync.aligned.m64n64k16.f32.bf16.bf16 {%0,%1,%2,%3,%4,%5,%6,%7,%8,%9,%10,%11,%12,%13,%14,%15,"
        "%16,%17,%18,%19,%20,%21,%22,%23,%24,%25,%26,%27,%28,%29,%30,%31}, {%32,%33,%34,%35}, %36, %37, 1, 1, %38;", O32(G), O32(F), RS_IN);
}
template <int SD, int TA, int TB, int KEEP = 0> __device__ __forceinline__ void wgmma_ss24(float* d, uint64_t da, uint64_t db) {
  WG_OP("wgmma.mma_async.sync.aligned.m64n24k16.f32.bf16.bf16 {%0,%1,%2,%3,%4,%5,%6,%7,%8,%9,%10,%11}, %12, %13, %14, 1, 1, %15, %16;", O12(G), O12(F), SS_IN);
}
template <int SD, int TA, int TB, int KEEP = 0> __device__ __forceinline__ void wgmma_ss8(float* d, uint64_t da, uint64_t db) {
  WG_OP("wgmma.mma_async.sync.aligned.m64n8k16.f32.bf16.bf16 {%0,%1,%2,%3}, %4, %5, %6, 1, 1, %7, %8;", G4(0), F4(0), SS_IN);
}
__device__ __forceinline__ void bar_arrive(int id, int n) { asm volatile("bar.arrive %0, %1;" :: "r"(id), "r"(n) : "memory"); }
__device__ __forceinline__ uint32_t vis_bits(int pos, int t) {
  uint32_t m = 0;
#pragma unroll
  for (int i = 0; i < 8; i++) m |= (8 * (i / 2 + 1) + 2 * t + (i & 1) <= pos) ? 1u << i : 0u;
  return m;
}

__device__ __forceinline__ unsigned long long wait_words(const unsigned long long* p, uint32_t E) {
  int guard = 0; unsigned long long m;
  while (m = ld_rlxu64(p), !__all_sync(~0u, rfresh(m, E))) { __nanosleep(20); if (++guard > (1 << 22)) TRAP(); }
  fence_acq();
  return m;
}
__device__ __forceinline__ int route_step(int s, uint32_t E, int lane, unsigned long long& run) {
  const unsigned long long m = warp_max<2>(wait_words(f_h2[s][lane & 3], E));
  if (s == 0 || m > run) { run = m; return rtok(m) & 31; }
  return -1;
}

struct Params {
  const bf16 *x, *mem0, *wq, *wk, *wv, *wo, *wr, *wg, *wu, *wd;
  bf16* out;
  uint32_t zero2;
  unsigned long long zero;
};

constexpr uint32_t WSTG_STRIDE = 272;
__device__ __forceinline__ void stage_weights(uint32_t stg, const bf16* src, int ld, int tid, int nthr) {
  for (int i = tid; i < 512 * 16; i += nthr) {
    int k = i >> 4, c = i & 15;
    cp_async16(stg + k * WSTG_STRIDE + c * 16, src + (size_t)k * ld + c * 8);
  }
}
__device__ __forceinline__ void load_frags(uint32_t (*W)[4], uint32_t stg, int wg, int w, int lane) {
  uint32_t a = stg + ((lane >> 4) * 8 + (lane & 7)) * WSTG_STRIDE + (64 * wg + 16 * w + ((lane >> 3) & 1) * 8) * 2;
#pragma unroll
  for (int ks = 0; ks < 32; ks++) ldmatrix4_t(W[ks], a + ks * 16 * WSTG_STRIDE);
}

constexpr uint32_t M_H = 0;
constexpr uint32_t M_MEM = 65536;
constexpr uint32_t M_Q = M_MEM + 24576;
constexpr uint32_t M_K = M_Q + 12288;
constexpr uint32_t M_V = M_K + 12288;
constexpr uint32_t M_OM = M_V + 12288;
constexpr uint32_t M_OST = M_OM + 6144;
constexpr uint32_t M_TST = M_OST + 8192;
constexpr uint32_t M_WO = M_TST + 16384;
constexpr uint32_t M_M0 = M_WO + 49152;
constexpr uint32_t M_PT = M_M0 + 2048;
constexpr uint32_t M_BAR = M_PT + 12288;
constexpr uint32_t M_TOTAL = M_BAR + 384;
static_assert(M_TOTAL <= 232448, "main smem");
static_assert(M_WO >= 512 * WSTG_STRIDE, "staging overlaps Wo");
enum { B_LAND = 0  , B_QK = 3, B_V, B_TOK, B_OM, B_HA, B_HB, B_HAE, B_HBE, B_OST, B_OFREE, B_SYNC,
       B_STG, B_STG1, B_SS, B_TFREE, B_KFREE, B_VFREE, B_FIX  , B_NUM = B_FIX + 8 };
static_assert(B_NUM * 8 <= 256, "barriers");
constexpr uint32_t M_CAND = M_BAR + 256;
constexpr uint32_t M_BASE = M_BAR + 272;
constexpr uint32_t M_ZERO = M_BAR + 280;
constexpr uint32_t M_BAS2 = M_BAR + 328;
constexpr uint32_t M_NEAR = M_BAR + 288;
enum { N_GO1 = 2, N_GO2, N_GO3, N_GO4, N_AG, N_W };

#define GSTAMP(slot, i)
#define TSTAMP(slot, i, k)
#define STAMP(i)
#define ASTAMP(i)
#define WSTAMP(i)
#define CSTAMP(i, v)
#define PIN(x) asm volatile("" : "+r"(x))
#define SCHED(k) asm volatile("{\n.reg .pred p;\nsetp.ne.u32 p, %0, 0;\n@p trap;\n}" :: "r"(zz & (1u << (k))) : "memory")
#define HOLD(k, v) asm volatile("{\n.reg .pred p;\nsetp.ne.u32 p, %0, 0;\n@p st.shared.u32 [%0], %1;\n}" :: "r"(zz & (1u << (k))), "r"(v) : "memory")
#define DRAIN(a) (lds32((a) + zz) & zz)
#define BAR(i) (sb + M_BAR + 8 * (i))

__device__ __forceinline__ int probe(const uint8_t* p, int n) {
  int best = 1 << 30; uint32_t v = 0;
#pragma unroll 1
  for (int r = 0; r < n; r++) {
    uint32_t t0 = clk();
    asm volatile("atom.relaxed.gpu.global.or.b32 %0, [%1], %2;" : "=r"(v) : "l"(p + 3968), "r"(v & 0u) : "memory");
    if (v == 0x7fffffffu) t0++;
    best = min(best, (int)(clk() - t0));
  }
  return best;
}
__device__ __forceinline__ void load_mem0(uint4* u, int k0, int lane, const bf16* mem0) {
#pragma unroll
  for (int i = 0; i < 2; i++) {
    const unsigned short* m = (const unsigned short*)mem0 + k0 + lane + 32 * i;
    u[i] = make_uint4(m[0] | (uint32_t)m[512] << 16, m[1024] | (uint32_t)m[1536] << 16, m[2048] | (uint32_t)m[2560] << 16, m[3072] | (uint32_t)m[3584] << 16);
  }
}

__device__ __forceinline__ void paced_h(uint32_t dst, const uint8_t* src, uint32_t o0, uint32_t o1, uint32_t piece, uint32_t bar, int gap) {
  uint32_t t = clk32();
#pragma unroll 1
  for (uint32_t o = o0; o < o1; o += piece) {
    e_mc(dst + o, src + o, piece, bar, 7);
    spin_until(t += gap);
  }
}

__device__ __forceinline__ void paced_st(uint8_t* dst, uint32_t src, int gap) {
  uint32_t t = clk32();
#pragma unroll 1
  for (uint32_t o = 0; o < 8192; o += SPC_) {
    e_s2g(dst + o, src + o, SPC_);
    if (o + SPC_ < 8192) spin_until(t += gap);
  }
}
__device__ __forceinline__ int block_of(int head, int c) { return REMAP_ ? (c == 2 ? head : 32 + 2 * head + c) : head * 3 + c; }

__device__ __forceinline__ void weight_role(const Params& p, const uint32_t sb, const int warp, const int cta, const int C, const uint32_t E,
                                            const uint8_t* const memg) {
  const int tid = fresh_tid(), lane = tid & 31;
  const int wg = warp >> 2, w = warp & 3;
  uint32_t W[32][4];
  cp_async_wait();
  bar_sync(1, 256);
  load_frags(W, sb, wg, w, lane);
  bar_sync(1, 256);
  if (tid < 128) sts128(sb + M_V + 5 * 2048 + tid * 16, make_uint4(0, 0, 0, 0));
  fence_async_smem();
  cluster_sync();
  if (tid == 0 && cta == 0) GSTAMP(0, 1);
  if (tid == 0) TSTAMP(13, cta, 0);

  const uint32_t rba = mapa(sb, C == 2 ? 0 : 2), rbc = mapa(sb, C == 1 ? 0 : 1);
  const uint32_t MYBAR = M_BAR + 8 * (C < 2 ? B_QK : B_V);
  uint32_t qoff = M_Q + C * 12288 + warp * 256 + lane * 4;
  uint32_t toff = sb + warp * 256 + (lane >> 4) * 2048 + (lane & 15) * 16;
  uint32_t rbar = mapa(sb + M_BAR, min(lane, 2));
  uint32_t sv = sb + M_MEM + lane * 32 + ((lane >> 2) & 3) * 8;
  PIN(qoff); PIN(toff); PIN(rbar); PIN(sv);
  const uint32_t gen0 = (E - 1) * (uint32_t)(NSTEP - 1);
  uint32_t fix = 0;
  const bool sig = w == 0 && lane < 3;
  const int blk = block_of(cta / 3, C);
  const int pk = (blk < 24 ? PAUSE_ : PAUS2_) + (wg ? -PST2_ : PST2_);
  int cand = -1;
  float d[16];
#pragma unroll
  for (int i = 0; i < 16; i++) d[i] = 0.f;
  uint32_t tp[8];
#pragma unroll 1
  for (int T = -1; T < NSTEP; T++) {
    const uint32_t ph = T & 1;
    const uint64_t Z = p.zero << ph;
    const uint32_t zz = p.zero2;
    if (T >= 0) {
      WSTAMP(0);
      const uint64_t db = mkdesc(M_MEM, 128, 256, 0) + Z;
      stmatrix4(toff + M_TST + 8192, tp[0], tp[1], tp[2], tp[3]); stmatrix4(toff + M_TST + 12288, tp[4], tp[5], tp[6], tp[7]);
      if (sig) mbar_arrive_remote(rbar + 8 * B_HBE);
      mbar_wait(BAR(B_LAND), ph);
      WSTAMP(1);
      const uint32_t gt = gentag(gen0 + T);
      auto old = [&](uint32_t a) { return lds32(a) ^ gt; };
      uint32_t bad = 0;
      bool redo = false, ready = false;
      wg_fence();
      wgmma_rs24<0, 1, KP1_>(d, W[0], db);
#pragma unroll
      for (int ks = 1; ks < 32; ks++) {
        if (ks == 2) bad |= old(sv + min(warp, 5) * 1024);
        if (ks == 10 || ks == 22) bad |= xo2(lds32(sv + (ks == 10 ? 6 : 15) * 1024 + warp * 1024), lds32(sv + (ks == 10 ? 14 : 23) * 1024), gt);
        if (ks == 6) {
          const uint32_t z5 = DRAIN(toff + M_TST);
          __syncwarp();
          if (lane == 0) mbar_arrive(BAR(B_STG) + z5);
        }
        if (ks == 27) ready = mbar_test(BAR(C < 2 ? B_KFREE : B_VFREE), ph ^ 1) & mbar_test(BAR(B_HA), ph);
        if (ks == RED_) redo = bar_or(N_W, 256, T > 0 && (bad & 0x10001u));
        if (ks == 8 || ks == 20) { mbar_wait(BAR(B_LAND + (ks + 4) / 12), ph); WSTAMP(6 + (ks + 4) / 12); wg_fence(); }
        wgmma_rs24<1, 1>(d, W[ks], db + ks * 48);
      }
      wg_commit();
      uint32_t a0 = rba + qoff, a1 = a0 + 128, a2 = rbc + qoff, a3 = a2 + 128, ba = rba + MYBAR, bc = rbc + MYBAR;
      PIN(a0); PIN(a1); PIN(a2); PIN(a3); PIN(ba); PIN(bc);
      if (!ready) {
        mbar_wait(BAR(C < 2 ? B_KFREE : B_VFREE), ph ^ 1);
        if (T < NSTEP - 1) mbar_wait(BAR(B_HA), ph);
      }
      wg_wait<0>(); reg_fence(d);
      if (__builtin_expect(redo, 0)) {
        auto stale = [&]() { return __any_sync(~0u, (old(sv + warp * 3072) | old(sv + warp * 3072 + 1024) | old(sv + warp * 3072 + 2048)) & 0x10001u); };
        auto fetch = [&](int r) {
          e_expect(BAR(B_FIX + warp), 3072);
          e_g2s(sb + M_MEM + warp * 3072, memg + warp * 8192 + ((uni(lds32(sb + M_NEAR + warp * 4)) ^ r) & 1) * 4096, 3072, BAR(B_FIX + warp));
        };
        bool late = stale();
        if (late) fetch(0);
        constexpr uint64_t dc = mkdesc(M_MEM, 128, 256, 0);
#pragma unroll
        for (int ks = 0; ks < 32; ks++) {
          if (ks % 12 == 0) {
            if (ks) { wg_commit(); wg_wait<0>(); reg_fence(d); }
            if (warp / 3 == ks / 12) {
              for (int guard = 0; late; guard++) {
                mbar_wait(BAR(B_FIX + warp), fix); fix ^= 1;
                late = stale();
                if (late) fetch(ALT_ ? guard + 1 : 0);
                if (guard > (1 << 20)) TRAP();
              }
            }
            bar_sync(N_W, 256);
            wg_fence();
          }
          if (ks == 0) wgmma_rs24<0, 1, 1>(d, W[0], dc); else wgmma_rs24<1, 1>(d, W[ks], dc + ks * 48);
        }
        wg_commit();
        wg_wait<0>(); reg_fence(d);
      }
      WSTAMP(2);
      if (T == 0 && tid == 0) TSTAMP(13, cta, 2);
      uint32_t lo[3], hi[3];
#pragma unroll
      for (int j = 0; j < 3; j++) { lo[j] = pack2(d[4 * j], d[4 * j + 1]); hi[j] = pack2(d[4 * j + 2], d[4 * j + 3]); }
      if (__builtin_expect(T == 0, 0)) { sts32(sb + M_M0 + tid * 8, lo[0]); sts32(sb + M_M0 + tid * 8 + 4, hi[0]); }
      if (__builtin_expect(cand >= 0, 0)) {
        if (T == LAG) { lo[1] = lds32(sb + M_M0 + tid * 8); hi[1] = lds32(sb + M_M0 + tid * 8 + 4); }
        if (C < 2) { st_async32(a0 + 5 * 2048, lo[2], ba); st_async32(a1 + 5 * 2048, hi[2], ba); }
        else { sts32(sb + qoff + 5 * 2048, lo[2]); sts32(sb + qoff + 5 * 2048 + 128, hi[2]); }
        lo[2] = lo[1]; hi[2] = hi[1];
      }
      uint32_t z5;
      if (C == 0) {
        sts32(sb + qoff, lo[0]); sts32(sb + qoff + 128, hi[0]); z5 = DRAIN(sb + qoff);
        st_async32(a0, lo[2], ba); st_async32(a1, hi[2], ba); st_async32(a2, lo[1], bc); st_async32(a3, hi[1], bc);
      } else if (C == 1) {
        sts32(sb + qoff, lo[1]); sts32(sb + qoff + 128, hi[1]); z5 = DRAIN(sb + qoff);
        st_async32(a0, lo[2], ba); st_async32(a1, hi[2], ba); st_async32(a2, lo[0], bc); st_async32(a3, hi[0], bc);
      } else {
        sts32(sb + qoff, lo[2]); sts32(sb + qoff + 128, hi[2]); z5 = DRAIN(sb + qoff);
        st_async32(a0, lo[0], ba); st_async32(a1, hi[0], ba); st_async32(a2, lo[1], bc); st_async32(a3, hi[1], bc);
      }
      __syncwarp();
      if (lane == 0) { mbar_arrive(sb + MYBAR + z5); if (w == 3) mbar_arrive(BAR(B_SS)); }
      if (T == NSTEP - 1) break;
    }
    {
      const uint64_t dh = mkdesc(M_H, 16, 1024, 1) + Z;
      static_assert(E2 == 0 && E3 > 0 && PAUSE_ > 0, "config");
      if (T + 2 < NSEG) {
        if (T < 0) mbar_wait(BAR(B_HA), ph);
        WSTAMP(3);
        wg_fence();
        wgmma_rs32<0, 0, 1>(d, W[0], dh);
#pragma unroll
        for (int ks = 1; ks < EA; ks++) {
          if (ks == E1) { wg_commit(); if (T >= 0) bar_sync(N_GO2, 384); wg_fence(); }
          wgmma_rs32<1, 0>(d, W[ks], dh + (ks >> 2) * 256 + (ks & 3) * 2);
        }
        wg_commit();
        mbar_wait(BAR(B_HB), ph);
        wg_wait<0>();
        if (sig) mbar_arrive_remote(rbar + 8 * B_HAE);
        WSTAMP(4);
        if (T >= 0) bar_sync(N_GO3, 384);
        if (wg == 1) bar_sync(N_W, 256);
        wg_fence();
#pragma unroll
        for (int ks = EA; ks < 32; ks++) wgmma_rs32<1, 0>(d, W[ks], dh + (ks >> 2) * 256 + (ks & 3) * 2);
        wg_commit();
        if (wg == 0) bar_arrive(N_W, 256);
        mbar_wait(BAR(B_TFREE), ph ^ 1);
        wg_wait<0>(); reg_fence(d);
      } else {
        bar_sync(N_GO2, 384);
        mbar_wait(BAR(B_HB), ph);
        if (sig) mbar_arrive_remote(rbar + 8 * B_HAE);
        bar_sync(N_GO3, 384);
        mbar_wait(BAR(B_TFREE), ph ^ 1);
      }
#pragma unroll
      for (int i = 0; i < 8; i++) { tp[i] = pack2(d[2 * i], d[2 * i + 1]); PIN(tp[i]); }
      const uint32_t t1 = toff + (C == 0 && !ph ? M_Q + 2048 : M_TST);
      auto staged = [&]() {
        const uint32_t z5 = DRAIN(t1);
        __syncwarp();
        if (lane == 0) mbar_arrive(BAR(B_STG1) + z5);
      };
      if (T < 0 || (T + 2 >= LAG && T + 2 < NSTEP)) {
        wg_fence();
        wgmma_rs32<0, 0, 1>(d, W[0], dh + 2048);
        stmatrix4(t1, tp[0], tp[1], tp[2], tp[3]); stmatrix4(t1 + 4096, tp[4], tp[5], tp[6], tp[7]);
#pragma unroll
        for (int ks = 1; ks < 32; ks++) {
          if (ks == 5) staged();
          if (ks == PAUSE_ - PST2_ || ks == PAUSE_ + PST2_ || ks == PAUS2_ - PST2_ || ks == PAUS2_ + PST2_) {
            wg_commit();
            if (T >= 0 && ks == pk) bar_sync(N_GO4, 384);
            wg_fence();
          }
          wgmma_rs32<1, 0>(d, W[ks], dh + 2048 + (ks >> 2) * 256 + (ks & 3) * 2);
        }
        wg_commit();
      } else {
        stmatrix4(t1, tp[0], tp[1], tp[2], tp[3]); stmatrix4(t1 + 4096, tp[4], tp[5], tp[6], tp[7]);
        staged();
        bar_sync(N_GO4, 384);
      }
      if (T >= 0) cand = __shfl_sync(~0u, (int)lds32(sb + M_CAND + ((T + 1) & 3) * 4), 0);
      wg_wait<0>(); reg_fence(d);
      if (T >= 0) WSTAMP(6);
      if (T < 0 && tid == 0) TSTAMP(13, cta, 1);
#pragma unroll
      for (int i = 0; i < 8; i++) tp[i] = pack2(d[2 * i], d[2 * i + 1]);
    }
  }
  cluster_sync();
  if (tid == 0 && cta == 0) GSTAMP(0, 5);
}

__device__ __forceinline__ void attn_role(const Params& p, const uint32_t sb, const int w, const int cta, const int head, const int C, const uint32_t E,
                                          uint8_t* const part, uint8_t* const memg) {
  const int tid = fresh_tid(), lane = tid & 31;
  const int g = lane >> 2, t = lane & 3, blk = block_of(head, C);
  uint32_t tag = ((E - 1) * (uint32_t)(NSTEP - 1)) & 1;
  uint4 m0[2][2];
  load_mem0(m0[0], w * 64, lane, p.mem0); load_mem0(m0[1], w * 64 + 256, lane, p.mem0);
  cluster_sync();
#pragma unroll
  for (int k = 0; k < 2; k++) {
#pragma unroll 1
    for (int i = 0; i < 6; i++) sts128(sb + M_MEM + (w + 4 * k) * 3072 + lane * 16 + i * 512, make_uint4(0, 0, 0, 0));
    __syncwarp();
#pragma unroll
    for (int i = 0; i < 2; i++) sts128(sb + M_MEM + ((w + 4 * k) * 4 + (lane >> 4) + 2 * i) * 768 + (lane & 15) * 16, m0[k][i]);
  }
  fence_async_smem();
  bar_sync(N_AG, 128);
  if (w == 3 && lane < 3) mbar_arrive(BAR(B_LAND + lane));
  if (lane == 0) {
    if (w == 0) TSTAMP(15, cta, 0);
    sts32(sb + M_PT + w * 4, probe(part + blk * 16384 + w * 4096, NPROBE_ / 2));
    if (w == 0) TSTAMP(15, cta, 1);
  }
  bar_sync(N_AG, 128);
  const uint32_t inear = lds32(sb + M_PT + (w >> 1) * 8 + 4) < lds32(sb + M_PT + (w >> 1) * 8);
  if (lane == 0 && !(w & 1)) st_rlx(&f_choice[blk][w >> 1], (E << 1) | inear);
  if (w == 0) TSTAMP(15, cta, 2);
  uint32_t nb;
  {
    const int i = min(lane >> 1, C < 2 ? 8 : 5);
    const int r = ((i / 3 * 3 + C) * 4 + w) * 3 + i % 3;
    int guard = 0; uint32_t cw;
    while (__any_sync(~0u, ((cw = ld_rlx(&f_choice[r][lane & 1])) >> 1) != (E & 0x7FFFFFFFu))) { if (++guard > (1 << 22)) TRAP(); }
    nb = __ballot_sync(~0u, cw & 1) >> (lane >> 4);
    if (w == 0) TSTAMP(15, cta, 3);
  }
  bar_sync(N_AG, 128);
  const uint32_t pt0 = sb + M_PT + (tid & 127) * 16;
  {
    const uint32_t po = (C * 4 + w) * 49152 + (lane >> 4) * 8192 + head * 128 + (lane & 15) * 8;
    const uint8_t* in = part + (blk * 16384 + (w >> 1) * 8192 + inear * 4096 + (w & 1) * 64 + (lane >> 3) * 128 + (lane & 7) * 8);
    const uint8_t* outp = memg + ((blk / 12) * 8192 + (blk % 12) * 256 + w * 64 + (lane >> 4) * 4096 + (lane & 4) * 8 + (lane & 8) * 2 + (lane & 3) * 4);
#pragma unroll
    for (int i = 0; i < 12; i++) {
      const int j = i / 4 * 3 + (i & 3);
      const uint8_t* a = (i & 3) < 3 ? part + (po + i / 4 * 589824 + (i & 3) * 16384 + ((nb >> (2 * j)) & 1) * 4096) : i == 11 ? in : outp;
      asm volatile("st.shared.u64 [%0], %1;" :: "r"(pt0 + (i >> 1) * 2048 + (i & 1) * 8), "l"(a) : "memory");
    }
  }
  const int xd = __shfl_sync(~0u, XDLY_ + (blk < 24 ? 0 : blk < 60 ? X1_ : X2_), 0);
  const uint32_t rba = mapa(sb, C == 2 ? 0 : 2), rbc = mapa(sb, C == 1 ? 0 : 1);
  uint32_t vis = vis_bits(8 + 8 * w + g, t);
  uint32_t ln = lane;
#pragma unroll
  for (int i = 0; i < SALT_; i++) ln += lds32(sb + M_ZERO);
  PIN(vis); PIN(ln);
  if (tid == 256 && C == 0) st_rlx(&f_loaded[head], E);
  uint32_t fa[8][4];
#pragma unroll
  for (int ks = 0; ks < 8; ks++) ldmatrix4_t(fa[ks], sb + M_WO + 32768 + w * 256 + (lane >> 4) * 1024 + (lane & 15) * 16 + ks * 2048);
  if (w == 0) TSTAMP(14, cta, 0);
#pragma unroll 1
  for (int T = 0; T < NSTEP; T++) {
    const uint32_t ph = T & 1;
    const uint32_t zz = uni(lds32(sb + M_ZERO));
    const bool more = T < NSTEP - 1;
    const float sc = 0.08838834764831845f * 1.4426950408889634f;
    tag ^= 1;
    float s[20];
    const uint8_t* in; int cnext = -1; uint32_t tx; bool synced;
    float x[10], tm, ts;
    uint32_t pt[5];
    auto tok_max = [&]() {
      PIN(vis);
      x[0] = s[2]; x[1] = s[3];
#pragma unroll
      for (int i = 0; i < 8; i++) x[2 + i] = (vis >> i & 1) ? s[4 * (i / 2 + 1) + 2 + (i & 1)] : -INFINITY;
      tm = fmaxf(fmaxf(fmaxf(fmaxf(x[0], x[1]), fmaxf(x[2], x[3])), fmaxf(fmaxf(x[4], x[5]), fmaxf(x[6], x[7]))), fmaxf(x[8], x[9]));
      HOLD(7, __float_as_uint(tm));
    };
    auto tok_exp1 = [&]() {
      tm = fmaxf(tm, __shfl_xor_sync(~0u, tm, 1));
      tm = fmaxf(tm, __shfl_xor_sync(~0u, tm, 2));
      const float b = -tm * sc;
#pragma unroll
      for (int i = 0; i < 10; i++) x[i] = fmaf(x[i], sc, b);
      HOLD(10, __float_as_uint(x[9]));
    };
    auto tok_exp2 = [&]() {
#pragma unroll
      for (int i = 0; i < 10; i++) x[i] = ex2(x[i]);
      ts = (((x[0] + x[1]) + (x[2] + x[3])) + ((x[4] + x[5]) + (x[6] + x[7]))) + (x[8] + x[9]);
#pragma unroll
      for (int k = 0; k < 5; k++) pt[k] = pack2(x[2 * k], x[2 * k + 1]);
      HOLD(8, __float_as_uint(ts));
    };
    {
      uint32_t q[8][4];
      auto load_q = [&](uint32_t a, int h) {
#pragma unroll
        for (int k2 = 0; k2 < 4; k2++) {
          uint32_t r[4];
          ldmatrix4_t(r, a + k2 * 512);
          q[2 * k2][h] = r[0]; q[2 * k2][h + 2] = r[1]; q[2 * k2 + 1][h] = r[2]; q[2 * k2 + 1][h + 2] = r[3];
        }
      };
      PIN(ln);
      const uint32_t qa = sb + M_Q + ln * 16, qt = qa + w * 2048 + (C == 0 && ph ? M_TST - M_Q : 2048);
      const int cand = C == 2 ? (int)uni(lds32(sb + M_CAND + (T & 3) * 4)) : -1;
      mbar_wait(BAR(B_TOK), ph);
      load_q(qt, 1);
      mbar_wait(BAR(B_QK), ph);
      ASTAMP(0);
      if (T == 0 && w == 0) TSTAMP(13, cta, 3);
      if (__builtin_expect(cand >= 0, 0)) {
        mbar_wait(BAR(B_V), ph);
        PIN(ln);
        const int e = w * 32 + ln;
#pragma unroll
        for (int i = 0; i < 3; i++) {
          const uint32_t v = lds32(sb + M_Q + i * 12288 + 5 * 2048 + e * 16 + 4);
          asm volatile("st.shared.u16 [%0], %1;" :: "r"(sb + M_Q + i * 12288 + (1 + (cand >> 3)) * 2048 + e * 16 + (cand & 7) * 2), "h"((unsigned short)v) : "memory");
        }
        fence_async_smem();
        bar_sync(N_AG, 128);
        load_q(qt, 1);
      }
      load_q(qa, 0);
      if (!(NOF_ & 1)) fence_async_smem();
      constexpr uint64_t dk = mkdesc(M_K, 128, 2048, 0);
      wg_fence();
      wgmma_rs40<0, 1>(s, q[0], dk);
#pragma unroll
      for (int ks = 1; ks < 8; ks++) wgmma_rs40<1, 1>(s, q[ks], dk + ks * 16);
      wg_commit();
    }
    if (more) {
      uint32_t v[5][4];
      PIN(ln);
      const uint32_t va = sb + M_V + w * 512 + ((ln >> 3) & 1) * 128 + (ln >> 4) * 2048 + (ln & 7) * 16;
      const uint32_t ooff = M_OM + w * 1536 + C * 256 + ln * 4;
      mbar_wait(BAR(B_V), ph);
      wg_wait<0>(); reg_fence(s);
      if (ln < 3) mbar_arrive_remote(mapa(BAR(B_KFREE), ln));
      ldmatrix4(v[0], va); ldmatrix4(v[1], va + 256); ldmatrix4(v[2], va + 4096); ldmatrix4(v[3], va + 4096 + 256);
      ldmatrix4(v[4], sb + M_V + 8192 + w * 512 + ln * 16);
      ASTAMP(1);
      float m = fmaxf(fmaxf(fmaxf(fmaxf(s[0], s[1]), fmaxf(s[4], s[5])), fmaxf(fmaxf(s[8], s[9]), fmaxf(s[12], s[13]))), fmaxf(s[16], s[17]));
      m = fmaxf(m, __shfl_xor_sync(~0u, m, 1));
      m = fmaxf(m, __shfl_xor_sync(~0u, m, 2));
      const float b = -m * sc;
      uint32_t pm[5];
#pragma unroll
      for (int j = 0; j < 5; j++) pm[j] = pack2(ex2(fmaf(s[4 * j], sc, b)), ex2(fmaf(s[4 * j + 1], sc, b)));
      float o0[4] = {0.f, 0.f, 0.f, 0.f}, o1[4] = {0.f, 0.f, 0.f, 0.f}, l[4] = {0.f, 0.f, 0.f, 0.f};
      const uint32_t one[4] = {0x3f803f80u, 0x3f803f80u, 0x3f803f80u, 0x3f803f80u};
      hmma16(l, one, pm[0], pm[1]); hmma16(o0, v[0], pm[0], pm[1]); hmma16(o1, v[1], pm[0], pm[1]);
      hmma16(l, one, pm[2], pm[3]); hmma16(o0, v[2], pm[2], pm[3]); hmma16(o1, v[3], pm[2], pm[3]);
      hmma8(l, one[0], one[1], pm[4]); hmma8(o0, v[4][0], v[4][1], pm[4]); hmma8(o1, v[4][2], v[4][3], pm[4]);
      const float r0 = rcp(l[0]), r1 = rcp(l[1]);
      const uint32_t u0 = pack2(o0[0] * r0, o0[1] * r1), u1 = pack2(o0[2] * r0, o0[3] * r1), u2 = pack2(o1[0] * r0, o1[1] * r1), u3 = pack2(o1[2] * r0, o1[3] * r1);
      constexpr uint32_t OB = M_BAR + 8 * B_OM;
      const uint32_t a0 = rba + ooff, a1 = rbc + ooff;
      st_async32(a0, u0, rba + OB); st_async32(a1, u0, rbc + OB);
      st_async32(a0 + 128, u1, rba + OB); st_async32(a1 + 128, u1, rbc + OB);
      st_async32(a0 + 768, u2, rba + OB); st_async32(a1 + 768, u2, rbc + OB);
      st_async32(a0 + 896, u3, rba + OB); st_async32(a1 + 896, u3, rbc + OB);
      bar_arrive(N_GO2, 384);
      sts32(sb + ooff, u0); sts32(sb + ooff + 128, u1); sts32(sb + ooff + 768, u2); sts32(sb + ooff + 896, u3);
      ASTAMP(2);
      uint32_t fb[8][4];
      const uint32_t wa = sb + M_WO + 16384 + w * 256 + (ln >> 4) * 1024 + (ln & 15) * 16 + zz;
      ldmatrix4_t(fb[0], wa);
      SCHED(3);
#pragma unroll
      for (int ks = 1; ks < 8; ks++) {
        ldmatrix4_t(fb[ks], wa + ks * 2048);
        if (ks == ARR_) { __syncwarp(); if (ln == 0) mbar_arrive(BAR(B_OM) + (fb[0][0] & zz)); }
      }
      if (blk % 3 == 2) cnext = (int)uni(lds32(sb + M_CAND + ((T + 1) & 3) * 4));
      {
        float d[12], e[12];
        constexpr uint64_t ob = mkdesc(M_OM, 128, 256, 0);
        uint8_t* q[3][3];
        auto addr = [&](int i) {
          asm volatile("ld.shared.v2.u64 {%0,%1}, [%2];" : "=l"(q[i][0]), "=l"(q[i][1]) : "r"(pt0 + i * 4096) : "memory");
          if (i < 2) asm volatile("ld.shared.u64 %0, [%1];" : "=l"(q[i][2]) : "r"(pt0 + i * 4096 + 2048) : "memory");
          else asm volatile("ld.shared.v2.u64 {%0,%1}, [%2];" : "=l"(q[i][2]), "=l"(in) : "r"(pt0 + i * 4096 + 2048) : "memory");
        };
        auto put = [&](const float* d, int i) {
          st_rlx64(q[i][0], (pack2(d[0], d[1]) & ~1u) | tag, pack2(d[2], d[3]));
          st_rlx64(q[i][1], (pack2(d[4], d[5]) & ~1u) | tag, pack2(d[6], d[7]));
          st_rlx64(q[i][2], (pack2(d[8], d[9]) & ~1u) | tag, pack2(d[10], d[11]));
        };
        addr(0); addr(1);
        SCHED(6);
        tok_max();
        ASTAMP(3);
        mbar_wait(BAR(B_OM), ph);
        if (!(NOF_ & 2)) fence_async_smem();
        ASTAMP(4);
        constexpr uint64_t w0 = mkdesc(M_WO, 1024, 128, 0);
        float (&f)[12] = d;
        wg_fence();
        wgmma_ss24<0, 1, 1>(d, w0, ob);
#pragma unroll
        for (int ks = 1; ks < 8; ks++) wgmma_ss24<1, 1, 1>(d, w0 + ks * 128, ob + ks * 48);
        wg_commit();
        wgmma_rs24<0, 1>(e, fb[0], ob);
#pragma unroll
        for (int ks = 1; ks < HAND_; ks++) wgmma_rs24<1, 1>(e, fb[ks], ob + ks * 48);
        wg_commit();
        wg_wait<1>(); reg_fence(d);
        put(d, 0);
        addr(2);
        SCHED(4);
        ASTAMP(5);
        wg_fence();
#pragma unroll
        for (int ks = HAND_; ks < 8; ks++) wgmma_rs24<1, 1>(e, fb[ks], ob + ks * 48);
        wg_commit();
        wgmma_rs24<0, 1, 1>(f, fa[0], ob);
#pragma unroll
        for (int ks = 1; ks < HAND_; ks++) wgmma_rs24<1, 1>(f, fa[ks], ob + ks * 48);
        wg_commit();
        wg_wait<1>(); reg_fence(e);
        put(e, 1);
        SCHED(5);
        if (C < 2) {
          wg_fence();
#pragma unroll
          for (int ks = HAND_; ks < 8; ks++) wgmma_rs24<1, 1>(f, fa[ks], ob + ks * 48);
          wg_commit();
        }
        synced = __all_sync(~0u, mbar_test(BAR(B_SYNC), ph));
        tx = uni(lds32(sb + M_BASE + ph * 4)) + xd;
        wg_wait<0>(); reg_fence(f);
        if (C < 2) put(f, 2);
        bar_arrive(N_GO3, 384);
        ASTAMP(6);
        if (T == 0 && w == 0) TSTAMP(14, cta, 1);
      }
    } else {
      mbar_wait(BAR(B_V), ph);
      wg_wait<0>(); reg_fence(s);
      tok_max();
    }
    uint2 v[8];
#pragma unroll
    for (int i = 0; i < 8; i++) v[i] = make_uint2(zz, zz);
    auto poll = [&](uint2* v) {
      v[0] = ld_rlx64<0>(in); v[1] = ld_rlx64<512>(in); v[2] = ld_rlx64<1024>(in); v[3] = ld_rlx64<1536>(in);
      v[4] = ld_rlx64<2048>(in); v[5] = ld_rlx64<2560>(in); v[6] = ld_rlx64<3072>(in); v[7] = ld_rlx64<3584>(in);
    };
    uint8_t* outp;
    asm volatile("ld.shared.u64 %0, [%1];" : "=l"(outp) : "r"(pt0 + 2048 + 8) : "memory");
    const uint32_t itag = gentag((E - 1) * (uint32_t)(NSTEP - 1) + T + 1);
    const bool sum = more && cnext < 0;
    if (more) {
      if (!synced) { mbar_wait(BAR(B_SYNC), ph); tx = uni(lds32(sb + M_BASE + ph * 4)) + xd; }
      ASTAMP(7);
      if (__builtin_expect(cnext >= 0, 0)) {
        const unsigned long long* hp = (const unsigned long long*)&g_hc[T + 1 - LAG][0] + ((blk / 3) * 8 + 2 * w + ((ln >> 2) & 1));
        unsigned long long v0; int guard = 0;
        while (v0 = ld_rlxu64(hp), !__all_sync(~0u, (uint32_t)(v0 >> 32) == E)) { if (++guard > (1 << 22)) TRAP(); }
        st_rlx((uint32_t*)outp, (ln & 3) == 1 ? ((uint32_t)v0 >> ((ln & 8) * 2)) & 0xffffu : (ln & 1) ? 0u : itag);
      } else {
        spin_until(tx);
        ASTAMP(8);
        poll(v);
      }
    }
    auto late = [&](const uint2* v) {
      return __any_sync(~0u, (or3(xo2(v[0].x, v[1].x, tag), xo2(v[2].x, v[3].x, tag), xo2(v[4].x, v[5].x, tag)) | xo2(v[6].x, v[7].x, tag)) & 1u);
    };
    tok_exp1(); tok_exp2();
    auto reduce = [&]() {
      if (sum) {
        ASTAMP(9);
        int guard = 0;
        while (late(v)) {
          if (++guard > (1 << 22)) TRAP();
          poll(v);
        }
#pragma unroll
        for (int i = 0; i < 4; i++) { v[i].x = add2(v[i].x, v[i + 4].x); v[i].y = add2(v[i].y, v[i + 4].y); }
        const bool hi = ln & 8;
        const uint32_t x0 = add2(v[0].x, v[1].x), x1 = add2(v[2].x, v[3].x), y0 = add2(v[0].y, v[1].y), y1 = add2(v[2].y, v[3].y);
        const uint32_t m0 = hi ? y0 : x0, m1 = hi ? y1 : x1;
        const uint32_t n0 = __shfl_xor_sync(~0u, hi ? x0 : y0, 8), n1 = __shfl_xor_sync(~0u, hi ? x1 : y1, 8);
        float k0 = (blo(m0) + blo(m1)) + (blo(n0) + blo(n1)), k1 = (bhi(m0) + bhi(m1)) + (bhi(n0) + bhi(n1));
        k0 += __shfl_xor_sync(~0u, k0, 16); k1 += __shfl_xor_sync(~0u, k1, 16);
        st_rlx((uint32_t*)outp, (ln & 1) ? pack2(k0, k1) : pack2_tag(k0, k1, itag));
        ASTAMP(10);
        if (T == 0 && w == 0) TSTAMP(14, cta, 2);
        CSTAMP(12 + w, (clk() & ~15u) | min(guard + 1, 15));
      }
      if (more) bar_arrive(N_GO4, 384);
    };
    if (PVR_ < 0) reduce();
    {
      PIN(ln);
      const uint32_t oa = sb + M_OST + w * 128 + (ln >> 3) * 512 + (ln & 7) * 16;
      const uint32_t a[3][4] = {{0, pt[0], 0, pt[1]}, {0, pt[2], 0, pt[3]}, {0, pt[4], 0, 0}};
      constexpr uint64_t dv = mkdesc(M_V, 2048, 128, 0);
#pragma unroll 1
      for (int h = 0; h < 2; h++) {
        float o[32];
        const uint64_t dh = dv + (uint64_t)(h * 64);
        wg_fence();
        wgmma_rs64<0, 0>(o, a[0], dh); wgmma_rs64<1, 0>(o, a[1], dh + 256); wgmma_rs64<1, 0>(o, a[2], dh + 512);
        wg_commit();
        if (h == PVR_) reduce();
        if (h == 0) {
          ts += __shfl_xor_sync(~0u, ts, 1);
          ts += __shfl_xor_sync(~0u, ts, 2);
          ts = rcp(ts);
          mbar_wait(BAR(B_OFREE), ph ^ 1);
        }
        wg_wait<0>(); reg_fence(o);
        if (h == 1 && ln < 3) mbar_arrive_remote(mapa(BAR(B_VFREE), ln));
#define OT(i) pack2(o[4 * (i) + 2] * ts, o[4 * (i) + 3] * ts)
        stmatrix4(oa + h * 4096, OT(0), OT(1), OT(2), OT(3));
        stmatrix4(oa + h * 4096 + 2048, OT(4), OT(5), OT(6), OT(7));
      }
      const uint32_t z5 = DRAIN(oa);
      __syncwarp();
      if (ln == 0) mbar_arrive(BAR(B_OST) + z5);
      ASTAMP(11);
    }
  }
}

__global__ void __cluster_dims__(3, 1, 1) __launch_bounds__(512, 1) main_kernel(Params p) {
  extern __shared__ __align__(1024) uint8_t sm[];
  const uint32_t sb = smem_u32(sm);
  if ((sb & 0xFFFFFFu) != SBASE) TRAP();
  asm volatile("griddepcontrol.launch_dependents;");
  const int warp = __shfl_sync(~0u, threadIdx.x >> 5, 0);
  const int cta = blockIdx.x, head = cta / 3, c = cta % 3;
  const uint32_t E = __shfl_sync(~0u, *(volatile uint32_t*)&g_epoch + 1, 0);
  uint8_t* const part = (uint8_t*)(((uintptr_t)g_xch + 8191) & ~(uintptr_t)8191);
  uint8_t* const memg = part + 96 * 16384;

  if (threadIdx.x == 0 && cta == 0) GSTAMP(0, 0);
  if (threadIdx.x < B_NUM) {
    const int i = threadIdx.x;
    const uint32_t cnt = i == B_STG || i == B_STG1 ? 8 : i == B_OST ? 4 : i == B_HAE || i == B_HBE ? 6 : i == B_KFREE || i == B_VFREE ? 12 : i == B_SS ? 2 : i == B_OM ? 5 :
                         i == B_QK ? (c < 2 ? 9 : 1) : i == B_V ? (c < 2 ? 1 : 9) : 1;
    mbar_init(BAR(i), cnt);
    if (i == B_HA || i == B_HB || i == B_STG || i == B_HAE || i == B_HBE || i == B_TFREE)
      asm volatile("mbarrier.arrive.shared::cta.b64 _, [%0], %1;" :: "r"(BAR(i)), "r"(cnt) : "memory");
    asm volatile("fence.mbarrier_init.release.cluster;" ::: "memory");
  }
  if (warp < 8) {
    const int tid = threadIdx.x;
    uint4 wa[6], wb[6];
#pragma unroll
    for (int i = 0; i < 6; i++) {
      const int mi = i >> 1, e = (tid >> 2) + (i & 1) * 64;
      const uint4* src = (const uint4*)(p.wo + (size_t)(head * 128 + e) * 512 + min(3 * mi + c, 7) * 64 + (tid & 3) * 16);
      wa[i] = __ldg(src); wb[i] = __ldg(src + 1);
    }
    stage_weights(sb, (c == 0 ? p.wq : c == 1 ? p.wk : p.wv) + head * 128, 4096, tid, 256);
#pragma unroll
    for (int i = 0; i < 6; i++) {
      const int mi = i >> 1, e = (tid >> 2) + (i & 1) * 64;
      const uint4 a = wa[i], b = wb[i];
      const uint32_t dst = sb + M_WO + mi * 16384 + (e >> 3) * 1024 + (tid & 3) * 256 + (e & 7) * 16;
      sts128(dst, make_uint4(__byte_perm(a.x, a.y, 0x5410), __byte_perm(a.z, a.w, 0x5410), __byte_perm(b.x, b.y, 0x5410), __byte_perm(b.z, b.w, 0x5410)));
      sts128(dst + 128, make_uint4(__byte_perm(a.x, a.y, 0x7632), __byte_perm(a.z, a.w, 0x7632), __byte_perm(b.x, b.y, 0x7632), __byte_perm(b.z, b.w, 0x7632)));
    }
  } else {
    const int i0 = threadIdx.x - 256;
    const uint32_t tag0 = ((E - 1) * (uint32_t)(NSTEP - 1)) & 1;
    for (int i = i0; i < 1024; i += 256) *(uint4*)(part + block_of(head, c) * 16384 + i * 16) = make_uint4(tag0, 0, tag0, 0);
    if (i0 < 16) *(uint32_t*)(memg + i0 * 4096 + 3968) = 0;
    if (i0 < 2) st_rlx(&f_choice[block_of(head, c)][i0], 0);
    if (i0 < 8) st_rlx64(&g_sync[i0 >> 2][cta][i0 & 3], 0, 0);
    __threadfence();
    if (i0 < 12) sts32(sb + M_ZERO + i0 * 4, 0);
    if (i0 < 2) { sts32(sb + M_BASE + i0 * 4, clk32() - 65536); sts32(sb + M_BAS2 + i0 * 4, clk32() - 65536); sts32(sb + M_CAND + i0 * 4, (uint32_t)-1); }
  }

  if (warp < 8) {
    asm volatile("setmaxnreg.inc.sync.aligned.u32 " STR(RW_) ";");
    weight_role(p, sb, warp, cta, c, E, memg);
  } else if (warp < 12) {
    if (RA_ < 128) asm volatile("setmaxnreg.dec.sync.aligned.u32 " STR(RA_) ";");
    if (RA_ > 128) asm volatile("setmaxnreg.inc.sync.aligned.u32 " STR(RA_) ";");
    attn_role(p, sb, warp - 8, cta, head, c, E, part, memg);
    cluster_sync();
  } else {
    asm volatile("setmaxnreg.dec.sync.aligned.u32 " STR(RC_) ";");
    const int tid = fresh_tid(), lane = tid & 31;
    const int w = warp - 12;
    cluster_sync();
    if (w != 2) {
      const int tl = w == 0 ? c : w == 1 ? 2 + c : 5 + c;
      int near = 0;
      if (lane == 0) { const int t0 = probe(memg + tl * 8192, NPROBE_ / 2); near = probe(memg + tl * 8192 + 4096, NPROBE_ / 2) < t0; }
      near = uni(near);
      if (lane < 3) asm volatile("st.shared::cluster.u32 [%0], %1;" :: "r"(mapa(sb + M_NEAR + tl * 4, lane)), "r"(near) : "memory");
      __syncwarp();
    }
    if (w == 0) {
      int yadj = 0, dmin = 1 << 20; uint32_t prev = 0; bool cprev = false;
      uint32_t s1 = (2 + c) * 8192, s2 = (5 + c) * 8192;
#pragma unroll 1
      for (int T = 0; T < NSTEP - 1; T++) {
        const uint32_t ph = T & 1;
        mbar_wait(BAR(B_SS), ph);
        const uint32_t cq = clk();
        const uint32_t g0 = (uint32_t)gtime64(); uint32_t g1, ce;
        do { g1 = (uint32_t)gtime64(); ce = clk(); } while (g1 == g0);
        const uint32_t tn = g1 * 8 - (((ce - cq) * 37u) >> 3), id = E * 128u + T;
        if (lane < 4) st_rlx64(&g_sync[ph][cta][lane], tn, id);
        if (lane < 3) mbar_expect(BAR(B_LAND + lane), lane ? 9216 : 6144);
        if (T == 0) { s1 += uni(lds32(sb + M_NEAR + (2 + c) * 4)) * 4096; s2 += uni(lds32(sb + M_NEAR + (5 + c) * 4)) * 4096; }
        wait_until(cq + SDLY_);
        int guard = 0; unsigned long long v0, v1, v2;
        for (;;) {
          v0 = ld_rlxu64(g_sync[ph][lane]); v1 = ld_rlxu64(g_sync[ph][lane + 32]); v2 = ld_rlxu64(g_sync[ph][lane + 64]);
          if (__all_sync(~0u, (uint32_t)(v0 >> 32) == id && (uint32_t)(v1 >> 32) == id && (uint32_t)(v2 >> 32) == id)) break;
          if (++guard > (1 << 22)) TRAP();
        }
        const bool cnd = (int)uni(lds32(sb + M_CAND + (T & 3) * 4)) >= 0;
        const int dl = __reduce_max_sync(~0u, max(max((int)((uint32_t)v0 - tn), (int)((uint32_t)v1 - tn)), (int)((uint32_t)v2 - tn)));
        const uint32_t base = uni(cq + ((min(dl, 8 * 4096) * 7) >> 5)) + (T == 0 ? SLOW0_ : T == 1 ? SLOW1_ : 0) +
                              (cnd ? CDLY_ : 0) - (T + 2 < NSEG ? 0 : BOFF_);
        const int dur = (int)(base - prev);
        if (!cnd && !cprev) {
          yadj = T > 2 && dur > dmin + 700 ? min(yadj + YUP_, 400) : max(yadj - YDN_, 0);
          if (T > 1) dmin = min(dmin + 20, dur);
        }
        prev = base; cprev = cnd;
        if (lane == 0) { sts32(sb + M_BASE + ph * 4, base); sts32(sb + M_BAS2 + ph * 4, base + yadj); mbar_arrive(BAR(B_SYNC)); }
        CSTAMP(0, base); CSTAMP(1, clk());
        const uint32_t ts = base + YDLY_ + yadj - (T + 2 >= LAG && T + 2 < NSEG ? 0 : YOFF_);
        const uint8_t* const t0 = memg + uni(lds32(sb + M_NEAR)) * 4096, * const t1 = memg + 8192 + uni(lds32(sb + M_NEAR + 4)) * 4096;
        wait_until(ts);
        e_g2s(sb + M_MEM, t0, 3072, BAR(B_LAND)); e_g2s(sb + M_MEM + 3072, t1, 3072, BAR(B_LAND));
        CSTAMP(2, clk());
        spin_until(ts + Y1_);
        e_mc(sb + M_MEM + (2 + c) * 3072, memg + s1, 3072, BAR(B_LAND + 1), 7);
        CSTAMP(3, clk());
        spin_until(ts + Y2_);
        e_mc(sb + M_MEM + (5 + c) * 3072, memg + s2, 3072, BAR(B_LAND + 2), 7);
        CSTAMP(4, clk());
      }
    } else if (w == 1) {
#pragma unroll 1
      for (int T = 0; T < NSTEP; T++) {
        const uint32_t ph = T & 1;
        const int s = c == 0 ? T : T - LAG;
        const bool act = s >= 0 && s < NSEG;
        mbar_wait(BAR(B_OST), ph);
        if (cta == 0) TSTAMP(2, T, 0);
        fence_async_smem();
        if (T < NSTEP - 1) wait_until(uni(lds32(sb + M_BAS2 + ph * 4)) + ODLY_);
        STAMP(22);
        if (act) paced_st(g_o[c][s % ORING][head], sb + M_OST, OGAP_);
        if (c == 2 && T < NSTEP - 1) {
          mbar_wait(BAR(B_STG1), ph ^ 1);
          mbar_wait(BAR(B_VFREE), ph);
          STAMP(23);
          e_mc(sb + M_V + 2048, g_tok[cta][ph ^ 1] + 8192, 8192, BAR(B_V), 6);
          e_mc(sb + M_V + 2048, g_tok[cta][ph ^ 1], 8192, BAR(B_V), 1);
        }
        bulk_wait();
        __syncwarp();
        e_arrive(BAR(B_OFREE));
        if (cta == 0) TSTAMP(2, T, 1);
        if (act && lane < 8) st_rel(&f_o[T][head >> 2][c * 4 + (head & 3)][lane], E);
        __syncwarp();
        if (cta == 0) TSTAMP(2, T, 2);
      }
    } else if (w == 2) {
      unsigned long long run = 0;
      static_assert(LAG >= 2, "config");
      constexpr uint32_t NA = EA / 4 * 4096;
      e_expect(BAR(B_QK), c < 2 ? 2048 : 4096); e_expect(BAR(B_V), c == 0 ? 10240 : c == 1 ? 2048 : 0);
      e_expect(BAR(B_TOK), c == 0 ? 16384 : 0); e_expect(BAR(B_OM), 4096);
      e_expect(BAR(B_HA), NA); e_expect(BAR(B_HB), 65536 - NA);
      wait_eq(&f_h1[c == 1 ? 0 : 1], E); fence_async_glob();
      {
        const uint32_t o0 = c == 0 ? NA : 0, o1 = c == 2 ? NA : 32768;
        e_mc(sb + M_H + (c == 1 ? 32768 : 0) + o0, g_h[0][c == 1 ? 0 : 1] + o0, o1 - o0, BAR(c == 2 ? B_HA : B_HB), 7);
      }
      TSTAMP(14, cta, 3);
      if (c == 2) wait_eq(&f_h1[2], E);
      mbar_wait(BAR(B_HAE), 1);
      e_expect(BAR(B_HA), NA);
      if (c == 2) { fence_async_glob(); e_mc(sb + M_H, g_h[0][2], NA, BAR(B_HA), 7); }
      int cprev = -1;
#pragma unroll 1
      for (int T = 0; T < NSTEP - 1; T++) {
        const int s1 = T + 2, s2 = T + 2 - LAG;
        const uint32_t ph = T & 1;
        const bool l1 = s1 < NSEG, l2 = s2 >= 0 && s2 < NSEG, la = s1 + 1 < NSEG;
        const bool mine = c == 0 ? l1 : c == 1 ? l2 : la;
        const uint32_t* fl = c != 1 ? &f_h1[min(s1 + (c >> 1), NSEG - 1)] : (const uint32_t*)f_h2[max(s2, 0)][lane & 3] + 1;
        const uint32_t want = E & 0x1FFFFFu, sh = c != 1 ? 0 : 11;
        mbar_wait(BAR(B_HBE), ph ^ 1);
        const bool early = __all_sync(~0u, ((ld_acq(fl) >> sh) & 0x1FFFFFu) == want);
        mbar_wait(BAR(B_LAND + 2), ph);
        STAMP(16);
        e_expect(BAR(B_HB), (l1 ? 32768 - NA : 0) + (l2 ? 32768 : 0));
        if (mine) {
          if (!early) {
            int guard = 0;
            while (!__all_sync(~0u, ((ld_acq(fl) >> sh) & 0x1FFFFFu) == want)) { __nanosleep(32); if (++guard > (1 << 22)) TRAP(); }
          }
          fence_async_glob();
          if (c == 1) { mbar_wait(BAR(B_QK), ph); spin_until(clk32() + HDLY_); }
          if (c < 2) paced_h(sb + M_H + c * 32768, g_h[c][c ? s2 : s1], c ? 0 : NA, 32768, 4096, BAR(B_HB), HGAP_);
        }
        int cd = -1;
        if (l2) { cd = route_step(s2, E, lane, run); if (cta == 0) TSTAMP(5, s2, 0); }
        if (lane == 0) sts32(sb + M_CAND + ((T + 2) & 3) * 4, (uint32_t)cd);
        __syncwarp();
        STAMP(17);
        mbar_wait(BAR(B_HAE), ph);
        e_expect(BAR(B_HA), la ? NA : 0);
        if (c == 2 && la) {
          spin_until(clk32() + ADLY_);
          STAMP(18);
          paced_h(sb + M_H, g_h[0][s1 + 1], 0, NA, 4096, BAR(B_HA), AGAP_);
        }
        mbar_wait(BAR(B_OST), ph);
        e_expect(BAR(B_QK), c < 2 ? 2048 : cprev >= 0 ? 8192 : 4096);
        e_expect(BAR(B_V), c < 2 ? 10240 : 8192);
        e_expect(BAR(B_TOK), c == 0 ? 8192 : 16384);
        e_expect(BAR(B_OM), 4096);
        cprev = cd;
      }
    } else {
      const uint32_t mytok = sb + M_Q + c * 12288 + 2048, tb = BAR(c < 2 ? B_TOK : B_V);
      mbar_wait(BAR(B_STG1), 0);
      fence_async_smem();
      if (c) e_s2g(g_tok[cta][1], sb + M_TST, 8192);
#pragma unroll 1
      for (int T = 0; T < NSTEP - 1; T++) {
        const uint32_t ph = T & 1;
        uint8_t* const tok = g_tok[cta][ph ^ 1];
        mbar_wait(BAR(B_STG), ph ^ 1);
        fence_async_smem();
        if (cta == 0 && (T == 0 || T == NSEG || T == NSTEP - 2)) GSTAMP(0, T == 0 ? 2 : T == NSEG ? 3 : 4);
        if (T > 0 && TQ_) mbar_wait(BAR(B_QK), ph);
        STAMP(20);
        paced_st(tok + 8192, sb + M_TST + 8192, TGAP_);
        bulk_wait();
        __syncwarp();
        e_arrive(BAR(B_TFREE));
        if (T == 0) e_mc(mytok, tok + 8192, 8192, tb, 1);
        STAMP(21);
        if (c < 2) {
          mbar_wait(BAR(B_KFREE), ph);
          spin_until(clk32() + KDLY_);
          STAMP(23);
          if (c) e_mc(mytok, tok, 8192, tb, 1);
          e_mc(mytok, tok + 8192, 8192, tb, 6);
        }
        mbar_wait(BAR(B_STG1), ph ^ 1);
        fence_async_smem();
        wait_until(uni(lds32(sb + M_BAS2 + ph * 4)) + TDLY_);
        if (c) paced_st(g_tok[cta][ph], sb + M_TST, T1GAP_);
        STAMP(24);
      }
      bulk_wait();
    }
    __syncwarp();
    cluster_sync();
  }
}

constexpr uint32_t A_RING = 0;
constexpr int A_NST = 6;
constexpr uint32_t A_STG = A_RING + A_NST * 8192;
constexpr uint32_t A_WD = A_STG + 8192;
constexpr uint32_t A_WG = A_WD + 57344;
constexpr uint32_t A_WU = A_WG + 57344;
constexpr uint32_t A_XN = A_WU + 57344;
constexpr uint32_t A_BAR = A_XN + 2048;
constexpr uint32_t A_TOTAL = A_BAR + 256;
static_assert(A_TOTAL <= 232448, "aux smem");

__device__ __forceinline__ uint32_t ptag(int s) { return ((s / PRING) & 1) ^ 1; }
static_assert((NSEG / PRING) % 2 == 0, "tags");
__device__ __forceinline__ void load_row(uint32_t* v, const void* row, int lane) {
  const uint4 a = __ldcg((const uint4*)row + lane), b = __ldcg((const uint4*)row + 32 + lane);
  v[0] = a.x; v[1] = a.y; v[2] = a.z; v[3] = a.w; v[4] = b.x; v[5] = b.y; v[6] = b.z; v[7] = b.w;
}
__device__ __forceinline__ void store_row(void* row, const uint32_t* v, int lane) {
  ((uint4*)row)[lane] = make_uint4(v[0], v[1], v[2], v[3]); ((uint4*)row)[32 + lane] = make_uint4(v[4], v[5], v[6], v[7]);
}
__device__ __forceinline__ void store_img(uint8_t* img, int r, const uint32_t* v, int lane) {
  uint8_t* b = img + (lane >> 3) * 4096 + (r >> 3) * 1024 + (r & 7) * 128 + (((lane ^ r) & 7) << 4);
  *(uint4*)b = make_uint4(v[0], v[1], v[2], v[3]);
  *(uint4*)(b + 16384) = make_uint4(v[4], v[5], v[6], v[7]);
}
template <int NT> __device__ __forceinline__ void ln_rows(const uint32_t (*v)[8], uint32_t (*y)[8]) {
  float c[NT], sm[NT], sq[NT];
#pragma unroll
  for (int k = 0; k < NT; k++) {
    c[k] = blo(__shfl_sync(~0u, v[k][0], 0));
    float s0 = 0.f, s1 = 0.f, q0 = 0.f, q1 = 0.f;
#pragma unroll
    for (int i = 0; i < 8; i++) { const float a = blo(v[k][i]) - c[k], b = bhi(v[k][i]) - c[k]; s0 += a; s1 += b; q0 = fmaf(a, a, q0); q1 = fmaf(b, b, q1); }
    sm[k] = s0 + s1; sq[k] = q0 + q1;
  }
#pragma unroll
  for (int o = 16; o > 0; o >>= 1)
#pragma unroll
    for (int k = 0; k < NT; k++) {
      sm[k] += __shfl_xor_sync(~0u, sm[k], o); sq[k] += __shfl_xor_sync(~0u, sq[k], o);
    }
#pragma unroll
  for (int k = 0; k < NT; k++) {
    const float dm = sm[k] * (1.f / 512.f), var = fmaxf(fmaf(-dm, dm, sq[k] * (1.f / 512.f)), 0.f);
    const float mb = rbf(c[k] + dm), inv = rcp(rbf(sqrt_fast(rbf(rbf(var) + 1e-5f))));
#pragma unroll
    for (int i = 0; i < 8; i++) { const uint32_t a = pack2(blo(v[k][i]) - mb, bhi(v[k][i]) - mb); y[k][i] = pack2(blo(a) * inv, bhi(a) * inv); }
  }
}
__device__ __forceinline__ void input_ln_pair(const bf16* x, int s, int pr, int lane) {
  uint32_t v[2][8], y[2][8];
  load_row(v[0], x + (size_t)(s * 32 + 2 * pr) * 512, lane); load_row(v[1], x + (size_t)(s * 32 + 2 * pr + 1) * 512, lane);
  ln_rows<2>(v, y);
  store_img(g_h[0][s], 2 * pr, y[0], lane); store_img(g_h[0][s], 2 * pr + 1, y[1], lane);
}
__device__ __forceinline__ float load_wr(uint32_t* wv, const bf16* wr, int lane) {
  load_row(wv, wr, lane);
  float wsum = 0.f;
#pragma unroll
  for (int i = 0; i < 8; i++) wsum += blo(wv[i]) + bhi(wv[i]);
#pragma unroll
  for (int o = 16; o > 0; o >>= 1) wsum += __shfl_xor_sync(~0u, wsum, o);
  return wsum;
}

template <bool FAST>
__device__ __forceinline__ unsigned long long token_post(int st, int tk, const bf16* res, bf16* dst, bf16* req, unsigned long long best,
                                                         const uint32_t* wv, float wsum, uint32_t E, int lane) {
  const int s = tk >> 5;
  uint32_t x[8];
  load_row(x, res, lane);
  {
    int guard = 0;
    while (__popc(__ballot_sync(~0u, ld_rlx(f_acc[st][s][lane]) == E)) < (FAST ? HINT_ : 32)) { __nanosleep(FAST ? 20 : 100); if (++guard > (1 << 22)) TRAP(); }
  }
  if (tk == s * 32 && st == 0 && lane == 0) TSTAMP(4, s, 0);
  {
    const uint8_t* pp = g_pp[st][s % PRING] + (lane >> 4) * 8192 + (tk & 31) * 256 + (((lane & 15) ^ (tk & 7)) << 4);
    const uint32_t tag = ptag(s);
    uint4 q[8][2];
#define PLD(k, h) q[k][h] = ld_rlx128<(k) * 32768 + (h) * 16384>(pp)
#define PLD8(h) PLD(0, h); PLD(1, h); PLD(2, h); PLD(3, h); PLD(4, h); PLD(5, h); PLD(6, h); PLD(7, h)
#define PBAD(h) __any_sync(~0u, (or3(xo2(q[0][h].x, q[1][h].x, tag), xo2(q[2][h].x, q[3][h].x, tag), xo2(q[4][h].x, q[5][h].x, tag)) | xo2(q[6][h].x, q[7][h].x, tag)) & ~lane & (PST_ == 8192 ? 1u : 0u))
#define PSUM(f, h, m) (((f(q[0][h].m) + f(q[1][h].m)) + (f(q[2][h].m) + f(q[3][h].m))) + ((f(q[4][h].m) + f(q[5][h].m)) + (f(q[6][h].m) + f(q[7][h].m))))
    const uint32_t eye = (lane >> 2) == 2 * (lane & 3) ? 0x3f80u : (lane >> 2) == 2 * (lane & 3) + 1 ? 0x3f800000u : 0u;
    auto padd = [&](int h) {
      if (FAST) {
        float u[4] = {0.f, 0.f, 0.f, 0.f}, v[4] = {0.f, 0.f, 0.f, 0.f};
#pragma unroll
        for (int k = 0; k < 8; k++) { hmma8(u, q[k][h].x, q[k][h].y, eye); hmma8(v, q[k][h].z, q[k][h].w, eye); }
        x[4 * h] = add2(x[4 * h], pack2(u[0], u[1])); x[4 * h + 1] = add2(x[4 * h + 1], pack2(u[2], u[3]));
        x[4 * h + 2] = add2(x[4 * h + 2], pack2(v[0], v[1])); x[4 * h + 3] = add2(x[4 * h + 3], pack2(v[2], v[3]));
      } else {
        x[4 * h] = add2(x[4 * h], pack2(PSUM(blo, h, x), PSUM(bhi, h, x))); x[4 * h + 1] = add2(x[4 * h + 1], pack2(PSUM(blo, h, y), PSUM(bhi, h, y)));
        x[4 * h + 2] = add2(x[4 * h + 2], pack2(PSUM(blo, h, z), PSUM(bhi, h, z))); x[4 * h + 3] = add2(x[4 * h + 3], pack2(PSUM(blo, h, w), PSUM(bhi, h, w)));
      }
    };
    int guard = 0;
    PLD8(0);
    if (FAST) { PLD8(1); }
    while (PBAD(0)) { if (++guard > (1 << 20)) TRAP(); PLD8(0); }
    padd(0);
    if (!FAST) { PLD8(1); }
    while (PBAD(1)) { if (++guard > (1 << 20)) TRAP(); PLD8(1); }
    padd(1);
  }
  const float c = blo(__shfl_sync(~0u, x[0], 0));
  float s0 = 0.f, s1 = 0.f, q0 = 0.f, q1 = 0.f, r0 = 0.f, r1 = 0.f;
#pragma unroll
  for (int i = 0; i < 8; i++) {
    const float a = blo(x[i]) - c, b = bhi(x[i]) - c;
    s0 += a; s1 += b; q0 = fmaf(a, a, q0); q1 = fmaf(b, b, q1); r0 = fmaf(a, blo(wv[i]), r0); r1 = fmaf(b, bhi(wv[i]), r1);
  }
  s0 += s1; q0 += q1; r0 += r1;
#pragma unroll
  for (int o = 16; o > 0; o >>= 1) { s0 += __shfl_xor_sync(~0u, s0, o); q0 += __shfl_xor_sync(~0u, q0, o); r0 += __shfl_xor_sync(~0u, r0, o); }
  const float dm = s0 * (1.f / 512.f), m = c + dm, var = fmaxf(fmaf(-dm, dm, q0 * (1.f / 512.f)), 0.f);
  const float mb = rbf(m), inv = rcp(rbf(sqrt_fast(rbf(rbf(var) + 1e-5f))));
  const uint32_t nmb = pack2(-mb, -mb);
  const unsigned long long wd = rword(E, tk, fmaf(c - mb, wsum, r0) * inv);
  uint32_t xn[8], x2[8];
#pragma unroll
  for (int i = 0; i < 8; i++) { const uint32_t d = add2(x[i], nmb); xn[i] = pack2(blo(d) * inv, bhi(d) * inv); x2[i] = add2(x[i], xn[i]); }
  if (st == 0) {
    const float mb2 = rbf(fmaf(m - mb, inv, m)), inv2 = rcp(rbf(sqrt_fast(rbf(rbf(var * (1.f + inv) * (1.f + inv)) + 1e-5f))));
    const uint32_t nmb2 = pack2(-mb2, -mb2);
    uint32_t h[8];
#pragma unroll
    for (int i = 0; i < 8; i++) { const uint32_t d2 = add2(x2[i], nmb2); h[i] = pack2(blo(d2) * inv2, bhi(d2) * inv2); }
    store_img(g_h[1][s], tk & 31, h, lane);
  }
  store_row(dst, x2, lane);
  if (wd > best && !(EXPQ_ & (st == 0 ? 1 : 2))) { store_row(req, xn, lane); store_row(req + 512, x, lane); }
  return wd;
}

__device__ __forceinline__ void ffn_slice(uint32_t sb, const bf16* xn, float* yacc, uint32_t* flag, uint32_t E, int t, bool urgent) {
  const int w = t >> 5, g = (t >> 2) & 7;
  if (t == 0 && urgent) sts32(sb + A_BAR + 160, 1);
  { const uint2 u = __ldcg((const uint2*)xn + t); asm volatile("st.shared.v2.u32 [%0], {%1,%2};" :: "r"(sb + A_XN + t * 8), "r"(u.x), "r"(u.y) : "memory"); }
  fence_async_smem();
  bar_sync(4, 128);
  float ga[4], ua[4];
  constexpr uint64_t da = mkdesc(A_WG, 896, 128, 0), db = mkdesc(A_XN, 16, 128, 0);
  wg_fence();
  wgmma_ss8<0, 1, 0>(ga, da, db); wgmma_ss8<0, 1, 0>(ua, da + (A_WU - A_WG) / 16, db);
#pragma unroll
  for (int ks = 1; ks < 32; ks++) { wgmma_ss8<1, 1, 0>(ga, da + ks * 112, db + ks * 2); wgmma_ss8<1, 1, 0>(ua, da + (A_WU - A_WG) / 16 + ks * 112, db + ks * 2); }
  wg_commit(); wg_wait<0>(); reg_fence(ga); reg_fence(ua);
  if ((t & 3) == 0) {
#pragma unroll
    for (int h = 0; h < 2; h++) {
      const float gs = rbf(ga[2 * h]), us = rbf(ua[2 * h]);
      const float v = 16 * w + 8 * h < 56 ? rbf(gs * rcp(1.f + __expf(-gs))) * us : 0.f;
      asm volatile("st.shared.u16 [%0], %1;" :: "r"(sb + A_XN + 1280 + (16 * w + 8 * h + g) * 2), "h"((unsigned short)pack2(v, 0.f)) : "memory");
    }
  }
  fence_async_smem();
  bar_sync(4, 128);
#pragma unroll 1
  for (int j = 0; j < 2; j++) {
    float y[4][4];
    const uint64_t dd = mkdesc(A_WD, 8192, 128, 0) + (uint64_t)(j * 256);
    wg_fence();
#pragma unroll
    for (int m = 0; m < 4; m++) {
      wgmma_ss8<0, 1, 0>(y[m], dd + m * 64, mkdesc(A_XN + 1280, 16, 128, 0));
#pragma unroll
      for (int ks = 1; ks < 4; ks++) wgmma_ss8<1, 1, 0>(y[m], dd + m * 64 + ks * 1024, mkdesc(A_XN + 1280 + ks * 32, 16, 128, 0));
    }
    wg_commit(); wg_wait<0>();
#pragma unroll
    for (int m = 0; m < 4; m++) {
      reg_fence(y[m]);
      if ((t & 3) == 0) { float* o = yacc + j * 256 + m * 64 + 16 * w + g; o[0] = y[m][0]; o[8] = y[m][2]; }
    }
  }
  bar_sync(4, 128);
  if (t < 8) { sts32(sb + A_BAR + 160, 0); st_rel(flag + t, E); }
  __syncwarp();
}

__device__ __forceinline__ void ffn_gather(uint32_t sb, int q, int j, uint32_t E, int lane) {
  wait_all(f_y[q][4 * j + (lane & 3)], E);
  float4 y[4][4];
#pragma unroll
  for (int k = 0; k < 4; k++)
#pragma unroll
    for (int i = 0; i < 4; i++) y[k][i] = __ldcg((const float4*)g_y[q & 7][4 * j + k] + i * 32 + lane);
#pragma unroll
  for (int i = 0; i < 4; i++)
    sts128f(sb + 1024 + j * 2048 + i * 512 + lane * 16, (y[0][i].x + y[1][i].x) + (y[2][i].x + y[3][i].x), (y[0][i].y + y[1][i].y) + (y[2][i].y + y[3][i].y),
            (y[0][i].z + y[1][i].z) + (y[2][i].z + y[3][i].z), (y[0][i].w + y[1][i].w) + (y[2][i].w + y[3][i].w));
  bar_sync(9, 256);
}
__device__ __forceinline__ void ffn_finish(uint32_t sb, int q, const bf16* req, float r, uint32_t E, int lane, uint32_t* v) {
  if (lane == 0) sts32(sb + 16, q);
  bar_sync(8, 256);
  uint32_t xn[8];
  load_row(xn, req, lane); load_row(v, req + 512, lane);
  const float rs = rbf(1.f / (1.f + __expf(-rbf(r))));
  ffn_gather(sb, q, 7, E, lane);
#pragma unroll
  for (int i = 0; i < 4; i++) {
    float y[4] = {0.f, 0.f, 0.f, 0.f};
#pragma unroll
    for (int j = 0; j < 8; j++) {
      const uint4 u = lds128(sb + 1024 + j * 2048 + (i >> 1) * 1024 + lane * 32 + (i & 1) * 16);
      y[0] += __uint_as_float(u.x); y[1] += __uint_as_float(u.y); y[2] += __uint_as_float(u.z); y[3] += __uint_as_float(u.w);
    }
    v[2 * i] = add2(v[2 * i], add2(xn[2 * i], pack2(rbf(y[0]) * rs, rbf(y[1]) * rs)));
    v[2 * i + 1] = add2(v[2 * i + 1], add2(xn[2 * i + 1], pack2(rbf(y[2]) * rs, rbf(y[3]) * rs)));
  }
}

__global__ void __launch_bounds__(512, 1) aux_kernel(Params p) {
  extern __shared__ __align__(1024) uint8_t sm[];
  const uint32_t sb = smem_u32(sm);
  if ((sb & 0xFFFFFFu) != SBASE) TRAP();
  const int warp = __shfl_sync(~0u, threadIdx.x >> 5, 0);
  const int cta = blockIdx.x;
  const uint32_t E = __shfl_sync(~0u, *(volatile uint32_t*)&g_epoch + 1, 0);
  const uint32_t bars = sb + A_BAR;

  if (cta < 32) {
    const int cg = cta & 3, kg = cta >> 2;
    if (threadIdx.x == 0) {
      for (int i = 0; i < A_NST; i++) { mbar_init(bars + 8 * i, 1); mbar_init(bars + 64 + 8 * i, 2); }
      mbar_init(bars + 128, 8); mbar_init(bars + 136, 8); mbar_init(bars + 144, 1);
      sts32(bars + 160, 0);
      asm volatile("fence.mbarrier_init.release.cluster;" ::: "memory");
    }
    if (warp < 8) {
      asm volatile("setmaxnreg.inc.sync.aligned.u32 176;");
      const int tid = fresh_tid(), lane = tid & 31;
      uint32_t W[32][4];
      stage_weights(sb + A_WD, p.wo + (size_t)kg * 512 * 512 + cg * 128, 512, tid, 256);
      cp_async_wait();
      bar_sync(1, 256);
      load_frags(W, sb + A_WD, warp >> 2, warp & 3, lane);
      bar_sync(2, 512);
      const uint32_t so = sb + A_STG + ((lane >> 4) * 8 + (lane & 7)) * 256 + (((warp * 2 + ((lane >> 3) & 1)) ^ (lane & 7)) << 4);
      const uint32_t tm = lane < 4 ? 0x00010001u : 0u;
      int stage = 0; uint32_t ph = 0, job = 0;
#pragma unroll 1
      for (int T = 0; T < NSTEP; T++) {
#pragma unroll 1
        for (int k = 0; k < 3; k++) {
          const int st = k == 0 ? 0 : 3 - k, s = st == 0 ? T : T - LAG;
          if (s < 0 || s >= NSEG) continue;
          float d[16];
#pragma unroll
          for (int hh = 0; hh < 4; hh++) {
            mbar_wait(bars + 8 * stage, ph);
            while (uni(lds32(bars + 160))) __nanosleep(100);
            const uint64_t db = mkdesc(A_RING, 512, 128, 0) + (uint64_t)(stage * 512);
            wg_fence();
            if (hh == 0) wgmma_rs32<0, 0>(d, W[0], db); else wgmma_rs32<1, 0>(d, W[hh * 8], db);
#pragma unroll
            for (int ks = 1; ks < 8; ks++) wgmma_rs32<1, 0>(d, W[hh * 8 + ks], db + ks * 64);
            wg_commit();
            if (hh > 0) { wg_wait<1>(); if ((tid & 127) == 0) mbar_arrive(bars + 64 + 8 * (stage == 0 ? A_NST - 1 : stage - 1)); }
            if (++stage == A_NST) { stage = 0; ph ^= 1; }
          }
          mbar_wait(bars + 144, (job & 1) ^ 1);
          wg_wait<0>(); reg_fence(d);
          if ((tid & 127) == 0) mbar_arrive(bars + 64 + 8 * (stage == 0 ? A_NST - 1 : stage - 1));
          if (cta == 0 && tid == 0) TSTAMP(6, T, k);
          const uint32_t tv = tm * ptag(s);
#define TG(i) ((pack2(d[2 * (i)], d[2 * (i) + 1]) & ~tm) | tv)
          stmatrix4_t(so, TG(0), pack2(d[2], d[3]), TG(2), pack2(d[6], d[7]));
          stmatrix4_t(so + 4096, TG(4), pack2(d[10], d[11]), TG(6), pack2(d[14], d[15]));
          fence_async_smem();
          __syncwarp();
          if (lane == 0) mbar_arrive(bars + 128 + 8 * (job & 1));
          job++;
        }
      }
    } else if (warp < 12) {
      asm volatile("setmaxnreg.dec.sync.aligned.u32 120;");
      const int tid = fresh_tid(), lane = tid & 31;
      const int w = warp - 8, t = tid - 256;
#pragma unroll 1
      for (int s = cta + 4; s < NSEG; s += 32) {
#pragma unroll 1
        for (int pr = w; pr < 16; pr += 4) input_ln_pair(p.x, s, pr, lane);
        bar_sync(4, 128);
        if (t == 0) st_rel(&f_h1[s], E);
      }
      bar_sync(2, 512);
      { int guard = 0; while (ld_rlx(&f_loaded[cta]) != E) { __nanosleep(200); if (++guard > (1 << 22)) TRAP(); } }
#pragma unroll 1
      for (int i = t; i < 512 * 7; i += 128) {
        const int k = i / 7, pc = i % 7;
        cp_async16(sb + A_WG + (k >> 3) * 896 + pc * 128 + (k & 7) * 16, p.wg + (size_t)k * 1792 + cta * 56 + pc * 8);
        cp_async16(sb + A_WU + (k >> 3) * 896 + pc * 128 + (k & 7) * 16, p.wu + (size_t)k * 1792 + cta * 56 + pc * 8);
        cp_async16(sb + A_WD + (i >> 9) * 8192 + (i & 63) * 128 + ((i >> 6) & 7) * 16, p.wd + (size_t)cta * 56 * 512 + i * 8);
      }
      uint32_t wv[8];
      const float wsum = load_wr(wv, p.wr, lane);
      cp_async_wait();
      fence_async_smem();
      bar_sync(4, 128);
      const int tj = (cta * 4 + w) & 31, st = 1 + ((cta >> 3) & 1), sq = cta >> 4;
      unsigned long long run = 0, run2 = 0, best = 0, hist = 0;
      uint32_t open = 0;
#pragma unroll 1
      for (int i = 0; i <= NSTEP; i++) {
        int tok = -1; const bf16* req = nullptr;
        if (i < NSEG) {
          const int cd = (int)uni(route_step(i, E, lane, run));
          run = __shfl_sync(~0u, run, 0);
          hist = hist << 8 | (uint32_t)(cd + 1);
          if (cd >= 0) { tok = rtok(run); req = g_req1[tok][0]; }
        } else {
          const unsigned long long m = wait_words(f_l2[i - NSEG], E);
          const unsigned long long n = ld_rlxu64(f_l2[min(i - NSEG + 1 + (lane & 7), LAG)]);
          const bool over = bar_or(4, 128, rfresh(n, E) && n != m);
          if (m != run2 && !over) { run2 = m; tok = rtok(m); req = g_req2[(tok >> 5) < (rtok(run) >> 5) ? 0 : 1][tok][0]; }
        }
        tok = __shfl_sync(~0u, tok, 0);
        if (tok >= 0) {
          if (cta == 0 && t == 0) TSTAMP(8, i, 0);
          ffn_slice(sb, req, g_y[i & 7][cta], f_y[i][cta], E, t, i < NSEG);
          if (cta == 0 && t == 0) TSTAMP(8, i, 1);
        }
        const int s = i - LAG;
        if (s < 0 || i >= NSEG) continue;
        const int cd = (int)((hist >> (8 * LAG)) & 255) - 1;
        if (cd >= 0 && st == 2) best = 0;
        const int ts = rtok(run) >> 5;
        if ((s & 1) == sq) {
          const int tk = s * 32 + tj;
          unsigned long long wd = (unsigned long long)E << 43;
          if (st == 1 ? s < ts || i < NSEG - 1 : s >= ts) {
            if (st == 2 && cd == tj) wait_eq(&f_hc[s], E);
            wd = token_post<false>(st, tk, st == 2 && cd == tj ? g_x2c[s] : g_x2 + (size_t)tk * 512,
                                   (st == 2 || s < ts ? p.out : g_n) + (size_t)tk * 512, g_req2[st - 1][tk][0], best, wv, wsum, E, lane);
            best = max(best, wd);
            if (st == 1 && s >= ts) open |= 1u << (s >> 1);
          }
          __syncwarp();
          if (lane < 4) st_rel64(&f_w2[st - 1][s][tj][lane], wd);
          __syncwarp();
        }
        if (st == 1) {
          if (i == NSEG - 1 && t == 0 && cta == 0) GSTAMP(1, 0);
#pragma unroll 1
          for (int n = i == NSEG - 1 ? 32 : 2; n > 0 && open; n--) {
            const int s0 = 2 * (__ffs(open) - 1) + sq;
            if (s0 >= ts) break;
            open &= open - 1;
            uint32_t v[8];
            load_row(v, g_n + (size_t)(s0 * 32 + tj) * 512, lane);
            wait_words(f_w2[1][s0][tj], E);
            store_row(p.out + (size_t)(s0 * 32 + tj) * 512, v, lane);
          }
          if (i == NSEG - 1) {
            __syncwarp();
            if (lane == 0) st_rel(&f_cp[sq * 32 + tj], E);
            if (t == 0 && cta == 0) GSTAMP(1, 3);
          }
        }
      }
    } else {
      asm volatile("setmaxnreg.dec.sync.aligned.u32 40;");
      const int tid = fresh_tid(), lane = tid & 31;
      const int w = warp - 12;
      bar_sync(2, 512);
      if (w == 0) {
        int stage = 0; uint32_t ph = 1;
#pragma unroll 1
        for (int T = 0; T < NSTEP; T++) {
#pragma unroll 1
          for (int k = 0; k < 3; k++) {
            const int st = k == 0 ? 0 : 3 - k, s = st == 0 ? T : T - LAG;
            if (s < 0 || s >= NSEG) continue;
            const uint32_t* fl = f_o[T][kg][st * 4 + (lane & 3)];
            uint32_t ready = 0; int guard = 0;
#pragma unroll 1
            for (int hh = 0; hh < 4; hh++) {
              while (!((ready >> hh) & 1)) {
                ready = __ballot_sync(~0u, ld_rlx(fl) == E);
                if (++guard > (1 << 23)) TRAP();
              }
              fence_async_glob();
              mbar_wait(bars + 64 + 8 * stage, ph);
              e_expect(bars + 8 * stage, OLOAD_);
              e_g2s(sb + A_RING + stage * 8192, g_o[st][s % ORING][kg * 4 + hh], OLOAD_, bars + 8 * stage);
              if (++stage == A_NST) { stage = 0; ph ^= 1; }
            }
          }
          if (cta == 0 && lane == 0) TSTAMP(3, T, 0);
        }
      } else if (w < 3) {
        uint32_t job = 0;
#pragma unroll 1
        for (int T = 0; T < NSTEP; T++) {
#pragma unroll 1
          for (int k = 0; k < 3; k++) {
            const int st = k == 0 ? 0 : 3 - k, s = st == 0 ? T : T - LAG;
            if (s < 0 || s >= NSEG) continue;
            if ((job++ & 1) != w - 1) continue;
            if (s >= PRING) wait_words(st == 0 ? f_h2[s - PRING][lane & 3] : f_w2[st - 1][s - PRING][lane], E);
            mbar_wait(bars + 128 + 8 * (w - 1), ((job - 1) >> 1) & 1);
            if (cta == 0 && st == 0) TSTAMP(7, s, 0);
            e_s2g(g_pp[st][s % PRING] + cta * 8192, sb + A_STG, PST_);
            if (lane < 8) st_rlx(&f_acc[st][s][cta][lane], E);
            asm volatile("cp.async.bulk.commit_group;\n cp.async.bulk.wait_group.read 0;" ::: "memory");
            __syncwarp();
            e_arrive(bars + 144);
            __syncwarp();
            if (cta == 0 && st == 0) TSTAMP(7, s, 1);
          }
        }
        bulk_wait();
      }
    }
  } else {
    const int tid = fresh_tid(), lane = tid & 31;
    const int qd = cta - 32;
    input_ln_pair(p.x, qd, warp, lane);
    bar_sync(6, 512);
    if (tid == 0) st_rel(&f_h1[qd], E);
    volatile int* bc = (volatile int*)sm;
    if (warp == 15) {
      unsigned long long run = 0;
      unsigned long long b2[2][2] = {{0, 0}, {0, 0}};
      auto track = [&](int s) {
#pragma unroll
        for (int k = 0; k < 2; k++) {
          const unsigned long long m = warp_max<16>(wait_words(f_w2[k][s][lane], E));
          if (lane == (s & 31)) { if (s < 32) b2[k][0] = m; else b2[k][1] = m; }
        }
      };
#pragma unroll 1
      for (int s = 0; s < NSEG; s++) {
        const int cd = route_step(s, E, lane, run);
        if (cd >= 0 && qd == (s & 1)) {
          uint32_t v[1][8], h[1][8];
          ffn_finish(sb, s, g_req1[s * 32 + cd][0], rscore(run), E, lane, v[0]);
          if (lane == 0) TSTAMP(8, s, 2);
          ln_rows<1>(v, h);
#pragma unroll
          for (int i = 0; i < 8; i++) st_rlx64(&g_hc[s][(i >> 2) * 128 + 4 * lane + (i & 3)], h[0][i], E);
          if (lane == 0) TSTAMP(8, s, 3);
          store_row(g_x2c[s], v[0], lane);
          __syncwarp();
          if (lane == 0) st_rel(&f_hc[s], E);
        }
        if (qd == 2 && s > LAG) track(s - LAG - 1);
      }
      wait_eq(&f_hc[rtok(run) >> 5], E);
      if (lane == 0) *bc = rtok(run);
      bar_sync(7, 288);
      if (qd == 2) {
        uint32_t v[8];
        const int ts = rtok(run) >> 5;
        track(NSEG - LAG - 1);
        run = 0;
        int kl = 0;
#pragma unroll 1
        for (int k = 0; k <= LAG; k++) {
          const int s = NSEG - LAG - 1 + k;
          const unsigned long long m = warp_max<16>(k == 0 ? max(lane < ts ? b2[0][0] : b2[1][0], lane + 32 < ts ? b2[0][1] : b2[1][1])
                                                           : wait_words(f_w2[s < ts ? 0 : 1][s][lane], E));
          const bool lead = m > run;
          if (lead) { run = m; __threadfence(); }
          if (lane < 4) st_rlx64(&f_l2[k][lane], (uint32_t)run, (uint32_t)(run >> 32));
          if (lead) kl = k;
          if (k == LAG - 1) { wait_all(&f_cp[lane], E); wait_all(&f_cp[32 + lane], E); }
          if (k == LAG - 1 || (k == LAG && lead)) ffn_finish(sb, NSEG + kl, g_req2[(rtok(run) >> 5) < ts ? 0 : 1][rtok(run)][0], rscore(run), E, lane, v);
        }
        if (lane == 0) GSTAMP(1, 1);
        store_row(p.out + (size_t)rtok(run) * 512, v, lane);
        if (lane == 0) GSTAMP(1, 2);
      }
      if (lane == 0) sts32(sb + 16, (uint32_t)-1);
      bar_sync(8, 256);
      if (qd == 2) {
        asm volatile("griddepcontrol.wait;" ::: "memory");
        if (lane == 0) *(volatile uint32_t*)&g_epoch = E;
      }
    } else if (warp >= 8) {
#pragma unroll 1
      for (;;) {
        bar_sync(8, 256);
        const int q = (int)uni(lds32(sb + 16));
        if (q < 0) break;
        ffn_gather(sb, q, warp - 8, E, lane);
      }
    } else {
      uint32_t wv[8];
      const float wsum = load_wr(wv, p.wr, lane);
      unsigned long long best = 0;
      int ttok = 0;
#pragma unroll 1
      for (int i = 0; i < NSTEP; i++) {
        const bool last = i >= NSEG;
        if (i == NSEG) { bar_sync(7, 288); ttok = *bc; best = 0; }
        const int s = last ? i - LAG : i, st = !last ? 0 : s < (ttok >> 5) ? 1 : 2;
        const int tk = s * 32 + qd * 8 + warp;
        const unsigned long long wd = token_post<true>(st, tk, !last ? p.x + (size_t)tk * 512 : tk == ttok ? g_x2c[s] : g_x2 + (size_t)tk * 512,
                                                 (last ? p.out : g_x2) + (size_t)tk * 512, last ? g_req2[st - 1][tk][0] : g_req1[tk][0], best, wv, wsum, E, lane);
        best = max(best, wd);
        volatile unsigned long long* ws = (volatile unsigned long long*)(sm + 64) + (i & 1) * 8;
        if (lane == 0) ws[warp] = wd;
        bar_sync(5, 256);
        if (warp == 0) {
          if (qd == 0 && lane == 0) TSTAMP(4, i, 1);
          if (!last) { const unsigned long long m = warp_max<4>(ws[lane & 7]); if (lane < 4) st_rel64(&f_h2[s][qd][lane], m); }
          else {
            st_rel64(&f_w2[st - 1][s][qd * 8 + (lane >> 2)][lane & 3], ws[lane >> 2]);
            asm volatile("st.relaxed.gpu.global.u64 [%0], %1;" :: "l"(&f_w2[2 - st][s][qd * 8 + (lane >> 2)][lane & 3]), "l"((unsigned long long)E << 43) : "memory");
          }
          if (qd == 0 && lane == 0) TSTAMP(4, i, 2);
        }
        __syncwarp();
      }
    }
  }
}

}

extern "C" void kernel_launch(void* const* d_in, const int* in_sizes, int n_in, void* d_out, int out_size) {
  (void)in_sizes; (void)n_in; (void)out_size;
  static bool init = false;
  if (!init) {
    cudaFuncSetAttribute(main_kernel, cudaFuncAttributeMaxDynamicSharedMemorySize, M_TOTAL);
    cudaFuncSetAttribute(aux_kernel, cudaFuncAttributeMaxDynamicSharedMemorySize, A_TOTAL);
    init = true;
  }
  Params p;
  p.x = (const bf16*)d_in[0]; p.mem0 = (const bf16*)d_in[1]; p.wq = (const bf16*)d_in[2]; p.wk = (const bf16*)d_in[3];
  p.wv = (const bf16*)d_in[4]; p.wo = (const bf16*)d_in[5]; p.wr = (const bf16*)d_in[8]; p.wg = (const bf16*)d_in[9];
  p.wu = (const bf16*)d_in[10]; p.wd = (const bf16*)d_in[11]; p.out = (bf16*)d_out; p.zero = 0; p.zero2 = 0;
  cudaStream_t st = cudaStreamPerThread;
  main_kernel<<<96, 512, M_TOTAL, st>>>(p);
  cudaLaunchConfig_t cfg = {};
  cfg.gridDim = dim3(36); cfg.blockDim = dim3(512); cfg.dynamicSmemBytes = A_TOTAL; cfg.stream = st;
  cudaLaunchAttribute at[1];
  at[0].id = cudaLaunchAttributeProgrammaticStreamSerialization; at[0].val.programmaticStreamSerializationAllowed = 1;
  cfg.attrs = at; cfg.numAttrs = 1;
  cudaLaunchKernelEx(&cfg, aux_kernel, p);
}
```

```cpp
#include <cuda_runtime.h>
#include <cuda_bf16.h>
#include <stdint.h>

namespace {

typedef __nv_bfloat16 bf16;

constexpr int NSEG = 64;
#define LAG_ 5
constexpr int LAG = LAG_;
constexpr int NSTEP = NSEG + LAG;
constexpr int ORING = 8, PRING = 4;
static_assert(LAG < 8, "rings");
#define E1_ 10
#define E2_ 0
#define E3_ 10
constexpr int E1 = E1_, E2 = E2_, E3 = E3_, EA = E1 + E2 + E3;
static_assert(EA % 4 == 0 && EA > 0 && EA < 32 && E1 > 0, "early part: whole 64-column chunks");
#define RW_ 176
#define RA_ 136
#define RC_ 24
#define STR2(x) #x
#define STR(x) STR2(x)
#define RED_ 30
#define ARR_ 7
#define PAUSE_ 13
#define PAUS2_ 29
#define PST2_ 2
#define PVR_ -1
#define SALT_ 0
#define KP1_ 1
#define OLOAD_ 8192
#define PST_ 8192
#define ALT_ 1
#define TQ_ 1
#define NOF_ 2
#define EXPQ_ 0
#define SPC_ 4096
#define HINT_ 24
#define HADD_ 2
#define HAND_ 4
#define GO3_ 2
#define STK_ 0
#define REMAP_ 1
#define NPROBE_ 6
#define TP(i, v) (v)
#define XDLY_ TP(0, 2125)
#define YDLY_ TP(1, 3400)
#define X1_ TP(2, 100)
#define X2_ TP(3, 350)
#define Y1_ TP(4, 250)
#define Y2_ TP(5, 450)
#define HGAP_ TP(6, 50)
#define TGAP_ TP(7, 100)
#define ADLY_ TP(8, 600)
#define ODLY_ TP(9, 2800)
#define LDLY_ TP(10, 3800)
#define HDLY_ TP(11, 0)
#define TDLY_ TP(15, 4150)
#define SDLY_ TP(12, 800)
#define AGAP_ 100
#define BOFF_ TP(13, 200)
#define YOFF_ TP(16, 150)
#define YUP_ TP(20, 40)
#define YDN_ TP(21, 4)
#define T1GAP_ TP(22, 0)
#define OGAP_ TP(23, 0)
#define CDLY_ TP(17, 300)
#define SLOW0_ TP(18, 400)
#define SLOW1_ TP(19, 300)
#define KDLY_ TP(14, 300)
__device__ uint32_t g_epoch;
__device__ __align__(1024) uint8_t g_h[2][NSEG][32768];
__device__ __align__(128) uint2 g_hc[NSEG][256];
__device__ __align__(128) bf16 g_x2[2048 * 512];
__device__ __align__(128) bf16 g_x2c[NSEG][512];
__device__ __align__(128) uint8_t g_o[3][ORING][32][8192];
__device__ __align__(128) uint8_t g_pp[3][PRING][8 * 32768];
__device__ __align__(128) bf16 g_n[2048 * 512];
__device__ __align__(128) uint8_t g_xch[96 * 16384 + 65536 + 8192];
__device__ __align__(128) bf16 g_req1[2048][2][512];
__device__ __align__(128) bf16 g_req2[2][2048][2][512];
__device__ __align__(128) float g_y[8][32][512];
__device__ __align__(128) uint8_t g_tok[96][2][16384];
__device__ uint32_t f_choice[96][2], f_loaded[32];
__device__ uint32_t f_h1[NSEG], f_hc[NSEG];
__device__ __align__(128) unsigned long long f_h2[NSEG][4][4];
__device__ __align__(128) unsigned long long f_w2[2][NSEG][32][4];
__device__ __align__(128) unsigned long long f_l2[LAG + 1][4];
__device__ __align__(128) uint32_t f_o[NSTEP][8][12][8];
__device__ __align__(128) uint32_t f_acc[3][NSEG][32][8], f_y[NSTEP + 1][32][8], f_cp[64];
__device__ __align__(128) unsigned long long g_sync[2][96][4];

#define TRAP() __trap()
__device__ __forceinline__ uint32_t smem_u32(const void* p) { return (uint32_t)__cvta_generic_to_shared(p); }
__device__ __forceinline__ int fresh_tid() { const int t = threadIdx.x; return __shfl_sync(~0u, t, t & 31); }
__device__ __forceinline__ unsigned long long gtime64() { unsigned long long t; asm volatile("mov.u64 %0, %%globaltimer;" : "=l"(t) :: "memory"); return t; }
__device__ __forceinline__ uint32_t clk() { unsigned long long c; asm volatile("mov.u64 %0, %%clock64;" : "=l"(c) :: "memory"); return (uint32_t)c; }
__device__ __forceinline__ void wait_until(uint32_t t) {
  while ((int)(t - clk()) > 450) __nanosleep(32);
  uint32_t c;
  do { asm volatile("mov.u32 %0, %%clock;" : "=r"(c) :: "memory"); } while ((int)(c - t) < 0);
}
__device__ __forceinline__ void mbar_init(uint32_t bar, uint32_t cnt) { asm volatile("mbarrier.init.shared::cta.b64 [%0], %1;" :: "r"(bar), "r"(cnt) : "memory"); }
__device__ __forceinline__ void mbar_arrive(uint32_t bar) { asm volatile("mbarrier.arrive.shared::cta.b64 _, [%0];" :: "r"(bar) : "memory"); }
__device__ __forceinline__ void mbar_arrive_remote(uint32_t bar) { asm volatile("mbarrier.arrive.relaxed.cluster.shared::cluster.b64 _, [%0];" :: "r"(bar) : "memory"); }
__device__ __forceinline__ void mbar_expect(uint32_t bar, uint32_t bytes) { asm volatile("mbarrier.arrive.expect_tx.shared::cta.b64 _, [%0], %1;" :: "r"(bar), "r"(bytes) : "memory"); }
__device__ __forceinline__ bool mbar_try(uint32_t bar, uint32_t parity) {
  uint32_t ok;
  asm volatile("{.reg .pred p; mbarrier.try_wait.parity.shared::cta.b64 p, [%1], %2; selp.u32 %0, 1, 0, p;}" : "=r"(ok) : "r"(bar), "r"(parity) : "memory");
  return ok;
}
__device__ __forceinline__ bool mbar_test(uint32_t bar, uint32_t parity) {
  uint32_t ok;
  asm volatile("{.reg .pred p; mbarrier.test_wait.parity.shared::cta.b64 p, [%1], %2; selp.u32 %0, 1, 0, p;}" : "=r"(ok) : "r"(bar), "r"(parity) : "memory");
  return ok;
}
__device__ __forceinline__ void mbar_wait(uint32_t bar, uint32_t parity) {
  asm volatile("{\n.reg .pred p;\nWAIT:\nmbarrier.try_wait.parity.shared::cta.b64 p, [%0], %1;\n@!p bra WAIT;\n}" :: "r"(bar), "r"(parity) : "memory");
}
__device__ __forceinline__ uint32_t ld_acq(const uint32_t* p) { uint32_t v; asm volatile("ld.acquire.gpu.global.u32 %0, [%1];" : "=r"(v) : "l"(p) : "memory"); return v; }
__device__ __forceinline__ unsigned long long ld_acq64(const unsigned long long* p) { unsigned long long v; asm volatile("ld.acquire.gpu.global.u64 %0, [%1];" : "=l"(v) : "l"(p) : "memory"); return v; }
__device__ __forceinline__ void st_rel(uint32_t* p, uint32_t v) { asm volatile("st.release.gpu.global.u32 [%0], %1;" :: "l"(p), "r"(v) : "memory"); }
__device__ __forceinline__ void st_rel64(unsigned long long* p, unsigned long long v) { asm volatile("st.release.gpu.global.u64 [%0], %1;" :: "l"(p), "l"(v) : "memory"); }
__device__ __forceinline__ void red_rel(uint32_t* p, uint32_t v) { asm volatile("red.release.gpu.global.add.u32 [%0], %1;" :: "l"(p), "r"(v) : "memory"); }
__device__ __forceinline__ uint32_t ld_rlx(const uint32_t* p) { uint32_t v; asm volatile("ld.relaxed.gpu.global.u32 %0, [%1];" : "=r"(v) : "l"(p) : "memory"); return v; }
__device__ __forceinline__ unsigned long long ld_rlxu64(const unsigned long long* p) { unsigned long long v; asm volatile("ld.relaxed.gpu.global.u64 %0, [%1];" : "=l"(v) : "l"(p) : "memory"); return v; }
__device__ __forceinline__ void st_rlx(uint32_t* p, uint32_t v) { asm volatile("st.relaxed.gpu.global.u32 [%0], %1;" :: "l"(p), "r"(v) : "memory"); }
__device__ __forceinline__ void bulk_wait() { asm volatile("cp.async.bulk.commit_group;\n cp.async.bulk.wait_group 0;" ::: "memory"); }
__device__ __forceinline__ void fence_acq() { asm volatile("fence.acquire.gpu;" ::: "memory"); }
__device__ __forceinline__ void wait_all(const uint32_t* p, uint32_t v, bool acquire = true) {
  int guard = 0;
  while (!__all_sync(~0u, ld_rlx(p) == v)) { __nanosleep(32); if (++guard > (1 << 22)) TRAP(); }
  if (acquire) fence_acq();
}
__device__ __forceinline__ void wait_eq(const uint32_t* p, uint32_t v) {
  int guard = 0;
  while (ld_rlx(p) != v) { __nanosleep(64); if (++guard > (1 << 22)) TRAP(); }
  fence_acq();
}
__device__ __forceinline__ unsigned long long rword(uint32_t E, int tok, float r) {
  uint32_t u = __float_as_uint(r + 0.f);
  u = r != r ? 0u : (u >> 31) ? ~u : u | 0x80000000u;
  return (unsigned long long)(E & 0x1FFFFFu) << 43 | (unsigned long long)u << 11 | (uint32_t)(2047 - tok);
}
__device__ __forceinline__ int rtok(unsigned long long v) { return 2047 - (int)(v & 2047u); }
__device__ __forceinline__ float rscore(unsigned long long v) { const uint32_t u = (uint32_t)(v >> 11); return __uint_as_float((u >> 31) ? u & 0x7fffffffu : ~u); }
__device__ __forceinline__ bool rfresh(unsigned long long v, uint32_t E) { return (uint32_t)(v >> 43) == (E & 0x1FFFFFu); }
template <int TOP> __device__ __forceinline__ unsigned long long warp_max(unsigned long long v) {
#pragma unroll
  for (int o = TOP; o > 0; o >>= 1) { const unsigned long long ov = __shfl_xor_sync(~0u, v, o); v = ov > v ? ov : v; }
  return v;
}
template <int off> __device__ __forceinline__ uint2 ld_rlx64(const void* p) { unsigned long long v; asm volatile("ld.relaxed.gpu.global.b64 %0, [%1+%2];" : "=l"(v) : "l"(p), "n"(off) : "memory"); return make_uint2((uint32_t)v, (uint32_t)(v >> 32)); }
template <int off> __device__ __forceinline__ uint4 ld_rlx128(const void* p) {
  unsigned long long a, b; asm volatile("ld.relaxed.gpu.global.v2.b64 {%0,%1}, [%2+%3];" : "=l"(a), "=l"(b) : "l"(p), "n"(off) : "memory");
  return make_uint4((uint32_t)a, (uint32_t)(a >> 32), (uint32_t)b, (uint32_t)(b >> 32));
}
__device__ __forceinline__ void st_rlx64(void* p, uint32_t lo, uint32_t hi) { asm volatile("{.reg .b64 t; mov.b64 t, {%1,%2}; st.relaxed.gpu.global.b64 [%0], t;}" :: "l"(p), "r"(lo), "r"(hi) : "memory"); }
__device__ __forceinline__ void cp_async16(uint32_t dst, const void* src) { asm volatile("cp.async.cg.shared.global [%0], [%1], 16;" :: "r"(dst), "l"(src) : "memory"); }
__device__ __forceinline__ void cp_async_wait() { asm volatile("cp.async.wait_all;" ::: "memory"); }
__device__ __forceinline__ void fence_async_smem() { asm volatile("fence.proxy.async.shared::cta;" ::: "memory"); }
__device__ __forceinline__ void fence_async_glob() { asm volatile("fence.proxy.async.global;" ::: "memory"); }
__device__ __forceinline__ void fence_async_acq() { asm volatile("fence.proxy.async::generic.acquire.sync_restrict::shared::cluster.cluster;" ::: "memory"); }
__device__ __forceinline__ float ex2(float x) { float y; asm("ex2.approx.ftz.f32 %0, %1;" : "=f"(y) : "f"(x)); return y; }
__device__ __forceinline__ float sqrt_fast(float x) { float y; asm("sqrt.approx.ftz.f32 %0, %1;" : "=f"(y) : "f"(x)); return y; }
__device__ __forceinline__ float rcp(float x) { float y; asm("rcp.approx.ftz.f32 %0, %1;" : "=f"(y) : "f"(x)); return y; }
__device__ __forceinline__ void bar_sync(int id, int n) { asm volatile("bar.sync %0, %1;" :: "r"(id), "r"(n) : "memory"); }
__device__ __forceinline__ bool bar_or(int id, int n, bool v) {
  uint32_t r;
  asm volatile("{.reg .pred p, q; setp.ne.u32 p, %3, 0; barrier.cta.red.or.aligned.pred q, %1, %2, p; selp.u32 %0, 1, 0, q;}" : "=r"(r) : "r"(id), "r"(n), "r"((uint32_t)v) : "memory");
  return r;
}
__device__ __forceinline__ uint32_t mapa(uint32_t a, uint32_t rank) { uint32_t r; asm volatile("mapa.shared::cluster.u32 %0, %1, %2;" : "=r"(r) : "r"(a), "r"(rank)); return r; }
__device__ __forceinline__ void cluster_sync() { asm volatile("barrier.cluster.arrive.release.aligned; barrier.cluster.wait.acquire.aligned;" ::: "memory"); }
__device__ __forceinline__ void st_async32(uint32_t dst, uint32_t v, uint32_t bar) { asm volatile("st.async.shared::cluster.mbarrier::complete_tx::bytes.b32 [%0], %1, [%2];" :: "r"(dst), "r"(v), "r"(bar) : "memory"); }
__device__ __forceinline__ void bulk_g2s(uint32_t dst, const void* src, uint32_t bytes, uint32_t bar) {
  asm volatile("cp.async.bulk.shared::cluster.global.mbarrier::complete_tx::bytes [%0], [%1], %2, [%3];" :: "r"(dst), "l"(src), "r"(bytes), "r"(bar) : "memory");
}
__device__ __forceinline__ void bulk_g2s_mc(uint32_t dst, const void* src, uint32_t bytes, uint32_t bar, uint16_t mask) {
  asm volatile("cp.async.bulk.shared::cluster.global.mbarrier::complete_tx::bytes.multicast::cluster [%0], [%1], %2, [%3], %4;"
               :: "r"(dst), "l"(src), "r"(bytes), "r"(bar), "h"(mask) : "memory");
}
__device__ __forceinline__ void bulk_s2c(uint32_t dst, uint32_t src, uint32_t bytes, uint32_t bar) {
  asm volatile("cp.async.bulk.shared::cluster.shared::cta.mbarrier::complete_tx::bytes [%0], [%1], %2, [%3];" :: "r"(dst), "r"(src), "r"(bytes), "r"(bar) : "memory");
}
__device__ __forceinline__ void bulk_s2g(void* dst, uint32_t src, uint32_t bytes) {
  asm volatile("cp.async.bulk.global.shared::cta.bulk_group [%0], [%1], %2;" :: "l"(dst), "r"(src), "r"(bytes) : "memory");
}
#define ELECT(op) "{.reg .pred p; elect.sync _|p, 0xffffffff; @p " op "}"
__device__ __forceinline__ void e_arrive(uint32_t bar) { asm volatile(ELECT("mbarrier.arrive.shared::cta.b64 _, [%0];") :: "r"(bar) : "memory"); }
__device__ __forceinline__ void e_expect(uint32_t bar, uint32_t bytes) { asm volatile(ELECT("mbarrier.arrive.expect_tx.shared::cta.b64 _, [%0], %1;") :: "r"(bar), "r"(bytes) : "memory"); }
__device__ __forceinline__ void e_g2s(uint32_t dst, const void* src, uint32_t bytes, uint32_t bar) {
  asm volatile(ELECT("cp.async.bulk.shared::cluster.global.mbarrier::complete_tx::bytes [%0], [%1], %2, [%3];") :: "r"(dst), "l"(src), "r"(bytes), "r"(bar) : "memory");
}
__device__ __forceinline__ void e_mc(uint32_t dst, const void* src, uint32_t bytes, uint32_t bar, uint16_t mask) {
  asm volatile(ELECT("cp.async.bulk.shared::cluster.global.mbarrier::complete_tx::bytes.multicast::cluster [%0], [%1], %2, [%3], %4;")
               :: "r"(dst), "l"(src), "r"(bytes), "r"(bar), "h"(mask) : "memory");
}
__device__ __forceinline__ void e_s2g(void* dst, uint32_t src, uint32_t bytes) {
  asm volatile(ELECT("cp.async.bulk.global.shared::cta.bulk_group [%0], [%1], %2;") :: "l"(dst), "r"(src), "r"(bytes) : "memory");
}
__device__ __forceinline__ void e_st_rel(uint32_t* p, uint32_t v) { asm volatile(ELECT("st.release.gpu.global.u32 [%0], %1;") :: "l"(p), "r"(v) : "memory"); }
__device__ __forceinline__ uint32_t clk32() { uint32_t c; asm volatile("mov.u32 %0, %%clock;" : "=r"(c) :: "memory"); return c; }
__device__ __forceinline__ void spin_until(uint32_t t) { while ((int)(clk32() - t) < 0) {} }
__device__ __forceinline__ uint32_t uni(uint32_t v) { return __shfl_sync(~0u, v, 0); }
__device__ __forceinline__ uint32_t pack2(float lo, float hi) { uint32_t r; asm("cvt.rn.bf16x2.f32 %0, %1, %2;" : "=r"(r) : "f"(hi), "f"(lo)); return r; }
__device__ __forceinline__ uint32_t add2(uint32_t a, uint32_t b) { uint32_t r; asm("add.rn.bf16x2 %0, %1, %2;" : "=r"(r) : "r"(a), "r"(b)); return r; }
__device__ __forceinline__ float rbf(float x) { return __bfloat162float(__float2bfloat16_rn(x)); }
__device__ __forceinline__ float blo(uint32_t u) { return __uint_as_float(u << 16); }
__device__ __forceinline__ float bhi(uint32_t u) { return __uint_as_float(u & 0xffff0000u); }
__device__ __forceinline__ uint32_t gentag(uint32_t g) { return (g & 1u) | (g & 2u) << 15; }
__device__ __forceinline__ uint32_t pack2_tag(float lo, float hi, uint32_t tag) {
  const uint32_t u = __byte_perm(__float_as_uint(lo), __float_as_uint(hi), 0x7632);
  return u + ((u ^ tag) & 0x10001u);
}
__device__ __forceinline__ uint32_t xo2(uint32_t a, uint32_t b, uint32_t t) { uint32_t r; asm("lop3.b32 %0, %1, %2, %3, 0x7e;" : "=r"(r) : "r"(a), "r"(b), "r"(t)); return r; }
__device__ __forceinline__ uint32_t or3(uint32_t a, uint32_t b, uint32_t c) { uint32_t r; asm("lop3.b32 %0, %1, %2, %3, 0xfe;" : "=r"(r) : "r"(a), "r"(b), "r"(c)); return r; }
__device__ __forceinline__ void stmatrix4(uint32_t a, uint32_t r0, uint32_t r1, uint32_t r2, uint32_t r3) {
  asm volatile("stmatrix.sync.aligned.m8n8.x4.shared.b16 [%0], {%1,%2,%3,%4};" :: "r"(a), "r"(r0), "r"(r1), "r"(r2), "r"(r3) : "memory");
}
__device__ __forceinline__ void stmatrix4_t(uint32_t a, uint32_t r0, uint32_t r1, uint32_t r2, uint32_t r3) {
  asm volatile("stmatrix.sync.aligned.m8n8.x4.trans.shared.b16 [%0], {%1,%2,%3,%4};" :: "r"(a), "r"(r0), "r"(r1), "r"(r2), "r"(r3) : "memory");
}
__device__ __forceinline__ void ldmatrix4_t(uint32_t* r, uint32_t a) {
  asm volatile("ldmatrix.sync.aligned.m8n8.x4.trans.shared.b16 {%0,%1,%2,%3}, [%4];" : "=r"(r[0]), "=r"(r[1]), "=r"(r[2]), "=r"(r[3]) : "r"(a) : "memory");
}
__device__ __forceinline__ void ldmatrix4(uint32_t* r, uint32_t a) {
  asm volatile("ldmatrix.sync.aligned.m8n8.x4.shared.b16 {%0,%1,%2,%3}, [%4];" : "=r"(r[0]), "=r"(r[1]), "=r"(r[2]), "=r"(r[3]) : "r"(a) : "memory");
}
__device__ __forceinline__ void hmma16(float* c, const uint32_t* a, uint32_t b0, uint32_t b1) {
  asm volatile("mma.sync.aligned.m16n8k16.row.col.f32.bf16.bf16.f32 {%0,%1,%2,%3}, {%4,%5,%6,%7}, {%8,%9}, {%0,%1,%2,%3};"
               : "+f"(c[0]), "+f"(c[1]), "+f"(c[2]), "+f"(c[3]) : "r"(a[0]), "r"(a[1]), "r"(a[2]), "r"(a[3]), "r"(b0), "r"(b1));
}
__device__ __forceinline__ void hmma8(float* c, uint32_t a0, uint32_t a1, uint32_t b0) {
  asm volatile("mma.sync.aligned.m16n8k8.row.col.f32.bf16.bf16.f32 {%0,%1,%2,%3}, {%4,%5}, {%6}, {%0,%1,%2,%3};"
               : "+f"(c[0]), "+f"(c[1]), "+f"(c[2]), "+f"(c[3]) : "r"(a0), "r"(a1), "r"(b0));
}
__device__ __forceinline__ uint4 lds128(uint32_t a) { uint4 v; asm volatile("ld.shared.v4.u32 {%0,%1,%2,%3}, [%4];" : "=r"(v.x), "=r"(v.y), "=r"(v.z), "=r"(v.w) : "r"(a) : "memory"); return v; }
__device__ __forceinline__ void sts128(uint32_t a, uint4 v) { asm volatile("st.shared.v4.u32 [%0], {%1,%2,%3,%4};" :: "r"(a), "r"(v.x), "r"(v.y), "r"(v.z), "r"(v.w) : "memory"); }
__device__ __forceinline__ void sts128f(uint32_t a, float x, float y, float z, float w) { asm volatile("st.shared.v4.f32 [%0], {%1,%2,%3,%4};" :: "r"(a), "f"(x), "f"(y), "f"(z), "f"(w) : "memory"); }
__device__ __forceinline__ void sts64f(uint32_t a, float x, float y) { asm volatile("st.shared.v2.f32 [%0], {%1,%2};" :: "r"(a), "f"(x), "f"(y) : "memory"); }
__device__ __forceinline__ uint32_t lds32(uint32_t a) { uint32_t v; asm volatile("ld.shared.u32 %0, [%1];" : "=r"(v) : "r"(a) : "memory"); return v; }
__device__ __forceinline__ void sts32(uint32_t a, uint32_t v) { asm volatile("st.shared.u32 [%0], %1;" :: "r"(a), "r"(v) : "memory"); }

constexpr uint32_t SBASE = 1024;
__host__ __device__ constexpr uint64_t mkdesc(uint32_t off, uint32_t lbo, uint32_t sbo, uint32_t swz) {
  return (uint64_t)(((SBASE + off) & 0x3FFFF) >> 4) | ((uint64_t)(lbo >> 4) << 16) | ((uint64_t)(sbo >> 4) << 32) | ((uint64_t)swz << 62);
}
__device__ __forceinline__ void wg_fence() { asm volatile("wgmma.fence.sync.aligned;" ::: "memory"); }
__device__ __forceinline__ void wg_commit() { asm volatile("wgmma.commit_group.sync.aligned;" ::: "memory"); }
template <int N> __device__ __forceinline__ void wg_wait() { asm volatile("wgmma.wait_group.sync.aligned %0;" :: "n"(N) : "memory"); }

template <int N> __device__ __forceinline__ void reg_fence(float (&d)[N], int n = N) {
#pragma unroll
  for (int i = 0; i < N; i++) if (i < n) asm volatile("" : "+f"(d[i]) :: "memory");
}
#define F4(b) "+f"(d[b]), "+f"(d[b + 1]), "+f"(d[b + 2]), "+f"(d[b + 3])
#define F8(b) F4(b), F4(b + 4)
#define F16(b) F8(b), F8(b + 8)
#define G4(b) "=f"(d[b]), "=f"(d[b + 1]), "=f"(d[b + 2]), "=f"(d[b + 3])
#define G8(b) G4(b), G4(b + 4)
#define G16(b) G8(b), G8(b + 8)
#define RS_IN "r"(a[0]), "r"(a[1]), "r"(a[2]), "r"(a[3]), "l"(db), "n"(SD), "n"(TB)
#define SS_IN "l"(da), "l"(db), "n"(SD), "n"(TA), "n"(TB)
#define WG_OP(str, out0, out1, in) do { if (SD || KEEP) asm volatile(str : out1 : in); else asm volatile(str : out0 : in); } while (0)
#define O12(X) X##8(0), X##4(8)
#define O20(X) X##16(0), X##4(16)
#define O32(X) X##16(0), X##16(16)
template <int SD, int TB, int KEEP = 0> __device__ __forceinline__ void wgmma_rs24(float* d, const uint32_t* a, uint64_t db) {
  WG_OP("wgmma.mma_async.sync.aligned.m64n24k16.f32.bf16.bf16 {%0,%1,%2,%3,%4,%5,%6,%7,%8,%9,%10,%11}, {%12,%13,%14,%15}, %16, %17, 1, 1, %18;", O12(G), O12(F), RS_IN);
}
template <int SD, int TB, int KEEP = 0> __device__ __forceinline__ void wgmma_rs32(float* d, const uint32_t* a, uint64_t db) {
  WG_OP("wgmma.mma_async.sync.aligned.m64n32k16.f32.bf16.bf16 {%0,%1,%2,%3,%4,%5,%6,%7,%8,%9,%10,%11,%12,%13,%14,%15}, {%16,%17,%18,%19}, %20, %21, 1, 1, %22;", G16(0), F16(0), RS_IN);
}
template <int SD, int TB, int KEEP = 0> __device__ __forceinline__ void wgmma_rs40(float* d, const uint32_t* a, uint64_t db) {
  WG_OP("wgmma.mma_async.sync.aligned.m64n40k16.f32.bf16.bf16 {%0,%1,%2,%3,%4,%5,%6,%7,%8,%9,%10,%11,%12,%13,%14,%15,"
        "%16,%17,%18,%19}, {%20,%21,%22,%23}, %24, %25, 1, 1, %26;", O20(G), O20(F), RS_IN);
}
template <int SD, int TB, int KEEP = 0> __device__ __forceinline__ void wgmma_rs64(float* d, const uint32_t* a, uint64_t db) {
  WG_OP("wgmma.mma_async.sync.aligned.m64n64k16.f32.bf16.bf16 {%0,%1,%2,%3,%4,%5,%6,%7,%8,%9,%10,%11,%12,%13,%14,%15,"
        "%16,%17,%18,%19,%20,%21,%22,%23,%24,%25,%26,%27,%28,%29,%30,%31}, {%32,%33,%34,%35}, %36, %37, 1, 1, %38;", O32(G), O32(F), RS_IN);
}
template <int SD, int TA, int TB, int KEEP = 0> __device__ __forceinline__ void wgmma_ss24(float* d, uint64_t da, uint64_t db) {
  WG_OP("wgmma.mma_async.sync.aligned.m64n24k16.f32.bf16.bf16 {%0,%1,%2,%3,%4,%5,%6,%7,%8,%9,%10,%11}, %12, %13, %14, 1, 1, %15, %16;", O12(G), O12(F), SS_IN);
}
template <int SD, int TA, int TB, int KEEP = 0> __device__ __forceinline__ void wgmma_ss8(float* d, uint64_t da, uint64_t db) {
  WG_OP("wgmma.mma_async.sync.aligned.m64n8k16.f32.bf16.bf16 {%0,%1,%2,%3}, %4, %5, %6, 1, 1, %7, %8;", G4(0), F4(0), SS_IN);
}
__device__ __forceinline__ void bar_arrive(int id, int n) { asm volatile("bar.arrive %0, %1;" :: "r"(id), "r"(n) : "memory"); }
__device__ __forceinline__ uint32_t vis_bits(int pos, int t) {
  uint32_t m = 0;
#pragma unroll
  for (int i = 0; i < 8; i++) m |= (8 * (i / 2 + 1) + 2 * t + (i & 1) <= pos) ? 1u << i : 0u;
  return m;
}

__device__ __forceinline__ unsigned long long wait_words(const unsigned long long* p, uint32_t E) {
  int guard = 0; unsigned long long m;
  while (m = ld_rlxu64(p), !__all_sync(~0u, rfresh(m, E))) { __nanosleep(20); if (++guard > (1 << 22)) TRAP(); }
  fence_acq();
  return m;
}
__device__ __forceinline__ int route_step(int s, uint32_t E, int lane, unsigned long long& run) {
  const unsigned long long m = warp_max<2>(wait_words(f_h2[s][lane & 3], E));
  if (s == 0 || m > run) { run = m; return rtok(m) & 31; }
  return -1;
}

struct Params {
  const bf16 *x, *mem0, *wq, *wk, *wv, *wo, *wr, *wg, *wu, *wd;
  bf16* out;
  uint32_t zero2;
  unsigned long long zero;
};

constexpr uint32_t WSTG_STRIDE = 272;
__device__ __forceinline__ void stage_weights(uint32_t stg, const bf16* src, int ld, int tid, int nthr) {
  for (int i = tid; i < 512 * 16; i += nthr) {
    int k = i >> 4, c = i & 15;
    cp_async16(stg + k * WSTG_STRIDE + c * 16, src + (size_t)k * ld + c * 8);
  }
}
__device__ __forceinline__ void load_frags(uint32_t (*W)[4], uint32_t stg, int wg, int w, int lane) {
  uint32_t a = stg + ((lane >> 4) * 8 + (lane & 7)) * WSTG_STRIDE + (64 * wg + 16 * w + ((lane >> 3) & 1) * 8) * 2;
#pragma unroll
  for (int ks = 0; ks < 32; ks++) ldmatrix4_t(W[ks], a + ks * 16 * WSTG_STRIDE);
}

constexpr uint32_t M_H = 0;
constexpr uint32_t M_MEM = 65536;
constexpr uint32_t M_Q = M_MEM + 24576;
constexpr uint32_t M_K = M_Q + 12288;
constexpr uint32_t M_V = M_K + 12288;
constexpr uint32_t M_OM = M_V + 12288;
constexpr uint32_t M_OST = M_OM + 6144;
constexpr uint32_t M_TST = M_OST + 8192;
constexpr uint32_t M_WO = M_TST + 16384;
constexpr uint32_t M_M0 = M_WO + 49152;
constexpr uint32_t M_PT = M_M0 + 2048;
constexpr uint32_t M_BAR = M_PT + 12288;
constexpr uint32_t M_TOTAL = M_BAR + 384;
static_assert(M_TOTAL <= 232448, "main smem");
static_assert(M_WO >= 512 * WSTG_STRIDE, "staging overlaps Wo");
enum { B_LAND = 0  , B_QK = 3, B_V, B_TOK, B_OM, B_HA, B_HB, B_HAE, B_HBE, B_OST, B_OFREE, B_SYNC,
       B_STG, B_STG1, B_SS, B_TFREE, B_KFREE, B_VFREE, B_FIX  , B_NUM = B_FIX + 8 };
static_assert(B_NUM * 8 <= 256, "barriers");
constexpr uint32_t M_CAND = M_BAR + 256;
constexpr uint32_t M_BASE = M_BAR + 272;
constexpr uint32_t M_ZERO = M_BAR + 280;
constexpr uint32_t M_BAS2 = M_BAR + 328;
constexpr uint32_t M_NEAR = M_BAR + 288;
enum { N_GO1 = 2, N_GO2, N_GO3, N_GO4, N_AG, N_W };

#define GSTAMP(slot, i)
#define TSTAMP(slot, i, k)
#define STAMP(i)
#define ASTAMP(i)
#define WSTAMP(i)
#define CSTAMP(i, v)
#define PIN(x) asm volatile("" : "+r"(x))
#define SCHED(k) asm volatile("{\n.reg .pred p;\nsetp.ne.u32 p, %0, 0;\n@p trap;\n}" :: "r"(zz & (1u << (k))) : "memory")
#define HOLD(k, v) asm volatile("{\n.reg .pred p;\nsetp.ne.u32 p, %0, 0;\n@p st.shared.u32 [%0], %1;\n}" :: "r"(zz & (1u << (k))), "r"(v) : "memory")
#define DRAIN(a) (lds32((a) + zz) & zz)
#define BAR(i) (sb + M_BAR + 8 * (i))

__device__ __forceinline__ int probe(const uint8_t* p, int n) {
  int best = 1 << 30; uint32_t v = 0;
#pragma unroll 1
  for (int r = 0; r < n; r++) {
    uint32_t t0 = clk();
    asm volatile("atom.relaxed.gpu.global.or.b32 %0, [%1], %2;" : "=r"(v) : "l"(p + 3968), "r"(v & 0u) : "memory");
    if (v == 0x7fffffffu) t0++;
    best = min(best, (int)(clk() - t0));
  }
  return best;
}
__device__ __forceinline__ void load_mem0(uint4* u, int k0, int lane, const bf16* mem0) {
#pragma unroll
  for (int i = 0; i < 2; i++) {
    const unsigned short* m = (const unsigned short*)mem0 + k0 + lane + 32 * i;
    u[i] = make_uint4(m[0] | (uint32_t)m[512] << 16, m[1024] | (uint32_t)m[1536] << 16, m[2048] | (uint32_t)m[2560] << 16, m[3072] | (uint32_t)m[3584] << 16);
  }
}

__device__ __forceinline__ void paced_h(uint32_t dst, const uint8_t* src, uint32_t o0, uint32_t o1, uint32_t piece, uint32_t bar, int gap) {
  uint32_t t = clk32();
#pragma unroll 1
  for (uint32_t o = o0; o < o1; o += piece) {
    e_mc(dst + o, src + o, piece, bar, 7);
    spin_until(t += gap);
  }
}

__device__ __forceinline__ void paced_st(uint8_t* dst, uint32_t src, int gap) {
  uint32_t t = clk32();
#pragma unroll 1
  for (uint32_t o = 0; o < 8192; o += SPC_) {
    e_s2g(dst + o, src + o, SPC_);
    if (o + SPC_ < 8192) spin_until(t += gap);
  }
}
__device__ __forceinline__ int block_of(int head, int c) { return REMAP_ ? (c == 2 ? head : 32 + 2 * head + c) : head * 3 + c; }

__device__ __forceinline__ void weight_role(const Params& p, const uint32_t sb, const int warp, const int cta, const int C, const uint32_t E,
                                            const uint8_t* const memg) {
  const int tid = fresh_tid(), lane = tid & 31;
  const int wg = warp >> 2, w = warp & 3;
  uint32_t W[32][4];
  cp_async_wait();
  bar_sync(1, 256);
  load_frags(W, sb, wg, w, lane);
  bar_sync(1, 256);
  if (tid < 128) sts128(sb + M_V + 5 * 2048 + tid * 16, make_uint4(0, 0, 0, 0));
  fence_async_smem();
  cluster_sync();
  if (tid == 0 && cta == 0) GSTAMP(0, 1);
  if (tid == 0) TSTAMP(13, cta, 0);

  const uint32_t rba = mapa(sb, C == 2 ? 0 : 2), rbc = mapa(sb, C == 1 ? 0 : 1);
  const uint32_t MYBAR = M_BAR + 8 * (C < 2 ? B_QK : B_V);
  uint32_t qoff = M_Q + C * 12288 + warp * 256 + lane * 4;
  uint32_t toff = sb + warp * 256 + (lane >> 4) * 2048 + (lane & 15) * 16;
  uint32_t rbar = mapa(sb + M_BAR, min(lane, 2));
  uint32_t sv = sb + M_MEM + lane * 32 + ((lane >> 2) & 3) * 8;
  PIN(qoff); PIN(toff); PIN(rbar); PIN(sv);
  const uint32_t gen0 = (E - 1) * (uint32_t)(NSTEP - 1);
  uint32_t fix = 0;
  const bool sig = w == 0 && lane < 3;
  const int blk = block_of(cta / 3, C);
  const int pk = (blk < 24 ? PAUSE_ : PAUS2_) + (wg ? -PST2_ : PST2_);
  int cand = -1;
  float d[16];
#pragma unroll
  for (int i = 0; i < 16; i++) d[i] = 0.f;
  uint32_t tp[8];
#pragma unroll 1
  for (int T = -1; T < NSTEP; T++) {
    const uint32_t ph = T & 1;
    const uint64_t Z = p.zero << ph;
    const uint32_t zz = p.zero2;
    if (T >= 0) {
      WSTAMP(0);
      const uint64_t db = mkdesc(M_MEM, 128, 256, 0) + Z;
      auto stage = [&]() {
        stmatrix4(toff + M_TST + 8192, tp[0], tp[1], tp[2], tp[3]); stmatrix4(toff + M_TST + 12288, tp[4], tp[5], tp[6], tp[7]);
        if (sig) mbar_arrive_remote(rbar + 8 * B_HBE);
      };
      if (STK_ == 0) stage();
      mbar_wait(BAR(B_LAND), ph);
      WSTAMP(1);
      const uint32_t gt = gentag(gen0 + T);
      auto old = [&](uint32_t a) { return lds32(a) ^ gt; };
      uint32_t bad = 0;
      bool redo = false, ready = false;
      wg_fence();
      wgmma_rs24<0, 1, KP1_>(d, W[0], db);
#pragma unroll
      for (int ks = 1; ks < 32; ks++) {
        if (ks == STK_) stage();
        if (ks == 2) bad |= old(sv + min(warp, 5) * 1024);
        if (ks == 10 || ks == 22) bad |= xo2(lds32(sv + (ks == 10 ? 6 : 15) * 1024 + warp * 1024), lds32(sv + (ks == 10 ? 14 : 23) * 1024), gt);
        if (ks == 6) {
          const uint32_t z5 = DRAIN(toff + M_TST);
          __syncwarp();
          if (lane == 0) mbar_arrive(BAR(B_STG) + z5);
        }
        if (ks == 27) ready = mbar_test(BAR(C < 2 ? B_KFREE : B_VFREE), ph ^ 1) & mbar_test(BAR(B_HA), ph);
        if (ks == RED_) redo = bar_or(N_W, 256, T > 0 && (bad & 0x10001u));
        if (ks == 8 || ks == 20) { mbar_wait(BAR(B_LAND + (ks + 4) / 12), ph); WSTAMP(6 + (ks + 4) / 12); wg_fence(); }
        wgmma_rs24<1, 1>(d, W[ks], db + ks * 48);
      }
      wg_commit();
      uint32_t a0 = rba + qoff, a1 = a0 + 128, a2 = rbc + qoff, a3 = a2 + 128, ba = rba + MYBAR, bc = rbc + MYBAR;
      PIN(a0); PIN(a1); PIN(a2); PIN(a3); PIN(ba); PIN(bc);
      if (!ready) {
        mbar_wait(BAR(C < 2 ? B_KFREE : B_VFREE), ph ^ 1);
        if (T < NSTEP - 1) mbar_wait(BAR(B_HA), ph);
      }
      wg_wait<0>(); reg_fence(d);
      if (__builtin_expect(redo, 0)) {
        auto stale = [&]() { return __any_sync(~0u, (old(sv + warp * 3072) | old(sv + warp * 3072 + 1024) | old(sv + warp * 3072 + 2048)) & 0x10001u); };
        auto fetch = [&](int r) {
          e_expect(BAR(B_FIX + warp), 3072);
          e_g2s(sb + M_MEM + warp * 3072, memg + warp * 8192 + ((uni(lds32(sb + M_NEAR + warp * 4)) ^ r) & 1) * 4096, 3072, BAR(B_FIX + warp));
        };
        bool late = stale();
        if (late) fetch(0);
        constexpr uint64_t dc = mkdesc(M_MEM, 128, 256, 0);
#pragma unroll
        for (int ks = 0; ks < 32; ks++) {
          if (ks % 12 == 0) {
            if (ks) { wg_commit(); wg_wait<0>(); reg_fence(d); }
            if (warp / 3 == ks / 12) {
              for (int guard = 0; late; guard++) {
                mbar_wait(BAR(B_FIX + warp), fix); fix ^= 1;
                late = stale();
                if (late) fetch(ALT_ ? guard + 1 : 0);
                if (guard > (1 << 20)) TRAP();
              }
            }
            bar_sync(N_W, 256);
            wg_fence();
          }
          if (ks == 0) wgmma_rs24<0, 1, 1>(d, W[0], dc); else wgmma_rs24<1, 1>(d, W[ks], dc + ks * 48);
        }
        wg_commit();
        wg_wait<0>(); reg_fence(d);
      }
      WSTAMP(2);
      if (T == 0 && tid == 0) TSTAMP(13, cta, 2);
      uint32_t lo[3], hi[3];
#pragma unroll
      for (int j = 0; j < 3; j++) { lo[j] = pack2(d[4 * j], d[4 * j + 1]); hi[j] = pack2(d[4 * j + 2], d[4 * j + 3]); }
      if (__builtin_expect(T == 0, 0)) { sts32(sb + M_M0 + tid * 8, lo[0]); sts32(sb + M_M0 + tid * 8 + 4, hi[0]); }
      if (__builtin_expect(cand >= 0, 0)) {
        if (T == LAG) { lo[1] = lds32(sb + M_M0 + tid * 8); hi[1] = lds32(sb + M_M0 + tid * 8 + 4); }
        if (C < 2) { st_async32(a0 + 5 * 2048, lo[2], ba); st_async32(a1 + 5 * 2048, hi[2], ba); }
        else { sts32(sb + qoff + 5 * 2048, lo[2]); sts32(sb + qoff + 5 * 2048 + 128, hi[2]); }
        lo[2] = lo[1]; hi[2] = hi[1];
      }
      uint32_t z5;
      if (C == 0) {
        sts32(sb + qoff, lo[0]); sts32(sb + qoff + 128, hi[0]); z5 = DRAIN(sb + qoff);
        st_async32(a0, lo[2], ba); st_async32(a1, hi[2], ba); st_async32(a2, lo[1], bc); st_async32(a3, hi[1], bc);
      } else if (C == 1) {
        sts32(sb + qoff, lo[1]); sts32(sb + qoff + 128, hi[1]); z5 = DRAIN(sb + qoff);
        st_async32(a0, lo[2], ba); st_async32(a1, hi[2], ba); st_async32(a2, lo[0], bc); st_async32(a3, hi[0], bc);
      } else {
        sts32(sb + qoff, lo[2]); sts32(sb + qoff + 128, hi[2]); z5 = DRAIN(sb + qoff);
        st_async32(a0, lo[0], ba); st_async32(a1, hi[0], ba); st_async32(a2, lo[1], bc); st_async32(a3, hi[1], bc);
      }
      __syncwarp();
      if (lane == 0) { mbar_arrive(sb + MYBAR + z5); if (w == 3) mbar_arrive(BAR(B_SS)); }
      if (T == NSTEP - 1) break;
    }
    {
      const uint64_t dh = mkdesc(M_H, 16, 1024, 1) + Z;
      static_assert(E2 == 0 && E3 > 0 && PAUSE_ > 0, "config");
      if (T + 2 < NSEG) {
        if (T < 0) mbar_wait(BAR(B_HA), ph);
        WSTAMP(3);
        wg_fence();
        wgmma_rs32<0, 0, 1>(d, W[0], dh);
#pragma unroll
        for (int ks = 1; ks < EA; ks++) {
          if (ks == E1) { wg_commit(); if (T >= 0) bar_sync(N_GO2, 384); wg_fence(); }
          wgmma_rs32<1, 0>(d, W[ks], dh + (ks >> 2) * 256 + (ks & 3) * 2);
        }
        wg_commit();
        mbar_wait(BAR(B_HB), ph);
        wg_wait<0>();
        if (sig) mbar_arrive_remote(rbar + 8 * B_HAE);
        WSTAMP(4);
        if (T >= 0) bar_sync(N_GO3, 384);
        if (wg == 1) bar_sync(N_W, 256);
        wg_fence();
#pragma unroll
        for (int ks = EA; ks < 32; ks++) wgmma_rs32<1, 0>(d, W[ks], dh + (ks >> 2) * 256 + (ks & 3) * 2);
        wg_commit();
        if (wg == 0) bar_arrive(N_W, 256);
        mbar_wait(BAR(B_TFREE), ph ^ 1);
        wg_wait<0>(); reg_fence(d);
      } else {
        bar_sync(N_GO2, 384);
        mbar_wait(BAR(B_HB), ph);
        if (sig) mbar_arrive_remote(rbar + 8 * B_HAE);
        bar_sync(N_GO3, 384);
        mbar_wait(BAR(B_TFREE), ph ^ 1);
      }
#pragma unroll
      for (int i = 0; i < 8; i++) { tp[i] = pack2(d[2 * i], d[2 * i + 1]); PIN(tp[i]); }
      const uint32_t t1 = toff + (C == 0 && !ph ? M_Q + 2048 : M_TST);
      auto staged = [&]() {
        const uint32_t z5 = DRAIN(t1);
        __syncwarp();
        if (lane == 0) mbar_arrive(BAR(B_STG1) + z5);
      };
      if (T < 0 || (T + 2 >= LAG && T + 2 < NSTEP)) {
        wg_fence();
        wgmma_rs32<0, 0, 1>(d, W[0], dh + 2048);
        stmatrix4(t1, tp[0], tp[1], tp[2], tp[3]); stmatrix4(t1 + 4096, tp[4], tp[5], tp[6], tp[7]);
#pragma unroll
        for (int ks = 1; ks < 32; ks++) {
          if (ks == 5) staged();
          if (ks == PAUSE_ - PST2_ || ks == PAUSE_ + PST2_ || ks == PAUS2_ - PST2_ || ks == PAUS2_ + PST2_) {
            wg_commit();
            if (T >= 0 && ks == pk) bar_sync(N_GO4, 384);
            wg_fence();
          }
          wgmma_rs32<1, 0>(d, W[ks], dh + 2048 + (ks >> 2) * 256 + (ks & 3) * 2);
        }
        wg_commit();
      } else {
        stmatrix4(t1, tp[0], tp[1], tp[2], tp[3]); stmatrix4(t1 + 4096, tp[4], tp[5], tp[6], tp[7]);
        staged();
        bar_sync(N_GO4, 384);
      }
      if (T >= 0) cand = __shfl_sync(~0u, (int)lds32(sb + M_CAND + ((T + 1) & 3) * 4), 0);
      wg_wait<0>(); reg_fence(d);
      if (T >= 0) WSTAMP(6);
      if (T < 0 && tid == 0) TSTAMP(13, cta, 1);
#pragma unroll
      for (int i = 0; i < 8; i++) tp[i] = pack2(d[2 * i], d[2 * i + 1]);
    }
  }
  cluster_sync();
  if (tid == 0 && cta == 0) GSTAMP(0, 5);
}

__device__ __forceinline__ void attn_role(const Params& p, const uint32_t sb, const int w, const int cta, const int head, const int C, const uint32_t E,
                                          uint8_t* const part, uint8_t* const memg) {
  const int tid = fresh_tid(), lane = tid & 31;
  const int g = lane >> 2, t = lane & 3, blk = block_of(head, C);
  uint32_t tag = ((E - 1) * (uint32_t)(NSTEP - 1)) & 1;
  uint4 m0[2][2];
  load_mem0(m0[0], w * 64, lane, p.mem0); load_mem0(m0[1], w * 64 + 256, lane, p.mem0);
  cluster_sync();
#pragma unroll
  for (int k = 0; k < 2; k++) {
#pragma unroll 1
    for (int i = 0; i < 6; i++) sts128(sb + M_MEM + (w + 4 * k) * 3072 + lane * 16 + i * 512, make_uint4(0, 0, 0, 0));
    __syncwarp();
#pragma unroll
    for (int i = 0; i < 2; i++) sts128(sb + M_MEM + ((w + 4 * k) * 4 + (lane >> 4) + 2 * i) * 768 + (lane & 15) * 16, m0[k][i]);
  }
  fence_async_smem();
  bar_sync(N_AG, 128);
  if (w == 3 && lane < 3) mbar_arrive(BAR(B_LAND + lane));
  if (lane == 0) {
    if (w == 0) TSTAMP(15, cta, 0);
    sts32(sb + M_PT + w * 4, probe(part + blk * 16384 + w * 4096, NPROBE_ / 2));
    if (w == 0) TSTAMP(15, cta, 1);
  }
  bar_sync(N_AG, 128);
  const uint32_t inear = lds32(sb + M_PT + (w >> 1) * 8 + 4) < lds32(sb + M_PT + (w >> 1) * 8);
  if (lane == 0 && !(w & 1)) st_rlx(&f_choice[blk][w >> 1], (E << 1) | inear);
  if (w == 0) TSTAMP(15, cta, 2);
  uint32_t nb;
  {
    const int i = min(lane >> 1, C < 2 ? 8 : 5);
    const int r = ((i / 3 * 3 + C) * 4 + w) * 3 + i % 3;
    int guard = 0; uint32_t cw;
    while (__any_sync(~0u, ((cw = ld_rlx(&f_choice[r][lane & 1])) >> 1) != (E & 0x7FFFFFFFu))) { if (++guard > (1 << 22)) TRAP(); }
    nb = __ballot_sync(~0u, cw & 1) >> (lane >> 4);
    if (w == 0) TSTAMP(15, cta, 3);
  }
  bar_sync(N_AG, 128);
  const uint32_t pt0 = sb + M_PT + (tid & 127) * 16;
  {
    const uint32_t po = (C * 4 + w) * 49152 + (lane >> 4) * 8192 + head * 128 + (lane & 15) * 8;
    const uint8_t* in = part + (blk * 16384 + (w >> 1) * 8192 + inear * 4096 + (w & 1) * 64 + (lane >> 3) * 128 + (lane & 7) * 8);
    const uint8_t* outp = memg + ((blk / 12) * 8192 + (blk % 12) * 256 + w * 64 + (lane >> 4) * 4096 + (lane & 4) * 8 + (lane & 8) * 2 + (lane & 3) * 4);
#pragma unroll
    for (int i = 0; i < 12; i++) {
      const int j = i / 4 * 3 + (i & 3);
      const uint8_t* a = (i & 3) < 3 ? part + (po + i / 4 * 589824 + (i & 3) * 16384 + ((nb >> (2 * j)) & 1) * 4096) : i == 11 ? in : outp;
      asm volatile("st.shared.u64 [%0], %1;" :: "r"(pt0 + (i >> 1) * 2048 + (i & 1) * 8), "l"(a) : "memory");
    }
  }
  const int xd = __shfl_sync(~0u, XDLY_ + (blk < 24 ? 0 : blk < 60 ? X1_ : X2_), 0);
  const uint32_t rba = mapa(sb, C == 2 ? 0 : 2), rbc = mapa(sb, C == 1 ? 0 : 1);
  uint32_t vis = vis_bits(8 + 8 * w + g, t);
  uint32_t ln = lane;
#pragma unroll
  for (int i = 0; i < SALT_; i++) ln += lds32(sb + M_ZERO);
  PIN(vis); PIN(ln);
  if (tid == 256 && C == 0) st_rlx(&f_loaded[head], E);
  uint32_t fa[8][4];
#pragma unroll
  for (int ks = 0; ks < 8; ks++) ldmatrix4_t(fa[ks], sb + M_WO + 32768 + w * 256 + (lane >> 4) * 1024 + (lane & 15) * 16 + ks * 2048);
  if (w == 0) TSTAMP(14, cta, 0);
#pragma unroll 1
  for (int T = 0; T < NSTEP; T++) {
    const uint32_t ph = T & 1;
    const uint32_t zz = uni(lds32(sb + M_ZERO));
    const bool more = T < NSTEP - 1;
    const float sc = 0.08838834764831845f * 1.4426950408889634f;
    tag ^= 1;
    float s[20];
    const uint8_t* in; int cnext = -1; uint32_t tx; bool synced;
    float x[10], tm, ts;
    uint32_t pt[5];
    auto tok_max = [&]() {
      PIN(vis);
      x[0] = s[2]; x[1] = s[3];
#pragma unroll
      for (int i = 0; i < 8; i++) x[2 + i] = (vis >> i & 1) ? s[4 * (i / 2 + 1) + 2 + (i & 1)] : -INFINITY;
      tm = fmaxf(fmaxf(fmaxf(fmaxf(x[0], x[1]), fmaxf(x[2], x[3])), fmaxf(fmaxf(x[4], x[5]), fmaxf(x[6], x[7]))), fmaxf(x[8], x[9]));
      HOLD(7, __float_as_uint(tm));
    };
    auto tok_exp1 = [&]() {
      tm = fmaxf(tm, __shfl_xor_sync(~0u, tm, 1));
      tm = fmaxf(tm, __shfl_xor_sync(~0u, tm, 2));
      const float b = -tm * sc;
#pragma unroll
      for (int i = 0; i < 10; i++) x[i] = fmaf(x[i], sc, b);
      HOLD(10, __float_as_uint(x[9]));
    };
    auto tok_exp2 = [&]() {
#pragma unroll
      for (int i = 0; i < 10; i++) x[i] = ex2(x[i]);
      ts = (((x[0] + x[1]) + (x[2] + x[3])) + ((x[4] + x[5]) + (x[6] + x[7]))) + (x[8] + x[9]);
#pragma unroll
      for (int k = 0; k < 5; k++) pt[k] = pack2(x[2 * k], x[2 * k + 1]);
      HOLD(8, __float_as_uint(ts));
    };
    {
      uint32_t q[8][4];
      auto load_q = [&](uint32_t a, int h) {
#pragma unroll
        for (int k2 = 0; k2 < 4; k2++) {
          uint32_t r[4];
          ldmatrix4_t(r, a + k2 * 512);
          q[2 * k2][h] = r[0]; q[2 * k2][h + 2] = r[1]; q[2 * k2 + 1][h] = r[2]; q[2 * k2 + 1][h + 2] = r[3];
        }
      };
      PIN(ln);
      const uint32_t qa = sb + M_Q + ln * 16, qt = qa + w * 2048 + (C == 0 && ph ? M_TST - M_Q : 2048);
      const int cand = C == 2 ? (int)uni(lds32(sb + M_CAND + (T & 3) * 4)) : -1;
      mbar_wait(BAR(B_TOK), ph);
      load_q(qt, 1);
      mbar_wait(BAR(B_QK), ph);
      ASTAMP(0);
      if (T == 0 && w == 0) TSTAMP(13, cta, 3);
      if (__builtin_expect(cand >= 0, 0)) {
        mbar_wait(BAR(B_V), ph);
        PIN(ln);
        const int e = w * 32 + ln;
#pragma unroll
        for (int i = 0; i < 3; i++) {
          const uint32_t v = lds32(sb + M_Q + i * 12288 + 5 * 2048 + e * 16 + 4);
          asm volatile("st.shared.u16 [%0], %1;" :: "r"(sb + M_Q + i * 12288 + (1 + (cand >> 3)) * 2048 + e * 16 + (cand & 7) * 2), "h"((unsigned short)v) : "memory");
        }
        fence_async_smem();
        bar_sync(N_AG, 128);
        load_q(qt, 1);
      }
      load_q(qa, 0);
      if (!(NOF_ & 1)) fence_async_smem();
      constexpr uint64_t dk = mkdesc(M_K, 128, 2048, 0);
      wg_fence();
      wgmma_rs40<0, 1>(s, q[0], dk);
#pragma unroll
      for (int ks = 1; ks < 8; ks++) wgmma_rs40<1, 1>(s, q[ks], dk + ks * 16);
      wg_commit();
    }
    if (more) {
      uint32_t v[5][4];
      PIN(ln);
      const uint32_t va = sb + M_V + w * 512 + ((ln >> 3) & 1) * 128 + (ln >> 4) * 2048 + (ln & 7) * 16;
      const uint32_t ooff = M_OM + w * 1536 + C * 256 + ln * 4;
      mbar_wait(BAR(B_V), ph);
      wg_wait<0>(); reg_fence(s);
      if (ln < 3) mbar_arrive_remote(mapa(BAR(B_KFREE), ln));
      ldmatrix4(v[0], va); ldmatrix4(v[1], va + 256); ldmatrix4(v[2], va + 4096); ldmatrix4(v[3], va + 4096 + 256);
      ldmatrix4(v[4], sb + M_V + 8192 + w * 512 + ln * 16);
      ASTAMP(1);
      float m = fmaxf(fmaxf(fmaxf(fmaxf(s[0], s[1]), fmaxf(s[4], s[5])), fmaxf(fmaxf(s[8], s[9]), fmaxf(s[12], s[13]))), fmaxf(s[16], s[17]));
      m = fmaxf(m, __shfl_xor_sync(~0u, m, 1));
      m = fmaxf(m, __shfl_xor_sync(~0u, m, 2));
      const float b = -m * sc;
      uint32_t pm[5];
#pragma unroll
      for (int j = 0; j < 5; j++) pm[j] = pack2(ex2(fmaf(s[4 * j], sc, b)), ex2(fmaf(s[4 * j + 1], sc, b)));
      float o0[4] = {0.f, 0.f, 0.f, 0.f}, o1[4] = {0.f, 0.f, 0.f, 0.f}, l[4] = {0.f, 0.f, 0.f, 0.f};
      const uint32_t one[4] = {0x3f803f80u, 0x3f803f80u, 0x3f803f80u, 0x3f803f80u};
      hmma16(l, one, pm[0], pm[1]); hmma16(o0, v[0], pm[0], pm[1]); hmma16(o1, v[1], pm[0], pm[1]);
      hmma16(l, one, pm[2], pm[3]); hmma16(o0, v[2], pm[2], pm[3]); hmma16(o1, v[3], pm[2], pm[3]);
      hmma8(l, one[0], one[1], pm[4]); hmma8(o0, v[4][0], v[4][1], pm[4]); hmma8(o1, v[4][2], v[4][3], pm[4]);
      const float r0 = rcp(l[0]), r1 = rcp(l[1]);
      const uint32_t u0 = pack2(o0[0] * r0, o0[1] * r1), u1 = pack2(o0[2] * r0, o0[3] * r1), u2 = pack2(o1[0] * r0, o1[1] * r1), u3 = pack2(o1[2] * r0, o1[3] * r1);
      constexpr uint32_t OB = M_BAR + 8 * B_OM;
      const uint32_t a0 = rba + ooff, a1 = rbc + ooff;
      st_async32(a0, u0, rba + OB); st_async32(a1, u0, rbc + OB);
      st_async32(a0 + 128, u1, rba + OB); st_async32(a1 + 128, u1, rbc + OB);
      st_async32(a0 + 768, u2, rba + OB); st_async32(a1 + 768, u2, rbc + OB);
      st_async32(a0 + 896, u3, rba + OB); st_async32(a1 + 896, u3, rbc + OB);
      bar_arrive(N_GO2, 384);
      sts32(sb + ooff, u0); sts32(sb + ooff + 128, u1); sts32(sb + ooff + 768, u2); sts32(sb + ooff + 896, u3);
      ASTAMP(2);
      uint32_t fb[8][4];
      const uint32_t wa = sb + M_WO + 16384 + w * 256 + (ln >> 4) * 1024 + (ln & 15) * 16 + zz;
      ldmatrix4_t(fb[0], wa);
      SCHED(3);
#pragma unroll
      for (int ks = 1; ks < 8; ks++) {
        ldmatrix4_t(fb[ks], wa + ks * 2048);
        if (ks == ARR_) { __syncwarp(); if (ln == 0) mbar_arrive(BAR(B_OM) + (fb[0][0] & zz)); }
      }
      if (blk % 3 == 2) cnext = (int)uni(lds32(sb + M_CAND + ((T + 1) & 3) * 4));
      {
        float d[12], e[12];
        constexpr uint64_t ob = mkdesc(M_OM, 128, 256, 0);
        uint8_t* q[3][3];
        auto addr = [&](int i) {
          asm volatile("ld.shared.v2.u64 {%0,%1}, [%2];" : "=l"(q[i][0]), "=l"(q[i][1]) : "r"(pt0 + i * 4096) : "memory");
          if (i < 2) asm volatile("ld.shared.u64 %0, [%1];" : "=l"(q[i][2]) : "r"(pt0 + i * 4096 + 2048) : "memory");
          else asm volatile("ld.shared.v2.u64 {%0,%1}, [%2];" : "=l"(q[i][2]), "=l"(in) : "r"(pt0 + i * 4096 + 2048) : "memory");
        };
        auto put = [&](const float* d, int i) {
          st_rlx64(q[i][0], (pack2(d[0], d[1]) & ~1u) | tag, pack2(d[2], d[3]));
          st_rlx64(q[i][1], (pack2(d[4], d[5]) & ~1u) | tag, pack2(d[6], d[7]));
          st_rlx64(q[i][2], (pack2(d[8], d[9]) & ~1u) | tag, pack2(d[10], d[11]));
        };
        addr(0); addr(1);
        SCHED(6);
        tok_max();
        ASTAMP(3);
        mbar_wait(BAR(B_OM), ph);
        if (!(NOF_ & 2)) fence_async_smem();
        ASTAMP(4);
        constexpr uint64_t w0 = mkdesc(M_WO, 1024, 128, 0);
        float (&f)[12] = d;
        wg_fence();
        wgmma_ss24<0, 1, 1>(d, w0, ob);
#pragma unroll
        for (int ks = 1; ks < 8; ks++) wgmma_ss24<1, 1, 1>(d, w0 + ks * 128, ob + ks * 48);
        wg_commit();
        wgmma_rs24<0, 1>(e, fb[0], ob);
#pragma unroll
        for (int ks = 1; ks < HAND_; ks++) wgmma_rs24<1, 1>(e, fb[ks], ob + ks * 48);
        wg_commit();
        wg_wait<1>(); reg_fence(d);
        put(d, 0);
        addr(2);
        SCHED(4);
        ASTAMP(5);
        wg_fence();
#pragma unroll
        for (int ks = HAND_; ks < 8; ks++) wgmma_rs24<1, 1>(e, fb[ks], ob + ks * 48);
        wg_commit();
        wgmma_rs24<0, 1, 1>(f, fa[0], ob);
#pragma unroll
        for (int ks = 1; ks < HAND_; ks++) wgmma_rs24<1, 1>(f, fa[ks], ob + ks * 48);
        wg_commit();
        wg_wait<1>(); reg_fence(e);
        put(e, 1);
        SCHED(5);
        if (C < 2) {
          wg_fence();
#pragma unroll
          for (int ks = HAND_; ks < 8; ks++) wgmma_rs24<1, 1>(f, fa[ks], ob + ks * 48);
          wg_commit();
        }
        if (GO3_ == 0) bar_arrive(N_GO3, 384);
        synced = __all_sync(~0u, mbar_test(BAR(B_SYNC), ph));
        tx = uni(lds32(sb + M_BASE + ph * 4)) + xd;
        wg_wait<0>(); reg_fence(f);
        if (GO3_ == 1) bar_arrive(N_GO3, 384);
        if (C < 2) put(f, 2);
        if (GO3_ == 2) bar_arrive(N_GO3, 384);
        ASTAMP(6);
        if (T == 0 && w == 0) TSTAMP(14, cta, 1);
      }
    } else {
      mbar_wait(BAR(B_V), ph);
      wg_wait<0>(); reg_fence(s);
      tok_max();
    }
    uint2 v[8];
#pragma unroll
    for (int i = 0; i < 8; i++) v[i] = make_uint2(zz, zz);
    auto poll = [&](uint2* v) {
      v[0] = ld_rlx64<0>(in); v[1] = ld_rlx64<512>(in); v[2] = ld_rlx64<1024>(in); v[3] = ld_rlx64<1536>(in);
      v[4] = ld_rlx64<2048>(in); v[5] = ld_rlx64<2560>(in); v[6] = ld_rlx64<3072>(in); v[7] = ld_rlx64<3584>(in);
    };
    uint8_t* outp;
    asm volatile("ld.shared.u64 %0, [%1];" : "=l"(outp) : "r"(pt0 + 2048 + 8) : "memory");
    const uint32_t itag = gentag((E - 1) * (uint32_t)(NSTEP - 1) + T + 1);
    const bool sum = more && cnext < 0;
    if (more) {
      if (!synced) { mbar_wait(BAR(B_SYNC), ph); tx = uni(lds32(sb + M_BASE + ph * 4)) + xd; }
      ASTAMP(7);
      if (__builtin_expect(cnext >= 0, 0)) {
        const unsigned long long* hp = (const unsigned long long*)&g_hc[T + 1 - LAG][0] + ((blk / 3) * 8 + 2 * w + ((ln >> 2) & 1));
        unsigned long long v0; int guard = 0;
        while (v0 = ld_rlxu64(hp), !__all_sync(~0u, (uint32_t)(v0 >> 32) == E)) { if (++guard > (1 << 22)) TRAP(); }
        st_rlx((uint32_t*)outp, (ln & 3) == 1 ? ((uint32_t)v0 >> ((ln & 8) * 2)) & 0xffffu : (ln & 1) ? 0u : itag);
      } else {
        spin_until(tx);
        ASTAMP(8);
        poll(v);
      }
    }
    auto late = [&](const uint2* v) {
      return __any_sync(~0u, (or3(xo2(v[0].x, v[1].x, tag), xo2(v[2].x, v[3].x, tag), xo2(v[4].x, v[5].x, tag)) | xo2(v[6].x, v[7].x, tag)) & 1u);
    };
    tok_exp1(); tok_exp2();
    auto reduce = [&]() {
      if (sum) {
        ASTAMP(9);
        int guard = 0;
        while (late(v)) {
          if (++guard > (1 << 22)) TRAP();
          poll(v);
        }
#pragma unroll
        for (int i = 0; i < 4; i++) { v[i].x = add2(v[i].x, v[i + 4].x); v[i].y = add2(v[i].y, v[i + 4].y); }
        const bool hi = ln & 8;
        const uint32_t x0 = add2(v[0].x, v[1].x), x1 = add2(v[2].x, v[3].x), y0 = add2(v[0].y, v[1].y), y1 = add2(v[2].y, v[3].y);
        const uint32_t m0 = hi ? y0 : x0, m1 = hi ? y1 : x1;
        const uint32_t n0 = __shfl_xor_sync(~0u, hi ? x0 : y0, 8), n1 = __shfl_xor_sync(~0u, hi ? x1 : y1, 8);
        float k0 = (blo(m0) + blo(m1)) + (blo(n0) + blo(n1)), k1 = (bhi(m0) + bhi(m1)) + (bhi(n0) + bhi(n1));
        k0 += __shfl_xor_sync(~0u, k0, 16); k1 += __shfl_xor_sync(~0u, k1, 16);
        st_rlx((uint32_t*)outp, (ln & 1) ? pack2(k0, k1) : pack2_tag(k0, k1, itag));
        ASTAMP(10);
        if (T == 0 && w == 0) TSTAMP(14, cta, 2);
        CSTAMP(12 + w, (clk() & ~15u) | min(guard + 1, 15));
      }
      if (more) bar_arrive(N_GO4, 384);
    };
    if (PVR_ < 0) reduce();
    {
      PIN(ln);
      const uint32_t oa = sb + M_OST + w * 128 + (ln >> 3) * 512 + (ln & 7) * 16;
      const uint32_t a[3][4] = {{0, pt[0], 0, pt[1]}, {0, pt[2], 0, pt[3]}, {0, pt[4], 0, 0}};
      constexpr uint64_t dv = mkdesc(M_V, 2048, 128, 0);
#pragma unroll 1
      for (int h = 0; h < 2; h++) {
        float o[32];
        const uint64_t dh = dv + (uint64_t)(h * 64);
        wg_fence();
        wgmma_rs64<0, 0>(o, a[0], dh); wgmma_rs64<1, 0>(o, a[1], dh + 256); wgmma_rs64<1, 0>(o, a[2], dh + 512);
        wg_commit();
        if (h == PVR_) reduce();
        if (h == 0) {
          ts += __shfl_xor_sync(~0u, ts, 1);
          ts += __shfl_xor_sync(~0u, ts, 2);
          ts = rcp(ts);
          mbar_wait(BAR(B_OFREE), ph ^ 1);
        }
        wg_wait<0>(); reg_fence(o);
        if (h == 1 && ln < 3) mbar_arrive_remote(mapa(BAR(B_VFREE), ln));
#define OT(i) pack2(o[4 * (i) + 2] * ts, o[4 * (i) + 3] * ts)
        stmatrix4(oa + h * 4096, OT(0), OT(1), OT(2), OT(3));
        stmatrix4(oa + h * 4096 + 2048, OT(4), OT(5), OT(6), OT(7));
      }
      const uint32_t z5 = DRAIN(oa);
      __syncwarp();
      if (ln == 0) mbar_arrive(BAR(B_OST) + z5);
      ASTAMP(11);
    }
  }
}

__global__ void __cluster_dims__(3, 1, 1) __launch_bounds__(512, 1) main_kernel(Params p) {
  extern __shared__ __align__(1024) uint8_t sm[];
  const uint32_t sb = smem_u32(sm);
  if ((sb & 0xFFFFFFu) != SBASE) TRAP();
  asm volatile("griddepcontrol.launch_dependents;");
  const int warp = __shfl_sync(~0u, threadIdx.x >> 5, 0);
  const int cta = blockIdx.x, head = cta / 3, c = cta % 3;
  const uint32_t E = __shfl_sync(~0u, *(volatile uint32_t*)&g_epoch + 1, 0);
  uint8_t* const part = (uint8_t*)(((uintptr_t)g_xch + 8191) & ~(uintptr_t)8191);
  uint8_t* const memg = part + 96 * 16384;

  if (threadIdx.x == 0 && cta == 0) GSTAMP(0, 0);
  if (threadIdx.x < B_NUM) {
    const int i = threadIdx.x;
    const uint32_t cnt = i == B_STG || i == B_STG1 ? 8 : i == B_OST ? 4 : i == B_HAE || i == B_HBE ? 6 : i == B_KFREE || i == B_VFREE ? 12 : i == B_SS ? 2 : i == B_OM ? 5 :
                         i == B_QK ? (c < 2 ? 9 : 1) : i == B_V ? (c < 2 ? 1 : 9) : 1;
    mbar_init(BAR(i), cnt);
    if (i == B_HA || i == B_HB || i == B_STG || i == B_HAE || i == B_HBE || i == B_TFREE)
      asm volatile("mbarrier.arrive.shared::cta.b64 _, [%0], %1;" :: "r"(BAR(i)), "r"(cnt) : "memory");
    asm volatile("fence.mbarrier_init.release.cluster;" ::: "memory");
  }
  if (warp < 8) {
    const int tid = threadIdx.x;
    uint4 wa[6], wb[6];
#pragma unroll
    for (int i = 0; i < 6; i++) {
      const int mi = i >> 1, e = (tid >> 2) + (i & 1) * 64;
      const uint4* src = (const uint4*)(p.wo + (size_t)(head * 128 + e) * 512 + min(3 * mi + c, 7) * 64 + (tid & 3) * 16);
      wa[i] = __ldg(src); wb[i] = __ldg(src + 1);
    }
    stage_weights(sb, (c == 0 ? p.wq : c == 1 ? p.wk : p.wv) + head * 128, 4096, tid, 256);
#pragma unroll
    for (int i = 0; i < 6; i++) {
      const int mi = i >> 1, e = (tid >> 2) + (i & 1) * 64;
      const uint4 a = wa[i], b = wb[i];
      const uint32_t dst = sb + M_WO + mi * 16384 + (e >> 3) * 1024 + (tid & 3) * 256 + (e & 7) * 16;
      sts128(dst, make_uint4(__byte_perm(a.x, a.y, 0x5410), __byte_perm(a.z, a.w, 0x5410), __byte_perm(b.x, b.y, 0x5410), __byte_perm(b.z, b.w, 0x5410)));
      sts128(dst + 128, make_uint4(__byte_perm(a.x, a.y, 0x7632), __byte_perm(a.z, a.w, 0x7632), __byte_perm(b.x, b.y, 0x7632), __byte_perm(b.z, b.w, 0x7632)));
    }
  } else {
    const int i0 = threadIdx.x - 256;
    const uint32_t tag0 = ((E - 1) * (uint32_t)(NSTEP - 1)) & 1;
    for (int i = i0; i < 1024; i += 256) *(uint4*)(part + block_of(head, c) * 16384 + i * 16) = make_uint4(tag0, 0, tag0, 0);
    if (i0 < 16) *(uint32_t*)(memg + i0 * 4096 + 3968) = 0;
    if (i0 < 2) st_rlx(&f_choice[block_of(head, c)][i0], 0);
    if (i0 < 8) st_rlx64(&g_sync[i0 >> 2][cta][i0 & 3], 0, 0);
    __threadfence();
    if (i0 < 12) sts32(sb + M_ZERO + i0 * 4, 0);
    if (i0 < 2) { sts32(sb + M_BASE + i0 * 4, clk32() - 65536); sts32(sb + M_BAS2 + i0 * 4, clk32() - 65536); sts32(sb + M_CAND + i0 * 4, (uint32_t)-1); }
  }

  if (warp < 8) {
    asm volatile("setmaxnreg.inc.sync.aligned.u32 " STR(RW_) ";");
    weight_role(p, sb, warp, cta, c, E, memg);
  } else if (warp < 12) {
    if (RA_ < 128) asm volatile("setmaxnreg.dec.sync.aligned.u32 " STR(RA_) ";");
    if (RA_ > 128) asm volatile("setmaxnreg.inc.sync.aligned.u32 " STR(RA_) ";");
    attn_role(p, sb, warp - 8, cta, head, c, E, part, memg);
    cluster_sync();
  } else {
    asm volatile("setmaxnreg.dec.sync.aligned.u32 " STR(RC_) ";");
    const int tid = fresh_tid(), lane = tid & 31;
    const int w = warp - 12;
    cluster_sync();
    if (w != 2) {
      const int tl = w == 0 ? c : w == 1 ? 2 + c : 5 + c;
      int near = 0;
      if (lane == 0) { const int t0 = probe(memg + tl * 8192, NPROBE_ / 2); near = probe(memg + tl * 8192 + 4096, NPROBE_ / 2) < t0; }
      near = uni(near);
      if (lane < 3) asm volatile("st.shared::cluster.u32 [%0], %1;" :: "r"(mapa(sb + M_NEAR + tl * 4, lane)), "r"(near) : "memory");
      __syncwarp();
    }
    if (w == 0) {
      int yadj = 0, dmin = 1 << 20; uint32_t prev = 0; bool cprev = false;
      uint32_t s1 = (2 + c) * 8192, s2 = (5 + c) * 8192;
#pragma unroll 1
      for (int T = 0; T < NSTEP - 1; T++) {
        const uint32_t ph = T & 1;
        mbar_wait(BAR(B_SS), ph);
        const uint32_t cq = clk();
        const uint32_t g0 = (uint32_t)gtime64(); uint32_t g1, ce;
        do { g1 = (uint32_t)gtime64(); ce = clk(); } while (g1 == g0);
        const uint32_t tn = g1 * 8 - (((ce - cq) * 37u) >> 3), id = E * 128u + T;
        if (lane < 4) st_rlx64(&g_sync[ph][cta][lane], tn, id);
        if (lane < 3) mbar_expect(BAR(B_LAND + lane), lane ? 9216 : 6144);
        if (T == 0) { s1 += uni(lds32(sb + M_NEAR + (2 + c) * 4)) * 4096; s2 += uni(lds32(sb + M_NEAR + (5 + c) * 4)) * 4096; }
        wait_until(cq + SDLY_);
        int guard = 0; unsigned long long v0, v1, v2;
        for (;;) {
          v0 = ld_rlxu64(g_sync[ph][lane]); v1 = ld_rlxu64(g_sync[ph][lane + 32]); v2 = ld_rlxu64(g_sync[ph][lane + 64]);
          if (__all_sync(~0u, (uint32_t)(v0 >> 32) == id && (uint32_t)(v1 >> 32) == id && (uint32_t)(v2 >> 32) == id)) break;
          if (++guard > (1 << 22)) TRAP();
        }
        const bool cnd = (int)uni(lds32(sb + M_CAND + (T & 3) * 4)) >= 0;
        const int dl = __reduce_max_sync(~0u, max(max((int)((uint32_t)v0 - tn), (int)((uint32_t)v1 - tn)), (int)((uint32_t)v2 - tn)));
        const uint32_t base = uni(cq + ((min(dl, 8 * 4096) * 7) >> 5)) + (T == 0 ? SLOW0_ : T == 1 ? SLOW1_ : 0) +
                              (cnd ? CDLY_ : 0) - (T + 2 < NSEG ? 0 : BOFF_);
        const int dur = (int)(base - prev);
        if (!cnd && !cprev) {
          yadj = T > 2 && dur > dmin + 700 ? min(yadj + YUP_, 400) : max(yadj - YDN_, 0);
          if (T > 1) dmin = min(dmin + 20, dur);
        }
        prev = base; cprev = cnd;
        if (lane == 0) { sts32(sb + M_BASE + ph * 4, base); sts32(sb + M_BAS2 + ph * 4, base + yadj); mbar_arrive(BAR(B_SYNC)); }
        CSTAMP(0, base); CSTAMP(1, clk());
        const uint32_t ts = base + YDLY_ + yadj - (T + 2 >= LAG && T + 2 < NSEG ? 0 : YOFF_);
        const uint8_t* const t0 = memg + uni(lds32(sb + M_NEAR)) * 4096, * const t1 = memg + 8192 + uni(lds32(sb + M_NEAR + 4)) * 4096;
        wait_until(ts);
        e_g2s(sb + M_MEM, t0, 3072, BAR(B_LAND)); e_g2s(sb + M_MEM + 3072, t1, 3072, BAR(B_LAND));
        CSTAMP(2, clk());
        spin_until(ts + Y1_);
        e_mc(sb + M_MEM + (2 + c) * 3072, memg + s1, 3072, BAR(B_LAND + 1), 7);
        CSTAMP(3, clk());
        spin_until(ts + Y2_);
        e_mc(sb + M_MEM + (5 + c) * 3072, memg + s2, 3072, BAR(B_LAND + 2), 7);
        CSTAMP(4, clk());
      }
    } else if (w == 1) {
#pragma unroll 1
      for (int T = 0; T < NSTEP; T++) {
        const uint32_t ph = T & 1;
        const int s = c == 0 ? T : T - LAG;
        const bool act = s >= 0 && s < NSEG;
        mbar_wait(BAR(B_OST), ph);
        if (cta == 0) TSTAMP(2, T, 0);
        fence_async_smem();
        if (T < NSTEP - 1) wait_until(uni(lds32(sb + M_BAS2 + ph * 4)) + ODLY_);
        STAMP(22);
        if (act) paced_st(g_o[c][s % ORING][head], sb + M_OST, OGAP_);
        if (c == 2 && T < NSTEP - 1) {
          mbar_wait(BAR(B_STG1), ph ^ 1);
          mbar_wait(BAR(B_VFREE), ph);
          STAMP(23);
          e_mc(sb + M_V + 2048, g_tok[cta][ph ^ 1] + 8192, 8192, BAR(B_V), 6);
          e_mc(sb + M_V + 2048, g_tok[cta][ph ^ 1], 8192, BAR(B_V), 1);
        }
        bulk_wait();
        __syncwarp();
        e_arrive(BAR(B_OFREE));
        if (cta == 0) TSTAMP(2, T, 1);
        if (act && lane < 8) st_rel(&f_o[T][head >> 2][c * 4 + (head & 3)][lane], E);
        __syncwarp();
        if (cta == 0) TSTAMP(2, T, 2);
      }
    } else if (w == 2) {
      unsigned long long run = 0;
      static_assert(LAG >= 2, "config");
      constexpr uint32_t NA = EA / 4 * 4096;
      e_expect(BAR(B_QK), c < 2 ? 2048 : 4096); e_expect(BAR(B_V), c == 0 ? 10240 : c == 1 ? 2048 : 0);
      e_expect(BAR(B_TOK), c == 0 ? 16384 : 0); e_expect(BAR(B_OM), 4096);
      e_expect(BAR(B_HA), NA); e_expect(BAR(B_HB), 65536 - NA);
      wait_eq(&f_h1[c == 1 ? 0 : 1], E); fence_async_glob();
      {
        const uint32_t o0 = c == 0 ? NA : 0, o1 = c == 2 ? NA : 32768;
        e_mc(sb + M_H + (c == 1 ? 32768 : 0) + o0, g_h[0][c == 1 ? 0 : 1] + o0, o1 - o0, BAR(c == 2 ? B_HA : B_HB), 7);
      }
      TSTAMP(14, cta, 3);
      if (c == 2) wait_eq(&f_h1[2], E);
      mbar_wait(BAR(B_HAE), 1);
      e_expect(BAR(B_HA), NA);
      if (c == 2) { fence_async_glob(); e_mc(sb + M_H, g_h[0][2], NA, BAR(B_HA), 7); }
      int cprev = -1;
#pragma unroll 1
      for (int T = 0; T < NSTEP - 1; T++) {
        const int s1 = T + 2, s2 = T + 2 - LAG;
        const uint32_t ph = T & 1;
        const bool l1 = s1 < NSEG, l2 = s2 >= 0 && s2 < NSEG, la = s1 + 1 < NSEG;
        const bool mine = c == 0 ? l1 : c == 1 ? l2 : la;
        const uint32_t* fl = c != 1 ? &f_h1[min(s1 + (c >> 1), NSEG - 1)] : (const uint32_t*)f_h2[max(s2, 0)][lane & 3] + 1;
        const uint32_t want = E & 0x1FFFFFu, sh = c != 1 ? 0 : 11;
        mbar_wait(BAR(B_HBE), ph ^ 1);
        const bool early = __all_sync(~0u, ((ld_acq(fl) >> sh) & 0x1FFFFFu) == want);
        mbar_wait(BAR(B_LAND + 2), ph);
        STAMP(16);
        e_expect(BAR(B_HB), (l1 ? 32768 - NA : 0) + (l2 ? 32768 : 0));
        if (mine) {
          if (!early) {
            int guard = 0;
            while (!__all_sync(~0u, ((ld_acq(fl) >> sh) & 0x1FFFFFu) == want)) { __nanosleep(32); if (++guard > (1 << 22)) TRAP(); }
          }
          fence_async_glob();
          if (c == 1) { mbar_wait(BAR(B_QK), ph); spin_until(clk32() + HDLY_); }
          if (c < 2) paced_h(sb + M_H + c * 32768, g_h[c][c ? s2 : s1], c ? 0 : NA, 32768, 4096, BAR(B_HB), HGAP_);
        }
        int cd = -1;
        if (l2) { cd = route_step(s2, E, lane, run); if (cta == 0) TSTAMP(5, s2, 0); }
        if (lane == 0) sts32(sb + M_CAND + ((T + 2) & 3) * 4, (uint32_t)cd);
        __syncwarp();
        STAMP(17);
        mbar_wait(BAR(B_HAE), ph);
        e_expect(BAR(B_HA), la ? NA : 0);
        if (c == 2 && la) {
          spin_until(clk32() + ADLY_);
          STAMP(18);
          paced_h(sb + M_H, g_h[0][s1 + 1], 0, NA, 4096, BAR(B_HA), AGAP_);
        }
        mbar_wait(BAR(B_OST), ph);
        e_expect(BAR(B_QK), c < 2 ? 2048 : cprev >= 0 ? 8192 : 4096);
        e_expect(BAR(B_V), c < 2 ? 10240 : 8192);
        e_expect(BAR(B_TOK), c == 0 ? 8192 : 16384);
        e_expect(BAR(B_OM), 4096);
        cprev = cd;
      }
    } else {
      const uint32_t mytok = sb + M_Q + c * 12288 + 2048, tb = BAR(c < 2 ? B_TOK : B_V);
      mbar_wait(BAR(B_STG1), 0);
      fence_async_smem();
      if (c) e_s2g(g_tok[cta][1], sb + M_TST, 8192);
#pragma unroll 1
      for (int T = 0; T < NSTEP - 1; T++) {
        const uint32_t ph = T & 1;
        uint8_t* const tok = g_tok[cta][ph ^ 1];
        mbar_wait(BAR(B_STG), ph ^ 1);
        fence_async_smem();
        if (cta == 0 && (T == 0 || T == NSEG || T == NSTEP - 2)) GSTAMP(0, T == 0 ? 2 : T == NSEG ? 3 : 4);
        if (T > 0 && TQ_) mbar_wait(BAR(B_QK), ph);
        STAMP(20);
        paced_st(tok + 8192, sb + M_TST + 8192, TGAP_);
        bulk_wait();
        __syncwarp();
        e_arrive(BAR(B_TFREE));
        if (T == 0) e_mc(mytok, tok + 8192, 8192, tb, 1);
        STAMP(21);
        if (c < 2) {
          mbar_wait(BAR(B_KFREE), ph);
          spin_until(clk32() + KDLY_);
          STAMP(23);
          if (c) e_mc(mytok, tok, 8192, tb, 1);
          e_mc(mytok, tok + 8192, 8192, tb, 6);
        }
        mbar_wait(BAR(B_STG1), ph ^ 1);
        fence_async_smem();
        wait_until(uni(lds32(sb + M_BAS2 + ph * 4)) + TDLY_);
        if (c) paced_st(g_tok[cta][ph], sb + M_TST, T1GAP_);
        STAMP(24);
      }
      bulk_wait();
    }
    __syncwarp();
    cluster_sync();
  }
}

constexpr uint32_t A_RING = 0;
constexpr int A_NST = 6;
constexpr uint32_t A_STG = A_RING + A_NST * 8192;
constexpr uint32_t A_WD = A_STG + 8192;
constexpr uint32_t A_WG = A_WD + 57344;
constexpr uint32_t A_WU = A_WG + 57344;
constexpr uint32_t A_XN = A_WU + 57344;
constexpr uint32_t A_BAR = A_XN + 2048;
constexpr uint32_t A_TOTAL = A_BAR + 256;
static_assert(A_TOTAL <= 232448, "aux smem");

__device__ __forceinline__ uint32_t ptag(int s) { return ((s / PRING) & 1) ^ 1; }
static_assert((NSEG / PRING) % 2 == 0, "tags");
__device__ __forceinline__ void load_row(uint32_t* v, const void* row, int lane) {
  const uint4 a = __ldcg((const uint4*)row + lane), b = __ldcg((const uint4*)row + 32 + lane);
  v[0] = a.x; v[1] = a.y; v[2] = a.z; v[3] = a.w; v[4] = b.x; v[5] = b.y; v[6] = b.z; v[7] = b.w;
}
__device__ __forceinline__ void store_row(void* row, const uint32_t* v, int lane) {
  ((uint4*)row)[lane] = make_uint4(v[0], v[1], v[2], v[3]); ((uint4*)row)[32 + lane] = make_uint4(v[4], v[5], v[6], v[7]);
}
__device__ __forceinline__ void store_img(uint8_t* img, int r, const uint32_t* v, int lane) {
  uint8_t* b = img + (lane >> 3) * 4096 + (r >> 3) * 1024 + (r & 7) * 128 + (((lane ^ r) & 7) << 4);
  *(uint4*)b = make_uint4(v[0], v[1], v[2], v[3]);
  *(uint4*)(b + 16384) = make_uint4(v[4], v[5], v[6], v[7]);
}
template <int NT> __device__ __forceinline__ void ln_rows(const uint32_t (*v)[8], uint32_t (*y)[8]) {
  float c[NT], sm[NT], sq[NT];
#pragma unroll
  for (int k = 0; k < NT; k++) {
    c[k] = blo(__shfl_sync(~0u, v[k][0], 0));
    float s0 = 0.f, s1 = 0.f, q0 = 0.f, q1 = 0.f;
#pragma unroll
    for (int i = 0; i < 8; i++) { const float a = blo(v[k][i]) - c[k], b = bhi(v[k][i]) - c[k]; s0 += a; s1 += b; q0 = fmaf(a, a, q0); q1 = fmaf(b, b, q1); }
    sm[k] = s0 + s1; sq[k] = q0 + q1;
  }
#pragma unroll
  for (int o = 16; o > 0; o >>= 1)
#pragma unroll
    for (int k = 0; k < NT; k++) {
      sm[k] += __shfl_xor_sync(~0u, sm[k], o); sq[k] += __shfl_xor_sync(~0u, sq[k], o);
    }
#pragma unroll
  for (int k = 0; k < NT; k++) {
    const float dm = sm[k] * (1.f / 512.f), var = fmaxf(fmaf(-dm, dm, sq[k] * (1.f / 512.f)), 0.f);
    const float mb = rbf(c[k] + dm), inv = rcp(rbf(sqrt_fast(rbf(rbf(var) + 1e-5f))));
#pragma unroll
    for (int i = 0; i < 8; i++) { const uint32_t a = pack2(blo(v[k][i]) - mb, bhi(v[k][i]) - mb); y[k][i] = pack2(blo(a) * inv, bhi(a) * inv); }
  }
}
__device__ __forceinline__ void input_ln_pair(const bf16* x, int s, int pr, int lane) {
  uint32_t v[2][8], y[2][8];
  load_row(v[0], x + (size_t)(s * 32 + 2 * pr) * 512, lane); load_row(v[1], x + (size_t)(s * 32 + 2 * pr + 1) * 512, lane);
  ln_rows<2>(v, y);
  store_img(g_h[0][s], 2 * pr, y[0], lane); store_img(g_h[0][s], 2 * pr + 1, y[1], lane);
}
__device__ __forceinline__ float load_wr(uint32_t* wv, const bf16* wr, int lane) {
  load_row(wv, wr, lane);
  float wsum = 0.f;
#pragma unroll
  for (int i = 0; i < 8; i++) wsum += blo(wv[i]) + bhi(wv[i]);
#pragma unroll
  for (int o = 16; o > 0; o >>= 1) wsum += __shfl_xor_sync(~0u, wsum, o);
  return wsum;
}

template <bool FAST>
__device__ __forceinline__ unsigned long long token_post(int st, int tk, const bf16* res, bf16* dst, bf16* req, unsigned long long best,
                                                         const uint32_t* wv, float wsum, uint32_t E, int lane) {
  const int s = tk >> 5;
  uint32_t x[8];
  load_row(x, res, lane);
  {
    int guard = 0;
    while (__popc(__ballot_sync(~0u, ld_rlx(f_acc[st][s][lane]) == E)) < (FAST ? HINT_ : 32)) { __nanosleep(FAST ? 20 : 100); if (++guard > (1 << 22)) TRAP(); }
  }
  if (tk == s * 32 && st == 0 && lane == 0) TSTAMP(4, s, 0);
  {
    const uint8_t* pp = g_pp[st][s % PRING] + (lane >> 4) * 8192 + (tk & 31) * 256 + (((lane & 15) ^ (tk & 7)) << 4);
    const uint32_t tag = ptag(s);
    uint4 q[8][2];
#define PLD(k, h) q[k][h] = ld_rlx128<(k) * 32768 + (h) * 16384>(pp)
#define PLD8(h) PLD(0, h); PLD(1, h); PLD(2, h); PLD(3, h); PLD(4, h); PLD(5, h); PLD(6, h); PLD(7, h)
#define PBAD(h) __any_sync(~0u, (or3(xo2(q[0][h].x, q[1][h].x, tag), xo2(q[2][h].x, q[3][h].x, tag), xo2(q[4][h].x, q[5][h].x, tag)) | xo2(q[6][h].x, q[7][h].x, tag)) & ~lane & (PST_ == 8192 ? 1u : 0u))
#define PSUM(f, h, m) (((f(q[0][h].m) + f(q[1][h].m)) + (f(q[2][h].m) + f(q[3][h].m))) + ((f(q[4][h].m) + f(q[5][h].m)) + (f(q[6][h].m) + f(q[7][h].m))))
    const uint32_t eye = (lane >> 2) == 2 * (lane & 3) ? 0x3f80u : (lane >> 2) == 2 * (lane & 3) + 1 ? 0x3f800000u : 0u;
    auto padd = [&](int h) {
      if (FAST) {
        float u[4] = {0.f, 0.f, 0.f, 0.f}, v[4] = {0.f, 0.f, 0.f, 0.f};
#pragma unroll
        for (int k = 0; k < 8; k++) { hmma8(u, q[k][h].x, q[k][h].y, eye); hmma8(v, q[k][h].z, q[k][h].w, eye); }
        x[4 * h] = add2(x[4 * h], pack2(u[0], u[1])); x[4 * h + 1] = add2(x[4 * h + 1], pack2(u[2], u[3]));
        x[4 * h + 2] = add2(x[4 * h + 2], pack2(v[0], v[1])); x[4 * h + 3] = add2(x[4 * h + 3], pack2(v[2], v[3]));
      } else {
        x[4 * h] = add2(x[4 * h], pack2(PSUM(blo, h, x), PSUM(bhi, h, x))); x[4 * h + 1] = add2(x[4 * h + 1], pack2(PSUM(blo, h, y), PSUM(bhi, h, y)));
        x[4 * h + 2] = add2(x[4 * h + 2], pack2(PSUM(blo, h, z), PSUM(bhi, h, z))); x[4 * h + 3] = add2(x[4 * h + 3], pack2(PSUM(blo, h, w), PSUM(bhi, h, w)));
      }
    };
    int guard = 0;
    PLD8(0);
    if (FAST) { PLD8(1); }
    while (PBAD(0)) { if (++guard > (1 << 20)) TRAP(); PLD8(0); }
    padd(0);
    if (!FAST) { PLD8(1); }
    while (PBAD(1)) { if (++guard > (1 << 20)) TRAP(); PLD8(1); }
    padd(1);
  }
  const float c = blo(__shfl_sync(~0u, x[0], 0));
  float s0 = 0.f, s1 = 0.f, q0 = 0.f, q1 = 0.f, r0 = 0.f, r1 = 0.f;
#pragma unroll
  for (int i = 0; i < 8; i++) {
    const float a = blo(x[i]) - c, b = bhi(x[i]) - c;
    s0 += a; s1 += b; q0 = fmaf(a, a, q0); q1 = fmaf(b, b, q1); r0 = fmaf(a, blo(wv[i]), r0); r1 = fmaf(b, bhi(wv[i]), r1);
  }
  s0 += s1; q0 += q1; r0 += r1;
#pragma unroll
  for (int o = 16; o > 0; o >>= 1) { s0 += __shfl_xor_sync(~0u, s0, o); q0 += __shfl_xor_sync(~0u, q0, o); r0 += __shfl_xor_sync(~0u, r0, o); }
  const float dm = s0 * (1.f / 512.f), m = c + dm, var = fmaxf(fmaf(-dm, dm, q0 * (1.f / 512.f)), 0.f);
  const float mb = rbf(m), inv = rcp(rbf(sqrt_fast(rbf(rbf(var) + 1e-5f))));
  const uint32_t nmb = pack2(-mb, -mb);
  const unsigned long long wd = rword(E, tk, fmaf(c - mb, wsum, r0) * inv);
  uint32_t xn[8], x2[8];
#pragma unroll
  for (int i = 0; i < 8; i++) { const uint32_t d = add2(x[i], nmb); xn[i] = pack2(blo(d) * inv, bhi(d) * inv); x2[i] = add2(x[i], xn[i]); }
  if (st == 0) {
    const float mb2 = rbf(fmaf(m - mb, inv, m)), inv2 = rcp(rbf(sqrt_fast(rbf(rbf(var * (1.f + inv) * (1.f + inv)) + 1e-5f))));
    const uint32_t nmb2 = pack2(-mb2, -mb2);
    uint32_t h[8];
#pragma unroll
    for (int i = 0; i < 8; i++) { const uint32_t d2 = add2(x2[i], nmb2); h[i] = pack2(blo(d2) * inv2, bhi(d2) * inv2); }
    store_img(g_h[1][s], tk & 31, h, lane);
  }
  store_row(dst, x2, lane);
  if (wd > best && !(EXPQ_ & (st == 0 ? 1 : 2))) { store_row(req, xn, lane); store_row(req + 512, x, lane); }
  return wd;
}

__device__ __forceinline__ void ffn_slice(uint32_t sb, const bf16* xn, float* yacc, uint32_t* flag, uint32_t E, int t, bool urgent) {
  const int w = t >> 5, g = (t >> 2) & 7;
  if (t == 0 && urgent) sts32(sb + A_BAR + 160, 1);
  { const uint2 u = __ldcg((const uint2*)xn + t); asm volatile("st.shared.v2.u32 [%0], {%1,%2};" :: "r"(sb + A_XN + t * 8), "r"(u.x), "r"(u.y) : "memory"); }
  fence_async_smem();
  bar_sync(4, 128);
  float ga[4], ua[4];
  constexpr uint64_t da = mkdesc(A_WG, 896, 128, 0), db = mkdesc(A_XN, 16, 128, 0);
  wg_fence();
  wgmma_ss8<0, 1, 0>(ga, da, db); wgmma_ss8<0, 1, 0>(ua, da + (A_WU - A_WG) / 16, db);
#pragma unroll
  for (int ks = 1; ks < 32; ks++) { wgmma_ss8<1, 1, 0>(ga, da + ks * 112, db + ks * 2); wgmma_ss8<1, 1, 0>(ua, da + (A_WU - A_WG) / 16 + ks * 112, db + ks * 2); }
  wg_commit(); wg_wait<0>(); reg_fence(ga); reg_fence(ua);
  if ((t & 3) == 0) {
#pragma unroll
    for (int h = 0; h < 2; h++) {
      const float gs = rbf(ga[2 * h]), us = rbf(ua[2 * h]);
      const float v = 16 * w + 8 * h < 56 ? rbf(gs * rcp(1.f + __expf(-gs))) * us : 0.f;
      asm volatile("st.shared.u16 [%0], %1;" :: "r"(sb + A_XN + 1280 + (16 * w + 8 * h + g) * 2), "h"((unsigned short)pack2(v, 0.f)) : "memory");
    }
  }
  fence_async_smem();
  bar_sync(4, 128);
#pragma unroll 1
  for (int j = 0; j < 2; j++) {
    float y[4][4];
    const uint64_t dd = mkdesc(A_WD, 8192, 128, 0) + (uint64_t)(j * 256);
    wg_fence();
#pragma unroll
    for (int m = 0; m < 4; m++) {
      wgmma_ss8<0, 1, 0>(y[m], dd + m * 64, mkdesc(A_XN + 1280, 16, 128, 0));
#pragma unroll
      for (int ks = 1; ks < 4; ks++) wgmma_ss8<1, 1, 0>(y[m], dd + m * 64 + ks * 1024, mkdesc(A_XN + 1280 + ks * 32, 16, 128, 0));
    }
    wg_commit(); wg_wait<0>();
#pragma unroll
    for (int m = 0; m < 4; m++) {
      reg_fence(y[m]);
      if ((t & 3) == 0) { float* o = yacc + j * 256 + m * 64 + 16 * w + g; o[0] = y[m][0]; o[8] = y[m][2]; }
    }
  }
  bar_sync(4, 128);
  if (t < 8) { sts32(sb + A_BAR + 160, 0); st_rel(flag + t, E); }
  __syncwarp();
}

__device__ __forceinline__ void ffn_gather(uint32_t sb, int q, int j, uint32_t E, int lane) {
  wait_all(f_y[q][4 * j + (lane & 3)], E);
  float4 y[4][4];
#pragma unroll
  for (int k = 0; k < 4; k++)
#pragma unroll
    for (int i = 0; i < 4; i++) y[k][i] = __ldcg((const float4*)g_y[q & 7][4 * j + k] + i * 32 + lane);
#pragma unroll
  for (int i = 0; i < 4; i++)
    sts128f(sb + 1024 + j * 2048 + i * 512 + lane * 16, (y[0][i].x + y[1][i].x) + (y[2][i].x + y[3][i].x), (y[0][i].y + y[1][i].y) + (y[2][i].y + y[3][i].y),
            (y[0][i].z + y[1][i].z) + (y[2][i].z + y[3][i].z), (y[0][i].w + y[1][i].w) + (y[2][i].w + y[3][i].w));
  bar_sync(9, 256);
}
__device__ __forceinline__ void ffn_finish(uint32_t sb, int q, const bf16* req, float r, uint32_t E, int lane, uint32_t* v) {
  if (lane == 0) sts32(sb + 16, q);
  bar_sync(8, 256);
  uint32_t xn[8];
  load_row(xn, req, lane); load_row(v, req + 512, lane);
  const float rs = rbf(1.f / (1.f + __expf(-rbf(r))));
  ffn_gather(sb, q, 7, E, lane);
#pragma unroll
  for (int i = 0; i < 4; i++) {
    float y[4] = {0.f, 0.f, 0.f, 0.f};
#pragma unroll
    for (int j = 0; j < 8; j++) {
      const uint4 u = lds128(sb + 1024 + j * 2048 + (i >> 1) * 1024 + lane * 32 + (i & 1) * 16);
      y[0] += __uint_as_float(u.x); y[1] += __uint_as_float(u.y); y[2] += __uint_as_float(u.z); y[3] += __uint_as_float(u.w);
    }
    v[2 * i] = add2(v[2 * i], add2(xn[2 * i], pack2(rbf(y[0]) * rs, rbf(y[1]) * rs)));
    v[2 * i + 1] = add2(v[2 * i + 1], add2(xn[2 * i + 1], pack2(rbf(y[2]) * rs, rbf(y[3]) * rs)));
  }
}

__global__ void __launch_bounds__(512, 1) aux_kernel(Params p) {
  extern __shared__ __align__(1024) uint8_t sm[];
  const uint32_t sb = smem_u32(sm);
  if ((sb & 0xFFFFFFu) != SBASE) TRAP();
  const int warp = __shfl_sync(~0u, threadIdx.x >> 5, 0);
  const int cta = blockIdx.x;
  const uint32_t E = __shfl_sync(~0u, *(volatile uint32_t*)&g_epoch + 1, 0);
  const uint32_t bars = sb + A_BAR;

  if (cta < 32) {
    const int cg = cta & 3, kg = cta >> 2;
    if (threadIdx.x == 0) {
      for (int i = 0; i < A_NST; i++) { mbar_init(bars + 8 * i, 1); mbar_init(bars + 64 + 8 * i, 2); }
      mbar_init(bars + 128, 8); mbar_init(bars + 136, 8); mbar_init(bars + 144, 1);
      sts32(bars + 160, 0);
      asm volatile("fence.mbarrier_init.release.cluster;" ::: "memory");
    }
    if (warp < 8) {
      asm volatile("setmaxnreg.inc.sync.aligned.u32 176;");
      const int tid = fresh_tid(), lane = tid & 31;
      uint32_t W[32][4];
      stage_weights(sb + A_WD, p.wo + (size_t)kg * 512 * 512 + cg * 128, 512, tid, 256);
      cp_async_wait();
      bar_sync(1, 256);
      load_frags(W, sb + A_WD, warp >> 2, warp & 3, lane);
      bar_sync(2, 512);
      const uint32_t so = sb + A_STG + ((lane >> 4) * 8 + (lane & 7)) * 256 + (((warp * 2 + ((lane >> 3) & 1)) ^ (lane & 7)) << 4);
      const uint32_t tm = lane < 4 ? 0x00010001u : 0u;
      int stage = 0; uint32_t ph = 0, job = 0;
#pragma unroll 1
      for (int T = 0; T < NSTEP; T++) {
#pragma unroll 1
        for (int k = 0; k < 3; k++) {
          const int st = k == 0 ? 0 : 3 - k, s = st == 0 ? T : T - LAG;
          if (s < 0 || s >= NSEG) continue;
          float d[16];
#pragma unroll
          for (int hh = 0; hh < 4; hh++) {
            mbar_wait(bars + 8 * stage, ph);
            while (uni(lds32(bars + 160))) __nanosleep(100);
            const uint64_t db = mkdesc(A_RING, 512, 128, 0) + (uint64_t)(stage * 512);
            wg_fence();
            if (hh == 0) wgmma_rs32<0, 0>(d, W[0], db); else wgmma_rs32<1, 0>(d, W[hh * 8], db);
#pragma unroll
            for (int ks = 1; ks < 8; ks++) wgmma_rs32<1, 0>(d, W[hh * 8 + ks], db + ks * 64);
            wg_commit();
            if (hh > 0) { wg_wait<1>(); if ((tid & 127) == 0) mbar_arrive(bars + 64 + 8 * (stage == 0 ? A_NST - 1 : stage - 1)); }
            if (++stage == A_NST) { stage = 0; ph ^= 1; }
          }
          mbar_wait(bars + 144, (job & 1) ^ 1);
          wg_wait<0>(); reg_fence(d);
          if ((tid & 127) == 0) mbar_arrive(bars + 64 + 8 * (stage == 0 ? A_NST - 1 : stage - 1));
          if (cta == 0 && tid == 0) TSTAMP(6, T, k);
          const uint32_t tv = tm * ptag(s);
#define TG(i) ((pack2(d[2 * (i)], d[2 * (i) + 1]) & ~tm) | tv)
          stmatrix4_t(so, TG(0), pack2(d[2], d[3]), TG(2), pack2(d[6], d[7]));
          stmatrix4_t(so + 4096, TG(4), pack2(d[10], d[11]), TG(6), pack2(d[14], d[15]));
          fence_async_smem();
          __syncwarp();
          if (lane == 0) mbar_arrive(bars + 128 + 8 * (job & 1));
          job++;
        }
      }
    } else if (warp < 12) {
      asm volatile("setmaxnreg.dec.sync.aligned.u32 120;");
      const int tid = fresh_tid(), lane = tid & 31;
      const int w = warp - 8, t = tid - 256;
#pragma unroll 1
      for (int s = cta + 4; s < NSEG; s += 32) {
#pragma unroll 1
        for (int pr = w; pr < 16; pr += 4) input_ln_pair(p.x, s, pr, lane);
        bar_sync(4, 128);
        if (t == 0) st_rel(&f_h1[s], E);
      }
      bar_sync(2, 512);
      { int guard = 0; while (ld_rlx(&f_loaded[cta]) != E) { __nanosleep(200); if (++guard > (1 << 22)) TRAP(); } }
#pragma unroll 1
      for (int i = t; i < 512 * 7; i += 128) {
        const int k = i / 7, pc = i % 7;
        cp_async16(sb + A_WG + (k >> 3) * 896 + pc * 128 + (k & 7) * 16, p.wg + (size_t)k * 1792 + cta * 56 + pc * 8);
        cp_async16(sb + A_WU + (k >> 3) * 896 + pc * 128 + (k & 7) * 16, p.wu + (size_t)k * 1792 + cta * 56 + pc * 8);
        cp_async16(sb + A_WD + (i >> 9) * 8192 + (i & 63) * 128 + ((i >> 6) & 7) * 16, p.wd + (size_t)cta * 56 * 512 + i * 8);
      }
      uint32_t wv[8];
      const float wsum = load_wr(wv, p.wr, lane);
      cp_async_wait();
      fence_async_smem();
      bar_sync(4, 128);
      const int tj = (cta * 4 + w) & 31, st = 1 + ((cta >> 3) & 1), sq = cta >> 4;
      unsigned long long run = 0, run2 = 0, best = 0, hist = 0;
      uint32_t open = 0;
#pragma unroll 1
      for (int i = 0; i <= NSTEP; i++) {
        int tok = -1; const bf16* req = nullptr;
        if (i < NSEG) {
          const int cd = (int)uni(route_step(i, E, lane, run));
          run = __shfl_sync(~0u, run, 0);
          hist = hist << 8 | (uint32_t)(cd + 1);
          if (cd >= 0) { tok = rtok(run); req = g_req1[tok][0]; }
        } else {
          const unsigned long long m = wait_words(f_l2[i - NSEG], E);
          const unsigned long long n = ld_rlxu64(f_l2[min(i - NSEG + 1 + (lane & 7), LAG)]);
          const bool over = bar_or(4, 128, rfresh(n, E) && n != m);
          if (m != run2 && !over) { run2 = m; tok = rtok(m); req = g_req2[(tok >> 5) < (rtok(run) >> 5) ? 0 : 1][tok][0]; }
        }
        tok = __shfl_sync(~0u, tok, 0);
        if (tok >= 0) {
          if (cta == 0 && t == 0) TSTAMP(8, i, 0);
          ffn_slice(sb, req, g_y[i & 7][cta], f_y[i][cta], E, t, i < NSEG);
          if (cta == 0 && t == 0) TSTAMP(8, i, 1);
        }
        const int s = i - LAG;
        if (s < 0 || i >= NSEG) continue;
        const int cd = (int)((hist >> (8 * LAG)) & 255) - 1;
        if (cd >= 0 && st == 2) best = 0;
        const int ts = rtok(run) >> 5;
        if ((s & 1) == sq) {
          const int tk = s * 32 + tj;
          unsigned long long wd = (unsigned long long)E << 43;
          if (st == 1 ? s < ts || i < NSEG - 1 : s >= ts) {
            if (st == 2 && cd == tj) wait_eq(&f_hc[s], E);
            wd = token_post<false>(st, tk, st == 2 && cd == tj ? g_x2c[s] : g_x2 + (size_t)tk * 512,
                                   (st == 2 || s < ts ? p.out : g_n) + (size_t)tk * 512, g_req2[st - 1][tk][0], best, wv, wsum, E, lane);
            best = max(best, wd);
            if (st == 1 && s >= ts) open |= 1u << (s >> 1);
          }
          __syncwarp();
          if (lane < 4) st_rel64(&f_w2[st - 1][s][tj][lane], wd);
          __syncwarp();
        }
        if (st == 1) {
          if (i == NSEG - 1 && t == 0 && cta == 0) GSTAMP(1, 0);
#pragma unroll 1
          for (int n = i == NSEG - 1 ? 32 : 2; n > 0 && open; n--) {
            const int s0 = 2 * (__ffs(open) - 1) + sq;
            if (s0 >= ts) break;
            open &= open - 1;
            uint32_t v[8];
            load_row(v, g_n + (size_t)(s0 * 32 + tj) * 512, lane);
            wait_words(f_w2[1][s0][tj], E);
            store_row(p.out + (size_t)(s0 * 32 + tj) * 512, v, lane);
          }
          if (i == NSEG - 1) {
            __syncwarp();
            if (lane == 0) st_rel(&f_cp[sq * 32 + tj], E);
            if (t == 0 && cta == 0) GSTAMP(1, 3);
          }
        }
      }
    } else {
      asm volatile("setmaxnreg.dec.sync.aligned.u32 40;");
      const int tid = fresh_tid(), lane = tid & 31;
      const int w = warp - 12;
      bar_sync(2, 512);
      if (w == 0) {
        int stage = 0; uint32_t ph = 1;
#pragma unroll 1
        for (int T = 0; T < NSTEP; T++) {
#pragma unroll 1
          for (int k = 0; k < 3; k++) {
            const int st = k == 0 ? 0 : 3 - k, s = st == 0 ? T : T - LAG;
            if (s < 0 || s >= NSEG) continue;
            const uint32_t* fl = f_o[T][kg][st * 4 + (lane & 3)];
            uint32_t ready = 0; int guard = 0;
#pragma unroll 1
            for (int hh = 0; hh < 4; hh++) {
              while (!((ready >> hh) & 1)) {
                ready = __ballot_sync(~0u, ld_rlx(fl) == E);
                if (++guard > (1 << 23)) TRAP();
              }
              fence_async_glob();
              mbar_wait(bars + 64 + 8 * stage, ph);
              e_expect(bars + 8 * stage, OLOAD_);
              e_g2s(sb + A_RING + stage * 8192, g_o[st][s % ORING][kg * 4 + hh], OLOAD_, bars + 8 * stage);
              if (++stage == A_NST) { stage = 0; ph ^= 1; }
            }
          }
          if (cta == 0 && lane == 0) TSTAMP(3, T, 0);
        }
      } else if (w < 3) {
        uint32_t job = 0;
#pragma unroll 1
        for (int T = 0; T < NSTEP; T++) {
#pragma unroll 1
          for (int k = 0; k < 3; k++) {
            const int st = k == 0 ? 0 : 3 - k, s = st == 0 ? T : T - LAG;
            if (s < 0 || s >= NSEG) continue;
            if ((job++ & 1) != w - 1) continue;
            if (s >= PRING) wait_words(st == 0 ? f_h2[s - PRING][lane & 3] : f_w2[st - 1][s - PRING][lane], E);
            mbar_wait(bars + 128 + 8 * (w - 1), ((job - 1) >> 1) & 1);
            if (cta == 0 && st == 0) TSTAMP(7, s, 0);
            e_s2g(g_pp[st][s % PRING] + cta * 8192, sb + A_STG, PST_);
            if (lane < 8) st_rlx(&f_acc[st][s][cta][lane], E);
            asm volatile("cp.async.bulk.commit_group;\n cp.async.bulk.wait_group.read 0;" ::: "memory");
            __syncwarp();
            e_arrive(bars + 144);
            __syncwarp();
            if (cta == 0 && st == 0) TSTAMP(7, s, 1);
          }
        }
        bulk_wait();
      }
    }
  } else {
    const int tid = fresh_tid(), lane = tid & 31;
    const int qd = cta - 32;
    input_ln_pair(p.x, qd, warp, lane);
    bar_sync(6, 512);
    if (tid == 0) st_rel(&f_h1[qd], E);
    volatile int* bc = (volatile int*)sm;
    if (warp == 15) {
      unsigned long long run = 0;
      unsigned long long b2[2][2] = {{0, 0}, {0, 0}};
      auto track = [&](int s) {
#pragma unroll
        for (int k = 0; k < 2; k++) {
          const unsigned long long m = warp_max<16>(wait_words(f_w2[k][s][lane], E));
          if (lane == (s & 31)) { if (s < 32) b2[k][0] = m; else b2[k][1] = m; }
        }
      };
#pragma unroll 1
      for (int s = 0; s < NSEG; s++) {
        const int cd = route_step(s, E, lane, run);
        if (cd >= 0 && qd == (s & 1)) {
          uint32_t v[1][8], h[1][8];
          ffn_finish(sb, s, g_req1[s * 32 + cd][0], rscore(run), E, lane, v[0]);
          if (lane == 0) TSTAMP(8, s, 2);
          ln_rows<1>(v, h);
#pragma unroll
          for (int i = 0; i < 8; i++) st_rlx64(&g_hc[s][(i >> 2) * 128 + 4 * lane + (i & 3)], h[0][i], E);
          if (lane == 0) TSTAMP(8, s, 3);
          store_row(g_x2c[s], v[0], lane);
          __syncwarp();
          if (lane == 0) st_rel(&f_hc[s], E);
        }
        if (qd == 2 && s > LAG) track(s - LAG - 1);
      }
      wait_eq(&f_hc[rtok(run) >> 5], E);
      if (lane == 0) *bc = rtok(run);
      bar_sync(7, 288);
      if (qd == 2) {
        uint32_t v[8];
        const int ts = rtok(run) >> 5;
        track(NSEG - LAG - 1);
        run = 0;
        int kl = 0;
#pragma unroll 1
        for (int k = 0; k <= LAG; k++) {
          const int s = NSEG - LAG - 1 + k;
          const unsigned long long m = warp_max<16>(k == 0 ? max(lane < ts ? b2[0][0] : b2[1][0], lane + 32 < ts ? b2[0][1] : b2[1][1])
                                                           : wait_words(f_w2[s < ts ? 0 : 1][s][lane], E));
          const bool lead = m > run;
          if (lead) { run = m; __threadfence(); }
          if (lane < 4) st_rlx64(&f_l2[k][lane], (uint32_t)run, (uint32_t)(run >> 32));
          if (lead) kl = k;
          if (k == LAG - 1) { wait_all(&f_cp[lane], E); wait_all(&f_cp[32 + lane], E); }
          if (k == LAG - 1 || (k == LAG && lead)) ffn_finish(sb, NSEG + kl, g_req2[(rtok(run) >> 5) < ts ? 0 : 1][rtok(run)][0], rscore(run), E, lane, v);
        }
        if (lane == 0) GSTAMP(1, 1);
        store_row(p.out + (size_t)rtok(run) * 512, v, lane);
        if (lane == 0) GSTAMP(1, 2);
      }
      if (lane == 0) sts32(sb + 16, (uint32_t)-1);
      bar_sync(8, 256);
      if (qd == 2) {
        asm volatile("griddepcontrol.wait;" ::: "memory");
        if (lane == 0) *(volatile uint32_t*)&g_epoch = E;
      }
    } else if (warp >= 8) {
#pragma unroll 1
      for (;;) {
        bar_sync(8, 256);
        const int q = (int)uni(lds32(sb + 16));
        if (q < 0) break;
        ffn_gather(sb, q, warp - 8, E, lane);
      }
    } else {
      uint32_t wv[8];
      const float wsum = load_wr(wv, p.wr, lane);
      unsigned long long best = 0;
      int ttok = 0;
#pragma unroll 1
      for (int i = 0; i < NSTEP; i++) {
        const bool last = i >= NSEG;
        if (i == NSEG) { bar_sync(7, 288); ttok = *bc; best = 0; }
        const int s = last ? i - LAG : i, st = !last ? 0 : s < (ttok >> 5) ? 1 : 2;
        const int tk = s * 32 + qd * 8 + warp;
        const unsigned long long wd = token_post<true>(st, tk, !last ? p.x + (size_t)tk * 512 : tk == ttok ? g_x2c[s] : g_x2 + (size_t)tk * 512,
                                                 (last ? p.out : g_x2) + (size_t)tk * 512, last ? g_req2[st - 1][tk][0] : g_req1[tk][0], best, wv, wsum, E, lane);
        best = max(best, wd);
        volatile unsigned long long* ws = (volatile unsigned long long*)(sm + 64) + (i & 1) * 8;
        if (lane == 0) ws[warp] = wd;
        bar_sync(5, 256);
        if (warp == 0) {
          if (qd == 0 && lane == 0) TSTAMP(4, i, 1);
          if (!last) { const unsigned long long m = warp_max<4>(ws[lane & 7]); if (lane < 4) st_rel64(&f_h2[s][qd][lane], m); }
          else {
            st_rel64(&f_w2[st - 1][s][qd * 8 + (lane >> 2)][lane & 3], ws[lane >> 2]);
            asm volatile("st.relaxed.gpu.global.u64 [%0], %1;" :: "l"(&f_w2[2 - st][s][qd * 8 + (lane >> 2)][lane & 3]), "l"((unsigned long long)E << 43) : "memory");
          }
          if (qd == 0 && lane == 0) TSTAMP(4, i, 2);
        }
        __syncwarp();
      }
    }
  }
}

}

extern "C" void kernel_launch(void* const* d_in, const int* in_sizes, int n_in, void* d_out, int out_size) {
  (void)in_sizes; (void)n_in; (void)out_size;
  static bool init = false;
  if (!init) {
    cudaFuncSetAttribute(main_kernel, cudaFuncAttributeMaxDynamicSharedMemorySize, M_TOTAL);
    cudaFuncSetAttribute(aux_kernel, cudaFuncAttributeMaxDynamicSharedMemorySize, A_TOTAL);
    init = true;
  }
  Params p;
  p.x = (const bf16*)d_in[0]; p.mem0 = (const bf16*)d_in[1]; p.wq = (const bf16*)d_in[2]; p.wk = (const bf16*)d_in[3];
  p.wv = (const bf16*)d_in[4]; p.wo = (const bf16*)d_in[5]; p.wr = (const bf16*)d_in[8]; p.wg = (const bf16*)d_in[9];
  p.wu = (const bf16*)d_in[10]; p.wd = (const bf16*)d_in[11]; p.out = (bf16*)d_out; p.zero = 0; p.zero2 = 0;
  cudaStream_t st = cudaStreamPerThread;
  main_kernel<<<96, 512, M_TOTAL, st>>>(p);
  cudaLaunchConfig_t cfg = {};
  cfg.gridDim = dim3(36); cfg.blockDim = dim3(512); cfg.dynamicSmemBytes = A_TOTAL; cfg.stream = st;
  cudaLaunchAttribute at[1];
  at[0].id = cudaLaunchAttributeProgrammaticStreamSerialization; at[0].val.programmaticStreamSerializationAllowed = 1;
  cfg.attrs = at; cfg.numAttrs = 1;
  cudaLaunchKernelEx(&cfg, aux_kernel, p);
}
```

```cpp
#include <cuda_runtime.h>
#include <cuda_bf16.h>
#include <stdint.h>

namespace {

typedef __nv_bfloat16 bf16;

constexpr int NSEG = 64;
#define LAG_ 5
constexpr int LAG = LAG_;
constexpr int NSTEP = NSEG + LAG;
constexpr int ORING = 8, PRING = 4;
static_assert(LAG < 8, "rings");
#define E1_ 10
#define E2_ 0
#define E3_ 10
constexpr int E1 = E1_, E2 = E2_, E3 = E3_, EA = E1 + E2 + E3;
static_assert(EA % 4 == 0 && EA > 0 && EA < 32 && E1 > 0, "early part: whole 64-column chunks");
#define RW_ 176
#define RA_ 136
#define RC_ 24
#define STR2(x) #x
#define STR(x) STR2(x)
#define RED_ 30
#define ARR_ 7
#define PAUSE_ 13
#define PAUS2_ 29
#define PST2_ 2
#define PVR_ -1
#define SALT_ 0
#define KP1_ 1
#define OLOAD_ 8192
#define PST_ 8192
#define ALT_ 1
#define TQ_ 1
#define NOF_ 2
#define EXPQ_ 0
#define SPC_ 4096
#define HINT_ 24
#define HADD_ 2
#define HAND_ 4
#define GO3_ 2
#define STK_ 0
#define REMAP_ 1
#define NPROBE_ 6
#define TP(i, v) (v)
#define XDLY_ TP(0, 2075)
#define YDLY_ TP(1, 3400)
#define X1_ TP(2, 100)
#define X2_ TP(3, 350)
#define Y1_ TP(4, 200)
#define Y2_ TP(5, 450)
#define HGAP_ TP(6, 50)
#define TGAP_ TP(7, 100)
#define ADLY_ TP(8, 600)
#define ODLY_ TP(9, 2800)
#define LDLY_ TP(10, 3800)
#define HDLY_ TP(11, 0)
#define TDLY_ TP(15, 4150)
#define SDLY_ TP(12, 800)
#define AGAP_ 100
#define BOFF_ TP(13, 200)
#define YOFF_ TP(16, 150)
#define YUP_ TP(20, 40)
#define YDN_ TP(21, 4)
#define T1GAP_ TP(22, 0)
#define OGAP_ TP(23, 0)
#define CDLY_ TP(17, 300)
#define SLOW0_ TP(18, 800)
#define SLOW1_ TP(19, 300)
#define KDLY_ TP(14, 300)
__device__ uint32_t g_epoch;
__device__ __align__(1024) uint8_t g_h[2][NSEG][32768];
__device__ __align__(128) uint2 g_hc[NSEG][256];
__device__ __align__(128) bf16 g_x2[2048 * 512];
__device__ __align__(128) bf16 g_x2c[NSEG][512];
__device__ __align__(128) uint8_t g_o[3][ORING][32][8192];
__device__ __align__(128) uint8_t g_pp[3][PRING][8 * 32768];
__device__ __align__(128) bf16 g_n[2048 * 512];
__device__ __align__(128) uint8_t g_xch[96 * 16384 + 65536 + 8192];
__device__ __align__(128) bf16 g_req1[2048][2][512];
__device__ __align__(128) bf16 g_req2[2][2048][2][512];
__device__ __align__(128) float g_y[8][32][512];
__device__ __align__(128) uint8_t g_tok[96][2][16384];
__device__ uint32_t f_choice[96][2], f_loaded[32];
__device__ uint32_t f_h1[NSEG], f_hc[NSEG];
__device__ __align__(128) unsigned long long f_h2[NSEG][4][4];
__device__ __align__(128) unsigned long long f_w2[2][NSEG][32][4];
__device__ __align__(128) unsigned long long f_l2[LAG + 1][4];
__device__ __align__(128) uint32_t f_o[NSTEP][8][12][8];
__device__ __align__(128) uint32_t f_acc[3][NSEG][32][8], f_y[NSTEP + 1][32][8], f_cp[64];
__device__ __align__(128) unsigned long long g_sync[2][96][4];

#define TRAP() __trap()
__device__ __forceinline__ uint32_t smem_u32(const void* p) { return (uint32_t)__cvta_generic_to_shared(p); }
__device__ __forceinline__ int fresh_tid() { const int t = threadIdx.x; return __shfl_sync(~0u, t, t & 31); }
__device__ __forceinline__ unsigned long long gtime64() { unsigned long long t; asm volatile("mov.u64 %0, %%globaltimer;" : "=l"(t) :: "memory"); return t; }
__device__ __forceinline__ uint32_t clk() { unsigned long long c; asm volatile("mov.u64 %0, %%clock64;" : "=l"(c) :: "memory"); return (uint32_t)c; }
__device__ __forceinline__ void wait_until(uint32_t t) {
  while ((int)(t - clk()) > 450) __nanosleep(32);
  uint32_t c;
  do { asm volatile("mov.u32 %0, %%clock;" : "=r"(c) :: "memory"); } while ((int)(c - t) < 0);
}
__device__ __forceinline__ void mbar_init(uint32_t bar, uint32_t cnt) { asm volatile("mbarrier.init.shared::cta.b64 [%0], %1;" :: "r"(bar), "r"(cnt) : "memory"); }
__device__ __forceinline__ void mbar_arrive(uint32_t bar) { asm volatile("mbarrier.arrive.shared::cta.b64 _, [%0];" :: "r"(bar) : "memory"); }
__device__ __forceinline__ void mbar_arrive_remote(uint32_t bar) { asm volatile("mbarrier.arrive.relaxed.cluster.shared::cluster.b64 _, [%0];" :: "r"(bar) : "memory"); }
__device__ __forceinline__ void mbar_expect(uint32_t bar, uint32_t bytes) { asm volatile("mbarrier.arrive.expect_tx.shared::cta.b64 _, [%0], %1;" :: "r"(bar), "r"(bytes) : "memory"); }
__device__ __forceinline__ bool mbar_try(uint32_t bar, uint32_t parity) {
  uint32_t ok;
  asm volatile("{.reg .pred p; mbarrier.try_wait.parity.shared::cta.b64 p, [%1], %2; selp.u32 %0, 1, 0, p;}" : "=r"(ok) : "r"(bar), "r"(parity) : "memory");
  return ok;
}
__device__ __forceinline__ bool mbar_test(uint32_t bar, uint32_t parity) {
  uint32_t ok;
  asm volatile("{.reg .pred p; mbarrier.test_wait.parity.shared::cta.b64 p, [%1], %2; selp.u32 %0, 1, 0, p;}" : "=r"(ok) : "r"(bar), "r"(parity) : "memory");
  return ok;
}
__device__ __forceinline__ void mbar_wait(uint32_t bar, uint32_t parity) {
  asm volatile("{\n.reg .pred p;\nWAIT:\nmbarrier.try_wait.parity.shared::cta.b64 p, [%0], %1;\n@!p bra WAIT;\n}" :: "r"(bar), "r"(parity) : "memory");
}
__device__ __forceinline__ uint32_t ld_acq(const uint32_t* p) { uint32_t v; asm volatile("ld.acquire.gpu.global.u32 %0, [%1];" : "=r"(v) : "l"(p) : "memory"); return v; }
__device__ __forceinline__ unsigned long long ld_acq64(const unsigned long long* p) { unsigned long long v; asm volatile("ld.acquire.gpu.global.u64 %0, [%1];" : "=l"(v) : "l"(p) : "memory"); return v; }
__device__ __forceinline__ void st_rel(uint32_t* p, uint32_t v) { asm volatile("st.release.gpu.global.u32 [%0], %1;" :: "l"(p), "r"(v) : "memory"); }
__device__ __forceinline__ void st_rel64(unsigned long long* p, unsigned long long v) { asm volatile("st.release.gpu.global.u64 [%0], %1;" :: "l"(p), "l"(v) : "memory"); }
__device__ __forceinline__ void red_rel(uint32_t* p, uint32_t v) { asm volatile("red.release.gpu.global.add.u32 [%0], %1;" :: "l"(p), "r"(v) : "memory"); }
__device__ __forceinline__ uint32_t ld_rlx(const uint32_t* p) { uint32_t v; asm volatile("ld.relaxed.gpu.global.u32 %0, [%1];" : "=r"(v) : "l"(p) : "memory"); return v; }
__device__ __forceinline__ unsigned long long ld_rlxu64(const unsigned long long* p) { unsigned long long v; asm volatile("ld.relaxed.gpu.global.u64 %0, [%1];" : "=l"(v) : "l"(p) : "memory"); return v; }
__device__ __forceinline__ void st_rlx(uint32_t* p, uint32_t v) { asm volatile("st.relaxed.gpu.global.u32 [%0], %1;" :: "l"(p), "r"(v) : "memory"); }
__device__ __forceinline__ void bulk_wait() { asm volatile("cp.async.bulk.commit_group;\n cp.async.bulk.wait_group 0;" ::: "memory"); }
__device__ __forceinline__ void fence_acq() { asm volatile("fence.acquire.gpu;" ::: "memory"); }
__device__ __forceinline__ void wait_all(const uint32_t* p, uint32_t v, bool acquire = true) {
  int guard = 0;
  while (!__all_sync(~0u, ld_rlx(p) == v)) { __nanosleep(32); if (++guard > (1 << 22)) TRAP(); }
  if (acquire) fence_acq();
}
__device__ __forceinline__ void wait_eq(const uint32_t* p, uint32_t v) {
  int guard = 0;
  while (ld_rlx(p) != v) { __nanosleep(64); if (++guard > (1 << 22)) TRAP(); }
  fence_acq();
}
__device__ __forceinline__ unsigned long long rword(uint32_t E, int tok, float r) {
  uint32_t u = __float_as_uint(r + 0.f);
  u = r != r ? 0u : (u >> 31) ? ~u : u | 0x80000000u;
  return (unsigned long long)(E & 0x1FFFFFu) << 43 | (unsigned long long)u << 11 | (uint32_t)(2047 - tok);
}
__device__ __forceinline__ int rtok(unsigned long long v) { return 2047 - (int)(v & 2047u); }
__device__ __forceinline__ float rscore(unsigned long long v) { const uint32_t u = (uint32_t)(v >> 11); return __uint_as_float((u >> 31) ? u & 0x7fffffffu : ~u); }
__device__ __forceinline__ bool rfresh(unsigned long long v, uint32_t E) { return (uint32_t)(v >> 43) == (E & 0x1FFFFFu); }
template <int TOP> __device__ __forceinline__ unsigned long long warp_max(unsigned long long v) {
#pragma unroll
  for (int o = TOP; o > 0; o >>= 1) { const unsigned long long ov = __shfl_xor_sync(~0u, v, o); v = ov > v ? ov : v; }
  return v;
}
template <int off> __device__ __forceinline__ uint2 ld_rlx64(const void* p) { unsigned long long v; asm volatile("ld.relaxed.gpu.global.b64 %0, [%1+%2];" : "=l"(v) : "l"(p), "n"(off) : "memory"); return make_uint2((uint32_t)v, (uint32_t)(v >> 32)); }
template <int off> __device__ __forceinline__ uint4 ld_rlx128(const void* p) {
  unsigned long long a, b; asm volatile("ld.relaxed.gpu.global.v2.b64 {%0,%1}, [%2+%3];" : "=l"(a), "=l"(b) : "l"(p), "n"(off) : "memory");
  return make_uint4((uint32_t)a, (uint32_t)(a >> 32), (uint32_t)b, (uint32_t)(b >> 32));
}
__device__ __forceinline__ void st_rlx64(void* p, uint32_t lo, uint32_t hi) { asm volatile("{.reg .b64 t; mov.b64 t, {%1,%2}; st.relaxed.gpu.global.b64 [%0], t;}" :: "l"(p), "r"(lo), "r"(hi) : "memory"); }
__device__ __forceinline__ void cp_async16(uint32_t dst, const void* src) { asm volatile("cp.async.cg.shared.global [%0], [%1], 16;" :: "r"(dst), "l"(src) : "memory"); }
__device__ __forceinline__ void cp_async_wait() { asm volatile("cp.async.wait_all;" ::: "memory"); }
__device__ __forceinline__ void fence_async_smem() { asm volatile("fence.proxy.async.shared::cta;" ::: "memory"); }
__device__ __forceinline__ void fence_async_glob() { asm volatile("fence.proxy.async.global;" ::: "memory"); }
__device__ __forceinline__ void fence_async_acq() { asm volatile("fence.proxy.async::generic.acquire.sync_restrict::shared::cluster.cluster;" ::: "memory"); }
__device__ __forceinline__ float ex2(float x) { float y; asm("ex2.approx.ftz.f32 %0, %1;" : "=f"(y) : "f"(x)); return y; }
__device__ __forceinline__ float sqrt_fast(float x) { float y; asm("sqrt.approx.ftz.f32 %0, %1;" : "=f"(y) : "f"(x)); return y; }
__device__ __forceinline__ float rcp(float x) { float y; asm("rcp.approx.ftz.f32 %0, %1;" : "=f"(y) : "f"(x)); return y; }
__device__ __forceinline__ void bar_sync(int id, int n) { asm volatile("bar.sync %0, %1;" :: "r"(id), "r"(n) : "memory"); }
__device__ __forceinline__ bool bar_or(int id, int n, bool v) {
  uint32_t r;
  asm volatile("{.reg .pred p, q; setp.ne.u32 p, %3, 0; barrier.cta.red.or.aligned.pred q, %1, %2, p; selp.u32 %0, 1, 0, q;}" : "=r"(r) : "r"(id), "r"(n), "r"((uint32_t)v) : "memory");
  return r;
}
__device__ __forceinline__ uint32_t mapa(uint32_t a, uint32_t rank) { uint32_t r; asm volatile("mapa.shared::cluster.u32 %0, %1, %2;" : "=r"(r) : "r"(a), "r"(rank)); return r; }
__device__ __forceinline__ void cluster_sync() { asm volatile("barrier.cluster.arrive.release.aligned; barrier.cluster.wait.acquire.aligned;" ::: "memory"); }
__device__ __forceinline__ void st_async32(uint32_t dst, uint32_t v, uint32_t bar) { asm volatile("st.async.shared::cluster.mbarrier::complete_tx::bytes.b32 [%0], %1, [%2];" :: "r"(dst), "r"(v), "r"(bar) : "memory"); }
__device__ __forceinline__ void bulk_g2s(uint32_t dst, const void* src, uint32_t bytes, uint32_t bar) {
  asm volatile("cp.async.bulk.shared::cluster.global.mbarrier::complete_tx::bytes [%0], [%1], %2, [%3];" :: "r"(dst), "l"(src), "r"(bytes), "r"(bar) : "memory");
}
__device__ __forceinline__ void bulk_g2s_mc(uint32_t dst, const void* src, uint32_t bytes, uint32_t bar, uint16_t mask) {
  asm volatile("cp.async.bulk.shared::cluster.global.mbarrier::complete_tx::bytes.multicast::cluster [%0], [%1], %2, [%3], %4;"
               :: "r"(dst), "l"(src), "r"(bytes), "r"(bar), "h"(mask) : "memory");
}
__device__ __forceinline__ void bulk_s2c(uint32_t dst, uint32_t src, uint32_t bytes, uint32_t bar) {
  asm volatile("cp.async.bulk.shared::cluster.shared::cta.mbarrier::complete_tx::bytes [%0], [%1], %2, [%3];" :: "r"(dst), "r"(src), "r"(bytes), "r"(bar) : "memory");
}
__device__ __forceinline__ void bulk_s2g(void* dst, uint32_t src, uint32_t bytes) {
  asm volatile("cp.async.bulk.global.shared::cta.bulk_group [%0], [%1], %2;" :: "l"(dst), "r"(src), "r"(bytes) : "memory");
}
#define ELECT(op) "{.reg .pred p; elect.sync _|p, 0xffffffff; @p " op "}"
__device__ __forceinline__ void e_arrive(uint32_t bar) { asm volatile(ELECT("mbarrier.arrive.shared::cta.b64 _, [%0];") :: "r"(bar) : "memory"); }
__device__ __forceinline__ void e_expect(uint32_t bar, uint32_t bytes) { asm volatile(ELECT("mbarrier.arrive.expect_tx.shared::cta.b64 _, [%0], %1;") :: "r"(bar), "r"(bytes) : "memory"); }
__device__ __forceinline__ void e_g2s(uint32_t dst, const void* src, uint32_t bytes, uint32_t bar) {
  asm volatile(ELECT("cp.async.bulk.shared::cluster.global.mbarrier::complete_tx::bytes [%0], [%1], %2, [%3];") :: "r"(dst), "l"(src), "r"(bytes), "r"(bar) : "memory");
}
__device__ __forceinline__ void e_mc(uint32_t dst, const void* src, uint32_t bytes, uint32_t bar, uint16_t mask) {
  asm volatile(ELECT("cp.async.bulk.shared::cluster.global.mbarrier::complete_tx::bytes.multicast::cluster [%0], [%1], %2, [%3], %4;")
               :: "r"(dst), "l"(src), "r"(bytes), "r"(bar), "h"(mask) : "memory");
}
__device__ __forceinline__ void e_s2g(void* dst, uint32_t src, uint32_t bytes) {
  asm volatile(ELECT("cp.async.bulk.global.shared::cta.bulk_group [%0], [%1], %2;") :: "l"(dst), "r"(src), "r"(bytes) : "memory");
}
__device__ __forceinline__ void e_st_rel(uint32_t* p, uint32_t v) { asm volatile(ELECT("st.release.gpu.global.u32 [%0], %1;") :: "l"(p), "r"(v) : "memory"); }
__device__ __forceinline__ uint32_t clk32() { uint32_t c; asm volatile("mov.u32 %0, %%clock;" : "=r"(c) :: "memory"); return c; }
__device__ __forceinline__ void spin_until(uint32_t t) { while ((int)(clk32() - t) < 0) {} }
__device__ __forceinline__ uint32_t uni(uint32_t v) { return __shfl_sync(~0u, v, 0); }
__device__ __forceinline__ uint32_t pack2(float lo, float hi) { uint32_t r; asm("cvt.rn.bf16x2.f32 %0, %1, %2;" : "=r"(r) : "f"(hi), "f"(lo)); return r; }
__device__ __forceinline__ uint32_t add2(uint32_t a, uint32_t b) { uint32_t r; asm("add.rn.bf16x2 %0, %1, %2;" : "=r"(r) : "r"(a), "r"(b)); return r; }
__device__ __forceinline__ float rbf(float x) { return __bfloat162float(__float2bfloat16_rn(x)); }
__device__ __forceinline__ float blo(uint32_t u) { return __uint_as_float(u << 16); }
__device__ __forceinline__ float bhi(uint32_t u) { return __uint_as_float(u & 0xffff0000u); }
__device__ __forceinline__ uint32_t gentag(uint32_t g) { return (g & 1u) | (g & 2u) << 15; }
__device__ __forceinline__ uint32_t pack2_tag(float lo, float hi, uint32_t tag) {
  const uint32_t u = __byte_perm(__float_as_uint(lo), __float_as_uint(hi), 0x7632);
  return u + ((u ^ tag) & 0x10001u);
}
__device__ __forceinline__ uint32_t xo2(uint32_t a, uint32_t b, uint32_t t) { uint32_t r; asm("lop3.b32 %0, %1, %2, %3, 0x7e;" : "=r"(r) : "r"(a), "r"(b), "r"(t)); return r; }
__device__ __forceinline__ uint32_t or3(uint32_t a, uint32_t b, uint32_t c) { uint32_t r; asm("lop3.b32 %0, %1, %2, %3, 0xfe;" : "=r"(r) : "r"(a), "r"(b), "r"(c)); return r; }
__device__ __forceinline__ void stmatrix4(uint32_t a, uint32_t r0, uint32_t r1, uint32_t r2, uint32_t r3) {
  asm volatile("stmatrix.sync.aligned.m8n8.x4.shared.b16 [%0], {%1,%2,%3,%4};" :: "r"(a), "r"(r0), "r"(r1), "r"(r2), "r"(r3) : "memory");
}
__device__ __forceinline__ void stmatrix4_t(uint32_t a, uint32_t r0, uint32_t r1, uint32_t r2, uint32_t r3) {
  asm volatile("stmatrix.sync.aligned.m8n8.x4.trans.shared.b16 [%0], {%1,%2,%3,%4};" :: "r"(a), "r"(r0), "r"(r1), "r"(r2), "r"(r3) : "memory");
}
__device__ __forceinline__ void ldmatrix4_t(uint32_t* r, uint32_t a) {
  asm volatile("ldmatrix.sync.aligned.m8n8.x4.trans.shared.b16 {%0,%1,%2,%3}, [%4];" : "=r"(r[0]), "=r"(r[1]), "=r"(r[2]), "=r"(r[3]) : "r"(a) : "memory");
}
__device__ __forceinline__ void ldmatrix4(uint32_t* r, uint32_t a) {
  asm volatile("ldmatrix.sync.aligned.m8n8.x4.shared.b16 {%0,%1,%2,%3}, [%4];" : "=r"(r[0]), "=r"(r[1]), "=r"(r[2]), "=r"(r[3]) : "r"(a) : "memory");
}
__device__ __forceinline__ void hmma16(float* c, const uint32_t* a, uint32_t b0, uint32_t b1) {
  asm volatile("mma.sync.aligned.m16n8k16.row.col.f32.bf16.bf16.f32 {%0,%1,%2,%3}, {%4,%5,%6,%7}, {%8,%9}, {%0,%1,%2,%3};"
               : "+f"(c[0]), "+f"(c[1]), "+f"(c[2]), "+f"(c[3]) : "r"(a[0]), "r"(a[1]), "r"(a[2]), "r"(a[3]), "r"(b0), "r"(b1));
}
__device__ __forceinline__ void hmma8(float* c, uint32_t a0, uint32_t a1, uint32_t b0) {
  asm volatile("mma.sync.aligned.m16n8k8.row.col.f32.bf16.bf16.f32 {%0,%1,%2,%3}, {%4,%5}, {%6}, {%0,%1,%2,%3};"
               : "+f"(c[0]), "+f"(c[1]), "+f"(c[2]), "+f"(c[3]) : "r"(a0), "r"(a1), "r"(b0));
}
__device__ __forceinline__ uint4 lds128(uint32_t a) { uint4 v; asm volatile("ld.shared.v4.u32 {%0,%1,%2,%3}, [%4];" : "=r"(v.x), "=r"(v.y), "=r"(v.z), "=r"(v.w) : "r"(a) : "memory"); return v; }
__device__ __forceinline__ void sts128(uint32_t a, uint4 v) { asm volatile("st.shared.v4.u32 [%0], {%1,%2,%3,%4};" :: "r"(a), "r"(v.x), "r"(v.y), "r"(v.z), "r"(v.w) : "memory"); }
__device__ __forceinline__ void sts128f(uint32_t a, float x, float y, float z, float w) { asm volatile("st.shared.v4.f32 [%0], {%1,%2,%3,%4};" :: "r"(a), "f"(x), "f"(y), "f"(z), "f"(w) : "memory"); }
__device__ __forceinline__ void sts64f(uint32_t a, float x, float y) { asm volatile("st.shared.v2.f32 [%0], {%1,%2};" :: "r"(a), "f"(x), "f"(y) : "memory"); }
__device__ __forceinline__ uint32_t lds32(uint32_t a) { uint32_t v; asm volatile("ld.shared.u32 %0, [%1];" : "=r"(v) : "r"(a) : "memory"); return v; }
__device__ __forceinline__ void sts32(uint32_t a, uint32_t v) { asm volatile("st.shared.u32 [%0], %1;" :: "r"(a), "r"(v) : "memory"); }

constexpr uint32_t SBASE = 1024;
__host__ __device__ constexpr uint64_t mkdesc(uint32_t off, uint32_t lbo, uint32_t sbo, uint32_t swz) {
  return (uint64_t)(((SBASE + off) & 0x3FFFF) >> 4) | ((uint64_t)(lbo >> 4) << 16) | ((uint64_t)(sbo >> 4) << 32) | ((uint64_t)swz << 62);
}
__device__ __forceinline__ void wg_fence() { asm volatile("wgmma.fence.sync.aligned;" ::: "memory"); }
__device__ __forceinline__ void wg_commit() { asm volatile("wgmma.commit_group.sync.aligned;" ::: "memory"); }
template <int N> __device__ __forceinline__ void wg_wait() { asm volatile("wgmma.wait_group.sync.aligned %0;" :: "n"(N) : "memory"); }

template <int N> __device__ __forceinline__ void reg_fence(float (&d)[N], int n = N) {
#pragma unroll
  for (int i = 0; i < N; i++) if (i < n) asm volatile("" : "+f"(d[i]) :: "memory");
}
#define F4(b) "+f"(d[b]), "+f"(d[b + 1]), "+f"(d[b + 2]), "+f"(d[b + 3])
#define F8(b) F4(b), F4(b + 4)
#define F16(b) F8(b), F8(b + 8)
#define G4(b) "=f"(d[b]), "=f"(d[b + 1]), "=f"(d[b + 2]), "=f"(d[b + 3])
#define G8(b) G4(b), G4(b + 4)
#define G16(b) G8(b), G8(b + 8)
#define RS_IN "r"(a[0]), "r"(a[1]), "r"(a[2]), "r"(a[3]), "l"(db), "n"(SD), "n"(TB)
#define SS_IN "l"(da), "l"(db), "n"(SD), "n"(TA), "n"(TB)
#define WG_OP(str, out0, out1, in) do { if (SD || KEEP) asm volatile(str : out1 : in); else asm volatile(str : out0 : in); } while (0)
#define O12(X) X##8(0), X##4(8)
#define O20(X) X##16(0), X##4(16)
#define O32(X) X##16(0), X##16(16)
template <int SD, int TB, int KEEP = 0> __device__ __forceinline__ void wgmma_rs24(float* d, const uint32_t* a, uint64_t db) {
  WG_OP("wgmma.mma_async.sync.aligned.m64n24k16.f32.bf16.bf16 {%0,%1,%2,%3,%4,%5,%6,%7,%8,%9,%10,%11}, {%12,%13,%14,%15}, %16, %17, 1, 1, %18;", O12(G), O12(F), RS_IN);
}
template <int SD, int TB, int KEEP = 0> __device__ __forceinline__ void wgmma_rs32(float* d, const uint32_t* a, uint64_t db) {
  WG_OP("wgmma.mma_async.sync.aligned.m64n32k16.f32.bf16.bf16 {%0,%1,%2,%3,%4,%5,%6,%7,%8,%9,%10,%11,%12,%13,%14,%15}, {%16,%17,%18,%19}, %20, %21, 1, 1, %22;", G16(0), F16(0), RS_IN);
}
template <int SD, int TB, int KEEP = 0> __device__ __forceinline__ void wgmma_rs40(float* d, const uint32_t* a, uint64_t db) {
  WG_OP("wgmma.mma_async.sync.aligned.m64n40k16.f32.bf16.bf16 {%0,%1,%2,%3,%4,%5,%6,%7,%8,%9,%10,%11,%12,%13,%14,%15,"
        "%16,%17,%18,%19}, {%20,%21,%22,%23}, %24, %25, 1, 1, %26;", O20(G), O20(F), RS_IN);
}
template <int SD, int TB, int KEEP = 0> __device__ __forceinline__ void wgmma_rs64(float* d, const uint32_t* a, uint64_t db) {
  WG_OP("wgmma.mma_async.sync.aligned.m64n64k16.f32.bf16.bf16 {%0,%1,%2,%3,%4,%5,%6,%7,%8,%9,%10,%11,%12,%13,%14,%15,"
        "%16,%17,%18,%19,%20,%21,%22,%23,%24,%25,%26,%27,%28,%29,%30,%31}, {%32,%33,%34,%35}, %36, %37, 1, 1, %38;", O32(G), O32(F), RS_IN);
}
template <int SD, int TA, int TB, int KEEP = 0> __device__ __forceinline__ void wgmma_ss24(float* d, uint64_t da, uint64_t db) {
  WG_OP("wgmma.mma_async.sync.aligned.m64n24k16.f32.bf16.bf16 {%0,%1,%2,%3,%4,%5,%6,%7,%8,%9,%10,%11}, %12, %13, %14, 1, 1, %15, %16;", O12(G), O12(F), SS_IN);
}
template <int SD, int TA, int TB, int KEEP = 0> __device__ __forceinline__ void wgmma_ss8(float* d, uint64_t da, uint64_t db) {
  WG_OP("wgmma.mma_async.sync.aligned.m64n8k16.f32.bf16.bf16 {%0,%1,%2,%3}, %4, %5, %6, 1, 1, %7, %8;", G4(0), F4(0), SS_IN);
}
__device__ __forceinline__ void bar_arrive(int id, int n) { asm volatile("bar.arrive %0, %1;" :: "r"(id), "r"(n) : "memory"); }
__device__ __forceinline__ uint32_t vis_bits(int pos, int t) {
  uint32_t m = 0;
#pragma unroll
  for (int i = 0; i < 8; i++) m |= (8 * (i / 2 + 1) + 2 * t + (i & 1) <= pos) ? 1u << i : 0u;
  return m;
}

__device__ __forceinline__ unsigned long long wait_words(const unsigned long long* p, uint32_t E) {
  int guard = 0; unsigned long long m;
  while (m = ld_rlxu64(p), !__all_sync(~0u, rfresh(m, E))) { __nanosleep(20); if (++guard > (1 << 22)) TRAP(); }
  fence_acq();
  return m;
}
__device__ __forceinline__ int route_step(int s, uint32_t E, int lane, unsigned long long& run) {
  const unsigned long long m = warp_max<2>(wait_words(f_h2[s][lane & 3], E));
  if (s == 0 || m > run) { run = m; return rtok(m) & 31; }
  return -1;
}

struct Params {
  const bf16 *x, *mem0, *wq, *wk, *wv, *wo, *wr, *wg, *wu, *wd;
  bf16* out;
  uint32_t zero2;
  unsigned long long zero;
};

constexpr uint32_t WSTG_STRIDE = 272;
__device__ __forceinline__ void stage_weights(uint32_t stg, const bf16* src, int ld, int tid, int nthr) {
  for (int i = tid; i < 512 * 16; i += nthr) {
    int k = i >> 4, c = i & 15;
    cp_async16(stg + k * WSTG_STRIDE + c * 16, src + (size_t)k * ld + c * 8);
  }
}
__device__ __forceinline__ void load_frags(uint32_t (*W)[4], uint32_t stg, int wg, int w, int lane) {
  uint32_t a = stg + ((lane >> 4) * 8 + (lane & 7)) * WSTG_STRIDE + (64 * wg + 16 * w + ((lane >> 3) & 1) * 8) * 2;
#pragma unroll
  for (int ks = 0; ks < 32; ks++) ldmatrix4_t(W[ks], a + ks * 16 * WSTG_STRIDE);
}

constexpr uint32_t M_H = 0;
constexpr uint32_t M_MEM = 65536;
constexpr uint32_t M_Q = M_MEM + 24576;
constexpr uint32_t M_K = M_Q + 12288;
constexpr uint32_t M_V = M_K + 12288;
constexpr uint32_t M_OM = M_V + 12288;
constexpr uint32_t M_OST = M_OM + 6144;
constexpr uint32_t M_TST = M_OST + 8192;
constexpr uint32_t M_WO = M_TST + 16384;
constexpr uint32_t M_M0 = M_WO + 49152;
constexpr uint32_t M_PT = M_M0 + 2048;
constexpr uint32_t M_BAR = M_PT + 12288;
constexpr uint32_t M_TOTAL = M_BAR + 384;
static_assert(M_TOTAL <= 232448, "main smem");
static_assert(M_WO >= 512 * WSTG_STRIDE, "staging overlaps Wo");
enum { B_LAND = 0  , B_QK = 3, B_V, B_TOK, B_OM, B_HA, B_HB, B_HAE, B_HBE, B_OST, B_OFREE, B_SYNC,
       B_STG, B_STG1, B_SS, B_TFREE, B_KFREE, B_VFREE, B_FIX  , B_NUM = B_FIX + 8 };
static_assert(B_NUM * 8 <= 256, "barriers");
constexpr uint32_t M_CAND = M_BAR + 256;
constexpr uint32_t M_BASE = M_BAR + 272;
constexpr uint32_t M_ZERO = M_BAR + 280;
constexpr uint32_t M_BAS2 = M_BAR + 328;
constexpr uint32_t M_NEAR = M_BAR + 288;
enum { N_GO1 = 2, N_GO2, N_GO3, N_GO4, N_AG, N_W };

#define GSTAMP(slot, i)
#define TSTAMP(slot, i, k)
#define STAMP(i)
#define ASTAMP(i)
#define WSTAMP(i)
#define CSTAMP(i, v)
#define PIN(x) asm volatile("" : "+r"(x))
#define SCHED(k) asm volatile("{\n.reg .pred p;\nsetp.ne.u32 p, %0, 0;\n@p trap;\n}" :: "r"(zz & (1u << (k))) : "memory")
#define HOLD(k, v) asm volatile("{\n.reg .pred p;\nsetp.ne.u32 p, %0, 0;\n@p st.shared.u32 [%0], %1;\n}" :: "r"(zz & (1u << (k))), "r"(v) : "memory")
#define DRAIN(a) (lds32((a) + zz) & zz)
#define BAR(i) (sb + M_BAR + 8 * (i))

__device__ __forceinline__ int probe(const uint8_t* p, int n) {
  int best = 1 << 30; uint32_t v = 0;
#pragma unroll 1
  for (int r = 0; r < n; r++) {
    uint32_t t0 = clk();
    asm volatile("atom.relaxed.gpu.global.or.b32 %0, [%1], %2;" : "=r"(v) : "l"(p + 3968), "r"(v & 0u) : "memory");
    if (v == 0x7fffffffu) t0++;
    best = min(best, (int)(clk() - t0));
  }
  return best;
}
__device__ __forceinline__ void load_mem0(uint4* u, int k0, int lane, const bf16* mem0) {
#pragma unroll
  for (int i = 0; i < 2; i++) {
    const unsigned short* m = (const unsigned short*)mem0 + k0 + lane + 32 * i;
    u[i] = make_uint4(m[0] | (uint32_t)m[512] << 16, m[1024] | (uint32_t)m[1536] << 16, m[2048] | (uint32_t)m[2560] << 16, m[3072] | (uint32_t)m[3584] << 16);
  }
}

__device__ __forceinline__ void paced_h(uint32_t dst, const uint8_t* src, uint32_t o0, uint32_t o1, uint32_t piece, uint32_t bar, int gap) {
  uint32_t t = clk32();
#pragma unroll 1
  for (uint32_t o = o0; o < o1; o += piece) {
    e_mc(dst + o, src + o, piece, bar, 7);
    spin_until(t += gap);
  }
}

__device__ __forceinline__ void paced_st(uint8_t* dst, uint32_t src, int gap) {
  uint32_t t = clk32();
#pragma unroll 1
  for (uint32_t o = 0; o < 8192; o += SPC_) {
    e_s2g(dst + o, src + o, SPC_);
    if (o + SPC_ < 8192) spin_until(t += gap);
  }
}
__device__ __forceinline__ int block_of(int head, int c) { return REMAP_ ? (c == 2 ? head : 32 + 2 * head + c) : head * 3 + c; }

__device__ __forceinline__ void weight_role(const Params& p, const uint32_t sb, const int warp, const int cta, const int C, const uint32_t E,
                                            const uint8_t* const memg) {
  const int tid = fresh_tid(), lane = tid & 31;
  const int wg = warp >> 2, w = warp & 3;
  uint32_t W[32][4];
  cp_async_wait();
  bar_sync(1, 256);
  load_frags(W, sb, wg, w, lane);
  bar_sync(1, 256);
  if (tid < 128) sts128(sb + M_V + 5 * 2048 + tid * 16, make_uint4(0, 0, 0, 0));
  fence_async_smem();
  cluster_sync();
  if (tid == 0 && cta == 0) GSTAMP(0, 1);
  if (tid == 0) TSTAMP(13, cta, 0);

  const uint32_t rba = mapa(sb, C == 2 ? 0 : 2), rbc = mapa(sb, C == 1 ? 0 : 1);
  const uint32_t MYBAR = M_BAR + 8 * (C < 2 ? B_QK : B_V);
  uint32_t qoff = M_Q + C * 12288 + warp * 256 + lane * 4;
  uint32_t toff = sb + warp * 256 + (lane >> 4) * 2048 + (lane & 15) * 16;
  uint32_t rbar = mapa(sb + M_BAR, min(lane, 2));
  uint32_t sv = sb + M_MEM + lane * 32 + ((lane >> 2) & 3) * 8;
  PIN(qoff); PIN(toff); PIN(rbar); PIN(sv);
  const uint32_t gen0 = (E - 1) * (uint32_t)(NSTEP - 1);
  uint32_t fix = 0;
  const bool sig = w == 0 && lane < 3;
  const int blk = block_of(cta / 3, C);
  const int pk = (blk < 24 ? PAUSE_ : PAUS2_) + (wg ? -PST2_ : PST2_);
  int cand = -1;
  float d[16];
#pragma unroll
  for (int i = 0; i < 16; i++) d[i] = 0.f;
  uint32_t tp[8];
#pragma unroll 1
  for (int T = -1; T < NSTEP; T++) {
    const uint32_t ph = T & 1;
    const uint64_t Z = p.zero << ph;
    const uint32_t zz = p.zero2;
    if (T >= 0) {
      WSTAMP(0);
      const uint64_t db = mkdesc(M_MEM, 128, 256, 0) + Z;
      auto stage = [&]() {
        stmatrix4(toff + M_TST + 8192, tp[0], tp[1], tp[2], tp[3]); stmatrix4(toff + M_TST + 12288, tp[4], tp[5], tp[6], tp[7]);
        if (sig) mbar_arrive_remote(rbar + 8 * B_HBE);
      };
      if (STK_ == 0) stage();
      mbar_wait(BAR(B_LAND), ph);
      WSTAMP(1);
      const uint32_t gt = gentag(gen0 + T);
      auto old = [&](uint32_t a) { return lds32(a) ^ gt; };
      uint32_t bad = 0;
      bool redo = false, ready = false;
      wg_fence();
      wgmma_rs24<0, 1, KP1_>(d, W[0], db);
#pragma unroll
      for (int ks = 1; ks < 32; ks++) {
        if (ks == STK_) stage();
        if (ks == 2) bad |= old(sv + min(warp, 5) * 1024);
        if (ks == 10 || ks == 22) bad |= xo2(lds32(sv + (ks == 10 ? 6 : 15) * 1024 + warp * 1024), lds32(sv + (ks == 10 ? 14 : 23) * 1024), gt);
        if (ks == 6) {
          const uint32_t z5 = DRAIN(toff + M_TST);
          __syncwarp();
          if (lane == 0) mbar_arrive(BAR(B_STG) + z5);
        }
        if (ks == 27) ready = mbar_test(BAR(C < 2 ? B_KFREE : B_VFREE), ph ^ 1) & mbar_test(BAR(B_HA), ph);
        if (ks == RED_) redo = bar_or(N_W, 256, T > 0 && (bad & 0x10001u));
        if (ks == 8 || ks == 20) { mbar_wait(BAR(B_LAND + (ks + 4) / 12), ph); WSTAMP(6 + (ks + 4) / 12); wg_fence(); }
        wgmma_rs24<1, 1>(d, W[ks], db + ks * 48);
      }
      wg_commit();
      uint32_t a0 = rba + qoff, a1 = a0 + 128, a2 = rbc + qoff, a3 = a2 + 128, ba = rba + MYBAR, bc = rbc + MYBAR;
      PIN(a0); PIN(a1); PIN(a2); PIN(a3); PIN(ba); PIN(bc);
      if (!ready) {
        mbar_wait(BAR(C < 2 ? B_KFREE : B_VFREE), ph ^ 1);
        if (T < NSTEP - 1) mbar_wait(BAR(B_HA), ph);
      }
      wg_wait<0>(); reg_fence(d);
      if (__builtin_expect(redo, 0)) {
        auto stale = [&]() { return __any_sync(~0u, (old(sv + warp * 3072) | old(sv + warp * 3072 + 1024) | old(sv + warp * 3072 + 2048)) & 0x10001u); };
        auto fetch = [&](int r) {
          e_expect(BAR(B_FIX + warp), 3072);
          e_g2s(sb + M_MEM + warp * 3072, memg + warp * 8192 + ((uni(lds32(sb + M_NEAR + warp * 4)) ^ r) & 1) * 4096, 3072, BAR(B_FIX + warp));
        };
        bool late = stale();
        if (late) fetch(0);
        constexpr uint64_t dc = mkdesc(M_MEM, 128, 256, 0);
#pragma unroll
        for (int ks = 0; ks < 32; ks++) {
          if (ks % 12 == 0) {
            if (ks) { wg_commit(); wg_wait<0>(); reg_fence(d); }
            if (warp / 3 == ks / 12) {
              for (int guard = 0; late; guard++) {
                mbar_wait(BAR(B_FIX + warp), fix); fix ^= 1;
                late = stale();
                if (late) fetch(ALT_ ? guard + 1 : 0);
                if (guard > (1 << 20)) TRAP();
              }
            }
            bar_sync(N_W, 256);
            wg_fence();
          }
          if (ks == 0) wgmma_rs24<0, 1, 1>(d, W[0], dc); else wgmma_rs24<1, 1>(d, W[ks], dc + ks * 48);
        }
        wg_commit();
        wg_wait<0>(); reg_fence(d);
      }
      WSTAMP(2);
      if (T == 0 && tid == 0) TSTAMP(13, cta, 2);
      uint32_t lo[3], hi[3];
#pragma unroll
      for (int j = 0; j < 3; j++) { lo[j] = pack2(d[4 * j], d[4 * j + 1]); hi[j] = pack2(d[4 * j + 2], d[4 * j + 3]); }
      if (__builtin_expect(T == 0, 0)) { sts32(sb + M_M0 + tid * 8, lo[0]); sts32(sb + M_M0 + tid * 8 + 4, hi[0]); }
      if (__builtin_expect(cand >= 0, 0)) {
        if (T == LAG) { lo[1] = lds32(sb + M_M0 + tid * 8); hi[1] = lds32(sb + M_M0 + tid * 8 + 4); }
        if (C < 2) { st_async32(a0 + 5 * 2048, lo[2], ba); st_async32(a1 + 5 * 2048, hi[2], ba); }
        else { sts32(sb + qoff + 5 * 2048, lo[2]); sts32(sb + qoff + 5 * 2048 + 128, hi[2]); }
        lo[2] = lo[1]; hi[2] = hi[1];
      }
      uint32_t z5;
      if (C == 0) {
        sts32(sb + qoff, lo[0]); sts32(sb + qoff + 128, hi[0]); z5 = DRAIN(sb + qoff);
        st_async32(a0, lo[2], ba); st_async32(a1, hi[2], ba); st_async32(a2, lo[1], bc); st_async32(a3, hi[1], bc);
      } else if (C == 1) {
        sts32(sb + qoff, lo[1]); sts32(sb + qoff + 128, hi[1]); z5 = DRAIN(sb + qoff);
        st_async32(a0, lo[2], ba); st_async32(a1, hi[2], ba); st_async32(a2, lo[0], bc); st_async32(a3, hi[0], bc);
      } else {
        sts32(sb + qoff, lo[2]); sts32(sb + qoff + 128, hi[2]); z5 = DRAIN(sb + qoff);
        st_async32(a0, lo[0], ba); st_async32(a1, hi[0], ba); st_async32(a2, lo[1], bc); st_async32(a3, hi[1], bc);
      }
      __syncwarp();
      if (lane == 0) { mbar_arrive(sb + MYBAR + z5); if (w == 3) mbar_arrive(BAR(B_SS)); }
      if (T == NSTEP - 1) break;
    }
    {
      const uint64_t dh = mkdesc(M_H, 16, 1024, 1) + Z;
      static_assert(E2 == 0 && E3 > 0 && PAUSE_ > 0, "config");
      if (T + 2 < NSEG) {
        if (T < 0) mbar_wait(BAR(B_HA), ph);
        WSTAMP(3);
        wg_fence();
        wgmma_rs32<0, 0, 1>(d, W[0], dh);
#pragma unroll
        for (int ks = 1; ks < EA; ks++) {
          if (ks == E1) { wg_commit(); if (T >= 0) bar_sync(N_GO2, 384); wg_fence(); }
          wgmma_rs32<1, 0>(d, W[ks], dh + (ks >> 2) * 256 + (ks & 3) * 2);
        }
        wg_commit();
        mbar_wait(BAR(B_HB), ph);
        wg_wait<0>();
        if (sig) mbar_arrive_remote(rbar + 8 * B_HAE);
        WSTAMP(4);
        if (T >= 0) bar_sync(N_GO3, 384);
        if (wg == 1) bar_sync(N_W, 256);
        wg_fence();
#pragma unroll
        for (int ks = EA; ks < 32; ks++) wgmma_rs32<1, 0>(d, W[ks], dh + (ks >> 2) * 256 + (ks & 3) * 2);
        wg_commit();
        if (wg == 0) bar_arrive(N_W, 256);
        mbar_wait(BAR(B_TFREE), ph ^ 1);
        wg_wait<0>(); reg_fence(d);
      } else {
        bar_sync(N_GO2, 384);
        mbar_wait(BAR(B_HB), ph);
        if (sig) mbar_arrive_remote(rbar + 8 * B_HAE);
        bar_sync(N_GO3, 384);
        mbar_wait(BAR(B_TFREE), ph ^ 1);
      }
#pragma unroll
      for (int i = 0; i < 8; i++) { tp[i] = pack2(d[2 * i], d[2 * i + 1]); PIN(tp[i]); }
      const uint32_t t1 = toff + (C == 0 && !ph ? M_Q + 2048 : M_TST);
      auto staged = [&]() {
        const uint32_t z5 = DRAIN(t1);
        __syncwarp();
        if (lane == 0) mbar_arrive(BAR(B_STG1) + z5);
      };
      if (T < 0 || (T + 2 >= LAG && T + 2 < NSTEP)) {
        wg_fence();
        wgmma_rs32<0, 0, 1>(d, W[0], dh + 2048);
        stmatrix4(t1, tp[0], tp[1], tp[2], tp[3]); stmatrix4(t1 + 4096, tp[4], tp[5], tp[6], tp[7]);
#pragma unroll
        for (int ks = 1; ks < 32; ks++) {
          if (ks == 5) staged();
          if (ks == PAUSE_ - PST2_ || ks == PAUSE_ + PST2_ || ks == PAUS2_ - PST2_ || ks == PAUS2_ + PST2_) {
            wg_commit();
            if (T >= 0 && ks == pk) bar_sync(N_GO4, 384);
            wg_fence();
          }
          wgmma_rs32<1, 0>(d, W[ks], dh + 2048 + (ks >> 2) * 256 + (ks & 3) * 2);
        }
        wg_commit();
      } else {
        stmatrix4(t1, tp[0], tp[1], tp[2], tp[3]); stmatrix4(t1 + 4096, tp[4], tp[5], tp[6], tp[7]);
        staged();
        bar_sync(N_GO4, 384);
      }
      if (T >= 0) cand = __shfl_sync(~0u, (int)lds32(sb + M_CAND + ((T + 1) & 3) * 4), 0);
      wg_wait<0>(); reg_fence(d);
      if (T >= 0) WSTAMP(6);
      if (T < 0 && tid == 0) TSTAMP(13, cta, 1);
#pragma unroll
      for (int i = 0; i < 8; i++) tp[i] = pack2(d[2 * i], d[2 * i + 1]);
    }
  }
  cluster_sync();
  if (tid == 0 && cta == 0) GSTAMP(0, 5);
}

__device__ __forceinline__ void attn_role(const Params& p, const uint32_t sb, const int w, const int cta, const int head, const int C, const uint32_t E,
                                          uint8_t* const part, uint8_t* const memg) {
  const int tid = fresh_tid(), lane = tid & 31;
  const int g = lane >> 2, t = lane & 3, blk = block_of(head, C);
  uint32_t tag = ((E - 1) * (uint32_t)(NSTEP - 1)) & 1;
  uint4 m0[2][2];
  load_mem0(m0[0], w * 64, lane, p.mem0); load_mem0(m0[1], w * 64 + 256, lane, p.mem0);
  cluster_sync();
#pragma unroll
  for (int k = 0; k < 2; k++) {
#pragma unroll 1
    for (int i = 0; i < 6; i++) sts128(sb + M_MEM + (w + 4 * k) * 3072 + lane * 16 + i * 512, make_uint4(0, 0, 0, 0));
    __syncwarp();
#pragma unroll
    for (int i = 0; i < 2; i++) sts128(sb + M_MEM + ((w + 4 * k) * 4 + (lane >> 4) + 2 * i) * 768 + (lane & 15) * 16, m0[k][i]);
  }
  fence_async_smem();
  bar_sync(N_AG, 128);
  if (w == 3 && lane < 3) mbar_arrive(BAR(B_LAND + lane));
  if (lane == 0) {
    if (w == 0) TSTAMP(15, cta, 0);
    sts32(sb + M_PT + w * 4, probe(part + blk * 16384 + w * 4096, NPROBE_ / 2));
    if (w == 0) TSTAMP(15, cta, 1);
  }
  bar_sync(N_AG, 128);
  const uint32_t inear = lds32(sb + M_PT + (w >> 1) * 8 + 4) < lds32(sb + M_PT + (w >> 1) * 8);
  if (lane == 0 && !(w & 1)) st_rlx(&f_choice[blk][w >> 1], (E << 1) | inear);
  if (w == 0) TSTAMP(15, cta, 2);
  uint32_t nb;
  {
    const int i = min(lane >> 1, C < 2 ? 8 : 5);
    const int r = ((i / 3 * 3 + C) * 4 + w) * 3 + i % 3;
    int guard = 0; uint32_t cw;
    while (__any_sync(~0u, ((cw = ld_rlx(&f_choice[r][lane & 1])) >> 1) != (E & 0x7FFFFFFFu))) { if (++guard > (1 << 22)) TRAP(); }
    nb = __ballot_sync(~0u, cw & 1) >> (lane >> 4);
    if (w == 0) TSTAMP(15, cta, 3);
  }
  bar_sync(N_AG, 128);
  const uint32_t pt0 = sb + M_PT + (tid & 127) * 16;
  {
    const uint32_t po = (C * 4 + w) * 49152 + (lane >> 4) * 8192 + head * 128 + (lane & 15) * 8;
    const uint8_t* in = part + (blk * 16384 + (w >> 1) * 8192 + inear * 4096 + (w & 1) * 64 + (lane >> 3) * 128 + (lane & 7) * 8);
    const uint8_t* outp = memg + ((blk / 12) * 8192 + (blk % 12) * 256 + w * 64 + (lane >> 4) * 4096 + (lane & 4) * 8 + (lane & 8) * 2 + (lane & 3) * 4);
#pragma unroll
    for (int i = 0; i < 12; i++) {
      const int j = i / 4 * 3 + (i & 3);
      const uint8_t* a = (i & 3) < 3 ? part + (po + i / 4 * 589824 + (i & 3) * 16384 + ((nb >> (2 * j)) & 1) * 4096) : i == 11 ? in : outp;
      asm volatile("st.shared.u64 [%0], %1;" :: "r"(pt0 + (i >> 1) * 2048 + (i & 1) * 8), "l"(a) : "memory");
    }
  }
  const int xd = __shfl_sync(~0u, XDLY_ + (blk < 24 ? 0 : blk < 60 ? X1_ : X2_), 0);
  const uint32_t rba = mapa(sb, C == 2 ? 0 : 2), rbc = mapa(sb, C == 1 ? 0 : 1);
  uint32_t vis = vis_bits(8 + 8 * w + g, t);
  uint32_t ln = lane;
#pragma unroll
  for (int i = 0; i < SALT_; i++) ln += lds32(sb + M_ZERO);
  PIN(vis); PIN(ln);
  if (tid == 256 && C == 0) st_rlx(&f_loaded[head], E);
  uint32_t fa[8][4];
#pragma unroll
  for (int ks = 0; ks < 8; ks++) ldmatrix4_t(fa[ks], sb + M_WO + 32768 + w * 256 + (lane >> 4) * 1024 + (lane & 15) * 16 + ks * 2048);
  if (w == 0) TSTAMP(14, cta, 0);
#pragma unroll 1
  for (int T = 0; T < NSTEP; T++) {
    const uint32_t ph = T & 1;
    const uint32_t zz = uni(lds32(sb + M_ZERO));
    const bool more = T < NSTEP - 1;
    const float sc = 0.08838834764831845f * 1.4426950408889634f;
    tag ^= 1;
    float s[20];
    const uint8_t* in; int cnext = -1; uint32_t tx; bool synced;
    float x[10], tm, ts;
    uint32_t pt[5];
    auto tok_max = [&]() {
      PIN(vis);
      x[0] = s[2]; x[1] = s[3];
#pragma unroll
      for (int i = 0; i < 8; i++) x[2 + i] = (vis >> i & 1) ? s[4 * (i / 2 + 1) + 2 + (i & 1)] : -INFINITY;
      tm = fmaxf(fmaxf(fmaxf(fmaxf(x[0], x[1]), fmaxf(x[2], x[3])), fmaxf(fmaxf(x[4], x[5]), fmaxf(x[6], x[7]))), fmaxf(x[8], x[9]));
      HOLD(7, __float_as_uint(tm));
    };
    auto tok_exp1 = [&]() {
      tm = fmaxf(tm, __shfl_xor_sync(~0u, tm, 1));
      tm = fmaxf(tm, __shfl_xor_sync(~0u, tm, 2));
      const float b = -tm * sc;
#pragma unroll
      for (int i = 0; i < 10; i++) x[i] = fmaf(x[i], sc, b);
      HOLD(10, __float_as_uint(x[9]));
    };
    auto tok_exp2 = [&]() {
#pragma unroll
      for (int i = 0; i < 10; i++) x[i] = ex2(x[i]);
      ts = (((x[0] + x[1]) + (x[2] + x[3])) + ((x[4] + x[5]) + (x[6] + x[7]))) + (x[8] + x[9]);
#pragma unroll
      for (int k = 0; k < 5; k++) pt[k] = pack2(x[2 * k], x[2 * k + 1]);
      HOLD(8, __float_as_uint(ts));
    };
    {
      uint32_t q[8][4];
      auto load_q = [&](uint32_t a, int h) {
#pragma unroll
        for (int k2 = 0; k2 < 4; k2++) {
          uint32_t r[4];
          ldmatrix4_t(r, a + k2 * 512);
          q[2 * k2][h] = r[0]; q[2 * k2][h + 2] = r[1]; q[2 * k2 + 1][h] = r[2]; q[2 * k2 + 1][h + 2] = r[3];
        }
      };
      PIN(ln);
      const uint32_t qa = sb + M_Q + ln * 16, qt = qa + w * 2048 + (C == 0 && ph ? M_TST - M_Q : 2048);
      const int cand = C == 2 ? (int)uni(lds32(sb + M_CAND + (T & 3) * 4)) : -1;
      mbar_wait(BAR(B_TOK), ph);
      load_q(qt, 1);
      mbar_wait(BAR(B_QK), ph);
      ASTAMP(0);
      if (T == 0 && w == 0) TSTAMP(13, cta, 3);
      if (__builtin_expect(cand >= 0, 0)) {
        mbar_wait(BAR(B_V), ph);
        PIN(ln);
        const int e = w * 32 + ln;
#pragma unroll
        for (int i = 0; i < 3; i++) {
          const uint32_t v = lds32(sb + M_Q + i * 12288 + 5 * 2048 + e * 16 + 4);
          asm volatile("st.shared.u16 [%0], %1;" :: "r"(sb + M_Q + i * 12288 + (1 + (cand >> 3)) * 2048 + e * 16 + (cand & 7) * 2), "h"((unsigned short)v) : "memory");
        }
        fence_async_smem();
        bar_sync(N_AG, 128);
        load_q(qt, 1);
      }
      constexpr uint64_t dk = mkdesc(M_K, 128, 2048, 0);
      fence_async_smem();
      uint32_t r[4][4];
#pragma unroll
      for (int k2 = 0; k2 < 4; k2++) ldmatrix4_t(r[k2], qa + k2 * 512);
#pragma unroll
      for (int k2 = 0; k2 < 4; k2++) {
        q[2 * k2][0] = r[k2][0]; q[2 * k2][2] = r[k2][1]; q[2 * k2 + 1][0] = r[k2][2]; q[2 * k2 + 1][2] = r[k2][3];
        if (k2 & 1) {
          wg_fence();
#pragma unroll
          for (int ks = 2 * k2 - 2; ks < 2 * k2 + 2; ks++) { if (ks == 0) wgmma_rs40<0, 1>(s, q[0], dk); else wgmma_rs40<1, 1>(s, q[ks], dk + ks * 16); }
        }
      }
      wg_commit();
    }
    if (more) {
      uint32_t v[5][4];
      PIN(ln);
      const uint32_t va = sb + M_V + w * 512 + ((ln >> 3) & 1) * 128 + (ln >> 4) * 2048 + (ln & 7) * 16;
      const uint32_t ooff = M_OM + w * 1536 + C * 256 + ln * 4;
      mbar_wait(BAR(B_V), ph);
      wg_wait<0>(); reg_fence(s);
      if (ln < 3) mbar_arrive_remote(mapa(BAR(B_KFREE), ln));
      ldmatrix4(v[0], va); ldmatrix4(v[1], va + 256); ldmatrix4(v[2], va + 4096); ldmatrix4(v[3], va + 4096 + 256);
      ldmatrix4(v[4], sb + M_V + 8192 + w * 512 + ln * 16);
      ASTAMP(1);
      float m = fmaxf(fmaxf(fmaxf(fmaxf(s[0], s[1]), fmaxf(s[4], s[5])), fmaxf(fmaxf(s[8], s[9]), fmaxf(s[12], s[13]))), fmaxf(s[16], s[17]));
      m = fmaxf(m, __shfl_xor_sync(~0u, m, 1));
      m = fmaxf(m, __shfl_xor_sync(~0u, m, 2));
      const float b = -m * sc;
      uint32_t pm[5];
#pragma unroll
      for (int j = 0; j < 5; j++) pm[j] = pack2(ex2(fmaf(s[4 * j], sc, b)), ex2(fmaf(s[4 * j + 1], sc, b)));
      float o0[4] = {0.f, 0.f, 0.f, 0.f}, o1[4] = {0.f, 0.f, 0.f, 0.f}, l[4] = {0.f, 0.f, 0.f, 0.f};
      const uint32_t one[4] = {0x3f803f80u, 0x3f803f80u, 0x3f803f80u, 0x3f803f80u};
      hmma16(l, one, pm[0], pm[1]); hmma16(o0, v[0], pm[0], pm[1]); hmma16(o1, v[1], pm[0], pm[1]);
      hmma16(l, one, pm[2], pm[3]); hmma16(o0, v[2], pm[2], pm[3]); hmma16(o1, v[3], pm[2], pm[3]);
      hmma8(l, one[0], one[1], pm[4]); hmma8(o0, v[4][0], v[4][1], pm[4]); hmma8(o1, v[4][2], v[4][3], pm[4]);
      const float r0 = rcp(l[0]), r1 = rcp(l[1]);
      const uint32_t u0 = pack2(o0[0] * r0, o0[1] * r1), u1 = pack2(o0[2] * r0, o0[3] * r1), u2 = pack2(o1[0] * r0, o1[1] * r1), u3 = pack2(o1[2] * r0, o1[3] * r1);
      constexpr uint32_t OB = M_BAR + 8 * B_OM;
      const uint32_t a0 = rba + ooff, a1 = rbc + ooff;
      st_async32(a0, u0, rba + OB); st_async32(a1, u0, rbc + OB);
      st_async32(a0 + 128, u1, rba + OB); st_async32(a1 + 128, u1, rbc + OB);
      st_async32(a0 + 768, u2, rba + OB); st_async32(a1 + 768, u2, rbc + OB);
      st_async32(a0 + 896, u3, rba + OB); st_async32(a1 + 896, u3, rbc + OB);
      bar_arrive(N_GO2, 384);
      sts32(sb + ooff, u0); sts32(sb + ooff + 128, u1); sts32(sb + ooff + 768, u2); sts32(sb + ooff + 896, u3);
      ASTAMP(2);
      uint32_t fb[8][4];
      const uint32_t wa = sb + M_WO + 16384 + w * 256 + (ln >> 4) * 1024 + (ln & 15) * 16 + zz;
      ldmatrix4_t(fb[0], wa);
      SCHED(3);
#pragma unroll
      for (int ks = 1; ks < 8; ks++) {
        ldmatrix4_t(fb[ks], wa + ks * 2048);
        if (ks == ARR_) { __syncwarp(); if (ln == 0) mbar_arrive(BAR(B_OM) + (fb[0][0] & zz)); }
      }
      if (blk % 3 == 2) cnext = (int)uni(lds32(sb + M_CAND + ((T + 1) & 3) * 4));
      {
        float d[12], e[12];
        constexpr uint64_t ob = mkdesc(M_OM, 128, 256, 0);
        uint8_t* q[3][3];
        auto addr = [&](int i) {
          asm volatile("ld.shared.v2.u64 {%0,%1}, [%2];" : "=l"(q[i][0]), "=l"(q[i][1]) : "r"(pt0 + i * 4096) : "memory");
          if (i < 2) asm volatile("ld.shared.u64 %0, [%1];" : "=l"(q[i][2]) : "r"(pt0 + i * 4096 + 2048) : "memory");
          else asm volatile("ld.shared.v2.u64 {%0,%1}, [%2];" : "=l"(q[i][2]), "=l"(in) : "r"(pt0 + i * 4096 + 2048) : "memory");
        };
        auto put = [&](const float* d, int i) {
          st_rlx64(q[i][0], (pack2(d[0], d[1]) & ~1u) | tag, pack2(d[2], d[3]));
          st_rlx64(q[i][1], (pack2(d[4], d[5]) & ~1u) | tag, pack2(d[6], d[7]));
          st_rlx64(q[i][2], (pack2(d[8], d[9]) & ~1u) | tag, pack2(d[10], d[11]));
        };
        addr(0); addr(1);
        SCHED(6);
        tok_max();
        ASTAMP(3);
        mbar_wait(BAR(B_OM), ph);
        if (!(NOF_ & 2)) fence_async_smem();
        ASTAMP(4);
        constexpr uint64_t w0 = mkdesc(M_WO, 1024, 128, 0);
        float (&f)[12] = d;
        wg_fence();
        wgmma_ss24<0, 1, 1>(d, w0, ob);
#pragma unroll
        for (int ks = 1; ks < 8; ks++) wgmma_ss24<1, 1, 1>(d, w0 + ks * 128, ob + ks * 48);
        wg_commit();
        wgmma_rs24<0, 1>(e, fb[0], ob);
#pragma unroll
        for (int ks = 1; ks < HAND_; ks++) wgmma_rs24<1, 1>(e, fb[ks], ob + ks * 48);
        wg_commit();
        wg_wait<1>(); reg_fence(d);
        put(d, 0);
        addr(2);
        SCHED(4);
        ASTAMP(5);
        wg_fence();
#pragma unroll
        for (int ks = HAND_; ks < 8; ks++) wgmma_rs24<1, 1>(e, fb[ks], ob + ks * 48);
        wg_commit();
        wgmma_rs24<0, 1, 1>(f, fa[0], ob);
#pragma unroll
        for (int ks = 1; ks < HAND_; ks++) wgmma_rs24<1, 1>(f, fa[ks], ob + ks * 48);
        wg_commit();
        wg_wait<1>(); reg_fence(e);
        put(e, 1);
        SCHED(5);
        if (C < 2) {
          wg_fence();
#pragma unroll
          for (int ks = HAND_; ks < 8; ks++) wgmma_rs24<1, 1>(f, fa[ks], ob + ks * 48);
          wg_commit();
        }
        if (GO3_ == 0) bar_arrive(N_GO3, 384);
        synced = __all_sync(~0u, mbar_test(BAR(B_SYNC), ph));
        tx = uni(lds32(sb + M_BASE + ph * 4)) + xd;
        wg_wait<0>(); reg_fence(f);
        if (GO3_ == 1) bar_arrive(N_GO3, 384);
        if (C < 2) put(f, 2);
        if (GO3_ == 2) bar_arrive(N_GO3, 384);
        ASTAMP(6);
        if (T == 0 && w == 0) TSTAMP(14, cta, 1);
      }
    } else {
      mbar_wait(BAR(B_V), ph);
      wg_wait<0>(); reg_fence(s);
      tok_max();
    }
    uint2 v[8];
#pragma unroll
    for (int i = 0; i < 8; i++) v[i] = make_uint2(zz, zz);
    auto poll = [&](uint2* v) {
      v[0] = ld_rlx64<0>(in); v[1] = ld_rlx64<512>(in); v[2] = ld_rlx64<1024>(in); v[3] = ld_rlx64<1536>(in);
      v[4] = ld_rlx64<2048>(in); v[5] = ld_rlx64<2560>(in); v[6] = ld_rlx64<3072>(in); v[7] = ld_rlx64<3584>(in);
    };
    uint8_t* outp;
    asm volatile("ld.shared.u64 %0, [%1];" : "=l"(outp) : "r"(pt0 + 2048 + 8) : "memory");
    const uint32_t itag = gentag((E - 1) * (uint32_t)(NSTEP - 1) + T + 1);
    const bool sum = more && cnext < 0;
    if (more) {
      if (!synced) { mbar_wait(BAR(B_SYNC), ph); tx = uni(lds32(sb + M_BASE + ph * 4)) + xd; }
      ASTAMP(7);
      if (__builtin_expect(cnext >= 0, 0)) {
        const unsigned long long* hp = (const unsigned long long*)&g_hc[T + 1 - LAG][0] + ((blk / 3) * 8 + 2 * w + ((ln >> 2) & 1));
        unsigned long long v0; int guard = 0;
        while (v0 = ld_rlxu64(hp), !__all_sync(~0u, (uint32_t)(v0 >> 32) == E)) { if (++guard > (1 << 22)) TRAP(); }
        st_rlx((uint32_t*)outp, (ln & 3) == 1 ? ((uint32_t)v0 >> ((ln & 8) * 2)) & 0xffffu : (ln & 1) ? 0u : itag);
      } else {
        spin_until(tx);
        ASTAMP(8);
        poll(v);
      }
    }
    auto late = [&](const uint2* v) {
      return __any_sync(~0u, (or3(xo2(v[0].x, v[1].x, tag), xo2(v[2].x, v[3].x, tag), xo2(v[4].x, v[5].x, tag)) | xo2(v[6].x, v[7].x, tag)) & 1u);
    };
    tok_exp1(); tok_exp2();
    auto reduce = [&]() {
      if (sum) {
        ASTAMP(9);
        int guard = 0;
        while (late(v)) {
          if (++guard > (1 << 22)) TRAP();
          poll(v);
        }
#pragma unroll
        for (int i = 0; i < 4; i++) { v[i].x = add2(v[i].x, v[i + 4].x); v[i].y = add2(v[i].y, v[i + 4].y); }
        const bool hi = ln & 8;
        const uint32_t x0 = add2(v[0].x, v[1].x), x1 = add2(v[2].x, v[3].x), y0 = add2(v[0].y, v[1].y), y1 = add2(v[2].y, v[3].y);
        const uint32_t m0 = hi ? y0 : x0, m1 = hi ? y1 : x1;
        const uint32_t n0 = __shfl_xor_sync(~0u, hi ? x0 : y0, 8), n1 = __shfl_xor_sync(~0u, hi ? x1 : y1, 8);
        float k0 = (blo(m0) + blo(m1)) + (blo(n0) + blo(n1)), k1 = (bhi(m0) + bhi(m1)) + (bhi(n0) + bhi(n1));
        k0 += __shfl_xor_sync(~0u, k0, 16); k1 += __shfl_xor_sync(~0u, k1, 16);
        st_rlx((uint32_t*)outp, (ln & 1) ? pack2(k0, k1) : pack2_tag(k0, k1, itag));
        ASTAMP(10);
        if (T == 0 && w == 0) TSTAMP(14, cta, 2);
        CSTAMP(12 + w, (clk() & ~15u) | min(guard + 1, 15));
      }
      if (more) bar_arrive(N_GO4, 384);
    };
    if (PVR_ < 0) reduce();
    {
      PIN(ln);
      const uint32_t oa = sb + M_OST + w * 128 + (ln >> 3) * 512 + (ln & 7) * 16;
      const uint32_t a[3][4] = {{0, pt[0], 0, pt[1]}, {0, pt[2], 0, pt[3]}, {0, pt[4], 0, 0}};
      constexpr uint64_t dv = mkdesc(M_V, 2048, 128, 0);
#pragma unroll 1
      for (int h = 0; h < 2; h++) {
        float o[32];
        const uint64_t dh = dv + (uint64_t)(h * 64);
        wg_fence();
        wgmma_rs64<0, 0>(o, a[0], dh); wgmma_rs64<1, 0>(o, a[1], dh + 256); wgmma_rs64<1, 0>(o, a[2], dh + 512);
        wg_commit();
        if (h == PVR_) reduce();
        if (h == 0) {
          ts += __shfl_xor_sync(~0u, ts, 1);
          ts += __shfl_xor_sync(~0u, ts, 2);
          ts = rcp(ts);
          mbar_wait(BAR(B_OFREE), ph ^ 1);
        }
        wg_wait<0>(); reg_fence(o);
        if (h == 1 && ln < 3) mbar_arrive_remote(mapa(BAR(B_VFREE), ln));
#define OT(i) pack2(o[4 * (i) + 2] * ts, o[4 * (i) + 3] * ts)
        stmatrix4(oa + h * 4096, OT(0), OT(1), OT(2), OT(3));
        stmatrix4(oa + h * 4096 + 2048, OT(4), OT(5), OT(6), OT(7));
      }
      const uint32_t z5 = DRAIN(oa);
      __syncwarp();
      if (ln == 0) mbar_arrive(BAR(B_OST) + z5);
      ASTAMP(11);
    }
  }
}

__global__ void __cluster_dims__(3, 1, 1) __launch_bounds__(512, 1) main_kernel(Params p) {
  extern __shared__ __align__(1024) uint8_t sm[];
  const uint32_t sb = smem_u32(sm);
  if ((sb & 0xFFFFFFu) != SBASE) TRAP();
  asm volatile("griddepcontrol.launch_dependents;");
  const int warp = __shfl_sync(~0u, threadIdx.x >> 5, 0);
  const int cta = blockIdx.x, head = cta / 3, c = cta % 3;
  const uint32_t E = __shfl_sync(~0u, *(volatile uint32_t*)&g_epoch + 1, 0);
  uint8_t* const part = (uint8_t*)(((uintptr_t)g_xch + 8191) & ~(uintptr_t)8191);
  uint8_t* const memg = part + 96 * 16384;

  if (threadIdx.x == 0 && cta == 0) GSTAMP(0, 0);
  if (threadIdx.x < B_NUM) {
    const int i = threadIdx.x;
    const uint32_t cnt = i == B_STG || i == B_STG1 ? 8 : i == B_OST ? 4 : i == B_HAE || i == B_HBE ? 6 : i == B_KFREE || i == B_VFREE ? 12 : i == B_SS ? 2 : i == B_OM ? 5 :
                         i == B_QK ? (c < 2 ? 9 : 1) : i == B_V ? (c < 2 ? 1 : 9) : 1;
    mbar_init(BAR(i), cnt);
    if (i == B_HA || i == B_HB || i == B_STG || i == B_HAE || i == B_HBE || i == B_TFREE)
      asm volatile("mbarrier.arrive.shared::cta.b64 _, [%0], %1;" :: "r"(BAR(i)), "r"(cnt) : "memory");
    asm volatile("fence.mbarrier_init.release.cluster;" ::: "memory");
  }
  if (warp < 8) {
    const int tid = threadIdx.x;
    uint4 wa[6], wb[6];
#pragma unroll
    for (int i = 0; i < 6; i++) {
      const int mi = i >> 1, e = (tid >> 2) + (i & 1) * 64;
      const uint4* src = (const uint4*)(p.wo + (size_t)(head * 128 + e) * 512 + min(3 * mi + c, 7) * 64 + (tid & 3) * 16);
      wa[i] = __ldg(src); wb[i] = __ldg(src + 1);
    }
    stage_weights(sb, (c == 0 ? p.wq : c == 1 ? p.wk : p.wv) + head * 128, 4096, tid, 256);
#pragma unroll
    for (int i = 0; i < 6; i++) {
      const int mi = i >> 1, e = (tid >> 2) + (i & 1) * 64;
      const uint4 a = wa[i], b = wb[i];
      const uint32_t dst = sb + M_WO + mi * 16384 + (e >> 3) * 1024 + (tid & 3) * 256 + (e & 7) * 16;
      sts128(dst, make_uint4(__byte_perm(a.x, a.y, 0x5410), __byte_perm(a.z, a.w, 0x5410), __byte_perm(b.x, b.y, 0x5410), __byte_perm(b.z, b.w, 0x5410)));
      sts128(dst + 128, make_uint4(__byte_perm(a.x, a.y, 0x7632), __byte_perm(a.z, a.w, 0x7632), __byte_perm(b.x, b.y, 0x7632), __byte_perm(b.z, b.w, 0x7632)));
    }
  } else {
    const int i0 = threadIdx.x - 256;
    const uint32_t tag0 = ((E - 1) * (uint32_t)(NSTEP - 1)) & 1;
    for (int i = i0; i < 1024; i += 256) *(uint4*)(part + block_of(head, c) * 16384 + i * 16) = make_uint4(tag0, 0, tag0, 0);
    if (i0 < 16) *(uint32_t*)(memg + i0 * 4096 + 3968) = 0;
    if (i0 < 2) st_rlx(&f_choice[block_of(head, c)][i0], 0);
    if (i0 < 8) st_rlx64(&g_sync[i0 >> 2][cta][i0 & 3], 0, 0);
    __threadfence();
    if (i0 < 12) sts32(sb + M_ZERO + i0 * 4, 0);
    if (i0 < 2) { sts32(sb + M_BASE + i0 * 4, clk32() - 65536); sts32(sb + M_BAS2 + i0 * 4, clk32() - 65536); sts32(sb + M_CAND + i0 * 4, (uint32_t)-1); }
  }

  if (warp < 8) {
    asm volatile("setmaxnreg.inc.sync.aligned.u32 " STR(RW_) ";");
    weight_role(p, sb, warp, cta, c, E, memg);
  } else if (warp < 12) {
    if (RA_ < 128) asm volatile("setmaxnreg.dec.sync.aligned.u32 " STR(RA_) ";");
    if (RA_ > 128) asm volatile("setmaxnreg.inc.sync.aligned.u32 " STR(RA_) ";");
    attn_role(p, sb, warp - 8, cta, head, c, E, part, memg);
    cluster_sync();
  } else {
    asm volatile("setmaxnreg.dec.sync.aligned.u32 " STR(RC_) ";");
    const int tid = fresh_tid(), lane = tid & 31;
    const int w = warp - 12;
    cluster_sync();
    if (w != 2) {
      const int tl = w == 0 ? c : w == 1 ? 2 + c : 5 + c;
      int near = 0;
      if (lane == 0) { const int t0 = probe(memg + tl * 8192, NPROBE_ / 2); near = probe(memg + tl * 8192 + 4096, NPROBE_ / 2) < t0; }
      near = uni(near);
      if (lane < 3) asm volatile("st.shared::cluster.u32 [%0], %1;" :: "r"(mapa(sb + M_NEAR + tl * 4, lane)), "r"(near) : "memory");
      __syncwarp();
    }
    if (w == 0) {
      int yadj = 0, dmin = 1 << 20; uint32_t prev = 0; bool cprev = false;
      uint32_t s1 = (2 + c) * 8192, s2 = (5 + c) * 8192;
#pragma unroll 1
      for (int T = 0; T < NSTEP - 1; T++) {
        const uint32_t ph = T & 1;
        mbar_wait(BAR(B_SS), ph);
        const uint32_t cq = clk();
        const uint32_t g0 = (uint32_t)gtime64(); uint32_t g1, ce;
        do { g1 = (uint32_t)gtime64(); ce = clk(); } while (g1 == g0);
        const uint32_t tn = g1 * 8 - (((ce - cq) * 37u) >> 3), id = E * 128u + T;
        if (lane < 4) st_rlx64(&g_sync[ph][cta][lane], tn, id);
        if (lane < 3) mbar_expect(BAR(B_LAND + lane), lane ? 9216 : 6144);
        if (T == 0) { s1 += uni(lds32(sb + M_NEAR + (2 + c) * 4)) * 4096; s2 += uni(lds32(sb + M_NEAR + (5 + c) * 4)) * 4096; }
        wait_until(cq + SDLY_);
        int guard = 0; unsigned long long v0, v1, v2;
        for (;;) {
          v0 = ld_rlxu64(g_sync[ph][lane]); v1 = ld_rlxu64(g_sync[ph][lane + 32]); v2 = ld_rlxu64(g_sync[ph][lane + 64]);
          if (__all_sync(~0u, (uint32_t)(v0 >> 32) == id && (uint32_t)(v1 >> 32) == id && (uint32_t)(v2 >> 32) == id)) break;
          if (++guard > (1 << 22)) TRAP();
        }
        const bool cnd = (int)uni(lds32(sb + M_CAND + (T & 3) * 4)) >= 0;
        const int dl = __reduce_max_sync(~0u, max(max((int)((uint32_t)v0 - tn), (int)((uint32_t)v1 - tn)), (int)((uint32_t)v2 - tn)));
        const uint32_t base = uni(cq + ((min(dl, 8 * 4096) * 7) >> 5)) + (T == 0 ? SLOW0_ : T == 1 ? SLOW1_ : 0) +
                              (cnd ? CDLY_ : 0) - (T + 2 < NSEG ? 0 : BOFF_);
        const int dur = (int)(base - prev);
        if (!cnd && !cprev) {
          yadj = T > 2 && dur > dmin + 700 ? min(yadj + YUP_, 400) : max(yadj - YDN_, 0);
          if (T > 1) dmin = min(dmin + 20, dur);
        }
        prev = base; cprev = cnd;
        if (lane == 0) { sts32(sb + M_BASE + ph * 4, base); sts32(sb + M_BAS2 + ph * 4, base + yadj); mbar_arrive(BAR(B_SYNC)); }
        CSTAMP(0, base); CSTAMP(1, clk());
        const uint32_t ts = base + YDLY_ + yadj - (T + 2 >= LAG && T + 2 < NSEG ? 0 : YOFF_);
        const uint8_t* const t0 = memg + uni(lds32(sb + M_NEAR)) * 4096, * const t1 = memg + 8192 + uni(lds32(sb + M_NEAR + 4)) * 4096;
        wait_until(ts);
        e_g2s(sb + M_MEM, t0, 3072, BAR(B_LAND)); e_g2s(sb + M_MEM + 3072, t1, 3072, BAR(B_LAND));
        CSTAMP(2, clk());
        spin_until(ts + Y1_);
        e_mc(sb + M_MEM + (2 + c) * 3072, memg + s1, 3072, BAR(B_LAND + 1), 7);
        CSTAMP(3, clk());
        spin_until(ts + Y2_);
        e_mc(sb + M_MEM + (5 + c) * 3072, memg + s2, 3072, BAR(B_LAND + 2), 7);
        CSTAMP(4, clk());
      }
    } else if (w == 1) {
#pragma unroll 1
      for (int T = 0; T < NSTEP; T++) {
        const uint32_t ph = T & 1;
        const int s = c == 0 ? T : T - LAG;
        const bool act = s >= 0 && s < NSEG;
        mbar_wait(BAR(B_OST), ph);
        if (cta == 0) TSTAMP(2, T, 0);
        fence_async_smem();
        if (T < NSTEP - 1) wait_until(uni(lds32(sb + M_BAS2 + ph * 4)) + ODLY_);
        STAMP(22);
        if (act) paced_st(g_o[c][s % ORING][head], sb + M_OST, OGAP_);
        if (c == 2 && T < NSTEP - 1) {
          mbar_wait(BAR(B_STG1), ph ^ 1);
          mbar_wait(BAR(B_VFREE), ph);
          STAMP(23);
          e_mc(sb + M_V + 2048, g_tok[cta][ph ^ 1] + 8192, 8192, BAR(B_V), 6);
          e_mc(sb + M_V + 2048, g_tok[cta][ph ^ 1], 8192, BAR(B_V), 1);
        }
        bulk_wait();
        __syncwarp();
        e_arrive(BAR(B_OFREE));
        if (cta == 0) TSTAMP(2, T, 1);
        if (act && lane < 8) st_rel(&f_o[T][head >> 2][c * 4 + (head & 3)][lane], E);
        __syncwarp();
        if (cta == 0) TSTAMP(2, T, 2);
      }
    } else if (w == 2) {
      unsigned long long run = 0;
      static_assert(LAG >= 2, "config");
      constexpr uint32_t NA = EA / 4 * 4096;
      e_expect(BAR(B_QK), c < 2 ? 2048 : 4096); e_expect(BAR(B_V), c == 0 ? 10240 : c == 1 ? 2048 : 0);
      e_expect(BAR(B_TOK), c == 0 ? 16384 : 0); e_expect(BAR(B_OM), 4096);
      e_expect(BAR(B_HA), NA); e_expect(BAR(B_HB), 65536 - NA);
      wait_eq(&f_h1[c == 1 ? 0 : 1], E); fence_async_glob();
      {
        const uint32_t o0 = c == 0 ? NA : 0, o1 = c == 2 ? NA : 32768;
        e_mc(sb + M_H + (c == 1 ? 32768 : 0) + o0, g_h[0][c == 1 ? 0 : 1] + o0, o1 - o0, BAR(c == 2 ? B_HA : B_HB), 7);
      }
      TSTAMP(14, cta, 3);
      if (c == 2) wait_eq(&f_h1[2], E);
      mbar_wait(BAR(B_HAE), 1);
      e_expect(BAR(B_HA), NA);
      if (c == 2) { fence_async_glob(); e_mc(sb + M_H, g_h[0][2], NA, BAR(B_HA), 7); }
      int cprev = -1;
#pragma unroll 1
      for (int T = 0; T < NSTEP - 1; T++) {
        const int s1 = T + 2, s2 = T + 2 - LAG;
        const uint32_t ph = T & 1;
        const bool l1 = s1 < NSEG, l2 = s2 >= 0 && s2 < NSEG, la = s1 + 1 < NSEG;
        const bool mine = c == 0 ? l1 : c == 1 ? l2 : la;
        const uint32_t* fl = c != 1 ? &f_h1[min(s1 + (c >> 1), NSEG - 1)] : (const uint32_t*)f_h2[max(s2, 0)][lane & 3] + 1;
        const uint32_t want = E & 0x1FFFFFu, sh = c != 1 ? 0 : 11;
        mbar_wait(BAR(B_HBE), ph ^ 1);
        const bool early = __all_sync(~0u, ((ld_acq(fl) >> sh) & 0x1FFFFFu) == want);
        mbar_wait(BAR(B_LAND + 2), ph);
        STAMP(16);
        e_expect(BAR(B_HB), (l1 ? 32768 - NA : 0) + (l2 ? 32768 : 0));
        if (mine) {
          if (!early) {
            int guard = 0;
            while (!__all_sync(~0u, ((ld_acq(fl) >> sh) & 0x1FFFFFu) == want)) { __nanosleep(32); if (++guard > (1 << 22)) TRAP(); }
          }
          fence_async_glob();
          if (c == 1) { mbar_wait(BAR(B_QK), ph); spin_until(clk32() + HDLY_); }
          if (c < 2) paced_h(sb + M_H + c * 32768, g_h[c][c ? s2 : s1], c ? 0 : NA, 32768, 4096, BAR(B_HB), HGAP_);
        }
        int cd = -1;
        if (l2) { cd = route_step(s2, E, lane, run); if (cta == 0) TSTAMP(5, s2, 0); }
        if (lane == 0) sts32(sb + M_CAND + ((T + 2) & 3) * 4, (uint32_t)cd);
        __syncwarp();
        STAMP(17);
        mbar_wait(BAR(B_HAE), ph);
        e_expect(BAR(B_HA), la ? NA : 0);
        if (c == 2 && la) {
          spin_until(clk32() + ADLY_);
          STAMP(18);
          paced_h(sb + M_H, g_h[0][s1 + 1], 0, NA, 4096, BAR(B_HA), AGAP_);
        }
        mbar_wait(BAR(B_OST), ph);
        e_expect(BAR(B_QK), c < 2 ? 2048 : cprev >= 0 ? 8192 : 4096);
        e_expect(BAR(B_V), c < 2 ? 10240 : 8192);
        e_expect(BAR(B_TOK), c == 0 ? 8192 : 16384);
        e_expect(BAR(B_OM), 4096);
        cprev = cd;
      }
    } else {
      const uint32_t mytok = sb + M_Q + c * 12288 + 2048, tb = BAR(c < 2 ? B_TOK : B_V);
      mbar_wait(BAR(B_STG1), 0);
      fence_async_smem();
      if (c) e_s2g(g_tok[cta][1], sb + M_TST, 8192);
#pragma unroll 1
      for (int T = 0; T < NSTEP - 1; T++) {
        const uint32_t ph = T & 1;
        uint8_t* const tok = g_tok[cta][ph ^ 1];
        mbar_wait(BAR(B_STG), ph ^ 1);
        fence_async_smem();
        if (cta == 0 && (T == 0 || T == NSEG || T == NSTEP - 2)) GSTAMP(0, T == 0 ? 2 : T == NSEG ? 3 : 4);
        if (T > 0 && TQ_) mbar_wait(BAR(B_QK), ph);
        STAMP(20);
        paced_st(tok + 8192, sb + M_TST + 8192, TGAP_);
        bulk_wait();
        __syncwarp();
        e_arrive(BAR(B_TFREE));
        if (T == 0) e_mc(mytok, tok + 8192, 8192, tb, 1);
        STAMP(21);
        if (c < 2) {
          mbar_wait(BAR(B_KFREE), ph);
          spin_until(clk32() + KDLY_);
          STAMP(23);
          if (c) e_mc(mytok, tok, 8192, tb, 1);
          e_mc(mytok, tok + 8192, 8192, tb, 6);
        }
        mbar_wait(BAR(B_STG1), ph ^ 1);
        fence_async_smem();
        wait_until(uni(lds32(sb + M_BAS2 + ph * 4)) + TDLY_);
        if (c) paced_st(g_tok[cta][ph], sb + M_TST, T1GAP_);
        STAMP(24);
      }
      bulk_wait();
    }
    __syncwarp();
    cluster_sync();
  }
}

constexpr uint32_t A_RING = 0;
constexpr int A_NST = 6;
constexpr uint32_t A_STG = A_RING + A_NST * 8192;
constexpr uint32_t A_WD = A_STG + 8192;
constexpr uint32_t A_WG = A_WD + 57344;
constexpr uint32_t A_WU = A_WG + 57344;
constexpr uint32_t A_XN = A_WU + 57344;
constexpr uint32_t A_BAR = A_XN + 2048;
constexpr uint32_t A_TOTAL = A_BAR + 256;
static_assert(A_TOTAL <= 232448, "aux smem");

__device__ __forceinline__ uint32_t ptag(int s) { return ((s / PRING) & 1) ^ 1; }
static_assert((NSEG / PRING) % 2 == 0, "tags");
__device__ __forceinline__ void load_row(uint32_t* v, const void* row, int lane) {
  const uint4 a = __ldcg((const uint4*)row + lane), b = __ldcg((const uint4*)row + 32 + lane);
  v[0] = a.x; v[1] = a.y; v[2] = a.z; v[3] = a.w; v[4] = b.x; v[5] = b.y; v[6] = b.z; v[7] = b.w;
}
__device__ __forceinline__ void store_row(void* row, const uint32_t* v, int lane) {
  ((uint4*)row)[lane] = make_uint4(v[0], v[1], v[2], v[3]); ((uint4*)row)[32 + lane] = make_uint4(v[4], v[5], v[6], v[7]);
}
__device__ __forceinline__ void store_img(uint8_t* img, int r, const uint32_t* v, int lane) {
  uint8_t* b = img + (lane >> 3) * 4096 + (r >> 3) * 1024 + (r & 7) * 128 + (((lane ^ r) & 7) << 4);
  *(uint4*)b = make_uint4(v[0], v[1], v[2], v[3]);
  *(uint4*)(b + 16384) = make_uint4(v[4], v[5], v[6], v[7]);
}
template <int NT> __device__ __forceinline__ void ln_rows(const uint32_t (*v)[8], uint32_t (*y)[8]) {
  float c[NT], sm[NT], sq[NT];
#pragma unroll
  for (int k = 0; k < NT; k++) {
    c[k] = blo(__shfl_sync(~0u, v[k][0], 0));
    float s0 = 0.f, s1 = 0.f, q0 = 0.f, q1 = 0.f;
#pragma unroll
    for (int i = 0; i < 8; i++) { const float a = blo(v[k][i]) - c[k], b = bhi(v[k][i]) - c[k]; s0 += a; s1 += b; q0 = fmaf(a, a, q0); q1 = fmaf(b, b, q1); }
    sm[k] = s0 + s1; sq[k] = q0 + q1;
  }
#pragma unroll
  for (int o = 16; o > 0; o >>= 1)
#pragma unroll
    for (int k = 0; k < NT; k++) {
      sm[k] += __shfl_xor_sync(~0u, sm[k], o); sq[k] += __shfl_xor_sync(~0u, sq[k], o);
    }
#pragma unroll
  for (int k = 0; k < NT; k++) {
    const float dm = sm[k] * (1.f / 512.f), var = fmaxf(fmaf(-dm, dm, sq[k] * (1.f / 512.f)), 0.f);
    const float mb = rbf(c[k] + dm), inv = rcp(rbf(sqrt_fast(rbf(rbf(var) + 1e-5f))));
#pragma unroll
    for (int i = 0; i < 8; i++) { const uint32_t a = pack2(blo(v[k][i]) - mb, bhi(v[k][i]) - mb); y[k][i] = pack2(blo(a) * inv, bhi(a) * inv); }
  }
}
__device__ __forceinline__ void input_ln_pair(const bf16* x, int s, int pr, int lane) {
  uint32_t v[2][8], y[2][8];
  load_row(v[0], x + (size_t)(s * 32 + 2 * pr) * 512, lane); load_row(v[1], x + (size_t)(s * 32 + 2 * pr + 1) * 512, lane);
  ln_rows<2>(v, y);
  store_img(g_h[0][s], 2 * pr, y[0], lane); store_img(g_h[0][s], 2 * pr + 1, y[1], lane);
}
__device__ __forceinline__ float load_wr(uint32_t* wv, const bf16* wr, int lane) {
  load_row(wv, wr, lane);
  float wsum = 0.f;
#pragma unroll
  for (int i = 0; i < 8; i++) wsum += blo(wv[i]) + bhi(wv[i]);
#pragma unroll
  for (int o = 16; o > 0; o >>= 1) wsum += __shfl_xor_sync(~0u, wsum, o);
  return wsum;
}

template <bool FAST>
__device__ __forceinline__ unsigned long long token_post(int st, int tk, const bf16* res, bf16* dst, bf16* req, unsigned long long best,
                                                         const uint32_t* wv, float wsum, uint32_t E, int lane) {
  const int s = tk >> 5;
  uint32_t x[8];
  load_row(x, res, lane);
  {
    int guard = 0;
    while (__popc(__ballot_sync(~0u, ld_rlx(f_acc[st][s][lane]) == E)) < (FAST ? HINT_ : 32)) { __nanosleep(FAST ? 20 : 100); if (++guard > (1 << 22)) TRAP(); }
  }
  if (tk == s * 32 && st == 0 && lane == 0) TSTAMP(4, s, 0);
  {
    const uint8_t* pp = g_pp[st][s % PRING] + (lane >> 4) * 8192 + (tk & 31) * 256 + (((lane & 15) ^ (tk & 7)) << 4);
    const uint32_t tag = ptag(s);
    uint4 q[8][2];
#define PLD(k, h) q[k][h] = ld_rlx128<(k) * 32768 + (h) * 16384>(pp)
#define PLD8(h) PLD(0, h); PLD(1, h); PLD(2, h); PLD(3, h); PLD(4, h); PLD(5, h); PLD(6, h); PLD(7, h)
#define PBAD(h) __any_sync(~0u, (or3(xo2(q[0][h].x, q[1][h].x, tag), xo2(q[2][h].x, q[3][h].x, tag), xo2(q[4][h].x, q[5][h].x, tag)) | xo2(q[6][h].x, q[7][h].x, tag)) & ~lane & (PST_ == 8192 ? 1u : 0u))
#define PSUM(f, h, m) (((f(q[0][h].m) + f(q[1][h].m)) + (f(q[2][h].m) + f(q[3][h].m))) + ((f(q[4][h].m) + f(q[5][h].m)) + (f(q[6][h].m) + f(q[7][h].m))))
    const uint32_t eye = (lane >> 2) == 2 * (lane & 3) ? 0x3f80u : (lane >> 2) == 2 * (lane & 3) + 1 ? 0x3f800000u : 0u;
    auto padd = [&](int h) {
      if (FAST) {
        float u[4] = {0.f, 0.f, 0.f, 0.f}, v[4] = {0.f, 0.f, 0.f, 0.f};
#pragma unroll
        for (int k = 0; k < 8; k++) { hmma8(u, q[k][h].x, q[k][h].y, eye); hmma8(v, q[k][h].z, q[k][h].w, eye); }
        x[4 * h] = add2(x[4 * h], pack2(u[0], u[1])); x[4 * h + 1] = add2(x[4 * h + 1], pack2(u[2], u[3]));
        x[4 * h + 2] = add2(x[4 * h + 2], pack2(v[0], v[1])); x[4 * h + 3] = add2(x[4 * h + 3], pack2(v[2], v[3]));
      } else {
        x[4 * h] = add2(x[4 * h], pack2(PSUM(blo, h, x), PSUM(bhi, h, x))); x[4 * h + 1] = add2(x[4 * h + 1], pack2(PSUM(blo, h, y), PSUM(bhi, h, y)));
        x[4 * h + 2] = add2(x[4 * h + 2], pack2(PSUM(blo, h, z), PSUM(bhi, h, z))); x[4 * h + 3] = add2(x[4 * h + 3], pack2(PSUM(blo, h, w), PSUM(bhi, h, w)));
      }
    };
    int guard = 0;
    PLD8(0);
    if (FAST) { PLD8(1); }
    while (PBAD(0)) { if (++guard > (1 << 20)) TRAP(); PLD8(0); }
    padd(0);
    if (!FAST) { PLD8(1); }
    while (PBAD(1)) { if (++guard > (1 << 20)) TRAP(); PLD8(1); }
    padd(1);
  }
  const float c = blo(__shfl_sync(~0u, x[0], 0));
  float s0 = 0.f, s1 = 0.f, q0 = 0.f, q1 = 0.f, r0 = 0.f, r1 = 0.f;
#pragma unroll
  for (int i = 0; i < 8; i++) {
    const float a = blo(x[i]) - c, b = bhi(x[i]) - c;
    s0 += a; s1 += b; q0 = fmaf(a, a, q0); q1 = fmaf(b, b, q1); r0 = fmaf(a, blo(wv[i]), r0); r1 = fmaf(b, bhi(wv[i]), r1);
  }
  s0 += s1; q0 += q1; r0 += r1;
#pragma unroll
  for (int o = 16; o > 0; o >>= 1) { s0 += __shfl_xor_sync(~0u, s0, o); q0 += __shfl_xor_sync(~0u, q0, o); r0 += __shfl_xor_sync(~0u, r0, o); }
  const float dm = s0 * (1.f / 512.f), m = c + dm, var = fmaxf(fmaf(-dm, dm, q0 * (1.f / 512.f)), 0.f);
  const float mb = rbf(m), inv = rcp(rbf(sqrt_fast(rbf(rbf(var) + 1e-5f))));
  const uint32_t nmb = pack2(-mb, -mb);
  const unsigned long long wd = rword(E, tk, fmaf(c - mb, wsum, r0) * inv);
  uint32_t xn[8], x2[8];
#pragma unroll
  for (int i = 0; i < 8; i++) { const uint32_t d = add2(x[i], nmb); xn[i] = pack2(blo(d) * inv, bhi(d) * inv); x2[i] = add2(x[i], xn[i]); }
  if (st == 0) {
    const float mb2 = rbf(fmaf(m - mb, inv, m)), inv2 = rcp(rbf(sqrt_fast(rbf(rbf(var * (1.f + inv) * (1.f + inv)) + 1e-5f))));
    const uint32_t nmb2 = pack2(-mb2, -mb2);
    uint32_t h[8];
#pragma unroll
    for (int i = 0; i < 8; i++) { const uint32_t d2 = add2(x2[i], nmb2); h[i] = pack2(blo(d2) * inv2, bhi(d2) * inv2); }
    store_img(g_h[1][s], tk & 31, h, lane);
  }
  store_row(dst, x2, lane);
  if (wd > best && !(EXPQ_ & (st == 0 ? 1 : 2))) { store_row(req, xn, lane); store_row(req + 512, x, lane); }
  return wd;
}

__device__ __forceinline__ void ffn_slice(uint32_t sb, const bf16* xn, float* yacc, uint32_t* flag, uint32_t E, int t, bool urgent) {
  const int w = t >> 5, g = (t >> 2) & 7;
  if (t == 0 && urgent) sts32(sb + A_BAR + 160, 1);
  { const uint2 u = __ldcg((const uint2*)xn + t); asm volatile("st.shared.v2.u32 [%0], {%1,%2};" :: "r"(sb + A_XN + t * 8), "r"(u.x), "r"(u.y) : "memory"); }
  fence_async_smem();
  bar_sync(4, 128);
  float ga[4], ua[4];
  constexpr uint64_t da = mkdesc(A_WG, 896, 128, 0), db = mkdesc(A_XN, 16, 128, 0);
  wg_fence();
  wgmma_ss8<0, 1, 0>(ga, da, db); wgmma_ss8<0, 1, 0>(ua, da + (A_WU - A_WG) / 16, db);
#pragma unroll
  for (int ks = 1; ks < 32; ks++) { wgmma_ss8<1, 1, 0>(ga, da + ks * 112, db + ks * 2); wgmma_ss8<1, 1, 0>(ua, da + (A_WU - A_WG) / 16 + ks * 112, db + ks * 2); }
  wg_commit(); wg_wait<0>(); reg_fence(ga); reg_fence(ua);
  if ((t & 3) == 0) {
#pragma unroll
    for (int h = 0; h < 2; h++) {
      const float gs = rbf(ga[2 * h]), us = rbf(ua[2 * h]);
      const float v = 16 * w + 8 * h < 56 ? rbf(gs * rcp(1.f + __expf(-gs))) * us : 0.f;
      asm volatile("st.shared.u16 [%0], %1;" :: "r"(sb + A_XN + 1280 + (16 * w + 8 * h + g) * 2), "h"((unsigned short)pack2(v, 0.f)) : "memory");
    }
  }
  fence_async_smem();
  bar_sync(4, 128);
#pragma unroll 1
  for (int j = 0; j < 2; j++) {
    float y[4][4];
    const uint64_t dd = mkdesc(A_WD, 8192, 128, 0) + (uint64_t)(j * 256);
    wg_fence();
#pragma unroll
    for (int m = 0; m < 4; m++) {
      wgmma_ss8<0, 1, 0>(y[m], dd + m * 64, mkdesc(A_XN + 1280, 16, 128, 0));
#pragma unroll
      for (int ks = 1; ks < 4; ks++) wgmma_ss8<1, 1, 0>(y[m], dd + m * 64 + ks * 1024, mkdesc(A_XN + 1280 + ks * 32, 16, 128, 0));
    }
    wg_commit(); wg_wait<0>();
#pragma unroll
    for (int m = 0; m < 4; m++) {
      reg_fence(y[m]);
      if ((t & 3) == 0) { float* o = yacc + j * 256 + m * 64 + 16 * w + g; o[0] = y[m][0]; o[8] = y[m][2]; }
    }
  }
  bar_sync(4, 128);
  if (t < 8) { sts32(sb + A_BAR + 160, 0); st_rel(flag + t, E); }
  __syncwarp();
}

__device__ __forceinline__ void ffn_gather(uint32_t sb, int q, int j, uint32_t E, int lane) {
  wait_all(f_y[q][4 * j + (lane & 3)], E);
  float4 y[4][4];
#pragma unroll
  for (int k = 0; k < 4; k++)
#pragma unroll
    for (int i = 0; i < 4; i++) y[k][i] = __ldcg((const float4*)g_y[q & 7][4 * j + k] + i * 32 + lane);
#pragma unroll
  for (int i = 0; i < 4; i++)
    sts128f(sb + 1024 + j * 2048 + i * 512 + lane * 16, (y[0][i].x + y[1][i].x) + (y[2][i].x + y[3][i].x), (y[0][i].y + y[1][i].y) + (y[2][i].y + y[3][i].y),
            (y[0][i].z + y[1][i].z) + (y[2][i].z + y[3][i].z), (y[0][i].w + y[1][i].w) + (y[2][i].w + y[3][i].w));
  bar_sync(9, 256);
}
__device__ __forceinline__ void ffn_finish(uint32_t sb, int q, const bf16* req, float r, uint32_t E, int lane, uint32_t* v) {
  if (lane == 0) sts32(sb + 16, q);
  bar_sync(8, 256);
  uint32_t xn[8];
  load_row(xn, req, lane); load_row(v, req + 512, lane);
  const float rs = rbf(1.f / (1.f + __expf(-rbf(r))));
  ffn_gather(sb, q, 7, E, lane);
#pragma unroll
  for (int i = 0; i < 4; i++) {
    float y[4] = {0.f, 0.f, 0.f, 0.f};
#pragma unroll
    for (int j = 0; j < 8; j++) {
      const uint4 u = lds128(sb + 1024 + j * 2048 + (i >> 1) * 1024 + lane * 32 + (i & 1) * 16);
      y[0] += __uint_as_float(u.x); y[1] += __uint_as_float(u.y); y[2] += __uint_as_float(u.z); y[3] += __uint_as_float(u.w);
    }
    v[2 * i] = add2(v[2 * i], add2(xn[2 * i], pack2(rbf(y[0]) * rs, rbf(y[1]) * rs)));
    v[2 * i + 1] = add2(v[2 * i + 1], add2(xn[2 * i + 1], pack2(rbf(y[2]) * rs, rbf(y[3]) * rs)));
  }
}

__global__ void __launch_bounds__(512, 1) aux_kernel(Params p) {
  extern __shared__ __align__(1024) uint8_t sm[];
  const uint32_t sb = smem_u32(sm);
  if ((sb & 0xFFFFFFu) != SBASE) TRAP();
  const int warp = __shfl_sync(~0u, threadIdx.x >> 5, 0);
  const int cta = blockIdx.x;
  const uint32_t E = __shfl_sync(~0u, *(volatile uint32_t*)&g_epoch + 1, 0);
  const uint32_t bars = sb + A_BAR;

  if (cta < 32) {
    const int cg = cta & 3, kg = cta >> 2;
    if (threadIdx.x == 0) {
      for (int i = 0; i < A_NST; i++) { mbar_init(bars + 8 * i, 1); mbar_init(bars + 64 + 8 * i, 2); }
      mbar_init(bars + 128, 8); mbar_init(bars + 136, 8); mbar_init(bars + 144, 1);
      sts32(bars + 160, 0);
      asm volatile("fence.mbarrier_init.release.cluster;" ::: "memory");
    }
    if (warp < 8) {
      asm volatile("setmaxnreg.inc.sync.aligned.u32 176;");
      const int tid = fresh_tid(), lane = tid & 31;
      uint32_t W[32][4];
      stage_weights(sb + A_WD, p.wo + (size_t)kg * 512 * 512 + cg * 128, 512, tid, 256);
      cp_async_wait();
      bar_sync(1, 256);
      load_frags(W, sb + A_WD, warp >> 2, warp & 3, lane);
      bar_sync(2, 512);
      const uint32_t so = sb + A_STG + ((lane >> 4) * 8 + (lane & 7)) * 256 + (((warp * 2 + ((lane >> 3) & 1)) ^ (lane & 7)) << 4);
      const uint32_t tm = lane < 4 ? 0x00010001u : 0u;
      int stage = 0; uint32_t ph = 0, job = 0;
#pragma unroll 1
      for (int T = 0; T < NSTEP; T++) {
#pragma unroll 1
        for (int k = 0; k < 3; k++) {
          const int st = k == 0 ? 0 : 3 - k, s = st == 0 ? T : T - LAG;
          if (s < 0 || s >= NSEG) continue;
          float d[16];
#pragma unroll
          for (int hh = 0; hh < 4; hh++) {
            mbar_wait(bars + 8 * stage, ph);
            while (uni(lds32(bars + 160))) __nanosleep(100);
            const uint64_t db = mkdesc(A_RING, 512, 128, 0) + (uint64_t)(stage * 512);
            wg_fence();
            if (hh == 0) wgmma_rs32<0, 0>(d, W[0], db); else wgmma_rs32<1, 0>(d, W[hh * 8], db);
#pragma unroll
            for (int ks = 1; ks < 8; ks++) wgmma_rs32<1, 0>(d, W[hh * 8 + ks], db + ks * 64);
            wg_commit();
            if (hh > 0) { wg_wait<1>(); if ((tid & 127) == 0) mbar_arrive(bars + 64 + 8 * (stage == 0 ? A_NST - 1 : stage - 1)); }
            if (++stage == A_NST) { stage = 0; ph ^= 1; }
          }
          mbar_wait(bars + 144, (job & 1) ^ 1);
          wg_wait<0>(); reg_fence(d);
          if ((tid & 127) == 0) mbar_arrive(bars + 64 + 8 * (stage == 0 ? A_NST - 1 : stage - 1));
          if (cta == 0 && tid == 0) TSTAMP(6, T, k);
          const uint32_t tv = tm * ptag(s);
#define TG(i) ((pack2(d[2 * (i)], d[2 * (i) + 1]) & ~tm) | tv)
          stmatrix4_t(so, TG(0), pack2(d[2], d[3]), TG(2), pack2(d[6], d[7]));
          stmatrix4_t(so + 4096, TG(4), pack2(d[10], d[11]), TG(6), pack2(d[14], d[15]));
          fence_async_smem();
          __syncwarp();
          if (lane == 0) mbar_arrive(bars + 128 + 8 * (job & 1));
          job++;
        }
      }
    } else if (warp < 12) {
      asm volatile("setmaxnreg.dec.sync.aligned.u32 120;");
      const int tid = fresh_tid(), lane = tid & 31;
      const int w = warp - 8, t = tid - 256;
#pragma unroll 1
      for (int s = cta + 4; s < NSEG; s += 32) {
#pragma unroll 1
        for (int pr = w; pr < 16; pr += 4) input_ln_pair(p.x, s, pr, lane);
        bar_sync(4, 128);
        if (t == 0) st_rel(&f_h1[s], E);
      }
      bar_sync(2, 512);
      { int guard = 0; while (ld_rlx(&f_loaded[cta]) != E) { __nanosleep(200); if (++guard > (1 << 22)) TRAP(); } }
#pragma unroll 1
      for (int i = t; i < 512 * 7; i += 128) {
        const int k = i / 7, pc = i % 7;
        cp_async16(sb + A_WG + (k >> 3) * 896 + pc * 128 + (k & 7) * 16, p.wg + (size_t)k * 1792 + cta * 56 + pc * 8);
        cp_async16(sb + A_WU + (k >> 3) * 896 + pc * 128 + (k & 7) * 16, p.wu + (size_t)k * 1792 + cta * 56 + pc * 8);
        cp_async16(sb + A_WD + (i >> 9) * 8192 + (i & 63) * 128 + ((i >> 6) & 7) * 16, p.wd + (size_t)cta * 56 * 512 + i * 8);
      }
      uint32_t wv[8];
      const float wsum = load_wr(wv, p.wr, lane);
      cp_async_wait();
      fence_async_smem();
      bar_sync(4, 128);
      const int tj = (cta * 4 + w) & 31, st = 1 + ((cta >> 3) & 1), sq = cta >> 4;
      unsigned long long run = 0, run2 = 0, best = 0, hist = 0;
      uint32_t open = 0;
#pragma unroll 1
      for (int i = 0; i <= NSTEP; i++) {
        int tok = -1; const bf16* req = nullptr;
        if (i < NSEG) {
          const int cd = (int)uni(route_step(i, E, lane, run));
          run = __shfl_sync(~0u, run, 0);
          hist = hist << 8 | (uint32_t)(cd + 1);
          if (cd >= 0) { tok = rtok(run); req = g_req1[tok][0]; }
        } else {
          const unsigned long long m = wait_words(f_l2[i - NSEG], E);
          const unsigned long long n = ld_rlxu64(f_l2[min(i - NSEG + 1 + (lane & 7), LAG)]);
          const bool over = bar_or(4, 128, rfresh(n, E) && n != m);
          if (m != run2 && !over) { run2 = m; tok = rtok(m); req = g_req2[(tok >> 5) < (rtok(run) >> 5) ? 0 : 1][tok][0]; }
        }
        tok = __shfl_sync(~0u, tok, 0);
        if (tok >= 0) {
          if (cta == 0 && t == 0) TSTAMP(8, i, 0);
          ffn_slice(sb, req, g_y[i & 7][cta], f_y[i][cta], E, t, i < NSEG);
          if (cta == 0 && t == 0) TSTAMP(8, i, 1);
        }
        const int s = i - LAG;
        if (s < 0 || i >= NSEG) continue;
        const int cd = (int)((hist >> (8 * LAG)) & 255) - 1;
        if (cd >= 0 && st == 2) best = 0;
        const int ts = rtok(run) >> 5;
        if ((s & 1) == sq) {
          const int tk = s * 32 + tj;
          unsigned long long wd = (unsigned long long)E << 43;
          if (st == 1 ? s < ts || i < NSEG - 1 : s >= ts) {
            if (st == 2 && cd == tj) wait_eq(&f_hc[s], E);
            wd = token_post<false>(st, tk, st == 2 && cd == tj ? g_x2c[s] : g_x2 + (size_t)tk * 512,
                                   (st == 2 || s < ts ? p.out : g_n) + (size_t)tk * 512, g_req2[st - 1][tk][0], best, wv, wsum, E, lane);
            best = max(best, wd);
            if (st == 1 && s >= ts) open |= 1u << (s >> 1);
          }
          __syncwarp();
          if (lane < 4) st_rel64(&f_w2[st - 1][s][tj][lane], wd);
          __syncwarp();
        }
        if (st == 1) {
          if (i == NSEG - 1 && t == 0 && cta == 0) GSTAMP(1, 0);
#pragma unroll 1
          for (int n = i == NSEG - 1 ? 32 : 2; n > 0 && open; n--) {
            const int s0 = 2 * (__ffs(open) - 1) + sq;
            if (s0 >= ts) break;
            open &= open - 1;
            uint32_t v[8];
            load_row(v, g_n + (size_t)(s0 * 32 + tj) * 512, lane);
            wait_words(f_w2[1][s0][tj], E);
            store_row(p.out + (size_t)(s0 * 32 + tj) * 512, v, lane);
          }
          if (i == NSEG - 1) {
            __syncwarp();
            if (lane == 0) st_rel(&f_cp[sq * 32 + tj], E);
            if (t == 0 && cta == 0) GSTAMP(1, 3);
          }
        }
      }
    } else {
      asm volatile("setmaxnreg.dec.sync.aligned.u32 40;");
      const int tid = fresh_tid(), lane = tid & 31;
      const int w = warp - 12;
      bar_sync(2, 512);
      if (w == 0) {
        int stage = 0; uint32_t ph = 1;
#pragma unroll 1
        for (int T = 0; T < NSTEP; T++) {
#pragma unroll 1
          for (int k = 0; k < 3; k++) {
            const int st = k == 0 ? 0 : 3 - k, s = st == 0 ? T : T - LAG;
            if (s < 0 || s >= NSEG) continue;
            const uint32_t* fl = f_o[T][kg][st * 4 + (lane & 3)];
            uint32_t ready = 0; int guard = 0;
#pragma unroll 1
            for (int hh = 0; hh < 4; hh++) {
              while (!((ready >> hh) & 1)) {
                ready = __ballot_sync(~0u, ld_rlx(fl) == E);
                if (++guard > (1 << 23)) TRAP();
              }
              fence_async_glob();
              mbar_wait(bars + 64 + 8 * stage, ph);
              e_expect(bars + 8 * stage, OLOAD_);
              e_g2s(sb + A_RING + stage * 8192, g_o[st][s % ORING][kg * 4 + hh], OLOAD_, bars + 8 * stage);
              if (++stage == A_NST) { stage = 0; ph ^= 1; }
            }
          }
          if (cta == 0 && lane == 0) TSTAMP(3, T, 0);
        }
      } else if (w < 3) {
        uint32_t job = 0;
#pragma unroll 1
        for (int T = 0; T < NSTEP; T++) {
#pragma unroll 1
          for (int k = 0; k < 3; k++) {
            const int st = k == 0 ? 0 : 3 - k, s = st == 0 ? T : T - LAG;
            if (s < 0 || s >= NSEG) continue;
            if ((job++ & 1) != w - 1) continue;
            if (s >= PRING) wait_words(st == 0 ? f_h2[s - PRING][lane & 3] : f_w2[st - 1][s - PRING][lane], E);
            mbar_wait(bars + 128 + 8 * (w - 1), ((job - 1) >> 1) & 1);
            if (cta == 0 && st == 0) TSTAMP(7, s, 0);
            e_s2g(g_pp[st][s % PRING] + cta * 8192, sb + A_STG, PST_);
            if (lane < 8) st_rlx(&f_acc[st][s][cta][lane], E);
            asm volatile("cp.async.bulk.commit_group;\n cp.async.bulk.wait_group.read 0;" ::: "memory");
            __syncwarp();
            e_arrive(bars + 144);
            __syncwarp();
            if (cta == 0 && st == 0) TSTAMP(7, s, 1);
          }
        }
        bulk_wait();
      }
    }
  } else {
    const int tid = fresh_tid(), lane = tid & 31;
    const int qd = cta - 32;
    input_ln_pair(p.x, qd, warp, lane);
    bar_sync(6, 512);
    if (tid == 0) st_rel(&f_h1[qd], E);
    volatile int* bc = (volatile int*)sm;
    if (warp == 15) {
      unsigned long long run = 0;
      unsigned long long b2[2][2] = {{0, 0}, {0, 0}};
      auto track = [&](int s) {
#pragma unroll
        for (int k = 0; k < 2; k++) {
          const unsigned long long m = warp_max<16>(wait_words(f_w2[k][s][lane], E));
          if (lane == (s & 31)) { if (s < 32) b2[k][0] = m; else b2[k][1] = m; }
        }
      };
#pragma unroll 1
      for (int s = 0; s < NSEG; s++) {
        const int cd = route_step(s, E, lane, run);
        if (cd >= 0 && qd == (s & 1)) {
          uint32_t v[1][8], h[1][8];
          ffn_finish(sb, s, g_req1[s * 32 + cd][0], rscore(run), E, lane, v[0]);
          if (lane == 0) TSTAMP(8, s, 2);
          ln_rows<1>(v, h);
#pragma unroll
          for (int i = 0; i < 8; i++) st_rlx64(&g_hc[s][(i >> 2) * 128 + 4 * lane + (i & 3)], h[0][i], E);
          if (lane == 0) TSTAMP(8, s, 3);
          store_row(g_x2c[s], v[0], lane);
          __syncwarp();
          if (lane == 0) st_rel(&f_hc[s], E);
        }
        if (qd == 2 && s > LAG) track(s - LAG - 1);
      }
      wait_eq(&f_hc[rtok(run) >> 5], E);
      if (lane == 0) *bc = rtok(run);
      bar_sync(7, 288);
      if (qd == 2) {
        uint32_t v[8];
        const int ts = rtok(run) >> 5;
        track(NSEG - LAG - 1);
        run = 0;
        int kl = 0;
#pragma unroll 1
        for (int k = 0; k <= LAG; k++) {
          const int s = NSEG - LAG - 1 + k;
          const unsigned long long m = warp_max<16>(k == 0 ? max(lane < ts ? b2[0][0] : b2[1][0], lane + 32 < ts ? b2[0][1] : b2[1][1])
                                                           : wait_words(f_w2[s < ts ? 0 : 1][s][lane], E));
          const bool lead = m > run;
          if (lead) { run = m; __threadfence(); }
          if (lane < 4) st_rlx64(&f_l2[k][lane], (uint32_t)run, (uint32_t)(run >> 32));
          if (lead) kl = k;
          if (k == LAG - 1) { wait_all(&f_cp[lane], E); wait_all(&f_cp[32 + lane], E); }
          if (k == LAG - 1 || (k == LAG && lead)) ffn_finish(sb, NSEG + kl, g_req2[(rtok(run) >> 5) < ts ? 0 : 1][rtok(run)][0], rscore(run), E, lane, v);
        }
        if (lane == 0) GSTAMP(1, 1);
        store_row(p.out + (size_t)rtok(run) * 512, v, lane);
        if (lane == 0) GSTAMP(1, 2);
      }
      if (lane == 0) sts32(sb + 16, (uint32_t)-1);
      bar_sync(8, 256);
      if (qd == 2) {
        asm volatile("griddepcontrol.wait;" ::: "memory");
        if (lane == 0) *(volatile uint32_t*)&g_epoch = E;
      }
    } else if (warp >= 8) {
#pragma unroll 1
      for (;;) {
        bar_sync(8, 256);
        const int q = (int)uni(lds32(sb + 16));
        if (q < 0) break;
        ffn_gather(sb, q, warp - 8, E, lane);
      }
    } else {
      uint32_t wv[8];
      const float wsum = load_wr(wv, p.wr, lane);
      unsigned long long best = 0;
      int ttok = 0;
#pragma unroll 1
      for (int i = 0; i < NSTEP; i++) {
        const bool last = i >= NSEG;
        if (i == NSEG) { bar_sync(7, 288); ttok = *bc; best = 0; }
        const int s = last ? i - LAG : i, st = !last ? 0 : s < (ttok >> 5) ? 1 : 2;
        const int tk = s * 32 + qd * 8 + warp;
        const unsigned long long wd = token_post<true>(st, tk, !last ? p.x + (size_t)tk * 512 : tk == ttok ? g_x2c[s] : g_x2 + (size_t)tk * 512,
                                                 (last ? p.out : g_x2) + (size_t)tk * 512, last ? g_req2[st - 1][tk][0] : g_req1[tk][0], best, wv, wsum, E, lane);
        best = max(best, wd);
        volatile unsigned long long* ws = (volatile unsigned long long*)(sm + 64) + (i & 1) * 8;
        if (lane == 0) ws[warp] = wd;
        bar_sync(5, 256);
        if (warp == 0) {
          if (qd == 0 && lane == 0) TSTAMP(4, i, 1);
          if (!last) { const unsigned long long m = warp_max<4>(ws[lane & 7]); if (lane < 4) st_rel64(&f_h2[s][qd][lane], m); }
          else {
            st_rel64(&f_w2[st - 1][s][qd * 8 + (lane >> 2)][lane & 3], ws[lane >> 2]);
            asm volatile("st.relaxed.gpu.global.u64 [%0], %1;" :: "l"(&f_w2[2 - st][s][qd * 8 + (lane >> 2)][lane & 3]), "l"((unsigned long long)E << 43) : "memory");
          }
          if (qd == 0 && lane == 0) TSTAMP(4, i, 2);
        }
        __syncwarp();
      }
    }
  }
}

}

extern "C" void kernel_launch(void* const* d_in, const int* in_sizes, int n_in, void* d_out, int out_size) {
  (void)in_sizes; (void)n_in; (void)out_size;
  static bool init = false;
  if (!init) {
    cudaFuncSetAttribute(main_kernel, cudaFuncAttributeMaxDynamicSharedMemorySize, M_TOTAL);
    cudaFuncSetAttribute(aux_kernel, cudaFuncAttributeMaxDynamicSharedMemorySize, A_TOTAL);
    init = true;
  }
  Params p;
  p.x = (const bf16*)d_in[0]; p.mem0 = (const bf16*)d_in[1]; p.wq = (const bf16*)d_in[2]; p.wk = (const bf16*)d_in[3];
  p.wv = (const bf16*)d_in[4]; p.wo = (const bf16*)d_in[5]; p.wr = (const bf16*)d_in[8]; p.wg = (const bf16*)d_in[9];
  p.wu = (const bf16*)d_in[10]; p.wd = (const bf16*)d_in[11]; p.out = (bf16*)d_out; p.zero = 0; p.zero2 = 0;
  cudaStream_t st = cudaStreamPerThread;
  main_kernel<<<96, 512, M_TOTAL, st>>>(p);
  cudaLaunchConfig_t cfg = {};
  cfg.gridDim = dim3(36); cfg.blockDim = dim3(512); cfg.dynamicSmemBytes = A_TOTAL; cfg.stream = st;
  cudaLaunchAttribute at[1];
  at[0].id = cudaLaunchAttributeProgrammaticStreamSerialization; at[0].val.programmaticStreamSerializationAllowed = 1;
  cfg.attrs = at; cfg.numAttrs = 1;
  cudaLaunchKernelEx(&cfg, aux_kernel, p);
}
```

```cpp
#include <cuda_runtime.h>
#include <cuda_bf16.h>
#include <stdint.h>
#include <stddef.h>

namespace {

typedef __nv_bfloat16 bf16;

constexpr int NSEG = 64;
#define LAG_ 5
constexpr int LAG = LAG_;
constexpr int NSTEP = NSEG + LAG;
constexpr int ORING = 8, PRING = 4;
static_assert(LAG < 8, "rings");

#define E1_ 10
#define E2_ 0
#define E3_ 10
constexpr int E1 = E1_, E2 = E2_, E3 = E3_, EA = E1 + E2 + E3;
static_assert(EA % 4 == 0 && EA > 0 && EA < 32 && E1 > 0, "early part: whole 64-column chunks");
#define RW_ 176
#define RA_ 136
#define RC_ 24
#define STR2(x) #x
#define STR(x) STR2(x)
#define RED_ 30
#define ARR_ 7
#define PAUSE_ 13
#define PAUS2_ 29
#define PST2_ 2
#define PVR_ -1
#define SALT_ 0
#define KP1_ 1
#define OLOAD_ 8192
#define PST_ 8192
#define ALT_ 1
#define TQ_ 1
#define NOF_ 2
#define EXPQ_ 0
#define SPC_ 4096
#define HINT_ 24
#define HADD_ 2
#define FPACE_ 4
#define HAND_ 4
#define GO3_ 2
#define STK_ 0
#define REMAP_ 1
#define NPROBE_ 6
#define TP(i, v) (v)
#define XDLY_ TP(0, 2075)
#define YDLY_ TP(1, 3400)
#define X1_ TP(2, 100)
#define X2_ TP(3, 350)
#define Y1_ TP(4, 200)
#define Y2_ TP(5, 450)
#define HGAP_ TP(6, 50)
#define TGAP_ TP(7, 100)
#define ADLY_ TP(8, 600)
#define ODLY_ TP(9, 2800)
#define LDLY_ TP(10, 3800)
#define HDLY_ TP(11, 0)
#define TDLY_ TP(15, 4150)
#define SDLY_ TP(12, 800)
#define AGAP_ 100
#define BOFF_ TP(13, 200)
#define YOFF_ TP(16, 150)
#define YUP_ TP(20, 40)
#define YDN_ TP(21, 4)
#define T1GAP_ TP(22, 0)
#define OGAP_ TP(23, 0)
#define CDLY_ TP(17, 300)
#define SLOW0_ TP(18, 800)
#define SLOW1_ TP(19, 300)
#define KDLY_ TP(14, 300)
__device__ uint32_t g_epoch;
struct Seg {
  uint8_t h[2][32768];
  bf16 x2[32][512], n[32][512];
  bf16 req1[32][2][512];
};
struct Mix {
  uint8_t tok[16][2][16384];
  uint8_t o[4][32][8192];
  uint8_t pp[2][8 * 32768];
};
struct Scratch {
  uint8_t xch[96 * 16384 + 65536];
  unsigned long long f_h2[NSEG][4][4];
  unsigned long long f_l2[8][4];
  unsigned long long sync[2][96][4];
  uint32_t f_o[NSTEP][8][12][8];
  uint32_t f_y[NSTEP + 1][32][8], f_cp[64];
  uint32_t f_choice[96][2], f_loaded[32], f_h1[NSEG], f_hc[NSEG];
  uint8_t pad0[2097152 - (96 * 16384 + 65536 + NSEG * 128 + 256 + 6144 + NSTEP * 3072 + (NSTEP + 1) * 1024 + 256 + 768 + 128 + NSEG * 8)];
  Mix mix[6];
  uint32_t f_acc[3][NSEG][32][8];
  unsigned long long f_w2[2][NSEG][32][4];
  uint2 hc[NSEG][256];
  bf16 x2c[NSEG][512];
  float y[8][32][512];
  Seg seg[NSEG];
  bf16 req2[2][2048][2][512];
};
static_assert(sizeof(Mix) == 2097152 && offsetof(Scratch, mix) == 2097152 && offsetof(Scratch, seg) % 1024 == 0 && ORING == 8 && PRING == 4, "layout");
__device__ uint8_t g_raw[sizeof(Scratch) + 2097152];
__device__ __forceinline__ Scratch& scr() { return *(Scratch*)(((uintptr_t)g_raw + 2097151) & ~(uintptr_t)2097151); }
#define G scr()
__device__ __forceinline__ uint8_t* o_slot(int st, int s, int head) { const int j = st * 8 + (s & 7); return G.mix[j % 6].o[j / 6][head]; }
__device__ __forceinline__ uint8_t* pp_slot(int st, int s) { const int j = st * 4 + (s & 3); return G.mix[j % 6].pp[j / 6]; }

#define TRAP() __trap()
__device__ __forceinline__ uint32_t smem_u32(const void* p) { return (uint32_t)__cvta_generic_to_shared(p); }
__device__ __forceinline__ int fresh_tid() { const int t = threadIdx.x; return __shfl_sync(~0u, t, t & 31); }
__device__ __forceinline__ unsigned long long gtime64() { unsigned long long t; asm volatile("mov.u64 %0, %%globaltimer;" : "=l"(t) :: "memory"); return t; }
__device__ __forceinline__ uint32_t clk() { unsigned long long c; asm volatile("mov.u64 %0, %%clock64;" : "=l"(c) :: "memory"); return (uint32_t)c; }
__device__ __forceinline__ void wait_until(uint32_t t) {
  while ((int)(t - clk()) > 450) __nanosleep(32);
  uint32_t c;
  do { asm volatile("mov.u32 %0, %%clock;" : "=r"(c) :: "memory"); } while ((int)(c - t) < 0);
}
__device__ __forceinline__ void mbar_init(uint32_t bar, uint32_t cnt) { asm volatile("mbarrier.init.shared::cta.b64 [%0], %1;" :: "r"(bar), "r"(cnt) : "memory"); }
__device__ __forceinline__ void mbar_arrive(uint32_t bar) { asm volatile("mbarrier.arrive.shared::cta.b64 _, [%0];" :: "r"(bar) : "memory"); }
__device__ __forceinline__ void mbar_arrive_remote(uint32_t bar) { asm volatile("mbarrier.arrive.relaxed.cluster.shared::cluster.b64 _, [%0];" :: "r"(bar) : "memory"); }
__device__ __forceinline__ void mbar_expect(uint32_t bar, uint32_t bytes) { asm volatile("mbarrier.arrive.expect_tx.shared::cta.b64 _, [%0], %1;" :: "r"(bar), "r"(bytes) : "memory"); }
__device__ __forceinline__ bool mbar_try(uint32_t bar, uint32_t parity) {
  uint32_t ok;
  asm volatile("{.reg .pred p; mbarrier.try_wait.parity.shared::cta.b64 p, [%1], %2; selp.u32 %0, 1, 0, p;}" : "=r"(ok) : "r"(bar), "r"(parity) : "memory");
  return ok;
}
__device__ __forceinline__ bool mbar_test(uint32_t bar, uint32_t parity) {
  uint32_t ok;
  asm volatile("{.reg .pred p; mbarrier.test_wait.parity.shared::cta.b64 p, [%1], %2; selp.u32 %0, 1, 0, p;}" : "=r"(ok) : "r"(bar), "r"(parity) : "memory");
  return ok;
}
__device__ __forceinline__ void mbar_wait(uint32_t bar, uint32_t parity) {
  asm volatile("{\n.reg .pred p;\nWAIT:\nmbarrier.try_wait.parity.shared::cta.b64 p, [%0], %1;\n@!p bra WAIT;\n}" :: "r"(bar), "r"(parity) : "memory");
}
__device__ __forceinline__ uint32_t ld_acq(const uint32_t* p) { uint32_t v; asm volatile("ld.acquire.gpu.global.u32 %0, [%1];" : "=r"(v) : "l"(p) : "memory"); return v; }
__device__ __forceinline__ unsigned long long ld_acq64(const unsigned long long* p) { unsigned long long v; asm volatile("ld.acquire.gpu.global.u64 %0, [%1];" : "=l"(v) : "l"(p) : "memory"); return v; }
__device__ __forceinline__ void st_rel(uint32_t* p, uint32_t v) { asm volatile("st.release.gpu.global.u32 [%0], %1;" :: "l"(p), "r"(v) : "memory"); }
__device__ __forceinline__ void st_rel64(unsigned long long* p, unsigned long long v) { asm volatile("st.release.gpu.global.u64 [%0], %1;" :: "l"(p), "l"(v) : "memory"); }
__device__ __forceinline__ void red_rel(uint32_t* p, uint32_t v) { asm volatile("red.release.gpu.global.add.u32 [%0], %1;" :: "l"(p), "r"(v) : "memory"); }
__device__ __forceinline__ uint32_t ld_rlx(const uint32_t* p) { uint32_t v; asm volatile("ld.relaxed.gpu.global.u32 %0, [%1];" : "=r"(v) : "l"(p) : "memory"); return v; }
__device__ __forceinline__ unsigned long long ld_rlxu64(const unsigned long long* p) { unsigned long long v; asm volatile("ld.relaxed.gpu.global.u64 %0, [%1];" : "=l"(v) : "l"(p) : "memory"); return v; }
__device__ __forceinline__ void st_rlx(uint32_t* p, uint32_t v) { asm volatile("st.relaxed.gpu.global.u32 [%0], %1;" :: "l"(p), "r"(v) : "memory"); }
__device__ __forceinline__ void bulk_wait() { asm volatile("cp.async.bulk.commit_group;\n cp.async.bulk.wait_group 0;" ::: "memory"); }
__device__ __forceinline__ void fence_acq() { asm volatile("fence.acquire.gpu;" ::: "memory"); }
__device__ __forceinline__ void wait_all(const uint32_t* p, uint32_t v, bool acquire = true) {
  int guard = 0;
  while (!__all_sync(~0u, ld_rlx(p) == v)) { __nanosleep(32); if (++guard > (1 << 22)) TRAP(); }
  if (acquire) fence_acq();
}
__device__ __forceinline__ void wait_eq(const uint32_t* p, uint32_t v) {
  int guard = 0;
  while (ld_rlx(p) != v) { __nanosleep(64); if (++guard > (1 << 22)) TRAP(); }
  fence_acq();
}
__device__ __forceinline__ unsigned long long rword(uint32_t E, int tok, float r) {
  uint32_t u = __float_as_uint(r + 0.f);
  u = r != r ? 0u : (u >> 31) ? ~u : u | 0x80000000u;
  return (unsigned long long)(E & 0x1FFFFFu) << 43 | (unsigned long long)u << 11 | (uint32_t)(2047 - tok);
}
__device__ __forceinline__ int rtok(unsigned long long v) { return 2047 - (int)(v & 2047u); }
__device__ __forceinline__ float rscore(unsigned long long v) { const uint32_t u = (uint32_t)(v >> 11); return __uint_as_float((u >> 31) ? u & 0x7fffffffu : ~u); }
__device__ __forceinline__ bool rfresh(unsigned long long v, uint32_t E) { return (uint32_t)(v >> 43) == (E & 0x1FFFFFu); }
template <int TOP> __device__ __forceinline__ unsigned long long warp_max(unsigned long long v) {
#pragma unroll
  for (int o = TOP; o > 0; o >>= 1) { const unsigned long long ov = __shfl_xor_sync(~0u, v, o); v = ov > v ? ov : v; }
  return v;
}
template <int off> __device__ __forceinline__ uint2 ld_rlx64(const void* p) { unsigned long long v; asm volatile("ld.relaxed.gpu.global.b64 %0, [%1+%2];" : "=l"(v) : "l"(p), "n"(off) : "memory"); return make_uint2((uint32_t)v, (uint32_t)(v >> 32)); }
template <int off> __device__ __forceinline__ uint4 ld_rlx128(const void* p) {
  unsigned long long a, b; asm volatile("ld.relaxed.gpu.global.v2.b64 {%0,%1}, [%2+%3];" : "=l"(a), "=l"(b) : "l"(p), "n"(off) : "memory");
  return make_uint4((uint32_t)a, (uint32_t)(a >> 32), (uint32_t)b, (uint32_t)(b >> 32));
}
__device__ __forceinline__ void st_rlx64(void* p, uint32_t lo, uint32_t hi) { asm volatile("{.reg .b64 t; mov.b64 t, {%1,%2}; st.relaxed.gpu.global.b64 [%0], t;}" :: "l"(p), "r"(lo), "r"(hi) : "memory"); }
__device__ __forceinline__ void cp_async16(uint32_t dst, const void* src) { asm volatile("cp.async.cg.shared.global [%0], [%1], 16;" :: "r"(dst), "l"(src) : "memory"); }
__device__ __forceinline__ void cp_async_wait() { asm volatile("cp.async.wait_all;" ::: "memory"); }
__device__ __forceinline__ void fence_async_smem() { asm volatile("fence.proxy.async.shared::cta;" ::: "memory"); }
__device__ __forceinline__ void fence_async_glob() { asm volatile("fence.proxy.async.global;" ::: "memory"); }
__device__ __forceinline__ void fence_async_acq() { asm volatile("fence.proxy.async::generic.acquire.sync_restrict::shared::cluster.cluster;" ::: "memory"); }
__device__ __forceinline__ float ex2(float x) { float y; asm("ex2.approx.ftz.f32 %0, %1;" : "=f"(y) : "f"(x)); return y; }
__device__ __forceinline__ float sqrt_fast(float x) { float y; asm("sqrt.approx.ftz.f32 %0, %1;" : "=f"(y) : "f"(x)); return y; }
__device__ __forceinline__ float rcp(float x) { float y; asm("rcp.approx.ftz.f32 %0, %1;" : "=f"(y) : "f"(x)); return y; }
__device__ __forceinline__ void bar_sync(int id, int n) { asm volatile("bar.sync %0, %1;" :: "r"(id), "r"(n) : "memory"); }
__device__ __forceinline__ bool bar_or(int id, int n, bool v) {
  uint32_t r;
  asm volatile("{.reg .pred p, q; setp.ne.u32 p, %3, 0; barrier.cta.red.or.aligned.pred q, %1, %2, p; selp.u32 %0, 1, 0, q;}" : "=r"(r) : "r"(id), "r"(n), "r"((uint32_t)v) : "memory");
  return r;
}
__device__ __forceinline__ uint32_t mapa(uint32_t a, uint32_t rank) { uint32_t r; asm volatile("mapa.shared::cluster.u32 %0, %1, %2;" : "=r"(r) : "r"(a), "r"(rank)); return r; }
__device__ __forceinline__ void cluster_sync() { asm volatile("barrier.cluster.arrive.release.aligned; barrier.cluster.wait.acquire.aligned;" ::: "memory"); }
__device__ __forceinline__ void st_async32(uint32_t dst, uint32_t v, uint32_t bar) { asm volatile("st.async.shared::cluster.mbarrier::complete_tx::bytes.b32 [%0], %1, [%2];" :: "r"(dst), "r"(v), "r"(bar) : "memory"); }
__device__ __forceinline__ void bulk_g2s(uint32_t dst, const void* src, uint32_t bytes, uint32_t bar) {
  asm volatile("cp.async.bulk.shared::cluster.global.mbarrier::complete_tx::bytes [%0], [%1], %2, [%3];" :: "r"(dst), "l"(src), "r"(bytes), "r"(bar) : "memory");
}
__device__ __forceinline__ void bulk_g2s_mc(uint32_t dst, const void* src, uint32_t bytes, uint32_t bar, uint16_t mask) {
  asm volatile("cp.async.bulk.shared::cluster.global.mbarrier::complete_tx::bytes.multicast::cluster [%0], [%1], %2, [%3], %4;"
               :: "r"(dst), "l"(src), "r"(bytes), "r"(bar), "h"(mask) : "memory");
}
__device__ __forceinline__ void bulk_s2c(uint32_t dst, uint32_t src, uint32_t bytes, uint32_t bar) {
  asm volatile("cp.async.bulk.shared::cluster.shared::cta.mbarrier::complete_tx::bytes [%0], [%1], %2, [%3];" :: "r"(dst), "r"(src), "r"(bytes), "r"(bar) : "memory");
}
__device__ __forceinline__ void bulk_s2g(void* dst, uint32_t src, uint32_t bytes) {
  asm volatile("cp.async.bulk.global.shared::cta.bulk_group [%0], [%1], %2;" :: "l"(dst), "r"(src), "r"(bytes) : "memory");
}
#define ELECT(op) "{.reg .pred p; elect.sync _|p, 0xffffffff; @p " op "}"
__device__ __forceinline__ void e_arrive(uint32_t bar) { asm volatile(ELECT("mbarrier.arrive.shared::cta.b64 _, [%0];") :: "r"(bar) : "memory"); }
__device__ __forceinline__ void e_expect(uint32_t bar, uint32_t bytes) { asm volatile(ELECT("mbarrier.arrive.expect_tx.shared::cta.b64 _, [%0], %1;") :: "r"(bar), "r"(bytes) : "memory"); }
__device__ __forceinline__ void e_g2s(uint32_t dst, const void* src, uint32_t bytes, uint32_t bar) {
  asm volatile(ELECT("cp.async.bulk.shared::cluster.global.mbarrier::complete_tx::bytes [%0], [%1], %2, [%3];") :: "r"(dst), "l"(src), "r"(bytes), "r"(bar) : "memory");
}
__device__ __forceinline__ void e_mc(uint32_t dst, const void* src, uint32_t bytes, uint32_t bar, uint16_t mask) {
  asm volatile(ELECT("cp.async.bulk.shared::cluster.global.mbarrier::complete_tx::bytes.multicast::cluster [%0], [%1], %2, [%3], %4;")
               :: "r"(dst), "l"(src), "r"(bytes), "r"(bar), "h"(mask) : "memory");
}
__device__ __forceinline__ void e_s2g(void* dst, uint32_t src, uint32_t bytes) {
  asm volatile(ELECT("cp.async.bulk.global.shared::cta.bulk_group [%0], [%1], %2;") :: "l"(dst), "r"(src), "r"(bytes) : "memory");
}
__device__ __forceinline__ void e_st_rel(uint32_t* p, uint32_t v) { asm volatile(ELECT("st.release.gpu.global.u32 [%0], %1;") :: "l"(p), "r"(v) : "memory"); }
__device__ __forceinline__ uint32_t clk32() { uint32_t c; asm volatile("mov.u32 %0, %%clock;" : "=r"(c) :: "memory"); return c; }
__device__ __forceinline__ void spin_until(uint32_t t) { while ((int)(clk32() - t) < 0) {} }
__device__ __forceinline__ uint32_t uni(uint32_t v) { return __shfl_sync(~0u, v, 0); }
__device__ __forceinline__ uint32_t pack2(float lo, float hi) { uint32_t r; asm("cvt.rn.bf16x2.f32 %0, %1, %2;" : "=r"(r) : "f"(hi), "f"(lo)); return r; }
__device__ __forceinline__ uint32_t add2(uint32_t a, uint32_t b) { uint32_t r; asm("add.rn.bf16x2 %0, %1, %2;" : "=r"(r) : "r"(a), "r"(b)); return r; }
__device__ __forceinline__ float rbf(float x) { return __bfloat162float(__float2bfloat16_rn(x)); }
__device__ __forceinline__ float blo(uint32_t u) { return __uint_as_float(u << 16); }
__device__ __forceinline__ float bhi(uint32_t u) { return __uint_as_float(u & 0xffff0000u); }
__device__ __forceinline__ uint32_t gentag(uint32_t g) { return (g & 1u) | (g & 2u) << 15; }
__device__ __forceinline__ uint32_t pack2_tag(float lo, float hi, uint32_t tag) {
  const uint32_t u = __byte_perm(__float_as_uint(lo), __float_as_uint(hi), 0x7632);
  return u + ((u ^ tag) & 0x10001u);
}
__device__ __forceinline__ uint32_t xo2(uint32_t a, uint32_t b, uint32_t t) { uint32_t r; asm("lop3.b32 %0, %1, %2, %3, 0x7e;" : "=r"(r) : "r"(a), "r"(b), "r"(t)); return r; }
__device__ __forceinline__ uint32_t or3(uint32_t a, uint32_t b, uint32_t c) { uint32_t r; asm("lop3.b32 %0, %1, %2, %3, 0xfe;" : "=r"(r) : "r"(a), "r"(b), "r"(c)); return r; }
__device__ __forceinline__ void stmatrix4(uint32_t a, uint32_t r0, uint32_t r1, uint32_t r2, uint32_t r3) {
  asm volatile("stmatrix.sync.aligned.m8n8.x4.shared.b16 [%0], {%1,%2,%3,%4};" :: "r"(a), "r"(r0), "r"(r1), "r"(r2), "r"(r3) : "memory");
}
__device__ __forceinline__ void stmatrix4_t(uint32_t a, uint32_t r0, uint32_t r1, uint32_t r2, uint32_t r3) {
  asm volatile("stmatrix.sync.aligned.m8n8.x4.trans.shared.b16 [%0], {%1,%2,%3,%4};" :: "r"(a), "r"(r0), "r"(r1), "r"(r2), "r"(r3) : "memory");
}
__device__ __forceinline__ void ldmatrix4_t(uint32_t* r, uint32_t a) {
  asm volatile("ldmatrix.sync.aligned.m8n8.x4.trans.shared.b16 {%0,%1,%2,%3}, [%4];" : "=r"(r[0]), "=r"(r[1]), "=r"(r[2]), "=r"(r[3]) : "r"(a) : "memory");
}
__device__ __forceinline__ void ldmatrix4(uint32_t* r, uint32_t a) {
  asm volatile("ldmatrix.sync.aligned.m8n8.x4.shared.b16 {%0,%1,%2,%3}, [%4];" : "=r"(r[0]), "=r"(r[1]), "=r"(r[2]), "=r"(r[3]) : "r"(a) : "memory");
}
__device__ __forceinline__ void hmma16(float* c, const uint32_t* a, uint32_t b0, uint32_t b1) {
  asm volatile("mma.sync.aligned.m16n8k16.row.col.f32.bf16.bf16.f32 {%0,%1,%2,%3}, {%4,%5,%6,%7}, {%8,%9}, {%0,%1,%2,%3};"
               : "+f"(c[0]), "+f"(c[1]), "+f"(c[2]), "+f"(c[3]) : "r"(a[0]), "r"(a[1]), "r"(a[2]), "r"(a[3]), "r"(b0), "r"(b1));
}
__device__ __forceinline__ void hmma8(float* c, uint32_t a0, uint32_t a1, uint32_t b0) {
  asm volatile("mma.sync.aligned.m16n8k8.row.col.f32.bf16.bf16.f32 {%0,%1,%2,%3}, {%4,%5}, {%6}, {%0,%1,%2,%3};"
               : "+f"(c[0]), "+f"(c[1]), "+f"(c[2]), "+f"(c[3]) : "r"(a0), "r"(a1), "r"(b0));
}
__device__ __forceinline__ uint4 lds128(uint32_t a) { uint4 v; asm volatile("ld.shared.v4.u32 {%0,%1,%2,%3}, [%4];" : "=r"(v.x), "=r"(v.y), "=r"(v.z), "=r"(v.w) : "r"(a) : "memory"); return v; }
__device__ __forceinline__ void sts128(uint32_t a, uint4 v) { asm volatile("st.shared.v4.u32 [%0], {%1,%2,%3,%4};" :: "r"(a), "r"(v.x), "r"(v.y), "r"(v.z), "r"(v.w) : "memory"); }
__device__ __forceinline__ void sts128f(uint32_t a, float x, float y, float z, float w) { asm volatile("st.shared.v4.f32 [%0], {%1,%2,%3,%4};" :: "r"(a), "f"(x), "f"(y), "f"(z), "f"(w) : "memory"); }
__device__ __forceinline__ void sts64f(uint32_t a, float x, float y) { asm volatile("st.shared.v2.f32 [%0], {%1,%2};" :: "r"(a), "f"(x), "f"(y) : "memory"); }
__device__ __forceinline__ uint32_t lds32(uint32_t a) { uint32_t v; asm volatile("ld.shared.u32 %0, [%1];" : "=r"(v) : "r"(a) : "memory"); return v; }
__device__ __forceinline__ void sts32(uint32_t a, uint32_t v) { asm volatile("st.shared.u32 [%0], %1;" :: "r"(a), "r"(v) : "memory"); }

constexpr uint32_t SBASE = 1024;
__host__ __device__ constexpr uint64_t mkdesc(uint32_t off, uint32_t lbo, uint32_t sbo, uint32_t swz) {
  return (uint64_t)(((SBASE + off) & 0x3FFFF) >> 4) | ((uint64_t)(lbo >> 4) << 16) | ((uint64_t)(sbo >> 4) << 32) | ((uint64_t)swz << 62);
}
__device__ __forceinline__ void wg_fence() { asm volatile("wgmma.fence.sync.aligned;" ::: "memory"); }
__device__ __forceinline__ void wg_commit() { asm volatile("wgmma.commit_group.sync.aligned;" ::: "memory"); }
template <int N> __device__ __forceinline__ void wg_wait() { asm volatile("wgmma.wait_group.sync.aligned %0;" :: "n"(N) : "memory"); }

template <int N> __device__ __forceinline__ void reg_fence(float (&d)[N], int n = N) {
#pragma unroll
  for (int i = 0; i < N; i++) if (i < n) asm volatile("" : "+f"(d[i]) :: "memory");
}
#define F4(b) "+f"(d[b]), "+f"(d[b + 1]), "+f"(d[b + 2]), "+f"(d[b + 3])
#define F8(b) F4(b), F4(b + 4)
#define F16(b) F8(b), F8(b + 8)
#define G4(b) "=f"(d[b]), "=f"(d[b + 1]), "=f"(d[b + 2]), "=f"(d[b + 3])
#define G8(b) G4(b), G4(b + 4)
#define G16(b) G8(b), G8(b + 8)
#define RS_IN "r"(a[0]), "r"(a[1]), "r"(a[2]), "r"(a[3]), "l"(db), "n"(SD), "n"(TB)
#define SS_IN "l"(da), "l"(db), "n"(SD), "n"(TA), "n"(TB)
#define WG_OP(str, out0, out1, in) do { if (SD || KEEP) asm volatile(str : out1 : in); else asm volatile(str : out0 : in); } while (0)
#define O12(X) X##8(0), X##4(8)
#define O20(X) X##16(0), X##4(16)
#define O32(X) X##16(0), X##16(16)
template <int SD, int TB, int KEEP = 0> __device__ __forceinline__ void wgmma_rs24(float* d, const uint32_t* a, uint64_t db) {
  WG_OP("wgmma.mma_async.sync.aligned.m64n24k16.f32.bf16.bf16 {%0,%1,%2,%3,%4,%5,%6,%7,%8,%9,%10,%11}, {%12,%13,%14,%15}, %16, %17, 1, 1, %18;", O12(G), O12(F), RS_IN);
}
template <int SD, int TB, int KEEP = 0> __device__ __forceinline__ void wgmma_rs32(float* d, const uint32_t* a, uint64_t db) {
  WG_OP("wgmma.mma_async.sync.aligned.m64n32k16.f32.bf16.bf16 {%0,%1,%2,%3,%4,%5,%6,%7,%8,%9,%10,%11,%12,%13,%14,%15}, {%16,%17,%18,%19}, %20, %21, 1, 1, %22;", G16(0), F16(0), RS_IN);
}
template <int SD, int TB, int KEEP = 0> __device__ __forceinline__ void wgmma_rs40(float* d, const uint32_t* a, uint64_t db) {
  WG_OP("wgmma.mma_async.sync.aligned.m64n40k16.f32.bf16.bf16 {%0,%1,%2,%3,%4,%5,%6,%7,%8,%9,%10,%11,%12,%13,%14,%15,"
        "%16,%17,%18,%19}, {%20,%21,%22,%23}, %24, %25, 1, 1, %26;", O20(G), O20(F), RS_IN);
}
template <int SD, int TB, int KEEP = 0> __device__ __forceinline__ void wgmma_rs64(float* d, const uint32_t* a, uint64_t db) {
  WG_OP("wgmma.mma_async.sync.aligned.m64n64k16.f32.bf16.bf16 {%0,%1,%2,%3,%4,%5,%6,%7,%8,%9,%10,%11,%12,%13,%14,%15,"
        "%16,%17,%18,%19,%20,%21,%22,%23,%24,%25,%26,%27,%28,%29,%30,%31}, {%32,%33,%34,%35}, %36, %37, 1, 1, %38;", O32(G), O32(F), RS_IN);
}
template <int SD, int TA, int TB, int KEEP = 0> __device__ __forceinline__ void wgmma_ss24(float* d, uint64_t da, uint64_t db) {
  WG_OP("wgmma.mma_async.sync.aligned.m64n24k16.f32.bf16.bf16 {%0,%1,%2,%3,%4,%5,%6,%7,%8,%9,%10,%11}, %12, %13, %14, 1, 1, %15, %16;", O12(G), O12(F), SS_IN);
}
template <int SD, int TA, int TB, int KEEP = 0> __device__ __forceinline__ void wgmma_ss8(float* d, uint64_t da, uint64_t db) {
  WG_OP("wgmma.mma_async.sync.aligned.m64n8k16.f32.bf16.bf16 {%0,%1,%2,%3}, %4, %5, %6, 1, 1, %7, %8;", G4(0), F4(0), SS_IN);
}
__device__ __forceinline__ void bar_arrive(int id, int n) { asm volatile("bar.arrive %0, %1;" :: "r"(id), "r"(n) : "memory"); }
__device__ __forceinline__ uint32_t vis_bits(int pos, int t) {
  uint32_t m = 0;
#pragma unroll
  for (int i = 0; i < 8; i++) m |= (8 * (i / 2 + 1) + 2 * t + (i & 1) <= pos) ? 1u << i : 0u;
  return m;
}

__device__ __forceinline__ unsigned long long wait_words(const unsigned long long* p, uint32_t E) {
  int guard = 0; unsigned long long m;
  while (m = ld_rlxu64(p), !__all_sync(~0u, rfresh(m, E))) { __nanosleep(20); if (++guard > (1 << 22)) TRAP(); }
  fence_acq();
  return m;
}
__device__ __forceinline__ int route_step(int s, uint32_t E, int lane, unsigned long long& run) {
  const unsigned long long m = warp_max<2>(wait_words(G.f_h2[s][lane & 3], E));
  if (s == 0 || m > run) { run = m; return rtok(m) & 31; }
  return -1;
}

struct Params {
  const bf16 *x, *mem0, *wq, *wk, *wv, *wo, *wr, *wg, *wu, *wd;
  bf16* out;
  uint32_t zero2;
  unsigned long long zero;
};

constexpr uint32_t WSTG_STRIDE = 272;
__device__ __forceinline__ void stage_weights(uint32_t stg, const bf16* src, int ld, int tid, int nthr) {
  for (int i = tid; i < 512 * 16; i += nthr) {
    int k = i >> 4, c = i & 15;
    cp_async16(stg + k * WSTG_STRIDE + c * 16, src + (size_t)k * ld + c * 8);
  }
}
__device__ __forceinline__ void load_frags(uint32_t (*W)[4], uint32_t stg, int wg, int w, int lane) {
  uint32_t a = stg + ((lane >> 4) * 8 + (lane & 7)) * WSTG_STRIDE + (64 * wg + 16 * w + ((lane >> 3) & 1) * 8) * 2;
#pragma unroll
  for (int ks = 0; ks < 32; ks++) ldmatrix4_t(W[ks], a + ks * 16 * WSTG_STRIDE);
}

constexpr uint32_t M_H = 0;
constexpr uint32_t M_MEM = 65536;
constexpr uint32_t M_Q = M_MEM + 24576;
constexpr uint32_t M_K = M_Q + 12288;
constexpr uint32_t M_V = M_K + 12288;
constexpr uint32_t M_OM = M_V + 12288;
constexpr uint32_t M_OST = M_OM + 6144;
constexpr uint32_t M_TST = M_OST + 8192;
constexpr uint32_t M_WO = M_TST + 16384;
constexpr uint32_t M_M0 = M_WO + 49152;
constexpr uint32_t M_PT = M_M0 + 2048;
constexpr uint32_t M_BAR = M_PT + 12288;
constexpr uint32_t M_TOTAL = M_BAR + 384;
static_assert(M_TOTAL <= 232448, "main smem");
static_assert(M_WO >= 512 * WSTG_STRIDE, "staging overlaps Wo");
enum { B_LAND = 0  , B_QK = 3, B_V, B_TOK, B_OM, B_HA, B_HB, B_HAE, B_HBE, B_OST, B_OFREE, B_SYNC,
       B_STG, B_STG1, B_SS, B_TFREE, B_KFREE, B_VFREE, B_FIX  , B_NUM = B_FIX + 8 };
static_assert(B_NUM * 8 <= 256, "barriers");
constexpr uint32_t M_CAND = M_BAR + 256;
constexpr uint32_t M_BASE = M_BAR + 272;
constexpr uint32_t M_ZERO = M_BAR + 280;
constexpr uint32_t M_BAS2 = M_BAR + 328;
constexpr uint32_t M_NEAR = M_BAR + 288;
enum { N_GO1 = 2, N_GO2, N_GO3, N_GO4, N_AG, N_W };

#define GSTAMP(slot, i)
#define TSTAMP(slot, i, k)
#define STAMP(i)
#define ASTAMP(i)
#define WSTAMP(i)
#define CSTAMP(i, v)
#define PIN(x) asm volatile("" : "+r"(x))
#define SCHED(k) asm volatile("{\n.reg .pred p;\nsetp.ne.u32 p, %0, 0;\n@p trap;\n}" :: "r"(zz & (1u << (k))) : "memory")
#define HOLD(k, v) asm volatile("{\n.reg .pred p;\nsetp.ne.u32 p, %0, 0;\n@p st.shared.u32 [%0], %1;\n}" :: "r"(zz & (1u << (k))), "r"(v) : "memory")
#define DRAIN(a) (lds32((a) + zz) & zz)
#define BAR(i) (sb + M_BAR + 8 * (i))

__device__ __forceinline__ int probe(const uint8_t* p, int n) {
  int best = 1 << 30; uint32_t v = 0;
#pragma unroll 1
  for (int r = 0; r < n; r++) {
    uint32_t t0 = clk();
    asm volatile("atom.relaxed.gpu.global.or.b32 %0, [%1], %2;" : "=r"(v) : "l"(p + 3968), "r"(v & 0u) : "memory");
    if (v == 0x7fffffffu) t0++;
    best = min(best, (int)(clk() - t0));
  }
  return best;
}
__device__ __forceinline__ void load_mem0(uint4* u, int k0, int lane, const bf16* mem0) {
#pragma unroll
  for (int i = 0; i < 2; i++) {
    const unsigned short* m = (const unsigned short*)mem0 + k0 + lane + 32 * i;
    u[i] = make_uint4(m[0] | (uint32_t)m[512] << 16, m[1024] | (uint32_t)m[1536] << 16, m[2048] | (uint32_t)m[2560] << 16, m[3072] | (uint32_t)m[3584] << 16);
  }
}

__device__ __forceinline__ void paced_h(uint32_t dst, const uint8_t* src, uint32_t o0, uint32_t o1, uint32_t piece, uint32_t bar, int gap) {
  uint32_t t = clk32();
#pragma unroll 1
  for (uint32_t o = o0; o < o1; o += piece) {
    e_mc(dst + o, src + o, piece, bar, 7);
    spin_until(t += gap);
  }
}

__device__ __forceinline__ void paced_st(uint8_t* dst, uint32_t src, int gap) {
  uint32_t t = clk32();
#pragma unroll 1
  for (uint32_t o = 0; o < 8192; o += SPC_) {
    e_s2g(dst + o, src + o, SPC_);
    if (o + SPC_ < 8192) spin_until(t += gap);
  }
}
__device__ __forceinline__ int block_of(int head, int c) { return REMAP_ ? (c == 2 ? head : 32 + 2 * head + c) : head * 3 + c; }

__device__ __forceinline__ void weight_role(const Params& p, const uint32_t sb, const int warp, const int cta, const int C, const uint32_t E,
                                            const uint8_t* const memg) {
  const int tid = fresh_tid(), lane = tid & 31;
  const int wg = warp >> 2, w = warp & 3;
  uint32_t W[32][4];
  cp_async_wait();
  bar_sync(1, 256);
  load_frags(W, sb, wg, w, lane);
  bar_sync(1, 256);
  if (tid < 128) sts128(sb + M_V + 5 * 2048 + tid * 16, make_uint4(0, 0, 0, 0));
  fence_async_smem();
  cluster_sync();
  if (tid == 0 && cta == 0) GSTAMP(0, 1);
  if (tid == 0) TSTAMP(13, cta, 0);

  const uint32_t rba = mapa(sb, C == 2 ? 0 : 2), rbc = mapa(sb, C == 1 ? 0 : 1);
  const uint32_t MYBAR = M_BAR + 8 * (C < 2 ? B_QK : B_V);
  uint32_t qoff = M_Q + C * 12288 + warp * 256 + lane * 4;
  uint32_t toff = sb + warp * 256 + (lane >> 4) * 2048 + (lane & 15) * 16;
  uint32_t rbar = mapa(sb + M_BAR, min(lane, 2));
  uint32_t sv = sb + M_MEM + lane * 32 + ((lane >> 2) & 3) * 8;
  PIN(qoff); PIN(toff); PIN(rbar); PIN(sv);
  const uint32_t gen0 = (E - 1) * (uint32_t)(NSTEP - 1);
  uint32_t fix = 0;
  const bool sig = w == 0 && lane < 3;
  const int blk = block_of(cta / 3, C);
  const int pk = (blk < 24 ? PAUSE_ : PAUS2_) + (wg ? -PST2_ : PST2_);
  int cand = -1;
  float d[16];
#pragma unroll
  for (int i = 0; i < 16; i++) d[i] = 0.f;
  uint32_t tp[8];
#pragma unroll 1
  for (int T = -1; T < NSTEP; T++) {
    const uint32_t ph = T & 1;
    const uint64_t Z = p.zero << ph;
    const uint32_t zz = p.zero2;
    if (T >= 0) {
      WSTAMP(0);
      const uint64_t db = mkdesc(M_MEM, 128, 256, 0) + Z;
      auto stage = [&]() {
        stmatrix4(toff + M_TST + 8192, tp[0], tp[1], tp[2], tp[3]); stmatrix4(toff + M_TST + 12288, tp[4], tp[5], tp[6], tp[7]);
        if (sig) mbar_arrive_remote(rbar + 8 * B_HBE);
      };
      if (STK_ == 0) stage();
      mbar_wait(BAR(B_LAND), ph);
      WSTAMP(1);
      const uint32_t gt = gentag(gen0 + T);
      auto old = [&](uint32_t a) { return lds32(a) ^ gt; };
      uint32_t bad = 0;
      bool redo = false, ready = false;
      wg_fence();
      wgmma_rs24<0, 1, KP1_>(d, W[0], db);
#pragma unroll
      for (int ks = 1; ks < 32; ks++) {
        if (ks == STK_) stage();
        if (ks == 2) bad |= old(sv + min(warp, 5) * 1024);
        if (ks == 10 || ks == 22) bad |= xo2(lds32(sv + (ks == 10 ? 6 : 15) * 1024 + warp * 1024), lds32(sv + (ks == 10 ? 14 : 23) * 1024), gt);
        if (ks == 6) {
          const uint32_t z5 = DRAIN(toff + M_TST);
          __syncwarp();
          if (lane == 0) mbar_arrive(BAR(B_STG) + z5);
        }
        if (ks == 27) ready = mbar_test(BAR(C < 2 ? B_KFREE : B_VFREE), ph ^ 1) & mbar_test(BAR(B_HA), ph);
        if (ks == RED_) redo = bar_or(N_W, 256, T > 0 && (bad & 0x10001u));
        if (ks == 8 || ks == 20) { mbar_wait(BAR(B_LAND + (ks + 4) / 12), ph); WSTAMP(6 + (ks + 4) / 12); wg_fence(); }
        wgmma_rs24<1, 1>(d, W[ks], db + ks * 48);
      }
      wg_commit();
      uint32_t a0 = rba + qoff, a1 = a0 + 128, a2 = rbc + qoff, a3 = a2 + 128, ba = rba + MYBAR, bc = rbc + MYBAR;
      PIN(a0); PIN(a1); PIN(a2); PIN(a3); PIN(ba); PIN(bc);
      if (!ready) {
        mbar_wait(BAR(C < 2 ? B_KFREE : B_VFREE), ph ^ 1);
        if (T < NSTEP - 1) mbar_wait(BAR(B_HA), ph);
      }
      wg_wait<0>(); reg_fence(d);
      if (__builtin_expect(redo, 0)) {
        auto stale = [&]() { return __any_sync(~0u, (old(sv + warp * 3072) | old(sv + warp * 3072 + 1024) | old(sv + warp * 3072 + 2048)) & 0x10001u); };
        auto fetch = [&](int r) {
          e_expect(BAR(B_FIX + warp), 3072);
          e_g2s(sb + M_MEM + warp * 3072, memg + warp * 8192 + ((uni(lds32(sb + M_NEAR + warp * 4)) ^ r) & 1) * 4096, 3072, BAR(B_FIX + warp));
        };
        bool late = stale();
        if (late) fetch(0);
        constexpr uint64_t dc = mkdesc(M_MEM, 128, 256, 0);
#pragma unroll
        for (int ks = 0; ks < 32; ks++) {
          if (ks % 12 == 0) {
            if (ks) { wg_commit(); wg_wait<0>(); reg_fence(d); }
            if (warp / 3 == ks / 12) {
              for (int guard = 0; late; guard++) {
                mbar_wait(BAR(B_FIX + warp), fix); fix ^= 1;
                late = stale();
                if (late) fetch(ALT_ ? guard + 1 : 0);
                if (guard > (1 << 20)) TRAP();
              }
            }
            bar_sync(N_W, 256);
            wg_fence();
          }
          if (ks == 0) wgmma_rs24<0, 1, 1>(d, W[0], dc); else wgmma_rs24<1, 1>(d, W[ks], dc + ks * 48);
        }
        wg_commit();
        wg_wait<0>(); reg_fence(d);
      }
      WSTAMP(2);
      if (T == 0 && tid == 0) TSTAMP(13, cta, 2);
      uint32_t lo[3], hi[3];
#pragma unroll
      for (int j = 0; j < 3; j++) { lo[j] = pack2(d[4 * j], d[4 * j + 1]); hi[j] = pack2(d[4 * j + 2], d[4 * j + 3]); }
      if (__builtin_expect(T == 0, 0)) { sts32(sb + M_M0 + tid * 8, lo[0]); sts32(sb + M_M0 + tid * 8 + 4, hi[0]); }
      if (__builtin_expect(cand >= 0, 0)) {
        if (T == LAG) { lo[1] = lds32(sb + M_M0 + tid * 8); hi[1] = lds32(sb + M_M0 + tid * 8 + 4); }
        if (C < 2) { st_async32(a0 + 5 * 2048, lo[2], ba); st_async32(a1 + 5 * 2048, hi[2], ba); }
        else { sts32(sb + qoff + 5 * 2048, lo[2]); sts32(sb + qoff + 5 * 2048 + 128, hi[2]); }
        lo[2] = lo[1]; hi[2] = hi[1];
      }
      uint32_t z5;
      if (C == 0) {
        sts32(sb + qoff, lo[0]); sts32(sb + qoff + 128, hi[0]); z5 = DRAIN(sb + qoff);
        st_async32(a0, lo[2], ba); st_async32(a1, hi[2], ba); st_async32(a2, lo[1], bc); st_async32(a3, hi[1], bc);
      } else if (C == 1) {
        sts32(sb + qoff, lo[1]); sts32(sb + qoff + 128, hi[1]); z5 = DRAIN(sb + qoff);
        st_async32(a0, lo[2], ba); st_async32(a1, hi[2], ba); st_async32(a2, lo[0], bc); st_async32(a3, hi[0], bc);
      } else {
        sts32(sb + qoff, lo[2]); sts32(sb + qoff + 128, hi[2]); z5 = DRAIN(sb + qoff);
        st_async32(a0, lo[0], ba); st_async32(a1, hi[0], ba); st_async32(a2, lo[1], bc); st_async32(a3, hi[1], bc);
      }
      __syncwarp();
      if (lane == 0) { mbar_arrive(sb + MYBAR + z5); if (w == 3) mbar_arrive(BAR(B_SS)); }
      if (T == NSTEP - 1) break;
    }
    {
      const uint64_t dh = mkdesc(M_H, 16, 1024, 1) + Z;
      static_assert(E2 == 0 && E3 > 0 && PAUSE_ > 0, "config");
      if (T + 2 < NSEG) {
        if (T < 0) mbar_wait(BAR(B_HA), ph);
        WSTAMP(3);
        wg_fence();
        wgmma_rs32<0, 0, 1>(d, W[0], dh);
#pragma unroll
        for (int ks = 1; ks < EA; ks++) {
          if (ks == E1) { wg_commit(); if (T >= 0) bar_sync(N_GO2, 384); wg_fence(); }
          wgmma_rs32<1, 0>(d, W[ks], dh + (ks >> 2) * 256 + (ks & 3) * 2);
        }
        wg_commit();
        mbar_wait(BAR(B_HB), ph);
        wg_wait<0>();
        if (sig) mbar_arrive_remote(rbar + 8 * B_HAE);
        WSTAMP(4);
        if (T >= 0) bar_sync(N_GO3, 384);
        if (wg == 1) bar_sync(N_W, 256);
        wg_fence();
#pragma unroll
        for (int ks = EA; ks < 32; ks++) wgmma_rs32<1, 0>(d, W[ks], dh + (ks >> 2) * 256 + (ks & 3) * 2);
        wg_commit();
        if (wg == 0) bar_arrive(N_W, 256);
        mbar_wait(BAR(B_TFREE), ph ^ 1);
        wg_wait<0>(); reg_fence(d);
      } else {
        bar_sync(N_GO2, 384);
        mbar_wait(BAR(B_HB), ph);
        if (sig) mbar_arrive_remote(rbar + 8 * B_HAE);
        bar_sync(N_GO3, 384);
        mbar_wait(BAR(B_TFREE), ph ^ 1);
      }
#pragma unroll
      for (int i = 0; i < 8; i++) { tp[i] = pack2(d[2 * i], d[2 * i + 1]); PIN(tp[i]); }
      const uint32_t t1 = toff + (C == 0 && !ph ? M_Q + 2048 : M_TST);
      auto staged = [&]() {
        const uint32_t z5 = DRAIN(t1);
        __syncwarp();
        if (lane == 0) mbar_arrive(BAR(B_STG1) + z5);
      };
      if (T < 0 || (T + 2 >= LAG && T + 2 < NSTEP)) {
        wg_fence();
        wgmma_rs32<0, 0, 1>(d, W[0], dh + 2048);
        stmatrix4(t1, tp[0], tp[1], tp[2], tp[3]); stmatrix4(t1 + 4096, tp[4], tp[5], tp[6], tp[7]);
#pragma unroll
        for (int ks = 1; ks < 32; ks++) {
          if (ks == 5) staged();
          if (ks == PAUSE_ - PST2_ || ks == PAUSE_ + PST2_ || ks == PAUS2_ - PST2_ || ks == PAUS2_ + PST2_) {
            wg_commit();
            if (T >= 0 && ks == pk) bar_sync(N_GO4, 384);
            wg_fence();
          }
          wgmma_rs32<1, 0>(d, W[ks], dh + 2048 + (ks >> 2) * 256 + (ks & 3) * 2);
        }
        wg_commit();
      } else {
        stmatrix4(t1, tp[0], tp[1], tp[2], tp[3]); stmatrix4(t1 + 4096, tp[4], tp[5], tp[6], tp[7]);
        staged();
        bar_sync(N_GO4, 384);
      }
      if (T >= 0) cand = __shfl_sync(~0u, (int)lds32(sb + M_CAND + ((T + 1) & 3) * 4), 0);
      wg_wait<0>(); reg_fence(d);
      if (T >= 0) WSTAMP(6);
      if (T < 0 && tid == 0) TSTAMP(13, cta, 1);
#pragma unroll
      for (int i = 0; i < 8; i++) tp[i] = pack2(d[2 * i], d[2 * i + 1]);
    }
  }
  cluster_sync();
  if (tid == 0 && cta == 0) GSTAMP(0, 5);
}

__device__ __forceinline__ void attn_role(const Params& p, const uint32_t sb, const int w, const int cta, const int head, const int C, const uint32_t E,
                                          uint8_t* const part, uint8_t* const memg) {
  const int tid = fresh_tid(), lane = tid & 31;
  const int g = lane >> 2, t = lane & 3, blk = block_of(head, C);
  uint32_t tag = ((E - 1) * (uint32_t)(NSTEP - 1)) & 1;
  uint4 m0[2][2];
  load_mem0(m0[0], w * 64, lane, p.mem0); load_mem0(m0[1], w * 64 + 256, lane, p.mem0);
  cluster_sync();
#pragma unroll
  for (int k = 0; k < 2; k++) {
#pragma unroll 1
    for (int i = 0; i < 6; i++) sts128(sb + M_MEM + (w + 4 * k) * 3072 + lane * 16 + i * 512, make_uint4(0, 0, 0, 0));
    __syncwarp();
#pragma unroll
    for (int i = 0; i < 2; i++) sts128(sb + M_MEM + ((w + 4 * k) * 4 + (lane >> 4) + 2 * i) * 768 + (lane & 15) * 16, m0[k][i]);
  }
  fence_async_smem();
  bar_sync(N_AG, 128);
  if (w == 3 && lane < 3) mbar_arrive(BAR(B_LAND + lane));
  if (lane == 0) {
    if (w == 0) TSTAMP(15, cta, 0);
    sts32(sb + M_PT + w * 4, probe(part + blk * 16384 + w * 4096, NPROBE_ / 2));
    if (w == 0) TSTAMP(15, cta, 1);
  }
  bar_sync(N_AG, 128);
  const uint32_t inear = lds32(sb + M_PT + (w >> 1) * 8 + 4) < lds32(sb + M_PT + (w >> 1) * 8);
  if (lane == 0 && !(w & 1)) st_rlx(&G.f_choice[blk][w >> 1], (E << 1) | inear);
  if (w == 0) TSTAMP(15, cta, 2);
  uint32_t nb;
  {
    const int i = min(lane >> 1, C < 2 ? 8 : 5);
    const int r = ((i / 3 * 3 + C) * 4 + w) * 3 + i % 3;
    int guard = 0; uint32_t cw;
    while (__any_sync(~0u, ((cw = ld_rlx(&G.f_choice[r][lane & 1])) >> 1) != (E & 0x7FFFFFFFu))) { if (++guard > (1 << 22)) TRAP(); }
    nb = __ballot_sync(~0u, cw & 1) >> (lane >> 4);
    if (w == 0) TSTAMP(15, cta, 3);
  }
  bar_sync(N_AG, 128);
  const uint32_t pt0 = sb + M_PT + (tid & 127) * 16;
  {
    const uint32_t po = (C * 4 + w) * 49152 + (lane >> 4) * 8192 + head * 128 + (lane & 15) * 8;
    const uint8_t* in = part + (blk * 16384 + (w >> 1) * 8192 + inear * 4096 + (w & 1) * 64 + (lane >> 3) * 128 + (lane & 7) * 8);
    const uint8_t* outp = memg + ((blk / 12) * 8192 + (blk % 12) * 256 + w * 64 + (lane >> 4) * 4096 + (lane & 4) * 8 + (lane & 8) * 2 + (lane & 3) * 4);
#pragma unroll
    for (int i = 0; i < 12; i++) {
      const int j = i / 4 * 3 + (i & 3);
      const uint8_t* a = (i & 3) < 3 ? part + (po + i / 4 * 589824 + (i & 3) * 16384 + ((nb >> (2 * j)) & 1) * 4096) : i == 11 ? in : outp;
      asm volatile("st.shared.u64 [%0], %1;" :: "r"(pt0 + (i >> 1) * 2048 + (i & 1) * 8), "l"(a) : "memory");
    }
  }
  const int xd = __shfl_sync(~0u, XDLY_ + (blk < 24 ? 0 : blk < 60 ? X1_ : X2_), 0);
  const uint32_t rba = mapa(sb, C == 2 ? 0 : 2), rbc = mapa(sb, C == 1 ? 0 : 1);
  uint32_t vis = vis_bits(8 + 8 * w + g, t);
  uint32_t ln = lane;
#pragma unroll
  for (int i = 0; i < SALT_; i++) ln += lds32(sb + M_ZERO);
  PIN(vis); PIN(ln);
  if (tid == 256 && C == 0) st_rlx(&G.f_loaded[head], E);
  uint32_t fa[8][4];
#pragma unroll
  for (int ks = 0; ks < 8; ks++) ldmatrix4_t(fa[ks], sb + M_WO + 32768 + w * 256 + (lane >> 4) * 1024 + (lane & 15) * 16 + ks * 2048);
  if (w == 0) TSTAMP(14, cta, 0);
#pragma unroll 1
  for (int T = 0; T < NSTEP; T++) {
    const uint32_t ph = T & 1;
    const uint32_t zz = uni(lds32(sb + M_ZERO));
    const bool more = T < NSTEP - 1;
    const float sc = 0.08838834764831845f * 1.4426950408889634f;
    tag ^= 1;
    float s[20];
    const uint8_t* in; int cnext = -1; uint32_t tx; bool synced;
    float x[10], tm, ts;
    uint32_t pt[5];
    auto tok_max = [&]() {
      PIN(vis);
      x[0] = s[2]; x[1] = s[3];
#pragma unroll
      for (int i = 0; i < 8; i++) x[2 + i] = (vis >> i & 1) ? s[4 * (i / 2 + 1) + 2 + (i & 1)] : -INFINITY;
      tm = fmaxf(fmaxf(fmaxf(fmaxf(x[0], x[1]), fmaxf(x[2], x[3])), fmaxf(fmaxf(x[4], x[5]), fmaxf(x[6], x[7]))), fmaxf(x[8], x[9]));
      HOLD(7, __float_as_uint(tm));
    };
    auto tok_exp1 = [&]() {
      tm = fmaxf(tm, __shfl_xor_sync(~0u, tm, 1));
      tm = fmaxf(tm, __shfl_xor_sync(~0u, tm, 2));
      const float b = -tm * sc;
#pragma unroll
      for (int i = 0; i < 10; i++) x[i] = fmaf(x[i], sc, b);
      HOLD(10, __float_as_uint(x[9]));
    };
    auto tok_exp2 = [&]() {
#pragma unroll
      for (int i = 0; i < 10; i++) x[i] = ex2(x[i]);
      ts = (((x[0] + x[1]) + (x[2] + x[3])) + ((x[4] + x[5]) + (x[6] + x[7]))) + (x[8] + x[9]);
#pragma unroll
      for (int k = 0; k < 5; k++) pt[k] = pack2(x[2 * k], x[2 * k + 1]);
      HOLD(8, __float_as_uint(ts));
    };
    {
      uint32_t q[8][4];
      auto load_q = [&](uint32_t a, int h) {
#pragma unroll
        for (int k2 = 0; k2 < 4; k2++) {
          uint32_t r[4];
          ldmatrix4_t(r, a + k2 * 512);
          q[2 * k2][h] = r[0]; q[2 * k2][h + 2] = r[1]; q[2 * k2 + 1][h] = r[2]; q[2 * k2 + 1][h + 2] = r[3];
        }
      };
      PIN(ln);
      const uint32_t qa = sb + M_Q + ln * 16, qt = qa + w * 2048 + (C == 0 && ph ? M_TST - M_Q : 2048);
      const int cand = C == 2 ? (int)uni(lds32(sb + M_CAND + (T & 3) * 4)) : -1;
      mbar_wait(BAR(B_TOK), ph);
      load_q(qt, 1);
      mbar_wait(BAR(B_QK), ph);
      ASTAMP(0);
      if (T == 0 && w == 0) TSTAMP(13, cta, 3);
      if (__builtin_expect(cand >= 0, 0)) {
        mbar_wait(BAR(B_V), ph);
        PIN(ln);
        const int e = w * 32 + ln;
#pragma unroll
        for (int i = 0; i < 3; i++) {
          const uint32_t v = lds32(sb + M_Q + i * 12288 + 5 * 2048 + e * 16 + 4);
          asm volatile("st.shared.u16 [%0], %1;" :: "r"(sb + M_Q + i * 12288 + (1 + (cand >> 3)) * 2048 + e * 16 + (cand & 7) * 2), "h"((unsigned short)v) : "memory");
        }
        fence_async_smem();
        bar_sync(N_AG, 128);
        load_q(qt, 1);
      }
      constexpr uint64_t dk = mkdesc(M_K, 128, 2048, 0);
      fence_async_smem();
      uint32_t r[4][4];
#pragma unroll
      for (int k2 = 0; k2 < 4; k2++) ldmatrix4_t(r[k2], qa + k2 * 512);
#pragma unroll
      for (int k2 = 0; k2 < 4; k2++) {
        q[2 * k2][0] = r[k2][0]; q[2 * k2][2] = r[k2][1]; q[2 * k2 + 1][0] = r[k2][2]; q[2 * k2 + 1][2] = r[k2][3];
        if (k2 & 1) {
          wg_fence();
#pragma unroll
          for (int ks = 2 * k2 - 2; ks < 2 * k2 + 2; ks++) { if (ks == 0) wgmma_rs40<0, 1>(s, q[0], dk); else wgmma_rs40<1, 1>(s, q[ks], dk + ks * 16); }
        }
      }
      wg_commit();
    }
    if (more) {
      uint32_t v[5][4];
      PIN(ln);
      const uint32_t va = sb + M_V + w * 512 + ((ln >> 3) & 1) * 128 + (ln >> 4) * 2048 + (ln & 7) * 16;
      const uint32_t ooff = M_OM + w * 1536 + C * 256 + ln * 4;
      mbar_wait(BAR(B_V), ph);
      wg_wait<0>(); reg_fence(s);
      if (ln < 3) mbar_arrive_remote(mapa(BAR(B_KFREE), ln));
      ldmatrix4(v[0], va); ldmatrix4(v[1], va + 256); ldmatrix4(v[2], va + 4096); ldmatrix4(v[3], va + 4096 + 256);
      ldmatrix4(v[4], sb + M_V + 8192 + w * 512 + ln * 16);
      ASTAMP(1);
      float m = fmaxf(fmaxf(fmaxf(fmaxf(s[0], s[1]), fmaxf(s[4], s[5])), fmaxf(fmaxf(s[8], s[9]), fmaxf(s[12], s[13]))), fmaxf(s[16], s[17]));
      m = fmaxf(m, __shfl_xor_sync(~0u, m, 1));
      m = fmaxf(m, __shfl_xor_sync(~0u, m, 2));
      const float b = -m * sc;
      uint32_t pm[5];
#pragma unroll
      for (int j = 0; j < 5; j++) pm[j] = pack2(ex2(fmaf(s[4 * j], sc, b)), ex2(fmaf(s[4 * j + 1], sc, b)));
      float o0[4] = {0.f, 0.f, 0.f, 0.f}, o1[4] = {0.f, 0.f, 0.f, 0.f}, l[4] = {0.f, 0.f, 0.f, 0.f};
      const uint32_t one[4] = {0x3f803f80u, 0x3f803f80u, 0x3f803f80u, 0x3f803f80u};
      hmma16(l, one, pm[0], pm[1]); hmma16(o0, v[0], pm[0], pm[1]); hmma16(o1, v[1], pm[0], pm[1]);
      hmma16(l, one, pm[2], pm[3]); hmma16(o0, v[2], pm[2], pm[3]); hmma16(o1, v[3], pm[2], pm[3]);
      hmma8(l, one[0], one[1], pm[4]); hmma8(o0, v[4][0], v[4][1], pm[4]); hmma8(o1, v[4][2], v[4][3], pm[4]);
      const float r0 = rcp(l[0]), r1 = rcp(l[1]);
      const uint32_t u0 = pack2(o0[0] * r0, o0[1] * r1), u1 = pack2(o0[2] * r0, o0[3] * r1), u2 = pack2(o1[0] * r0, o1[1] * r1), u3 = pack2(o1[2] * r0, o1[3] * r1);
      constexpr uint32_t OB = M_BAR + 8 * B_OM;
      const uint32_t a0 = rba + ooff, a1 = rbc + ooff;
      st_async32(a0, u0, rba + OB); st_async32(a1, u0, rbc + OB);
      st_async32(a0 + 128, u1, rba + OB); st_async32(a1 + 128, u1, rbc + OB);
      st_async32(a0 + 768, u2, rba + OB); st_async32(a1 + 768, u2, rbc + OB);
      st_async32(a0 + 896, u3, rba + OB); st_async32(a1 + 896, u3, rbc + OB);
      bar_arrive(N_GO2, 384);
      sts32(sb + ooff, u0); sts32(sb + ooff + 128, u1); sts32(sb + ooff + 768, u2); sts32(sb + ooff + 896, u3);
      ASTAMP(2);
      uint32_t fb[8][4];
      const uint32_t wa = sb + M_WO + 16384 + w * 256 + (ln >> 4) * 1024 + (ln & 15) * 16 + zz;
      ldmatrix4_t(fb[0], wa);
      SCHED(3);
#pragma unroll
      for (int ks = 1; ks < 8; ks++) {
        ldmatrix4_t(fb[ks], wa + ks * 2048);
        if (ks == ARR_) { __syncwarp(); if (ln == 0) mbar_arrive(BAR(B_OM) + (fb[0][0] & zz)); }
      }
      if (blk % 3 == 2) cnext = (int)uni(lds32(sb + M_CAND + ((T + 1) & 3) * 4));
      {
        float d[12], e[12];
        constexpr uint64_t ob = mkdesc(M_OM, 128, 256, 0);
        uint8_t* q[3][3];
        auto addr = [&](int i) {
          asm volatile("ld.shared.v2.u64 {%0,%1}, [%2];" : "=l"(q[i][0]), "=l"(q[i][1]) : "r"(pt0 + i * 4096) : "memory");
          if (i < 2) asm volatile("ld.shared.u64 %0, [%1];" : "=l"(q[i][2]) : "r"(pt0 + i * 4096 + 2048) : "memory");
          else asm volatile("ld.shared.v2.u64 {%0,%1}, [%2];" : "=l"(q[i][2]), "=l"(in) : "r"(pt0 + i * 4096 + 2048) : "memory");
        };
        auto put = [&](const float* d, int i) {
          st_rlx64(q[i][0], (pack2(d[0], d[1]) & ~1u) | tag, pack2(d[2], d[3]));
          st_rlx64(q[i][1], (pack2(d[4], d[5]) & ~1u) | tag, pack2(d[6], d[7]));
          st_rlx64(q[i][2], (pack2(d[8], d[9]) & ~1u) | tag, pack2(d[10], d[11]));
        };
        addr(0); addr(1);
        SCHED(6);
        tok_max();
        ASTAMP(3);
        mbar_wait(BAR(B_OM), ph);
        if (!(NOF_ & 2)) fence_async_smem();
        ASTAMP(4);
        constexpr uint64_t w0 = mkdesc(M_WO, 1024, 128, 0);
        float (&f)[12] = d;
        wg_fence();
        wgmma_ss24<0, 1, 1>(d, w0, ob);
#pragma unroll
        for (int ks = 1; ks < 8; ks++) wgmma_ss24<1, 1, 1>(d, w0 + ks * 128, ob + ks * 48);
        wg_commit();
        wgmma_rs24<0, 1>(e, fb[0], ob);
#pragma unroll
        for (int ks = 1; ks < HAND_; ks++) wgmma_rs24<1, 1>(e, fb[ks], ob + ks * 48);
        wg_commit();
        wg_wait<1>(); reg_fence(d);
        put(d, 0);
        addr(2);
        SCHED(4);
        ASTAMP(5);
        wg_fence();
#pragma unroll
        for (int ks = HAND_; ks < 8; ks++) wgmma_rs24<1, 1>(e, fb[ks], ob + ks * 48);
        wg_commit();
        wgmma_rs24<0, 1, 1>(f, fa[0], ob);
#pragma unroll
        for (int ks = 1; ks < HAND_; ks++) wgmma_rs24<1, 1>(f, fa[ks], ob + ks * 48);
        wg_commit();
        wg_wait<1>(); reg_fence(e);
        put(e, 1);
        SCHED(5);
        if (C < 2) {
          wg_fence();
#pragma unroll
          for (int ks = HAND_; ks < 8; ks++) wgmma_rs24<1, 1>(f, fa[ks], ob + ks * 48);
          wg_commit();
        }
        if (GO3_ == 0) bar_arrive(N_GO3, 384);
        synced = __all_sync(~0u, mbar_test(BAR(B_SYNC), ph));
        tx = uni(lds32(sb + M_BASE + ph * 4)) + xd;
        wg_wait<0>(); reg_fence(f);
        if (GO3_ == 1) bar_arrive(N_GO3, 384);
        if (C < 2) put(f, 2);
        if (GO3_ == 2) bar_arrive(N_GO3, 384);
        ASTAMP(6);
        if (T == 0 && w == 0) TSTAMP(14, cta, 1);
      }
    } else {
      mbar_wait(BAR(B_V), ph);
      wg_wait<0>(); reg_fence(s);
      tok_max();
    }
    uint2 v[8];
#pragma unroll
    for (int i = 0; i < 8; i++) v[i] = make_uint2(zz, zz);
    auto poll = [&](uint2* v) {
      v[0] = ld_rlx64<0>(in); v[1] = ld_rlx64<512>(in); v[2] = ld_rlx64<1024>(in); v[3] = ld_rlx64<1536>(in);
      v[4] = ld_rlx64<2048>(in); v[5] = ld_rlx64<2560>(in); v[6] = ld_rlx64<3072>(in); v[7] = ld_rlx64<3584>(in);
    };
    uint8_t* outp;
    asm volatile("ld.shared.u64 %0, [%1];" : "=l"(outp) : "r"(pt0 + 2048 + 8) : "memory");
    const uint32_t itag = gentag((E - 1) * (uint32_t)(NSTEP - 1) + T + 1);
    const bool sum = more && cnext < 0;
    if (more) {
      if (!synced) { mbar_wait(BAR(B_SYNC), ph); tx = uni(lds32(sb + M_BASE + ph * 4)) + xd; }
      ASTAMP(7);
      if (__builtin_expect(cnext >= 0, 0)) {
        const unsigned long long* hp = (const unsigned long long*)&G.hc[T + 1 - LAG][0] + ((blk / 3) * 8 + 2 * w + ((ln >> 2) & 1));
        unsigned long long v0; int guard = 0;
        while (v0 = ld_rlxu64(hp), !__all_sync(~0u, (uint32_t)(v0 >> 32) == E)) { if (++guard > (1 << 22)) TRAP(); }
        st_rlx((uint32_t*)outp, (ln & 3) == 1 ? ((uint32_t)v0 >> ((ln & 8) * 2)) & 0xffffu : (ln & 1) ? 0u : itag);
      } else {
        spin_until(tx);
        ASTAMP(8);
        poll(v);
      }
    }
    auto late = [&](const uint2* v) {
      return __any_sync(~0u, (or3(xo2(v[0].x, v[1].x, tag), xo2(v[2].x, v[3].x, tag), xo2(v[4].x, v[5].x, tag)) | xo2(v[6].x, v[7].x, tag)) & 1u);
    };
    tok_exp1(); tok_exp2();
    auto reduce = [&]() {
      if (sum) {
        ASTAMP(9);
        int guard = 0;
        while (late(v)) {
          if (++guard > (1 << 22)) TRAP();
          poll(v);
        }
#pragma unroll
        for (int i = 0; i < 4; i++) { v[i].x = add2(v[i].x, v[i + 4].x); v[i].y = add2(v[i].y, v[i + 4].y); }
        const bool hi = ln & 8;
        const uint32_t x0 = add2(v[0].x, v[1].x), x1 = add2(v[2].x, v[3].x), y0 = add2(v[0].y, v[1].y), y1 = add2(v[2].y, v[3].y);
        const uint32_t m0 = hi ? y0 : x0, m1 = hi ? y1 : x1;
        const uint32_t n0 = __shfl_xor_sync(~0u, hi ? x0 : y0, 8), n1 = __shfl_xor_sync(~0u, hi ? x1 : y1, 8);
        float k0 = (blo(m0) + blo(m1)) + (blo(n0) + blo(n1)), k1 = (bhi(m0) + bhi(m1)) + (bhi(n0) + bhi(n1));
        k0 += __shfl_xor_sync(~0u, k0, 16); k1 += __shfl_xor_sync(~0u, k1, 16);
        st_rlx((uint32_t*)outp, (ln & 1) ? pack2(k0, k1) : pack2_tag(k0, k1, itag));
        ASTAMP(10);
        if (T == 0 && w == 0) TSTAMP(14, cta, 2);
        CSTAMP(12 + w, (clk() & ~15u) | min(guard + 1, 15));
      }
      if (more) bar_arrive(N_GO4, 384);
    };
    if (PVR_ < 0) reduce();
    {
      PIN(ln);
      const uint32_t oa = sb + M_OST + w * 128 + (ln >> 3) * 512 + (ln & 7) * 16;
      const uint32_t a[3][4] = {{0, pt[0], 0, pt[1]}, {0, pt[2], 0, pt[3]}, {0, pt[4], 0, 0}};
      constexpr uint64_t dv = mkdesc(M_V, 2048, 128, 0);
#pragma unroll 1
      for (int h = 0; h < 2; h++) {
        float o[32];
        const uint64_t dh = dv + (uint64_t)(h * 64);
        wg_fence();
        wgmma_rs64<0, 0>(o, a[0], dh); wgmma_rs64<1, 0>(o, a[1], dh + 256); wgmma_rs64<1, 0>(o, a[2], dh + 512);
        wg_commit();
        if (h == PVR_) reduce();
        if (h == 0) {
          ts += __shfl_xor_sync(~0u, ts, 1);
          ts += __shfl_xor_sync(~0u, ts, 2);
          ts = rcp(ts);
          mbar_wait(BAR(B_OFREE), ph ^ 1);
        }
        wg_wait<0>(); reg_fence(o);
        if (h == 1 && ln < 3) mbar_arrive_remote(mapa(BAR(B_VFREE), ln));
#define OT(i) pack2(o[4 * (i) + 2] * ts, o[4 * (i) + 3] * ts)
        stmatrix4(oa + h * 4096, OT(0), OT(1), OT(2), OT(3));
        stmatrix4(oa + h * 4096 + 2048, OT(4), OT(5), OT(6), OT(7));
      }
      const uint32_t z5 = DRAIN(oa);
      __syncwarp();
      if (ln == 0) mbar_arrive(BAR(B_OST) + z5);
      ASTAMP(11);
    }
  }
}

__global__ void __cluster_dims__(3, 1, 1) __launch_bounds__(512, 1) main_kernel(Params p) {
  extern __shared__ __align__(1024) uint8_t sm[];
  const uint32_t sb = smem_u32(sm);
  if ((sb & 0xFFFFFFu) != SBASE) TRAP();
  asm volatile("griddepcontrol.launch_dependents;");
  const int warp = __shfl_sync(~0u, threadIdx.x >> 5, 0);
  const int cta = blockIdx.x, head = cta / 3, c = cta % 3;
  const uint32_t E = __shfl_sync(~0u, *(volatile uint32_t*)&g_epoch + 1, 0);
  uint8_t* const part = G.xch;
  uint8_t* const memg = part + 96 * 16384;

  if (threadIdx.x == 0 && cta == 0) GSTAMP(0, 0);
  if (threadIdx.x < B_NUM) {
    const int i = threadIdx.x;
    const uint32_t cnt = i == B_STG || i == B_STG1 ? 8 : i == B_OST ? 4 : i == B_HAE || i == B_HBE ? 6 : i == B_KFREE || i == B_VFREE ? 12 : i == B_SS ? 2 : i == B_OM ? 5 :
                         i == B_QK ? (c < 2 ? 9 : 1) : i == B_V ? (c < 2 ? 1 : 9) : 1;
    mbar_init(BAR(i), cnt);
    if (i == B_HA || i == B_HB || i == B_STG || i == B_HAE || i == B_HBE || i == B_TFREE)
      asm volatile("mbarrier.arrive.shared::cta.b64 _, [%0], %1;" :: "r"(BAR(i)), "r"(cnt) : "memory");
    asm volatile("fence.mbarrier_init.release.cluster;" ::: "memory");
  }
  if (warp < 8) {
    const int tid = threadIdx.x;
    uint4 wa[6], wb[6];
#pragma unroll
    for (int i = 0; i < 6; i++) {
      const int mi = i >> 1, e = (tid >> 2) + (i & 1) * 64;
      const uint4* src = (const uint4*)(p.wo + (size_t)(head * 128 + e) * 512 + min(3 * mi + c, 7) * 64 + (tid & 3) * 16);
      wa[i] = __ldg(src); wb[i] = __ldg(src + 1);
    }
    stage_weights(sb, (c == 0 ? p.wq : c == 1 ? p.wk : p.wv) + head * 128, 4096, tid, 256);
#pragma unroll
    for (int i = 0; i < 6; i++) {
      const int mi = i >> 1, e = (tid >> 2) + (i & 1) * 64;
      const uint4 a = wa[i], b = wb[i];
      const uint32_t dst = sb + M_WO + mi * 16384 + (e >> 3) * 1024 + (tid & 3) * 256 + (e & 7) * 16;
      sts128(dst, make_uint4(__byte_perm(a.x, a.y, 0x5410), __byte_perm(a.z, a.w, 0x5410), __byte_perm(b.x, b.y, 0x5410), __byte_perm(b.z, b.w, 0x5410)));
      sts128(dst + 128, make_uint4(__byte_perm(a.x, a.y, 0x7632), __byte_perm(a.z, a.w, 0x7632), __byte_perm(b.x, b.y, 0x7632), __byte_perm(b.z, b.w, 0x7632)));
    }
  } else {
    const int i0 = threadIdx.x - 256;
    const uint32_t tag0 = ((E - 1) * (uint32_t)(NSTEP - 1)) & 1;
    for (int i = i0; i < 1024; i += 256) *(uint4*)(part + block_of(head, c) * 16384 + i * 16) = make_uint4(tag0, 0, tag0, 0);
    if (i0 < 16) *(uint32_t*)(memg + i0 * 4096 + 3968) = 0;
    if (i0 < 2) st_rlx(&G.f_choice[block_of(head, c)][i0], 0);
    if (i0 < 8) st_rlx64(&G.sync[i0 >> 2][cta][i0 & 3], 0, 0);
    __threadfence();
    if (i0 < 12) sts32(sb + M_ZERO + i0 * 4, 0);
    if (i0 < 2) { sts32(sb + M_BASE + i0 * 4, clk32() - 65536); sts32(sb + M_BAS2 + i0 * 4, clk32() - 65536); sts32(sb + M_CAND + i0 * 4, (uint32_t)-1); }
  }

  if (warp < 8) {
    asm volatile("setmaxnreg.inc.sync.aligned.u32 " STR(RW_) ";");
    weight_role(p, sb, warp, cta, c, E, memg);
  } else if (warp < 12) {
    if (RA_ < 128) asm volatile("setmaxnreg.dec.sync.aligned.u32 " STR(RA_) ";");
    if (RA_ > 128) asm volatile("setmaxnreg.inc.sync.aligned.u32 " STR(RA_) ";");
    attn_role(p, sb, warp - 8, cta, head, c, E, part, memg);
    cluster_sync();
  } else {
    asm volatile("setmaxnreg.dec.sync.aligned.u32 " STR(RC_) ";");
    const int tid = fresh_tid(), lane = tid & 31;
    const int w = warp - 12;
    cluster_sync();
    if (w != 2) {
      const int tl = w == 0 ? c : w == 1 ? 2 + c : 5 + c;
      int near = 0;
      if (lane == 0) { const int t0 = probe(memg + tl * 8192, NPROBE_ / 2); near = probe(memg + tl * 8192 + 4096, NPROBE_ / 2) < t0; }
      near = uni(near);
      if (lane < 3) asm volatile("st.shared::cluster.u32 [%0], %1;" :: "r"(mapa(sb + M_NEAR + tl * 4, lane)), "r"(near) : "memory");
      __syncwarp();
    }
    if (w == 0) {
      int yadj = 0, dmin = 1 << 20; uint32_t prev = 0; bool cprev = false;
      uint32_t s1 = (2 + c) * 8192, s2 = (5 + c) * 8192;
#pragma unroll 1
      for (int T = 0; T < NSTEP - 1; T++) {
        const uint32_t ph = T & 1;
        mbar_wait(BAR(B_SS), ph);
        const uint32_t cq = clk();
        const uint32_t g0 = (uint32_t)gtime64(); uint32_t g1, ce;
        do { g1 = (uint32_t)gtime64(); ce = clk(); } while (g1 == g0);
        const uint32_t tn = g1 * 8 - (((ce - cq) * 37u) >> 3), id = E * 128u + T;
        if (lane < 4) st_rlx64(&G.sync[ph][cta][lane], tn, id);
        if (lane < 3) mbar_expect(BAR(B_LAND + lane), lane ? 9216 : 6144);
        if (T == 0) { s1 += uni(lds32(sb + M_NEAR + (2 + c) * 4)) * 4096; s2 += uni(lds32(sb + M_NEAR + (5 + c) * 4)) * 4096; }
        wait_until(cq + SDLY_);
        int guard = 0; unsigned long long v0, v1, v2;
        for (;;) {
          v0 = ld_rlxu64(G.sync[ph][lane]); v1 = ld_rlxu64(G.sync[ph][lane + 32]); v2 = ld_rlxu64(G.sync[ph][lane + 64]);
          if (__all_sync(~0u, (uint32_t)(v0 >> 32) == id && (uint32_t)(v1 >> 32) == id && (uint32_t)(v2 >> 32) == id)) break;
          if (++guard > (1 << 22)) TRAP();
        }
        const bool cnd = (int)uni(lds32(sb + M_CAND + (T & 3) * 4)) >= 0;
        const int dl = __reduce_max_sync(~0u, max(max((int)((uint32_t)v0 - tn), (int)((uint32_t)v1 - tn)), (int)((uint32_t)v2 - tn)));
        const uint32_t base = uni(cq + ((min(dl, 8 * 4096) * 7) >> 5)) + (T == 0 ? SLOW0_ : T == 1 ? SLOW1_ : 0) +
                              (cnd ? CDLY_ : 0) - (T + 2 < NSEG ? 0 : BOFF_);
        const int dur = (int)(base - prev);
        if (!cnd && !cprev) {
          yadj = T > 2 && dur > dmin + 700 ? min(yadj + YUP_, 400) : max(yadj - YDN_, 0);
          if (T > 1) dmin = min(dmin + 20, dur);
        }
        prev = base; cprev = cnd;
        if (lane == 0) { sts32(sb + M_BASE + ph * 4, base); sts32(sb + M_BAS2 + ph * 4, base + yadj); mbar_arrive(BAR(B_SYNC)); }
        CSTAMP(0, base); CSTAMP(1, clk());
        const uint32_t ts = base + YDLY_ + yadj - (T + 2 >= LAG && T + 2 < NSEG ? 0 : YOFF_);
        const uint8_t* const t0 = memg + uni(lds32(sb + M_NEAR)) * 4096, * const t1 = memg + 8192 + uni(lds32(sb + M_NEAR + 4)) * 4096;
        wait_until(ts);
        e_g2s(sb + M_MEM, t0, 3072, BAR(B_LAND)); e_g2s(sb + M_MEM + 3072, t1, 3072, BAR(B_LAND));
        CSTAMP(2, clk());
        spin_until(ts + Y1_);
        e_mc(sb + M_MEM + (2 + c) * 3072, memg + s1, 3072, BAR(B_LAND + 1), 7);
        CSTAMP(3, clk());
        spin_until(ts + Y2_);
        e_mc(sb + M_MEM + (5 + c) * 3072, memg + s2, 3072, BAR(B_LAND + 2), 7);
        CSTAMP(4, clk());
      }
    } else if (w == 1) {
#pragma unroll 1
      for (int T = 0; T < NSTEP; T++) {
        const uint32_t ph = T & 1;
        const int s = c == 0 ? T : T - LAG;
        const bool act = s >= 0 && s < NSEG;
        mbar_wait(BAR(B_OST), ph);
        if (cta == 0) TSTAMP(2, T, 0);
        fence_async_smem();
        if (T < NSTEP - 1) wait_until(uni(lds32(sb + M_BAS2 + ph * 4)) + ODLY_);
        STAMP(22);
        if (act) paced_st(o_slot(c, s, head), sb + M_OST, OGAP_);
        if (c == 2 && T < NSTEP - 1) {
          mbar_wait(BAR(B_STG1), ph ^ 1);
          mbar_wait(BAR(B_VFREE), ph);
          STAMP(23);
          e_mc(sb + M_V + 2048, G.mix[cta % 6].tok[cta / 6][ph ^ 1] + 8192, 8192, BAR(B_V), 6);
          e_mc(sb + M_V + 2048, G.mix[cta % 6].tok[cta / 6][ph ^ 1], 8192, BAR(B_V), 1);
        }
        bulk_wait();
        __syncwarp();
        e_arrive(BAR(B_OFREE));
        if (cta == 0) TSTAMP(2, T, 1);
        if (act && lane < 8) st_rel(&G.f_o[T][head >> 2][c * 4 + (head & 3)][lane], E);
        __syncwarp();
        if (cta == 0) TSTAMP(2, T, 2);
      }
    } else if (w == 2) {
      unsigned long long run = 0;
      static_assert(LAG >= 2, "config");
      constexpr uint32_t NA = EA / 4 * 4096;
      e_expect(BAR(B_QK), c < 2 ? 2048 : 4096); e_expect(BAR(B_V), c == 0 ? 10240 : c == 1 ? 2048 : 0);
      e_expect(BAR(B_TOK), c == 0 ? 16384 : 0); e_expect(BAR(B_OM), 4096);
      e_expect(BAR(B_HA), NA); e_expect(BAR(B_HB), 65536 - NA);
      wait_eq(&G.f_h1[c == 1 ? 0 : 1], E); fence_async_glob();
      {
        const uint32_t o0 = c == 0 ? NA : 0, o1 = c == 2 ? NA : 32768;
        e_mc(sb + M_H + (c == 1 ? 32768 : 0) + o0, G.seg[c == 1 ? 0 : 1].h[0] + o0, o1 - o0, BAR(c == 2 ? B_HA : B_HB), 7);
      }
      TSTAMP(14, cta, 3);
      if (c == 2) wait_eq(&G.f_h1[2], E);
      mbar_wait(BAR(B_HAE), 1);
      e_expect(BAR(B_HA), NA);
      if (c == 2) { fence_async_glob(); e_mc(sb + M_H, G.seg[2].h[0], NA, BAR(B_HA), 7); }
      int cprev = -1;
#pragma unroll 1
      for (int T = 0; T < NSTEP - 1; T++) {
        const int s1 = T + 2, s2 = T + 2 - LAG;
        const uint32_t ph = T & 1;
        const bool l1 = s1 < NSEG, l2 = s2 >= 0 && s2 < NSEG, la = s1 + 1 < NSEG;
        const bool mine = c == 0 ? l1 : c == 1 ? l2 : la;
        const uint32_t* fl = c != 1 ? &G.f_h1[min(s1 + (c >> 1), NSEG - 1)] : (const uint32_t*)G.f_h2[max(s2, 0)][lane & 3] + 1;
        const uint32_t want = E & 0x1FFFFFu, sh = c != 1 ? 0 : 11;
        mbar_wait(BAR(B_HBE), ph ^ 1);
        const bool early = __all_sync(~0u, ((ld_acq(fl) >> sh) & 0x1FFFFFu) == want);
        mbar_wait(BAR(B_LAND + 2), ph);
        STAMP(16);
        e_expect(BAR(B_HB), (l1 ? 32768 - NA : 0) + (l2 ? 32768 : 0));
        if (mine) {
          if (!early) {
            int guard = 0;
            while (!__all_sync(~0u, ((ld_acq(fl) >> sh) & 0x1FFFFFu) == want)) { __nanosleep(32); if (++guard > (1 << 22)) TRAP(); }
          }
          fence_async_glob();
          if (c == 1) { mbar_wait(BAR(B_QK), ph); spin_until(clk32() + HDLY_); }
          if (c < 2) paced_h(sb + M_H + c * 32768, G.seg[c ? s2 : s1].h[c], c ? 0 : NA, 32768, 4096, BAR(B_HB), HGAP_);
        }
        int cd = -1;
        if (l2) { cd = route_step(s2, E, lane, run); if (cta == 0) TSTAMP(5, s2, 0); }
        if (lane == 0) sts32(sb + M_CAND + ((T + 2) & 3) * 4, (uint32_t)cd);
        __syncwarp();
        STAMP(17);
        mbar_wait(BAR(B_HAE), ph);
        e_expect(BAR(B_HA), la ? NA : 0);
        if (c == 2 && la) {
          spin_until(clk32() + ADLY_);
          STAMP(18);
          paced_h(sb + M_H, G.seg[s1 + 1].h[0], 0, NA, 4096, BAR(B_HA), AGAP_);
        }
        mbar_wait(BAR(B_OST), ph);
        e_expect(BAR(B_QK), c < 2 ? 2048 : cprev >= 0 ? 8192 : 4096);
        e_expect(BAR(B_V), c < 2 ? 10240 : 8192);
        e_expect(BAR(B_TOK), c == 0 ? 8192 : 16384);
        e_expect(BAR(B_OM), 4096);
        cprev = cd;
      }
    } else {
      const uint32_t mytok = sb + M_Q + c * 12288 + 2048, tb = BAR(c < 2 ? B_TOK : B_V);
      mbar_wait(BAR(B_STG1), 0);
      fence_async_smem();
      if (c) e_s2g(G.mix[cta % 6].tok[cta / 6][1], sb + M_TST, 8192);
#pragma unroll 1
      for (int T = 0; T < NSTEP - 1; T++) {
        const uint32_t ph = T & 1;
        uint8_t* const tok = G.mix[cta % 6].tok[cta / 6][ph ^ 1];
        mbar_wait(BAR(B_STG), ph ^ 1);
        fence_async_smem();
        if (cta == 0 && (T == 0 || T == NSEG || T == NSTEP - 2)) GSTAMP(0, T == 0 ? 2 : T == NSEG ? 3 : 4);
        if (T > 0 && TQ_) mbar_wait(BAR(B_QK), ph);
        STAMP(20);
        paced_st(tok + 8192, sb + M_TST + 8192, TGAP_);
        bulk_wait();
        __syncwarp();
        e_arrive(BAR(B_TFREE));
        if (T == 0) e_mc(mytok, tok + 8192, 8192, tb, 1);
        STAMP(21);
        if (c < 2) {
          mbar_wait(BAR(B_KFREE), ph);
          spin_until(clk32() + KDLY_);
          STAMP(23);
          if (c) e_mc(mytok, tok, 8192, tb, 1);
          e_mc(mytok, tok + 8192, 8192, tb, 6);
        }
        mbar_wait(BAR(B_STG1), ph ^ 1);
        fence_async_smem();
        wait_until(uni(lds32(sb + M_BAS2 + ph * 4)) + TDLY_);
        if (c) paced_st(G.mix[cta % 6].tok[cta / 6][ph], sb + M_TST, T1GAP_);
        STAMP(24);
      }
      bulk_wait();
    }
    __syncwarp();
    cluster_sync();
  }
}

constexpr uint32_t A_RING = 0;
constexpr int A_NST = 6;
constexpr uint32_t A_STG = A_RING + A_NST * 8192;
constexpr uint32_t A_WD = A_STG + 8192;
constexpr uint32_t A_WG = A_WD + 57344;
constexpr uint32_t A_WU = A_WG + 57344;
constexpr uint32_t A_XN = A_WU + 57344;
constexpr uint32_t A_BAR = A_XN + 2048;
constexpr uint32_t A_TOTAL = A_BAR + 256;
static_assert(A_TOTAL <= 232448, "aux smem");

__device__ __forceinline__ uint32_t ptag(int s) { return ((s / PRING) & 1) ^ 1; }
static_assert((NSEG / PRING) % 2 == 0, "tags");
__device__ __forceinline__ void load_row(uint32_t* v, const void* row, int lane) {
  const uint4 a = __ldcg((const uint4*)row + lane), b = __ldcg((const uint4*)row + 32 + lane);
  v[0] = a.x; v[1] = a.y; v[2] = a.z; v[3] = a.w; v[4] = b.x; v[5] = b.y; v[6] = b.z; v[7] = b.w;
}
__device__ __forceinline__ void store_row(void* row, const uint32_t* v, int lane) {
  ((uint4*)row)[lane] = make_uint4(v[0], v[1], v[2], v[3]); ((uint4*)row)[32 + lane] = make_uint4(v[4], v[5], v[6], v[7]);
}
__device__ __forceinline__ void store_img(uint8_t* img, int r, const uint32_t* v, int lane) {
  uint8_t* b = img + (lane >> 3) * 4096 + (r >> 3) * 1024 + (r & 7) * 128 + (((lane ^ r) & 7) << 4);
  *(uint4*)b = make_uint4(v[0], v[1], v[2], v[3]);
  *(uint4*)(b + 16384) = make_uint4(v[4], v[5], v[6], v[7]);
}
template <int NT> __device__ __forceinline__ void ln_rows(const uint32_t (*v)[8], uint32_t (*y)[8]) {
  float c[NT], sm[NT], sq[NT];
#pragma unroll
  for (int k = 0; k < NT; k++) {
    c[k] = blo(__shfl_sync(~0u, v[k][0], 0));
    float s0 = 0.f, s1 = 0.f, q0 = 0.f, q1 = 0.f;
#pragma unroll
    for (int i = 0; i < 8; i++) { const float a = blo(v[k][i]) - c[k], b = bhi(v[k][i]) - c[k]; s0 += a; s1 += b; q0 = fmaf(a, a, q0); q1 = fmaf(b, b, q1); }
    sm[k] = s0 + s1; sq[k] = q0 + q1;
  }
#pragma unroll
  for (int o = 16; o > 0; o >>= 1)
#pragma unroll
    for (int k = 0; k < NT; k++) {
      sm[k] += __shfl_xor_sync(~0u, sm[k], o); sq[k] += __shfl_xor_sync(~0u, sq[k], o);
    }
#pragma unroll
  for (int k = 0; k < NT; k++) {
    const float dm = sm[k] * (1.f / 512.f), var = fmaxf(fmaf(-dm, dm, sq[k] * (1.f / 512.f)), 0.f);
    const float mb = rbf(c[k] + dm), inv = rcp(rbf(sqrt_fast(rbf(rbf(var) + 1e-5f))));
#pragma unroll
    for (int i = 0; i < 8; i++) { const uint32_t a = pack2(blo(v[k][i]) - mb, bhi(v[k][i]) - mb); y[k][i] = pack2(blo(a) * inv, bhi(a) * inv); }
  }
}
__device__ __forceinline__ void input_ln_pair(const bf16* x, int s, int pr, int lane) {
  uint32_t v[2][8], y[2][8];
  load_row(v[0], x + (size_t)(s * 32 + 2 * pr) * 512, lane); load_row(v[1], x + (size_t)(s * 32 + 2 * pr + 1) * 512, lane);
  ln_rows<2>(v, y);
  store_img(G.seg[s].h[0], 2 * pr, y[0], lane); store_img(G.seg[s].h[0], 2 * pr + 1, y[1], lane);
}
__device__ __forceinline__ float load_wr(uint32_t* wv, const bf16* wr, int lane) {
  load_row(wv, wr, lane);
  float wsum = 0.f;
#pragma unroll
  for (int i = 0; i < 8; i++) wsum += blo(wv[i]) + bhi(wv[i]);
#pragma unroll
  for (int o = 16; o > 0; o >>= 1) wsum += __shfl_xor_sync(~0u, wsum, o);
  return wsum;
}

template <bool FAST>
__device__ __forceinline__ unsigned long long token_post(int st, int tk, const bf16* res, bf16* dst, bf16* req, unsigned long long best,
                                                         const uint32_t* wv, float wsum, uint32_t E, int lane) {
  const int s = tk >> 5;
  uint32_t x[8];
  load_row(x, res, lane);
  {
    int guard = 0;
    while (__popc(__ballot_sync(~0u, ld_rlx(G.f_acc[st][s][lane]) == E)) < (FAST ? HINT_ : 32)) { __nanosleep(FAST ? 20 : 100); if (++guard > (1 << 22)) TRAP(); }
  }
  if (tk == s * 32 && st == 0 && lane == 0) TSTAMP(4, s, 0);
  {
    const uint8_t* pp = pp_slot(st, s) + (lane >> 4) * 8192 + (tk & 31) * 256 + (((lane & 15) ^ (tk & 7)) << 4);
    const uint32_t tag = ptag(s);
    uint4 q[8][2];
#define PLD(k, h) q[k][h] = ld_rlx128<(k) * 32768 + (h) * 16384>(pp)
#define PLD8(h) PLD(0, h); PLD(1, h); PLD(2, h); PLD(3, h); PLD(4, h); PLD(5, h); PLD(6, h); PLD(7, h)
#define PBAD(h) __any_sync(~0u, (or3(xo2(q[0][h].x, q[1][h].x, tag), xo2(q[2][h].x, q[3][h].x, tag), xo2(q[4][h].x, q[5][h].x, tag)) | xo2(q[6][h].x, q[7][h].x, tag)) & ~lane & (PST_ == 8192 ? 1u : 0u))
#define PSUM(f, h, m) (((f(q[0][h].m) + f(q[1][h].m)) + (f(q[2][h].m) + f(q[3][h].m))) + ((f(q[4][h].m) + f(q[5][h].m)) + (f(q[6][h].m) + f(q[7][h].m))))
    const uint32_t eye = (lane >> 2) == 2 * (lane & 3) ? 0x3f80u : (lane >> 2) == 2 * (lane & 3) + 1 ? 0x3f800000u : 0u;
    auto padd = [&](int h) {
      if (FAST) {
        float u[4] = {0.f, 0.f, 0.f, 0.f}, v[4] = {0.f, 0.f, 0.f, 0.f};
#pragma unroll
        for (int k = 0; k < 8; k++) { hmma8(u, q[k][h].x, q[k][h].y, eye); hmma8(v, q[k][h].z, q[k][h].w, eye); }
        x[4 * h] = add2(x[4 * h], pack2(u[0], u[1])); x[4 * h + 1] = add2(x[4 * h + 1], pack2(u[2], u[3]));
        x[4 * h + 2] = add2(x[4 * h + 2], pack2(v[0], v[1])); x[4 * h + 3] = add2(x[4 * h + 3], pack2(v[2], v[3]));
      } else {
        x[4 * h] = add2(x[4 * h], pack2(PSUM(blo, h, x), PSUM(bhi, h, x))); x[4 * h + 1] = add2(x[4 * h + 1], pack2(PSUM(blo, h, y), PSUM(bhi, h, y)));
        x[4 * h + 2] = add2(x[4 * h + 2], pack2(PSUM(blo, h, z), PSUM(bhi, h, z))); x[4 * h + 3] = add2(x[4 * h + 3], pack2(PSUM(blo, h, w), PSUM(bhi, h, w)));
      }
    };
    int guard = 0;
    PLD8(0);
    if (FAST) { PLD8(1); }
    while (PBAD(0)) { if (++guard > (1 << 20)) TRAP(); PLD8(0); }
    padd(0);
    if (!FAST) { PLD8(1); }
    while (PBAD(1)) { if (++guard > (1 << 20)) TRAP(); PLD8(1); }
    padd(1);
  }
  const float c = blo(__shfl_sync(~0u, x[0], 0));
  float s0 = 0.f, s1 = 0.f, q0 = 0.f, q1 = 0.f, r0 = 0.f, r1 = 0.f;
#pragma unroll
  for (int i = 0; i < 8; i++) {
    const float a = blo(x[i]) - c, b = bhi(x[i]) - c;
    s0 += a; s1 += b; q0 = fmaf(a, a, q0); q1 = fmaf(b, b, q1); r0 = fmaf(a, blo(wv[i]), r0); r1 = fmaf(b, bhi(wv[i]), r1);
  }
  s0 += s1; q0 += q1; r0 += r1;
#pragma unroll
  for (int o = 16; o > 0; o >>= 1) { s0 += __shfl_xor_sync(~0u, s0, o); q0 += __shfl_xor_sync(~0u, q0, o); r0 += __shfl_xor_sync(~0u, r0, o); }
  const float dm = s0 * (1.f / 512.f), m = c + dm, var = fmaxf(fmaf(-dm, dm, q0 * (1.f / 512.f)), 0.f);
  const float mb = rbf(m), inv = rcp(rbf(sqrt_fast(rbf(rbf(var) + 1e-5f))));
  const uint32_t nmb = pack2(-mb, -mb);
  const unsigned long long wd = rword(E, tk, fmaf(c - mb, wsum, r0) * inv);
  uint32_t xn[8], x2[8];
#pragma unroll
  for (int i = 0; i < 8; i++) { const uint32_t d = add2(x[i], nmb); xn[i] = pack2(blo(d) * inv, bhi(d) * inv); x2[i] = add2(x[i], xn[i]); }
  if (st == 0) {
    const float mb2 = rbf(fmaf(m - mb, inv, m)), inv2 = rcp(rbf(sqrt_fast(rbf(rbf(var * (1.f + inv) * (1.f + inv)) + 1e-5f))));
    const uint32_t nmb2 = pack2(-mb2, -mb2);
    uint32_t h[8];
#pragma unroll
    for (int i = 0; i < 8; i++) { const uint32_t d2 = add2(x2[i], nmb2); h[i] = pack2(blo(d2) * inv2, bhi(d2) * inv2); }
    store_img(G.seg[s].h[1], tk & 31, h, lane);
  }
  store_row(dst, x2, lane);
  if (wd > best && !(EXPQ_ & (st == 0 ? 1 : 2))) { store_row(req, xn, lane); store_row(req + 512, x, lane); }
  return wd;
}

__device__ __forceinline__ void ffn_slice(uint32_t sb, const bf16* xn, float* yacc, uint32_t* flag, uint32_t E, int t, bool urgent) {
  const int w = t >> 5, g = (t >> 2) & 7;
  if (t == 0 && urgent) sts32(sb + A_BAR + 160, 1);
  { const uint2 u = __ldcg((const uint2*)xn + t); asm volatile("st.shared.v2.u32 [%0], {%1,%2};" :: "r"(sb + A_XN + t * 8), "r"(u.x), "r"(u.y) : "memory"); }
  fence_async_smem();
  bar_sync(4, 128);
  float ga[4], ua[4];
  constexpr uint64_t da = mkdesc(A_WG, 896, 128, 0), db = mkdesc(A_XN, 16, 128, 0);
  wg_fence();
  wgmma_ss8<0, 1, 0>(ga, da, db); wgmma_ss8<0, 1, 0>(ua, da + (A_WU - A_WG) / 16, db);
#pragma unroll
  for (int ks = 1; ks < 32; ks++) { wgmma_ss8<1, 1, 0>(ga, da + ks * 112, db + ks * 2); wgmma_ss8<1, 1, 0>(ua, da + (A_WU - A_WG) / 16 + ks * 112, db + ks * 2); }
  wg_commit(); wg_wait<0>(); reg_fence(ga); reg_fence(ua);
  if ((t & 3) == 0) {
#pragma unroll
    for (int h = 0; h < 2; h++) {
      const float gs = rbf(ga[2 * h]), us = rbf(ua[2 * h]);
      const float v = 16 * w + 8 * h < 56 ? rbf(gs * rcp(1.f + __expf(-gs))) * us : 0.f;
      asm volatile("st.shared.u16 [%0], %1;" :: "r"(sb + A_XN + 1280 + (16 * w + 8 * h + g) * 2), "h"((unsigned short)pack2(v, 0.f)) : "memory");
    }
  }
  fence_async_smem();
  bar_sync(4, 128);
#pragma unroll 1
  for (int j = 0; j < 2; j++) {
    float y[4][4];
    const uint64_t dd = mkdesc(A_WD, 8192, 128, 0) + (uint64_t)(j * 256);
    wg_fence();
#pragma unroll
    for (int m = 0; m < 4; m++) {
      wgmma_ss8<0, 1, 0>(y[m], dd + m * 64, mkdesc(A_XN + 1280, 16, 128, 0));
#pragma unroll
      for (int ks = 1; ks < 4; ks++) wgmma_ss8<1, 1, 0>(y[m], dd + m * 64 + ks * 1024, mkdesc(A_XN + 1280 + ks * 32, 16, 128, 0));
    }
    wg_commit(); wg_wait<0>();
#pragma unroll
    for (int m = 0; m < 4; m++) {
      reg_fence(y[m]);
      if ((t & 3) == 0) { float* o = yacc + j * 256 + m * 64 + 16 * w + g; o[0] = y[m][0]; o[8] = y[m][2]; }
    }
  }
  bar_sync(4, 128);
  if (t < 8) { sts32(sb + A_BAR + 160, 0); st_rel(flag + t, E); }
  __syncwarp();
}

__device__ __forceinline__ void ffn_gather(uint32_t sb, int q, int j, uint32_t E, int lane) {
  wait_all(G.f_y[q][4 * j + (lane & 3)], E);
  float4 y[4][4];
#pragma unroll
  for (int k = 0; k < 4; k++)
#pragma unroll
    for (int i = 0; i < 4; i++) y[k][i] = __ldcg((const float4*)G.y[q & 7][4 * j + k] + i * 32 + lane);
#pragma unroll
  for (int i = 0; i < 4; i++)
    sts128f(sb + 1024 + j * 2048 + i * 512 + lane * 16, (y[0][i].x + y[1][i].x) + (y[2][i].x + y[3][i].x), (y[0][i].y + y[1][i].y) + (y[2][i].y + y[3][i].y),
            (y[0][i].z + y[1][i].z) + (y[2][i].z + y[3][i].z), (y[0][i].w + y[1][i].w) + (y[2][i].w + y[3][i].w));
  bar_sync(9, 256);
}
__device__ __forceinline__ void ffn_finish(uint32_t sb, int q, const bf16* req, float r, uint32_t E, int lane, uint32_t* v) {
  if (lane == 0) sts32(sb + 16, q);
  bar_sync(8, 256);
  uint32_t xn[8];
  load_row(xn, req, lane); load_row(v, req + 512, lane);
  const float rs = rbf(1.f / (1.f + __expf(-rbf(r))));
  ffn_gather(sb, q, 7, E, lane);
#pragma unroll
  for (int i = 0; i < 4; i++) {
    float y[4] = {0.f, 0.f, 0.f, 0.f};
#pragma unroll
    for (int j = 0; j < 8; j++) {
      const uint4 u = lds128(sb + 1024 + j * 2048 + (i >> 1) * 1024 + lane * 32 + (i & 1) * 16);
      y[0] += __uint_as_float(u.x); y[1] += __uint_as_float(u.y); y[2] += __uint_as_float(u.z); y[3] += __uint_as_float(u.w);
    }
    v[2 * i] = add2(v[2 * i], add2(xn[2 * i], pack2(rbf(y[0]) * rs, rbf(y[1]) * rs)));
    v[2 * i + 1] = add2(v[2 * i + 1], add2(xn[2 * i + 1], pack2(rbf(y[2]) * rs, rbf(y[3]) * rs)));
  }
}

__global__ void __launch_bounds__(512, 1) aux_kernel(Params p) {
  extern __shared__ __align__(1024) uint8_t sm[];
  const uint32_t sb = smem_u32(sm);
  if ((sb & 0xFFFFFFu) != SBASE) TRAP();
  const int warp = __shfl_sync(~0u, threadIdx.x >> 5, 0);
  const int cta = blockIdx.x;
  const uint32_t E = __shfl_sync(~0u, *(volatile uint32_t*)&g_epoch + 1, 0);
  const uint32_t bars = sb + A_BAR;

  if (cta < 32) {
    const int cg = cta & 3, kg = cta >> 2;
    if (threadIdx.x == 0) {
      for (int i = 0; i < A_NST; i++) { mbar_init(bars + 8 * i, 1); mbar_init(bars + 64 + 8 * i, 2); }
      mbar_init(bars + 128, 8); mbar_init(bars + 136, 8); mbar_init(bars + 144, 1);
      sts32(bars + 160, 0);
      asm volatile("fence.mbarrier_init.release.cluster;" ::: "memory");
    }
    if (warp < 8) {
      asm volatile("setmaxnreg.inc.sync.aligned.u32 176;");
      const int tid = fresh_tid(), lane = tid & 31;
      uint32_t W[32][4];
      bar_arrive(3, 384);
      stage_weights(sb + A_WD, p.wo + (size_t)kg * 512 * 512 + cg * 128, 512, tid, 256);
      cp_async_wait();
      bar_sync(1, 256);
      load_frags(W, sb + A_WD, warp >> 2, warp & 3, lane);
      PIN(W[31][3]);
      bar_sync(1, 256);
      bar_arrive(2, 384);
      const uint32_t so = sb + A_STG + ((lane >> 4) * 8 + (lane & 7)) * 256 + (((warp * 2 + ((lane >> 3) & 1)) ^ (lane & 7)) << 4);
      const uint32_t tm = lane < 4 ? 0x00010001u : 0u;
      int stage = 0; uint32_t ph = 0, job = 0;
#pragma unroll 1
      for (int T = 0; T < NSTEP; T++) {
#pragma unroll 1
        for (int k = 0; k < 3; k++) {
          const int st = k == 0 ? 0 : 3 - k, s = st == 0 ? T : T - LAG;
          if (s < 0 || s >= NSEG) continue;
          float d[16];
#pragma unroll
          for (int hh = 0; hh < 4; hh++) {
            mbar_wait(bars + 8 * stage, ph);
            while (uni(lds32(bars + 160))) __nanosleep(100);
            const uint64_t db = mkdesc(A_RING, 512, 128, 0) + (uint64_t)(stage * 512);
            wg_fence();
            if (hh == 0) wgmma_rs32<0, 0>(d, W[0], db); else wgmma_rs32<1, 0>(d, W[hh * 8], db);
#pragma unroll
            for (int ks = 1; ks < 8; ks++) wgmma_rs32<1, 0>(d, W[hh * 8 + ks], db + ks * 64);
            wg_commit();
            if (hh > 0) { wg_wait<1>(); if ((tid & 127) == 0) mbar_arrive(bars + 64 + 8 * (stage == 0 ? A_NST - 1 : stage - 1)); }
            if (++stage == A_NST) { stage = 0; ph ^= 1; }
          }
          mbar_wait(bars + 144, (job & 1) ^ 1);
          wg_wait<0>(); reg_fence(d);
          if ((tid & 127) == 0) mbar_arrive(bars + 64 + 8 * (stage == 0 ? A_NST - 1 : stage - 1));
          if (cta == 0 && tid == 0) TSTAMP(6, T, k);
          const uint32_t tv = tm * ptag(s);
#define TG(i) ((pack2(d[2 * (i)], d[2 * (i) + 1]) & ~tm) | tv)
          stmatrix4_t(so, TG(0), pack2(d[2], d[3]), TG(2), pack2(d[6], d[7]));
          stmatrix4_t(so + 4096, TG(4), pack2(d[10], d[11]), TG(6), pack2(d[14], d[15]));
          fence_async_smem();
          __syncwarp();
          if (lane == 0) mbar_arrive(bars + 128 + 8 * (job & 1));
          job++;
        }
      }
    } else if (warp < 12) {
      asm volatile("setmaxnreg.dec.sync.aligned.u32 120;");
      const int tid = fresh_tid(), lane = tid & 31;
      const int w = warp - 8, t = tid - 256;
      uint32_t wv[8];
      const float wsum = load_wr(wv, p.wr, lane);
#pragma unroll 1
      for (int s = cta + 4; s < NSEG; s += 32) {
#pragma unroll 1
        for (int pr = w; pr < 16; pr += 4) input_ln_pair(p.x, s, pr, lane);
        bar_sync(4, 128);
        if (t == 0) st_rel(&G.f_h1[s], E);
      }
      bar_sync(2, 384);
      { int guard = 0; while (ld_rlx(&G.f_loaded[cta]) != E) { __nanosleep(200); if (++guard > (1 << 22)) TRAP(); } }
#pragma unroll 1
      for (int i = t; i < 512 * 7; i += 128) {
        const int k = i / 7, pc = i % 7;
        cp_async16(sb + A_WG + (k >> 3) * 896 + pc * 128 + (k & 7) * 16, p.wg + (size_t)k * 1792 + cta * 56 + pc * 8);
        cp_async16(sb + A_WU + (k >> 3) * 896 + pc * 128 + (k & 7) * 16, p.wu + (size_t)k * 1792 + cta * 56 + pc * 8);
        cp_async16(sb + A_WD + (i >> 9) * 8192 + (i & 63) * 128 + ((i >> 6) & 7) * 16, p.wd + (size_t)cta * 56 * 512 + i * 8);
        if (FPACE_ && (i >> 7) % FPACE_ == FPACE_ - 1) cp_async_wait();
      }
      cp_async_wait();
      fence_async_smem();
      bar_sync(4, 128);
      const int tj = (cta * 4 + w) & 31, st = 1 + ((cta >> 3) & 1), sq = cta >> 4;
      unsigned long long run = 0, run2 = 0, best = 0, hist = 0;
      uint32_t open = 0;
#pragma unroll 1
      for (int i = 0; i <= NSTEP; i++) {
        int tok = -1; const bf16* req = nullptr;
        if (i < NSEG) {
          const int cd = (int)uni(route_step(i, E, lane, run));
          run = __shfl_sync(~0u, run, 0);
          hist = hist << 8 | (uint32_t)(cd + 1);
          if (cd >= 0) { tok = rtok(run); req = G.seg[tok >> 5].req1[tok & 31][0]; }
        } else {
          const unsigned long long m = wait_words(G.f_l2[i - NSEG], E);
          const unsigned long long n = ld_rlxu64(G.f_l2[min(i - NSEG + 1 + (lane & 7), LAG)]);
          const bool over = bar_or(4, 128, rfresh(n, E) && n != m);
          if (m != run2 && !over) { run2 = m; tok = rtok(m); req = G.req2[(tok >> 5) < (rtok(run) >> 5) ? 0 : 1][tok][0]; }
        }
        tok = __shfl_sync(~0u, tok, 0);
        if (tok >= 0) {
          if (cta == 0 && t == 0) TSTAMP(8, i & 127, 0);
          ffn_slice(sb, req, G.y[i & 7][cta], G.f_y[i][cta], E, t, i < NSEG);
          if (cta == 0 && t == 0) TSTAMP(8, i & 127, 1);
        }
        const int s = i - LAG;
        if (s < 0 || i >= NSEG) continue;
        const int cd = (int)((hist >> (8 * LAG)) & 255) - 1;
        if (cd >= 0 && st == 2) best = 0;
        const int ts = rtok(run) >> 5;
        if ((s & 1) == sq) {
          const int tk = s * 32 + tj;
          unsigned long long wd = (unsigned long long)E << 43;
          if (st == 1 ? s < ts || i < NSEG - 1 : s >= ts) {
            if (st == 2 && cd == tj) wait_eq(&G.f_hc[s], E);
            wd = token_post<false>(st, tk, st == 2 && cd == tj ? G.x2c[s] : G.seg[tk >> 5].x2[tk & 31],
                                   st == 2 || s < ts ? p.out + (size_t)tk * 512 : G.seg[s].n[tj], G.req2[st - 1][tk][0], best, wv, wsum, E, lane);
            best = max(best, wd);
            if (st == 1 && s >= ts) open |= 1u << (s >> 1);
          }
          __syncwarp();
          if (lane < 4) st_rel64(&G.f_w2[st - 1][s][tj][lane], wd);
          __syncwarp();
        }
        if (st == 1) {
          if (i == NSEG - 1 && t == 0 && cta == 0) GSTAMP(1, 0);
#pragma unroll 1
          for (int n = i == NSEG - 1 ? 32 : 2; n > 0 && open; n--) {
            const int s0 = 2 * (__ffs(open) - 1) + sq;
            if (s0 >= ts) break;
            open &= open - 1;
            uint32_t v[8];
            load_row(v, G.seg[s0].n[tj], lane);
            wait_words(G.f_w2[1][s0][tj], E);
            store_row(p.out + (size_t)(s0 * 32 + tj) * 512, v, lane);
          }
          if (i == NSEG - 1) {
            __syncwarp();
            if (lane == 0) st_rel(&G.f_cp[sq * 32 + tj], E);
            if (t == 0 && cta == 0) GSTAMP(1, 3);
          }
        }
      }
    } else {
      asm volatile("setmaxnreg.dec.sync.aligned.u32 40;");
      const int tid = fresh_tid(), lane = tid & 31;
      const int w = warp - 12;
      bar_sync(3, 384);
      if (w == 0) {
        int stage = 0; uint32_t ph = 1;
#pragma unroll 1
        for (int T = 0; T < NSTEP; T++) {
#pragma unroll 1
          for (int k = 0; k < 3; k++) {
            const int st = k == 0 ? 0 : 3 - k, s = st == 0 ? T : T - LAG;
            if (s < 0 || s >= NSEG) continue;
            const uint32_t* fl = G.f_o[T][kg][st * 4 + (lane & 3)];
            uint32_t ready = 0; int guard = 0;
#pragma unroll 1
            for (int hh = 0; hh < 4; hh++) {
              while (!((ready >> hh) & 1)) {
                ready = __ballot_sync(~0u, ld_rlx(fl) == E);
                if (++guard > (1 << 23)) TRAP();
              }
              fence_async_glob();
              mbar_wait(bars + 64 + 8 * stage, ph);
              e_expect(bars + 8 * stage, OLOAD_);
              e_g2s(sb + A_RING + stage * 8192, o_slot(st, s, kg * 4 + hh), OLOAD_, bars + 8 * stage);
              if (++stage == A_NST) { stage = 0; ph ^= 1; }
            }
          }
          if (cta == 0 && lane == 0) TSTAMP(3, T, 0);
        }
      } else if (w < 3) {
        uint32_t job = 0;
#pragma unroll 1
        for (int T = 0; T < NSTEP; T++) {
#pragma unroll 1
          for (int k = 0; k < 3; k++) {
            const int st = k == 0 ? 0 : 3 - k, s = st == 0 ? T : T - LAG;
            if (s < 0 || s >= NSEG) continue;
            if ((job++ & 1) != w - 1) continue;
            if (s >= PRING) wait_words(st == 0 ? G.f_h2[s - PRING][lane & 3] : G.f_w2[st - 1][s - PRING][lane], E);
            mbar_wait(bars + 128 + 8 * (w - 1), ((job - 1) >> 1) & 1);
            if (cta == 0 && st == 0) TSTAMP(7, s, 0);
            e_s2g(pp_slot(st, s) + cta * 8192, sb + A_STG, PST_);
            if (lane < 8) st_rlx(&G.f_acc[st][s][cta][lane], E);
            asm volatile("cp.async.bulk.commit_group;\n cp.async.bulk.wait_group.read 0;" ::: "memory");
            __syncwarp();
            e_arrive(bars + 144);
            __syncwarp();
            if (cta == 0 && st == 0) TSTAMP(7, s, 1);
          }
        }
        bulk_wait();
      }
    }
  } else {
    const int tid = fresh_tid(), lane = tid & 31;
    const int qd = cta - 32;
    input_ln_pair(p.x, qd, warp, lane);
    bar_sync(6, 512);
    if (tid == 0) st_rel(&G.f_h1[qd], E);
    volatile int* bc = (volatile int*)sm;
    if (warp == 15) {
      unsigned long long run = 0;
      unsigned long long b2[2][2] = {{0, 0}, {0, 0}};
      auto track = [&](int s) {
#pragma unroll
        for (int k = 0; k < 2; k++) {
          const unsigned long long m = warp_max<16>(wait_words(G.f_w2[k][s][lane], E));
          if (lane == (s & 31)) { if (s < 32) b2[k][0] = m; else b2[k][1] = m; }
        }
      };
#pragma unroll 1
      for (int s = 0; s < NSEG; s++) {
        const int cd = route_step(s, E, lane, run);
        if (cd >= 0 && qd == (s & 1)) {
          uint32_t v[1][8], h[1][8];
          ffn_finish(sb, s, G.seg[s].req1[cd][0], rscore(run), E, lane, v[0]);
          if (lane == 0) TSTAMP(8, s, 2);
          ln_rows<1>(v, h);
#pragma unroll
          for (int i = 0; i < 8; i++) st_rlx64(&G.hc[s][(i >> 2) * 128 + 4 * lane + (i & 3)], h[0][i], E);
          if (lane == 0) TSTAMP(8, s, 3);
          store_row(G.x2c[s], v[0], lane);
          __syncwarp();
          if (lane == 0) st_rel(&G.f_hc[s], E);
        }
        if (qd == 2 && s > LAG) track(s - LAG - 1);
      }
      wait_eq(&G.f_hc[rtok(run) >> 5], E);
      if (lane == 0) *bc = rtok(run);
      bar_sync(7, 288);
      if (qd == 2) {
        uint32_t v[8];
        const int ts = rtok(run) >> 5;
        track(NSEG - LAG - 1);
        run = 0;
        int kl = 0;
#pragma unroll 1
        for (int k = 0; k <= LAG; k++) {
          const int s = NSEG - LAG - 1 + k;
          const unsigned long long m = warp_max<16>(k == 0 ? max(lane < ts ? b2[0][0] : b2[1][0], lane + 32 < ts ? b2[0][1] : b2[1][1])
                                                           : wait_words(G.f_w2[s < ts ? 0 : 1][s][lane], E));
          const bool lead = m > run;
          if (lead) { run = m; __threadfence(); }
          if (lane < 4) st_rlx64(&G.f_l2[k][lane], (uint32_t)run, (uint32_t)(run >> 32));
          if (lead) kl = k;
          if (k == LAG - 1) { wait_all(&G.f_cp[lane], E); wait_all(&G.f_cp[32 + lane], E); }
          if (k == LAG - 1 || (k == LAG && lead)) ffn_finish(sb, NSEG + kl, G.req2[(rtok(run) >> 5) < ts ? 0 : 1][rtok(run)][0], rscore(run), E, lane, v);
        }
        if (lane == 0) GSTAMP(1, 1);
        store_row(p.out + (size_t)rtok(run) * 512, v, lane);
        if (lane == 0) GSTAMP(1, 2);
      }
      if (lane == 0) sts32(sb + 16, (uint32_t)-1);
      bar_sync(8, 256);
      if (qd == 2) {
        asm volatile("griddepcontrol.wait;" ::: "memory");
        if (lane == 0) *(volatile uint32_t*)&g_epoch = E;
      }
    } else if (warp >= 8) {
#pragma unroll 1
      for (;;) {
        bar_sync(8, 256);
        const int q = (int)uni(lds32(sb + 16));
        if (q < 0) break;
        ffn_gather(sb, q, warp - 8, E, lane);
      }
    } else {
      uint32_t wv[8];
      const float wsum = load_wr(wv, p.wr, lane);
      unsigned long long best = 0;
      int ttok = 0;
#pragma unroll 1
      for (int i = 0; i < NSTEP; i++) {
        const bool last = i >= NSEG;
        if (i == NSEG) { bar_sync(7, 288); ttok = *bc; best = 0; }
        const int s = last ? i - LAG : i, st = !last ? 0 : s < (ttok >> 5) ? 1 : 2;
        const int tk = s * 32 + qd * 8 + warp;
        const unsigned long long wd = token_post<true>(st, tk, !last ? p.x + (size_t)tk * 512 : tk == ttok ? G.x2c[s] : G.seg[tk >> 5].x2[tk & 31],
                                                 last ? p.out + (size_t)tk * 512 : G.seg[s].x2[tk & 31], last ? G.req2[st - 1][tk][0] : G.seg[s].req1[tk & 31][0], best, wv, wsum, E, lane);
        best = max(best, wd);
        volatile unsigned long long* ws = (volatile unsigned long long*)(sm + 64) + (i & 1) * 8;
        if (lane == 0) ws[warp] = wd;
        const unsigned long long lead = i == NSTEP - 1 ? ld_rlxu64(G.f_l2[LAG - 1]) : 0;
        bar_sync(5, 256);
        if (warp == 0) {
          if (qd == 0 && lane == 0) TSTAMP(4, i, 1);
          if (!last) { const unsigned long long m = warp_max<4>(ws[lane & 7]); if (lane < 4) st_rel64(&G.f_h2[s][qd][lane], m); }
          else {
            const unsigned long long v = ws[lane >> 2];
            if (!__all_sync(~0u, rfresh(lead, E) && v < lead)) __threadfence();
            st_rlx64(&G.f_w2[st - 1][s][qd * 8 + (lane >> 2)][lane & 3], (uint32_t)v, (uint32_t)(v >> 32));
            asm volatile("st.relaxed.gpu.global.u64 [%0], %1;" :: "l"(&G.f_w2[2 - st][s][qd * 8 + (lane >> 2)][lane & 3]), "l"((unsigned long long)E << 43) : "memory");
          }
          if (qd == 0 && lane == 0) TSTAMP(4, i, 2);
        }
        __syncwarp();
      }
    }
  }
}

}

extern "C" void kernel_launch(void* const* d_in, const int* in_sizes, int n_in, void* d_out, int out_size) {
  (void)in_sizes; (void)n_in; (void)out_size;
  static bool init = false;
  if (!init) {
    cudaFuncSetAttribute(main_kernel, cudaFuncAttributeMaxDynamicSharedMemorySize, M_TOTAL);
    cudaFuncSetAttribute(aux_kernel, cudaFuncAttributeMaxDynamicSharedMemorySize, A_TOTAL);
    init = true;
  }
  Params p;
  p.x = (const bf16*)d_in[0]; p.mem0 = (const bf16*)d_in[1]; p.wq = (const bf16*)d_in[2]; p.wk = (const bf16*)d_in[3];
  p.wv = (const bf16*)d_in[4]; p.wo = (const bf16*)d_in[5]; p.wr = (const bf16*)d_in[8]; p.wg = (const bf16*)d_in[9];
  p.wu = (const bf16*)d_in[10]; p.wd = (const bf16*)d_in[11]; p.out = (bf16*)d_out; p.zero = 0; p.zero2 = 0;
  cudaStream_t st = cudaStreamPerThread;
  main_kernel<<<96, 512, M_TOTAL, st>>>(p);
  cudaLaunchConfig_t cfg = {};
  cfg.gridDim = dim3(36); cfg.blockDim = dim3(512); cfg.dynamicSmemBytes = A_TOTAL; cfg.stream = st;
  cudaLaunchAttribute at[1];
  at[0].id = cudaLaunchAttributeProgrammaticStreamSerialization; at[0].val.programmaticStreamSerializationAllowed = 1;
  cfg.attrs = at; cfg.numAttrs = 1;
  cudaLaunchKernelEx(&cfg, aux_kernel, p);
}
```

```cpp
#include <cuda_runtime.h>
#include <cuda_bf16.h>
#include <stdint.h>
#include <stddef.h>

namespace {

typedef __nv_bfloat16 bf16;

constexpr int NSEG = 64;
#define LAG_ 5
constexpr int LAG = LAG_;
constexpr int NSTEP = NSEG + LAG;
constexpr int ORING = 8, PRING = 4;
static_assert(LAG < 8, "rings");

#define E1_ 10
#define E3_ 10
constexpr int E1 = E1_, EA = E1_ + E3_;
static_assert(EA % 4 == 0 && EA < 32, "early part: whole 64-column chunks");
#define PAUSE_ 13
#define PAUS2_ 29
#define PST2_ 2
#define HAND_ 4
#define SALT_ 0
#define TP(i, v) (v)
#define XDLY_ TP(0, 2075)
#define YDLY_ TP(1, 3400)
#define X1_ TP(2, 100)
#define X2_ TP(3, 350)
#define Y1_ TP(4, 200)
#define Y2_ TP(5, 450)
#define HGAP_ TP(6, 50)
#define TGAP_ TP(7, 100)
#define ADLY_ TP(8, 600)
#define ODLY_ TP(9, 2800)
#define HDLY_ TP(11, 0)
#define TDLY_ TP(15, 4150)
#define SDLY_ TP(12, 800)
#define AGAP_ 100
#define BOFF_ TP(13, 200)
#define YOFF_ TP(16, 150)
#define YUP_ TP(20, 40)
#define YDN_ TP(21, 4)
#define T1GAP_ TP(22, 0)
#define OGAP_ TP(23, 0)
#define CDLY_ TP(17, 300)
#define SLOW0_ TP(18, 800)
#define SLOW1_ TP(19, 300)
#define KDLY_ TP(14, 300)
__device__ uint32_t g_epoch;
struct Seg {
  uint8_t h[2][32768];
  bf16 x2[32][512], n[32][512];
  bf16 req1[32][2][512];
};
struct Mix {
  uint8_t tok[16][2][16384];
  uint8_t o[4][32][8192];
  uint8_t pp[2][8 * 32768];
};
struct Scratch {
  uint8_t xch[96 * 16384 + 65536];
  unsigned long long f_h2[NSEG][4][4];
  unsigned long long f_l2[8][4];
  unsigned long long sync[2][96][4];
  uint32_t f_o[NSTEP][8][12][8];
  uint32_t f_y[NSTEP + 1][32][8], f_cp[64];
  uint32_t f_choice[96][2], f_loaded[32], f_h1[NSEG], f_hc[NSEG];
  uint8_t pad0[2097152 - (96 * 16384 + 65536 + NSEG * 128 + 256 + 6144 + NSTEP * 3072 + (NSTEP + 1) * 1024 + 256 + 768 + 128 + NSEG * 8)];
  Mix mix[6];
  uint32_t f_acc[3][NSEG][32][8];
  unsigned long long f_w2[2][NSEG][32][4];
  uint2 hc[NSEG][256];
  bf16 x2c[NSEG][512];
  float y[8][32][512];
  Seg seg[NSEG];
  bf16 req2[2][2048][2][512];
};
static_assert(sizeof(Mix) == 2097152 && offsetof(Scratch, mix) == 2097152 && offsetof(Scratch, seg) % 1024 == 0 && ORING == 8 && PRING == 4, "layout");
__device__ uint8_t g_raw[sizeof(Scratch) + 2097152];
__device__ __forceinline__ Scratch& scr() { return *(Scratch*)(((uintptr_t)g_raw + 2097151) & ~(uintptr_t)2097151); }
#define G scr()
__device__ __forceinline__ uint8_t* o_slot(int st, int s, int head) { const int j = st * 8 + (s & 7); return G.mix[j % 6].o[j / 6][head]; }
__device__ __forceinline__ uint8_t* pp_slot(int st, int s) { const int j = st * 4 + (s & 3); return G.mix[j % 6].pp[j / 6]; }

#define TRAP() __trap()
__device__ __forceinline__ uint32_t smem_u32(const void* p) { return (uint32_t)__cvta_generic_to_shared(p); }
__device__ __forceinline__ int fresh_tid() { const int t = threadIdx.x; return __shfl_sync(~0u, t, t & 31); }
__device__ __forceinline__ unsigned long long gtime64() { unsigned long long t; asm volatile("mov.u64 %0, %%globaltimer;" : "=l"(t) :: "memory"); return t; }
__device__ __forceinline__ uint32_t clk() { unsigned long long c; asm volatile("mov.u64 %0, %%clock64;" : "=l"(c) :: "memory"); return (uint32_t)c; }
__device__ __forceinline__ void wait_until(uint32_t t) {
  while ((int)(t - clk()) > 450) __nanosleep(32);
  uint32_t c;
  do { asm volatile("mov.u32 %0, %%clock;" : "=r"(c) :: "memory"); } while ((int)(c - t) < 0);
}
__device__ __forceinline__ void mbar_init(uint32_t bar, uint32_t cnt) { asm volatile("mbarrier.init.shared::cta.b64 [%0], %1;" :: "r"(bar), "r"(cnt) : "memory"); }
__device__ __forceinline__ void mbar_arrive(uint32_t bar) { asm volatile("mbarrier.arrive.shared::cta.b64 _, [%0];" :: "r"(bar) : "memory"); }
__device__ __forceinline__ void mbar_arrive_remote(uint32_t bar) { asm volatile("mbarrier.arrive.relaxed.cluster.shared::cluster.b64 _, [%0];" :: "r"(bar) : "memory"); }
__device__ __forceinline__ void mbar_expect(uint32_t bar, uint32_t bytes) { asm volatile("mbarrier.arrive.expect_tx.shared::cta.b64 _, [%0], %1;" :: "r"(bar), "r"(bytes) : "memory"); }
__device__ __forceinline__ bool mbar_try(uint32_t bar, uint32_t parity) {
  uint32_t ok;
  asm volatile("{.reg .pred p; mbarrier.try_wait.parity.shared::cta.b64 p, [%1], %2; selp.u32 %0, 1, 0, p;}" : "=r"(ok) : "r"(bar), "r"(parity) : "memory");
  return ok;
}
__device__ __forceinline__ bool mbar_test(uint32_t bar, uint32_t parity) {
  uint32_t ok;
  asm volatile("{.reg .pred p; mbarrier.test_wait.parity.shared::cta.b64 p, [%1], %2; selp.u32 %0, 1, 0, p;}" : "=r"(ok) : "r"(bar), "r"(parity) : "memory");
  return ok;
}
__device__ __forceinline__ void mbar_wait(uint32_t bar, uint32_t parity) {
  asm volatile("{\n.reg .pred p;\nWAIT:\nmbarrier.try_wait.parity.shared::cta.b64 p, [%0], %1;\n@!p bra WAIT;\n}" :: "r"(bar), "r"(parity) : "memory");
}
__device__ __forceinline__ uint32_t ld_acq(const uint32_t* p) { uint32_t v; asm volatile("ld.acquire.gpu.global.u32 %0, [%1];" : "=r"(v) : "l"(p) : "memory"); return v; }
__device__ __forceinline__ void st_rel(uint32_t* p, uint32_t v) { asm volatile("st.release.gpu.global.u32 [%0], %1;" :: "l"(p), "r"(v) : "memory"); }
__device__ __forceinline__ void st_rel64(unsigned long long* p, unsigned long long v) { asm volatile("st.release.gpu.global.u64 [%0], %1;" :: "l"(p), "l"(v) : "memory"); }
__device__ __forceinline__ uint32_t ld_rlx(const uint32_t* p) { uint32_t v; asm volatile("ld.relaxed.gpu.global.u32 %0, [%1];" : "=r"(v) : "l"(p) : "memory"); return v; }
__device__ __forceinline__ unsigned long long ld_rlxu64(const unsigned long long* p) { unsigned long long v; asm volatile("ld.relaxed.gpu.global.u64 %0, [%1];" : "=l"(v) : "l"(p) : "memory"); return v; }
__device__ __forceinline__ void st_rlx(uint32_t* p, uint32_t v) { asm volatile("st.relaxed.gpu.global.u32 [%0], %1;" :: "l"(p), "r"(v) : "memory"); }
__device__ __forceinline__ void bulk_wait() { asm volatile("cp.async.bulk.commit_group;\n cp.async.bulk.wait_group 0;" ::: "memory"); }
__device__ __forceinline__ void fence_acq() { asm volatile("fence.acquire.gpu;" ::: "memory"); }
__device__ __forceinline__ void wait_all(const uint32_t* p, uint32_t v, bool acquire = true) {
  int guard = 0;
  while (!__all_sync(~0u, ld_rlx(p) == v)) { __nanosleep(32); if (++guard > (1 << 22)) TRAP(); }
  if (acquire) fence_acq();
}
__device__ __forceinline__ void wait_eq(const uint32_t* p, uint32_t v) {
  int guard = 0;
  while (ld_rlx(p) != v) { __nanosleep(64); if (++guard > (1 << 22)) TRAP(); }
  fence_acq();
}
__device__ __forceinline__ unsigned long long rword(uint32_t E, int tok, float r) {
  uint32_t u = __float_as_uint(r + 0.f);
  u = r != r ? 0u : (u >> 31) ? ~u : u | 0x80000000u;
  return (unsigned long long)(E & 0x1FFFFFu) << 43 | (unsigned long long)u << 11 | (uint32_t)(2047 - tok);
}
__device__ __forceinline__ int rtok(unsigned long long v) { return 2047 - (int)(v & 2047u); }
__device__ __forceinline__ float rscore(unsigned long long v) { const uint32_t u = (uint32_t)(v >> 11); return __uint_as_float((u >> 31) ? u & 0x7fffffffu : ~u); }
__device__ __forceinline__ bool rfresh(unsigned long long v, uint32_t E) { return (uint32_t)(v >> 43) == (E & 0x1FFFFFu); }
template <int TOP> __device__ __forceinline__ unsigned long long warp_max(unsigned long long v) {
#pragma unroll
  for (int o = TOP; o > 0; o >>= 1) { const unsigned long long ov = __shfl_xor_sync(~0u, v, o); v = ov > v ? ov : v; }
  return v;
}
template <int off> __device__ __forceinline__ uint2 ld_rlx64(const void* p) { unsigned long long v; asm volatile("ld.relaxed.gpu.global.b64 %0, [%1+%2];" : "=l"(v) : "l"(p), "n"(off) : "memory"); return make_uint2((uint32_t)v, (uint32_t)(v >> 32)); }
template <int off> __device__ __forceinline__ uint4 ld_rlx128(const void* p) {
  unsigned long long a, b; asm volatile("ld.relaxed.gpu.global.v2.b64 {%0,%1}, [%2+%3];" : "=l"(a), "=l"(b) : "l"(p), "n"(off) : "memory");
  return make_uint4((uint32_t)a, (uint32_t)(a >> 32), (uint32_t)b, (uint32_t)(b >> 32));
}
__device__ __forceinline__ void st_rlx64(void* p, uint32_t lo, uint32_t hi) { asm volatile("{.reg .b64 t; mov.b64 t, {%1,%2}; st.relaxed.gpu.global.b64 [%0], t;}" :: "l"(p), "r"(lo), "r"(hi) : "memory"); }
__device__ __forceinline__ void cp_async16(uint32_t dst, const void* src) { asm volatile("cp.async.cg.shared.global [%0], [%1], 16;" :: "r"(dst), "l"(src) : "memory"); }
__device__ __forceinline__ void cp_async_wait() { asm volatile("cp.async.wait_all;" ::: "memory"); }
__device__ __forceinline__ void fence_async_smem() { asm volatile("fence.proxy.async.shared::cta;" ::: "memory"); }
__device__ __forceinline__ void fence_async_glob() { asm volatile("fence.proxy.async.global;" ::: "memory"); }
__device__ __forceinline__ float ex2(float x) { float y; asm("ex2.approx.ftz.f32 %0, %1;" : "=f"(y) : "f"(x)); return y; }
__device__ __forceinline__ float sqrt_fast(float x) { float y; asm("sqrt.approx.ftz.f32 %0, %1;" : "=f"(y) : "f"(x)); return y; }
__device__ __forceinline__ float rcp(float x) { float y; asm("rcp.approx.ftz.f32 %0, %1;" : "=f"(y) : "f"(x)); return y; }
__device__ __forceinline__ void bar_sync(int id, int n) { asm volatile("bar.sync %0, %1;" :: "r"(id), "r"(n) : "memory"); }
__device__ __forceinline__ bool bar_or(int id, int n, bool v) {
  uint32_t r;
  asm volatile("{.reg .pred p, q; setp.ne.u32 p, %3, 0; barrier.cta.red.or.aligned.pred q, %1, %2, p; selp.u32 %0, 1, 0, q;}" : "=r"(r) : "r"(id), "r"(n), "r"((uint32_t)v) : "memory");
  return r;
}
__device__ __forceinline__ uint32_t mapa(uint32_t a, uint32_t rank) { uint32_t r; asm volatile("mapa.shared::cluster.u32 %0, %1, %2;" : "=r"(r) : "r"(a), "r"(rank)); return r; }
__device__ __forceinline__ void cluster_sync() { asm volatile("barrier.cluster.arrive.release.aligned; barrier.cluster.wait.acquire.aligned;" ::: "memory"); }
__device__ __forceinline__ void st_async32(uint32_t dst, uint32_t v, uint32_t bar) { asm volatile("st.async.shared::cluster.mbarrier::complete_tx::bytes.b32 [%0], %1, [%2];" :: "r"(dst), "r"(v), "r"(bar) : "memory"); }
#define ELECT(op) "{.reg .pred p; elect.sync _|p, 0xffffffff; @p " op "}"
__device__ __forceinline__ void e_arrive(uint32_t bar) { asm volatile(ELECT("mbarrier.arrive.shared::cta.b64 _, [%0];") :: "r"(bar) : "memory"); }
__device__ __forceinline__ void e_expect(uint32_t bar, uint32_t bytes) { asm volatile(ELECT("mbarrier.arrive.expect_tx.shared::cta.b64 _, [%0], %1;") :: "r"(bar), "r"(bytes) : "memory"); }
__device__ __forceinline__ void e_g2s(uint32_t dst, const void* src, uint32_t bytes, uint32_t bar) {
  asm volatile(ELECT("cp.async.bulk.shared::cluster.global.mbarrier::complete_tx::bytes [%0], [%1], %2, [%3];") :: "r"(dst), "l"(src), "r"(bytes), "r"(bar) : "memory");
}
__device__ __forceinline__ void e_mc(uint32_t dst, const void* src, uint32_t bytes, uint32_t bar, uint16_t mask) {
  asm volatile(ELECT("cp.async.bulk.shared::cluster.global.mbarrier::complete_tx::bytes.multicast::cluster [%0], [%1], %2, [%3], %4;")
               :: "r"(dst), "l"(src), "r"(bytes), "r"(bar), "h"(mask) : "memory");
}
__device__ __forceinline__ void e_s2g(void* dst, uint32_t src, uint32_t bytes) {
  asm volatile(ELECT("cp.async.bulk.global.shared::cta.bulk_group [%0], [%1], %2;") :: "l"(dst), "r"(src), "r"(bytes) : "memory");
}
__device__ __forceinline__ uint32_t clk32() { uint32_t c; asm volatile("mov.u32 %0, %%clock;" : "=r"(c) :: "memory"); return c; }
__device__ __forceinline__ void spin_until(uint32_t t) { while ((int)(clk32() - t) < 0) {} }
__device__ __forceinline__ uint32_t uni(uint32_t v) { return __shfl_sync(~0u, v, 0); }
__device__ __forceinline__ uint32_t pack2(float lo, float hi) { uint32_t r; asm("cvt.rn.bf16x2.f32 %0, %1, %2;" : "=r"(r) : "f"(hi), "f"(lo)); return r; }
__device__ __forceinline__ uint32_t add2(uint32_t a, uint32_t b) { uint32_t r; asm("add.rn.bf16x2 %0, %1, %2;" : "=r"(r) : "r"(a), "r"(b)); return r; }
__device__ __forceinline__ float rbf(float x) { return __bfloat162float(__float2bfloat16_rn(x)); }
__device__ __forceinline__ float blo(uint32_t u) { return __uint_as_float(u << 16); }
__device__ __forceinline__ float bhi(uint32_t u) { return __uint_as_float(u & 0xffff0000u); }
__device__ __forceinline__ uint32_t gentag(uint32_t g) { return (g & 1u) | (g & 2u) << 15; }
__device__ __forceinline__ uint32_t pack2_tag(float lo, float hi, uint32_t tag) {
  const uint32_t u = __byte_perm(__float_as_uint(lo), __float_as_uint(hi), 0x7632);
  return u + ((u ^ tag) & 0x10001u);
}
__device__ __forceinline__ uint32_t xo2(uint32_t a, uint32_t b, uint32_t t) { uint32_t r; asm("lop3.b32 %0, %1, %2, %3, 0x7e;" : "=r"(r) : "r"(a), "r"(b), "r"(t)); return r; }
__device__ __forceinline__ uint32_t or3(uint32_t a, uint32_t b, uint32_t c) { uint32_t r; asm("lop3.b32 %0, %1, %2, %3, 0xfe;" : "=r"(r) : "r"(a), "r"(b), "r"(c)); return r; }
__device__ __forceinline__ void stmatrix4(uint32_t a, uint32_t r0, uint32_t r1, uint32_t r2, uint32_t r3) {
  asm volatile("stmatrix.sync.aligned.m8n8.x4.shared.b16 [%0], {%1,%2,%3,%4};" :: "r"(a), "r"(r0), "r"(r1), "r"(r2), "r"(r3) : "memory");
}
__device__ __forceinline__ void stmatrix4_t(uint32_t a, uint32_t r0, uint32_t r1, uint32_t r2, uint32_t r3) {
  asm volatile("stmatrix.sync.aligned.m8n8.x4.trans.shared.b16 [%0], {%1,%2,%3,%4};" :: "r"(a), "r"(r0), "r"(r1), "r"(r2), "r"(r3) : "memory");
}
__device__ __forceinline__ void ldmatrix4_t(uint32_t* r, uint32_t a) {
  asm volatile("ldmatrix.sync.aligned.m8n8.x4.trans.shared.b16 {%0,%1,%2,%3}, [%4];" : "=r"(r[0]), "=r"(r[1]), "=r"(r[2]), "=r"(r[3]) : "r"(a) : "memory");
}
__device__ __forceinline__ void ldmatrix4(uint32_t* r, uint32_t a) {
  asm volatile("ldmatrix.sync.aligned.m8n8.x4.shared.b16 {%0,%1,%2,%3}, [%4];" : "=r"(r[0]), "=r"(r[1]), "=r"(r[2]), "=r"(r[3]) : "r"(a) : "memory");
}
__device__ __forceinline__ void hmma16(float* c, const uint32_t* a, uint32_t b0, uint32_t b1) {
  asm volatile("mma.sync.aligned.m16n8k16.row.col.f32.bf16.bf16.f32 {%0,%1,%2,%3}, {%4,%5,%6,%7}, {%8,%9}, {%0,%1,%2,%3};"
               : "+f"(c[0]), "+f"(c[1]), "+f"(c[2]), "+f"(c[3]) : "r"(a[0]), "r"(a[1]), "r"(a[2]), "r"(a[3]), "r"(b0), "r"(b1));
}
__device__ __forceinline__ void hmma8(float* c, uint32_t a0, uint32_t a1, uint32_t b0) {
  asm volatile("mma.sync.aligned.m16n8k8.row.col.f32.bf16.bf16.f32 {%0,%1,%2,%3}, {%4,%5}, {%6}, {%0,%1,%2,%3};"
               : "+f"(c[0]), "+f"(c[1]), "+f"(c[2]), "+f"(c[3]) : "r"(a0), "r"(a1), "r"(b0));
}
__device__ __forceinline__ uint4 lds128(uint32_t a) { uint4 v; asm volatile("ld.shared.v4.u32 {%0,%1,%2,%3}, [%4];" : "=r"(v.x), "=r"(v.y), "=r"(v.z), "=r"(v.w) : "r"(a) : "memory"); return v; }
__device__ __forceinline__ void sts128(uint32_t a, uint4 v) { asm volatile("st.shared.v4.u32 [%0], {%1,%2,%3,%4};" :: "r"(a), "r"(v.x), "r"(v.y), "r"(v.z), "r"(v.w) : "memory"); }
__device__ __forceinline__ void sts128f(uint32_t a, float x, float y, float z, float w) { asm volatile("st.shared.v4.f32 [%0], {%1,%2,%3,%4};" :: "r"(a), "f"(x), "f"(y), "f"(z), "f"(w) : "memory"); }
__device__ __forceinline__ uint32_t lds32(uint32_t a) { uint32_t v; asm volatile("ld.shared.u32 %0, [%1];" : "=r"(v) : "r"(a) : "memory"); return v; }
__device__ __forceinline__ void sts32(uint32_t a, uint32_t v) { asm volatile("st.shared.u32 [%0], %1;" :: "r"(a), "r"(v) : "memory"); }

constexpr uint32_t SBASE = 1024;
__host__ __device__ constexpr uint64_t mkdesc(uint32_t off, uint32_t lbo, uint32_t sbo, uint32_t swz) {
  return (uint64_t)(((SBASE + off) & 0x3FFFF) >> 4) | ((uint64_t)(lbo >> 4) << 16) | ((uint64_t)(sbo >> 4) << 32) | ((uint64_t)swz << 62);
}
__device__ __forceinline__ void wg_fence() { asm volatile("wgmma.fence.sync.aligned;" ::: "memory"); }
__device__ __forceinline__ void wg_commit() { asm volatile("wgmma.commit_group.sync.aligned;" ::: "memory"); }
template <int N> __device__ __forceinline__ void wg_wait() { asm volatile("wgmma.wait_group.sync.aligned %0;" :: "n"(N) : "memory"); }

template <int N> __device__ __forceinline__ void reg_fence(float (&d)[N], int n = N) {
#pragma unroll
  for (int i = 0; i < N; i++) if (i < n) asm volatile("" : "+f"(d[i]) :: "memory");
}
#define F4(b) "+f"(d[b]), "+f"(d[b + 1]), "+f"(d[b + 2]), "+f"(d[b + 3])
#define F8(b) F4(b), F4(b + 4)
#define F16(b) F8(b), F8(b + 8)
#define G4(b) "=f"(d[b]), "=f"(d[b + 1]), "=f"(d[b + 2]), "=f"(d[b + 3])
#define G8(b) G4(b), G4(b + 4)
#define G16(b) G8(b), G8(b + 8)
#define RS_IN "r"(a[0]), "r"(a[1]), "r"(a[2]), "r"(a[3]), "l"(db), "n"(SD), "n"(TB)
#define SS_IN "l"(da), "l"(db), "n"(SD), "n"(TA), "n"(TB)
#define WG_OP(str, out0, out1, in) do { if (SD || KEEP) asm volatile(str : out1 : in); else asm volatile(str : out0 : in); } while (0)
#define O12(X) X##8(0), X##4(8)
#define O20(X) X##16(0), X##4(16)
#define O32(X) X##16(0), X##16(16)
template <int SD, int TB, int KEEP = 0> __device__ __forceinline__ void wgmma_rs24(float* d, const uint32_t* a, uint64_t db) {
  WG_OP("wgmma.mma_async.sync.aligned.m64n24k16.f32.bf16.bf16 {%0,%1,%2,%3,%4,%5,%6,%7,%8,%9,%10,%11}, {%12,%13,%14,%15}, %16, %17, 1, 1, %18;", O12(G), O12(F), RS_IN);
}
template <int SD, int TB, int KEEP = 0> __device__ __forceinline__ void wgmma_rs32(float* d, const uint32_t* a, uint64_t db) {
  WG_OP("wgmma.mma_async.sync.aligned.m64n32k16.f32.bf16.bf16 {%0,%1,%2,%3,%4,%5,%6,%7,%8,%9,%10,%11,%12,%13,%14,%15}, {%16,%17,%18,%19}, %20, %21, 1, 1, %22;", G16(0), F16(0), RS_IN);
}
template <int SD, int TB, int KEEP = 0> __device__ __forceinline__ void wgmma_rs40(float* d, const uint32_t* a, uint64_t db) {
  WG_OP("wgmma.mma_async.sync.aligned.m64n40k16.f32.bf16.bf16 {%0,%1,%2,%3,%4,%5,%6,%7,%8,%9,%10,%11,%12,%13,%14,%15,"
        "%16,%17,%18,%19}, {%20,%21,%22,%23}, %24, %25, 1, 1, %26;", O20(G), O20(F), RS_IN);
}
template <int SD, int TB, int KEEP = 0> __device__ __forceinline__ void wgmma_rs64(float* d, const uint32_t* a, uint64_t db) {
  WG_OP("wgmma.mma_async.sync.aligned.m64n64k16.f32.bf16.bf16 {%0,%1,%2,%3,%4,%5,%6,%7,%8,%9,%10,%11,%12,%13,%14,%15,"
        "%16,%17,%18,%19,%20,%21,%22,%23,%24,%25,%26,%27,%28,%29,%30,%31}, {%32,%33,%34,%35}, %36, %37, 1, 1, %38;", O32(G), O32(F), RS_IN);
}
template <int SD, int TA, int TB, int KEEP = 0> __device__ __forceinline__ void wgmma_ss24(float* d, uint64_t da, uint64_t db) {
  WG_OP("wgmma.mma_async.sync.aligned.m64n24k16.f32.bf16.bf16 {%0,%1,%2,%3,%4,%5,%6,%7,%8,%9,%10,%11}, %12, %13, %14, 1, 1, %15, %16;", O12(G), O12(F), SS_IN);
}
template <int SD, int TA, int TB, int KEEP = 0> __device__ __forceinline__ void wgmma_ss8(float* d, uint64_t da, uint64_t db) {
  WG_OP("wgmma.mma_async.sync.aligned.m64n8k16.f32.bf16.bf16 {%0,%1,%2,%3}, %4, %5, %6, 1, 1, %7, %8;", G4(0), F4(0), SS_IN);
}
__device__ __forceinline__ void bar_arrive(int id, int n) { asm volatile("bar.arrive %0, %1;" :: "r"(id), "r"(n) : "memory"); }
__device__ __forceinline__ uint32_t vis_bits(int pos, int t) {
  uint32_t m = 0;
#pragma unroll
  for (int i = 0; i < 8; i++) m |= (8 * (i / 2 + 1) + 2 * t + (i & 1) <= pos) ? 1u << i : 0u;
  return m;
}

__device__ __forceinline__ unsigned long long wait_words(const unsigned long long* p, uint32_t E) {
  int guard = 0; unsigned long long m;
  while (m = ld_rlxu64(p), !__all_sync(~0u, rfresh(m, E))) { __nanosleep(20); if (++guard > (1 << 22)) TRAP(); }
  fence_acq();
  return m;
}
__device__ __forceinline__ int route_step(int s, uint32_t E, int lane, unsigned long long& run) {
  const unsigned long long m = warp_max<2>(wait_words(G.f_h2[s][lane & 3], E));
  if (s == 0 || m > run) { run = m; return rtok(m) & 31; }
  return -1;
}

struct Params {
  const bf16 *x, *mem0, *wq, *wk, *wv, *wo, *wr, *wg, *wu, *wd;
  bf16* out;
  uint32_t zero2;
  unsigned long long zero;
};

constexpr uint32_t WSTG_STRIDE = 272;
__device__ __forceinline__ void stage_weights(uint32_t stg, const bf16* src, int ld, int tid, int nthr) {
  for (int i = tid; i < 512 * 16; i += nthr) {
    int k = i >> 4, c = i & 15;
    cp_async16(stg + k * WSTG_STRIDE + c * 16, src + (size_t)k * ld + c * 8);
  }
}
__device__ __forceinline__ void load_frags(uint32_t (*W)[4], uint32_t stg, int wg, int w, int lane) {
  uint32_t a = stg + ((lane >> 4) * 8 + (lane & 7)) * WSTG_STRIDE + (64 * wg + 16 * w + ((lane >> 3) & 1) * 8) * 2;
#pragma unroll
  for (int ks = 0; ks < 32; ks++) ldmatrix4_t(W[ks], a + ks * 16 * WSTG_STRIDE);
}

constexpr uint32_t M_H = 0;
constexpr uint32_t M_MEM = 65536;
constexpr uint32_t M_Q = M_MEM + 24576;
constexpr uint32_t M_K = M_Q + 12288;
constexpr uint32_t M_V = M_K + 12288;
constexpr uint32_t M_OM = M_V + 12288;
constexpr uint32_t M_OST = M_OM + 6144;
constexpr uint32_t M_TST = M_OST + 8192;
constexpr uint32_t M_WO = M_TST + 16384;
constexpr uint32_t M_M0 = M_WO + 49152;
constexpr uint32_t M_PT = M_M0 + 2048;
constexpr uint32_t M_BAR = M_PT + 12288;
constexpr uint32_t M_TOTAL = M_BAR + 384;
static_assert(M_TOTAL <= 232448, "main smem");
static_assert(M_WO >= 512 * WSTG_STRIDE, "staging overlaps Wo");
enum { B_LAND = 0  , B_QK = 3, B_V, B_TOK, B_OM, B_HA, B_HB, B_HAE, B_HBE, B_OST, B_OFREE, B_SYNC,
       B_STG, B_STG1, B_SS, B_TFREE, B_KFREE, B_VFREE, B_FIX  , B_NUM = B_FIX + 8 };
static_assert(B_NUM * 8 <= 256, "barriers");
constexpr uint32_t M_CAND = M_BAR + 256;
constexpr uint32_t M_BASE = M_BAR + 272;
constexpr uint32_t M_ZERO = M_BAR + 280;
constexpr uint32_t M_BAS2 = M_BAR + 328;
constexpr uint32_t M_NEAR = M_BAR + 288;
enum { N_GO2 = 3, N_GO3, N_GO4, N_AG, N_W };

#define GSTAMP(slot, i)
#define TSTAMP(slot, i, k)
#define STAMP(i)
#define ASTAMP(i)
#define WSTAMP(i)
#define CSTAMP(i, v)
#define PIN(x) asm volatile("" : "+r"(x))
#define SCHED(k) asm volatile("{\n.reg .pred p;\nsetp.ne.u32 p, %0, 0;\n@p trap;\n}" :: "r"(zz & (1u << (k))) : "memory")
#define HOLD(k, v) asm volatile("{\n.reg .pred p;\nsetp.ne.u32 p, %0, 0;\n@p st.shared.u32 [%0], %1;\n}" :: "r"(zz & (1u << (k))), "r"(v) : "memory")
#define DRAIN(a) (lds32((a) + zz) & zz)
#define BAR(i) (sb + M_BAR + 8 * (i))

__device__ __forceinline__ int probe(const uint8_t* p, int n) {
  int best = 1 << 30; uint32_t v = 0;
#pragma unroll 1
  for (int r = 0; r < n; r++) {
    uint32_t t0 = clk();
    asm volatile("atom.relaxed.gpu.global.or.b32 %0, [%1], %2;" : "=r"(v) : "l"(p + 3968), "r"(v & 0u) : "memory");
    if (v == 0x7fffffffu) t0++;
    best = min(best, (int)(clk() - t0));
  }
  return best;
}
__device__ __forceinline__ void load_mem0(uint4* u, int k0, int lane, const bf16* mem0) {
#pragma unroll
  for (int i = 0; i < 2; i++) {
    const unsigned short* m = (const unsigned short*)mem0 + k0 + lane + 32 * i;
    u[i] = make_uint4(m[0] | (uint32_t)m[512] << 16, m[1024] | (uint32_t)m[1536] << 16, m[2048] | (uint32_t)m[2560] << 16, m[3072] | (uint32_t)m[3584] << 16);
  }
}

__device__ __forceinline__ void paced_h(uint32_t dst, const uint8_t* src, uint32_t o0, uint32_t o1, uint32_t piece, uint32_t bar, int gap) {
  uint32_t t = clk32();
#pragma unroll 1
  for (uint32_t o = o0; o < o1; o += piece) {
    e_mc(dst + o, src + o, piece, bar, 7);
    spin_until(t += gap);
  }
}

__device__ __forceinline__ void paced_st(uint8_t* dst, uint32_t src, int gap) {
  uint32_t t = clk32();
#pragma unroll 1
  for (uint32_t o = 0; o < 8192; o += 4096) {
    e_s2g(dst + o, src + o, 4096);
    if (o + 4096 < 8192) spin_until(t += gap);
  }
}
__device__ __forceinline__ int block_of(int head, int c) { return c == 2 ? head : 32 + 2 * head + c; }

__device__ __forceinline__ void weight_role(const Params& p, const uint32_t sb, const int warp, const int cta, const int C, const uint32_t E,
                                            const uint8_t* const memg) {
  const int tid = fresh_tid(), lane = tid & 31;
  const int wg = warp >> 2, w = warp & 3;
  uint32_t W[32][4];
  cp_async_wait();
  bar_sync(1, 256);
  load_frags(W, sb, wg, w, lane);
  bar_sync(1, 256);
  if (tid < 128) sts128(sb + M_V + 5 * 2048 + tid * 16, make_uint4(0, 0, 0, 0));
  fence_async_smem();
  cluster_sync();
  if (tid == 0 && cta == 0) GSTAMP(0, 1);
  if (tid == 0) TSTAMP(13, cta, 0);

  const uint32_t rba = mapa(sb, C == 2 ? 0 : 2), rbc = mapa(sb, C == 1 ? 0 : 1);
  const uint32_t MYBAR = M_BAR + 8 * (C < 2 ? B_QK : B_V);
  uint32_t qoff = M_Q + C * 12288 + warp * 256 + lane * 4;
  uint32_t toff = sb + warp * 256 + (lane >> 4) * 2048 + (lane & 15) * 16;
  uint32_t rbar = mapa(sb + M_BAR, min(lane, 2));
  uint32_t sv = sb + M_MEM + lane * 32 + ((lane >> 2) & 3) * 8;
  PIN(qoff); PIN(toff); PIN(rbar); PIN(sv);
  const uint32_t gen0 = (E - 1) * (uint32_t)(NSTEP - 1);
  uint32_t fix = 0;
  const bool sig = w == 0 && lane < 3;
  const int blk = block_of(cta / 3, C);
  const int pk = (blk < 24 ? PAUSE_ : PAUS2_) + (wg ? -PST2_ : PST2_);
  int cand = -1;
  float d[16];
#pragma unroll
  for (int i = 0; i < 16; i++) d[i] = 0.f;
  uint32_t tp[8];
#pragma unroll 1
  for (int T = -1; T < NSTEP; T++) {
    const uint32_t ph = T & 1;
    const uint64_t Z = p.zero << ph;
    const uint32_t zz = p.zero2;
    if (T >= 0) {
      WSTAMP(0);
      const uint64_t db = mkdesc(M_MEM, 128, 256, 0) + Z;
      stmatrix4(toff + M_TST + 8192, tp[0], tp[1], tp[2], tp[3]); stmatrix4(toff + M_TST + 12288, tp[4], tp[5], tp[6], tp[7]);
      if (sig) mbar_arrive_remote(rbar + 8 * B_HBE);
      mbar_wait(BAR(B_LAND), ph);
      WSTAMP(1);
      const uint32_t gt = gentag(gen0 + T);
      auto old = [&](uint32_t a) { return lds32(a) ^ gt; };
      uint32_t bad = 0;
      bool redo = false, ready = false;
      wg_fence();
      wgmma_rs24<0, 1, 1>(d, W[0], db);
#pragma unroll
      for (int ks = 1; ks < 32; ks++) {
        if (ks == 2) bad |= old(sv + min(warp, 5) * 1024);
        if (ks == 10 || ks == 22) bad |= xo2(lds32(sv + (ks == 10 ? 6 : 15) * 1024 + warp * 1024), lds32(sv + (ks == 10 ? 14 : 23) * 1024), gt);
        if (ks == 6) {
          const uint32_t z5 = DRAIN(toff + M_TST);
          __syncwarp();
          if (lane == 0) mbar_arrive(BAR(B_STG) + z5);
        }
        if (ks == 27) ready = mbar_test(BAR(C < 2 ? B_KFREE : B_VFREE), ph ^ 1) & mbar_test(BAR(B_HA), ph);
        if (ks == 30) redo = bar_or(N_W, 256, T > 0 && (bad & 0x10001u));
        if (ks == 8 || ks == 20) { mbar_wait(BAR(B_LAND + (ks + 4) / 12), ph); WSTAMP(6 + (ks + 4) / 12); wg_fence(); }
        wgmma_rs24<1, 1>(d, W[ks], db + ks * 48);
      }
      wg_commit();
      uint32_t a0 = rba + qoff, a1 = a0 + 128, a2 = rbc + qoff, a3 = a2 + 128, ba = rba + MYBAR, bc = rbc + MYBAR;
      PIN(a0); PIN(a1); PIN(a2); PIN(a3); PIN(ba); PIN(bc);
      if (!ready) {
        mbar_wait(BAR(C < 2 ? B_KFREE : B_VFREE), ph ^ 1);
        if (T < NSTEP - 1) mbar_wait(BAR(B_HA), ph);
      }
      wg_wait<0>(); reg_fence(d);
      if (__builtin_expect(redo, 0)) {
        auto stale = [&]() { return __any_sync(~0u, (old(sv + warp * 3072) | old(sv + warp * 3072 + 1024) | old(sv + warp * 3072 + 2048)) & 0x10001u); };
        auto fetch = [&](int r) {
          e_expect(BAR(B_FIX + warp), 3072);
          e_g2s(sb + M_MEM + warp * 3072, memg + warp * 8192 + ((uni(lds32(sb + M_NEAR + warp * 4)) ^ r) & 1) * 4096, 3072, BAR(B_FIX + warp));
        };
        bool late = stale();
        if (late) fetch(0);
        constexpr uint64_t dc = mkdesc(M_MEM, 128, 256, 0);
#pragma unroll
        for (int ks = 0; ks < 32; ks++) {
          if (ks % 12 == 0) {
            if (ks) { wg_commit(); wg_wait<0>(); reg_fence(d); }
            if (warp / 3 == ks / 12) {
              for (int guard = 0; late; guard++) {
                mbar_wait(BAR(B_FIX + warp), fix); fix ^= 1;
                late = stale();
                if (late) fetch(guard + 1);
                if (guard > (1 << 20)) TRAP();
              }
            }
            bar_sync(N_W, 256);
            wg_fence();
          }
          if (ks == 0) wgmma_rs24<0, 1, 1>(d, W[0], dc); else wgmma_rs24<1, 1>(d, W[ks], dc + ks * 48);
        }
        wg_commit();
        wg_wait<0>(); reg_fence(d);
      }
      WSTAMP(2);
      if (T == 0 && tid == 0) TSTAMP(13, cta, 2);
      uint32_t lo[3], hi[3];
#pragma unroll
      for (int j = 0; j < 3; j++) { lo[j] = pack2(d[4 * j], d[4 * j + 1]); hi[j] = pack2(d[4 * j + 2], d[4 * j + 3]); }
      if (__builtin_expect(T == 0, 0)) { sts32(sb + M_M0 + tid * 8, lo[0]); sts32(sb + M_M0 + tid * 8 + 4, hi[0]); }
      if (__builtin_expect(cand >= 0, 0)) {
        if (T == LAG) { lo[1] = lds32(sb + M_M0 + tid * 8); hi[1] = lds32(sb + M_M0 + tid * 8 + 4); }
        if (C < 2) { st_async32(a0 + 5 * 2048, lo[2], ba); st_async32(a1 + 5 * 2048, hi[2], ba); }
        else { sts32(sb + qoff + 5 * 2048, lo[2]); sts32(sb + qoff + 5 * 2048 + 128, hi[2]); }
        lo[2] = lo[1]; hi[2] = hi[1];
      }
      uint32_t z5;
      if (C == 0) {
        sts32(sb + qoff, lo[0]); sts32(sb + qoff + 128, hi[0]); z5 = DRAIN(sb + qoff);
        st_async32(a0, lo[2], ba); st_async32(a1, hi[2], ba); st_async32(a2, lo[1], bc); st_async32(a3, hi[1], bc);
      } else if (C == 1) {
        sts32(sb + qoff, lo[1]); sts32(sb + qoff + 128, hi[1]); z5 = DRAIN(sb + qoff);
        st_async32(a0, lo[2], ba); st_async32(a1, hi[2], ba); st_async32(a2, lo[0], bc); st_async32(a3, hi[0], bc);
      } else {
        sts32(sb + qoff, lo[2]); sts32(sb + qoff + 128, hi[2]); z5 = DRAIN(sb + qoff);
        st_async32(a0, lo[0], ba); st_async32(a1, hi[0], ba); st_async32(a2, lo[1], bc); st_async32(a3, hi[1], bc);
      }
      __syncwarp();
      if (lane == 0) { mbar_arrive(sb + MYBAR + z5); if (w == 3) mbar_arrive(BAR(B_SS)); }
      if (T == NSTEP - 1) break;
    }
    {
      const uint64_t dh = mkdesc(M_H, 16, 1024, 1) + Z;
      if (T + 2 < NSEG) {
        if (T < 0) mbar_wait(BAR(B_HA), ph);
        WSTAMP(3);
        wg_fence();
        wgmma_rs32<0, 0, 1>(d, W[0], dh);
#pragma unroll
        for (int ks = 1; ks < EA; ks++) {
          if (ks == E1) { wg_commit(); if (T >= 0) bar_sync(N_GO2, 384); wg_fence(); }
          wgmma_rs32<1, 0>(d, W[ks], dh + (ks >> 2) * 256 + (ks & 3) * 2);
        }
        wg_commit();
        mbar_wait(BAR(B_HB), ph);
        wg_wait<0>();
        if (sig) mbar_arrive_remote(rbar + 8 * B_HAE);
        WSTAMP(4);
        if (T >= 0) bar_sync(N_GO3, 384);
        if (wg == 1) bar_sync(N_W, 256);
        wg_fence();
#pragma unroll
        for (int ks = EA; ks < 32; ks++) wgmma_rs32<1, 0>(d, W[ks], dh + (ks >> 2) * 256 + (ks & 3) * 2);
        wg_commit();
        if (wg == 0) bar_arrive(N_W, 256);
        mbar_wait(BAR(B_TFREE), ph ^ 1);
        wg_wait<0>(); reg_fence(d);
      } else {
        bar_sync(N_GO2, 384);
        mbar_wait(BAR(B_HB), ph);
        if (sig) mbar_arrive_remote(rbar + 8 * B_HAE);
        bar_sync(N_GO3, 384);
        mbar_wait(BAR(B_TFREE), ph ^ 1);
      }
#pragma unroll
      for (int i = 0; i < 8; i++) { tp[i] = pack2(d[2 * i], d[2 * i + 1]); PIN(tp[i]); }
      const uint32_t t1 = toff + (C == 0 && !ph ? M_Q + 2048 : M_TST);
      auto staged = [&]() {
        const uint32_t z5 = DRAIN(t1);
        __syncwarp();
        if (lane == 0) mbar_arrive(BAR(B_STG1) + z5);
      };
      if (T < 0 || (T + 2 >= LAG && T + 2 < NSTEP)) {
        wg_fence();
        wgmma_rs32<0, 0, 1>(d, W[0], dh + 2048);
        stmatrix4(t1, tp[0], tp[1], tp[2], tp[3]); stmatrix4(t1 + 4096, tp[4], tp[5], tp[6], tp[7]);
#pragma unroll
        for (int ks = 1; ks < 32; ks++) {
          if (ks == 5) staged();
          if (ks == PAUSE_ - PST2_ || ks == PAUSE_ + PST2_ || ks == PAUS2_ - PST2_ || ks == PAUS2_ + PST2_) {
            wg_commit();
            if (T >= 0 && ks == pk) bar_sync(N_GO4, 384);
            wg_fence();
          }
          wgmma_rs32<1, 0>(d, W[ks], dh + 2048 + (ks >> 2) * 256 + (ks & 3) * 2);
        }
        wg_commit();
      } else {
        stmatrix4(t1, tp[0], tp[1], tp[2], tp[3]); stmatrix4(t1 + 4096, tp[4], tp[5], tp[6], tp[7]);
        staged();
        bar_sync(N_GO4, 384);
      }
      if (T >= 0) cand = __shfl_sync(~0u, (int)lds32(sb + M_CAND + ((T + 1) & 3) * 4), 0);
      wg_wait<0>(); reg_fence(d);
      if (T >= 0) WSTAMP(6);
      if (T < 0 && tid == 0) TSTAMP(13, cta, 1);
#pragma unroll
      for (int i = 0; i < 8; i++) tp[i] = pack2(d[2 * i], d[2 * i + 1]);
    }
  }
  cluster_sync();
  if (tid == 0 && cta == 0) GSTAMP(0, 5);
}

__device__ __forceinline__ void attn_role(const Params& p, const uint32_t sb, const int w, const int cta, const int head, const int C, const uint32_t E,
                                          uint8_t* const part, uint8_t* const memg) {
  const int tid = fresh_tid(), lane = tid & 31;
  const int g = lane >> 2, t = lane & 3, blk = block_of(head, C);
  uint32_t tag = ((E - 1) * (uint32_t)(NSTEP - 1)) & 1;
  uint4 m0[2][2];
  load_mem0(m0[0], w * 64, lane, p.mem0); load_mem0(m0[1], w * 64 + 256, lane, p.mem0);
  cluster_sync();
#pragma unroll
  for (int k = 0; k < 2; k++) {
#pragma unroll 1
    for (int i = 0; i < 6; i++) sts128(sb + M_MEM + (w + 4 * k) * 3072 + lane * 16 + i * 512, make_uint4(0, 0, 0, 0));
    __syncwarp();
#pragma unroll
    for (int i = 0; i < 2; i++) sts128(sb + M_MEM + ((w + 4 * k) * 4 + (lane >> 4) + 2 * i) * 768 + (lane & 15) * 16, m0[k][i]);
  }
  fence_async_smem();
  bar_sync(N_AG, 128);
  if (w == 3 && lane < 3) mbar_arrive(BAR(B_LAND + lane));
  if (lane == 0) {
    if (w == 0) TSTAMP(15, cta, 0);
    sts32(sb + M_PT + w * 4, probe(part + blk * 16384 + w * 4096, 3));
    if (w == 0) TSTAMP(15, cta, 1);
  }
  bar_sync(N_AG, 128);
  const uint32_t inear = lds32(sb + M_PT + (w >> 1) * 8 + 4) < lds32(sb + M_PT + (w >> 1) * 8);
  if (lane == 0 && !(w & 1)) st_rlx(&G.f_choice[blk][w >> 1], (E << 1) | inear);
  if (w == 0) TSTAMP(15, cta, 2);
  uint32_t nb;
  {
    const int i = min(lane >> 1, C < 2 ? 8 : 5);
    const int r = ((i / 3 * 3 + C) * 4 + w) * 3 + i % 3;
    int guard = 0; uint32_t cw;
    while (__any_sync(~0u, ((cw = ld_rlx(&G.f_choice[r][lane & 1])) >> 1) != (E & 0x7FFFFFFFu))) { if (++guard > (1 << 22)) TRAP(); }
    nb = __ballot_sync(~0u, cw & 1) >> (lane >> 4);
    if (w == 0) TSTAMP(15, cta, 3);
  }
  bar_sync(N_AG, 128);
  const uint32_t pt0 = sb + M_PT + (tid & 127) * 16;
  {
    const uint32_t po = (C * 4 + w) * 49152 + (lane >> 4) * 8192 + head * 128 + (lane & 15) * 8;
    const uint8_t* in = part + (blk * 16384 + (w >> 1) * 8192 + inear * 4096 + (w & 1) * 64 + (lane >> 3) * 128 + (lane & 7) * 8);
    const uint8_t* outp = memg + ((blk / 12) * 8192 + (blk % 12) * 256 + w * 64 + (lane >> 4) * 4096 + (lane & 4) * 8 + (lane & 8) * 2 + (lane & 3) * 4);
#pragma unroll
    for (int i = 0; i < 12; i++) {
      const int j = i / 4 * 3 + (i & 3);
      const uint8_t* a = (i & 3) < 3 ? part + (po + i / 4 * 589824 + (i & 3) * 16384 + ((nb >> (2 * j)) & 1) * 4096) : i == 11 ? in : outp;
      asm volatile("st.shared.u64 [%0], %1;" :: "r"(pt0 + (i >> 1) * 2048 + (i & 1) * 8), "l"(a) : "memory");
    }
  }
  const int xd = __shfl_sync(~0u, XDLY_ + (blk < 24 ? 0 : blk < 60 ? X1_ : X2_), 0);
  const uint32_t rba = mapa(sb, C == 2 ? 0 : 2), rbc = mapa(sb, C == 1 ? 0 : 1);
  uint32_t vis = vis_bits(8 + 8 * w + g, t);
  uint32_t ln = lane;
#pragma unroll
  for (int i = 0; i < SALT_; i++) ln += lds32(sb + M_ZERO);
  PIN(vis); PIN(ln);
  if (tid == 256 && C == 0) st_rlx(&G.f_loaded[head], E);
  uint32_t fa[8][4];
#pragma unroll
  for (int ks = 0; ks < 8; ks++) ldmatrix4_t(fa[ks], sb + M_WO + 32768 + w * 256 + (lane >> 4) * 1024 + (lane & 15) * 16 + ks * 2048);
  if (w == 0) TSTAMP(14, cta, 0);
#pragma unroll 1
  for (int T = 0; T < NSTEP; T++) {
    const uint32_t ph = T & 1;
    const uint32_t zz = uni(lds32(sb + M_ZERO));
    const bool more = T < NSTEP - 1;
    const float sc = 0.08838834764831845f * 1.4426950408889634f;
    tag ^= 1;
    float s[20];
    const uint8_t* in; int cnext = -1; uint32_t tx; bool synced;
    float x[10], tm, ts;
    uint32_t pt[5];
    auto tok_max = [&]() {
      PIN(vis);
      x[0] = s[2]; x[1] = s[3];
#pragma unroll
      for (int i = 0; i < 8; i++) x[2 + i] = (vis >> i & 1) ? s[4 * (i / 2 + 1) + 2 + (i & 1)] : -INFINITY;
      tm = fmaxf(fmaxf(fmaxf(fmaxf(x[0], x[1]), fmaxf(x[2], x[3])), fmaxf(fmaxf(x[4], x[5]), fmaxf(x[6], x[7]))), fmaxf(x[8], x[9]));
      HOLD(7, __float_as_uint(tm));
    };
    auto tok_exp1 = [&]() {
      tm = fmaxf(tm, __shfl_xor_sync(~0u, tm, 1));
      tm = fmaxf(tm, __shfl_xor_sync(~0u, tm, 2));
      const float b = -tm * sc;
#pragma unroll
      for (int i = 0; i < 10; i++) x[i] = fmaf(x[i], sc, b);
      HOLD(10, __float_as_uint(x[9]));
    };
    auto tok_exp2 = [&]() {
#pragma unroll
      for (int i = 0; i < 10; i++) x[i] = ex2(x[i]);
      ts = (((x[0] + x[1]) + (x[2] + x[3])) + ((x[4] + x[5]) + (x[6] + x[7]))) + (x[8] + x[9]);
#pragma unroll
      for (int k = 0; k < 5; k++) pt[k] = pack2(x[2 * k], x[2 * k + 1]);
      HOLD(8, __float_as_uint(ts));
    };
    {
      uint32_t q[8][4];
      auto load_q = [&](uint32_t a, int h) {
#pragma unroll
        for (int k2 = 0; k2 < 4; k2++) {
          uint32_t r[4];
          ldmatrix4_t(r, a + k2 * 512);
          q[2 * k2][h] = r[0]; q[2 * k2][h + 2] = r[1]; q[2 * k2 + 1][h] = r[2]; q[2 * k2 + 1][h + 2] = r[3];
        }
      };
      PIN(ln);
      const uint32_t qa = sb + M_Q + ln * 16, qt = qa + w * 2048 + (C == 0 && ph ? M_TST - M_Q : 2048);
      const int cand = C == 2 ? (int)uni(lds32(sb + M_CAND + (T & 3) * 4)) : -1;
      mbar_wait(BAR(B_TOK), ph);
      load_q(qt, 1);
      mbar_wait(BAR(B_QK), ph);
      ASTAMP(0);
      if (T == 0 && w == 0) TSTAMP(13, cta, 3);
      if (__builtin_expect(cand >= 0, 0)) {
        mbar_wait(BAR(B_V), ph);
        PIN(ln);
        const int e = w * 32 + ln;
#pragma unroll
        for (int i = 0; i < 3; i++) {
          const uint32_t v = lds32(sb + M_Q + i * 12288 + 5 * 2048 + e * 16 + 4);
          asm volatile("st.shared.u16 [%0], %1;" :: "r"(sb + M_Q + i * 12288 + (1 + (cand >> 3)) * 2048 + e * 16 + (cand & 7) * 2), "h"((unsigned short)v) : "memory");
        }
        fence_async_smem();
        bar_sync(N_AG, 128);
        load_q(qt, 1);
      }
      constexpr uint64_t dk = mkdesc(M_K, 128, 2048, 0);
      fence_async_smem();
      uint32_t r[4][4];
#pragma unroll
      for (int k2 = 0; k2 < 4; k2++) ldmatrix4_t(r[k2], qa + k2 * 512);
#pragma unroll
      for (int k2 = 0; k2 < 4; k2++) {
        q[2 * k2][0] = r[k2][0]; q[2 * k2][2] = r[k2][1]; q[2 * k2 + 1][0] = r[k2][2]; q[2 * k2 + 1][2] = r[k2][3];
        if (k2 & 1) {
          wg_fence();
#pragma unroll
          for (int ks = 2 * k2 - 2; ks < 2 * k2 + 2; ks++) { if (ks == 0) wgmma_rs40<0, 1>(s, q[0], dk); else wgmma_rs40<1, 1>(s, q[ks], dk + ks * 16); }
        }
      }
      wg_commit();
    }
    if (more) {
      uint32_t v[5][4];
      PIN(ln);
      const uint32_t va = sb + M_V + w * 512 + ((ln >> 3) & 1) * 128 + (ln >> 4) * 2048 + (ln & 7) * 16;
      const uint32_t ooff = M_OM + w * 1536 + C * 256 + ln * 4;
      mbar_wait(BAR(B_V), ph);
      wg_wait<0>(); reg_fence(s);
      if (ln < 3) mbar_arrive_remote(mapa(BAR(B_KFREE), ln));
      ldmatrix4(v[0], va); ldmatrix4(v[1], va + 256); ldmatrix4(v[2], va + 4096); ldmatrix4(v[3], va + 4096 + 256);
      ldmatrix4(v[4], sb + M_V + 8192 + w * 512 + ln * 16);
      ASTAMP(1);
      float m = fmaxf(fmaxf(fmaxf(fmaxf(s[0], s[1]), fmaxf(s[4], s[5])), fmaxf(fmaxf(s[8], s[9]), fmaxf(s[12], s[13]))), fmaxf(s[16], s[17]));
      m = fmaxf(m, __shfl_xor_sync(~0u, m, 1));
      m = fmaxf(m, __shfl_xor_sync(~0u, m, 2));
      const float b = -m * sc;
      uint32_t pm[5];
#pragma unroll
      for (int j = 0; j < 5; j++) pm[j] = pack2(ex2(fmaf(s[4 * j], sc, b)), ex2(fmaf(s[4 * j + 1], sc, b)));
      float o0[4] = {0.f, 0.f, 0.f, 0.f}, o1[4] = {0.f, 0.f, 0.f, 0.f}, l[4] = {0.f, 0.f, 0.f, 0.f};
      const uint32_t one[4] = {0x3f803f80u, 0x3f803f80u, 0x3f803f80u, 0x3f803f80u};
      hmma16(l, one, pm[0], pm[1]); hmma16(o0, v[0], pm[0], pm[1]); hmma16(o1, v[1], pm[0], pm[1]);
      hmma16(l, one, pm[2], pm[3]); hmma16(o0, v[2], pm[2], pm[3]); hmma16(o1, v[3], pm[2], pm[3]);
      hmma8(l, one[0], one[1], pm[4]); hmma8(o0, v[4][0], v[4][1], pm[4]); hmma8(o1, v[4][2], v[4][3], pm[4]);
      const float r0 = rcp(l[0]), r1 = rcp(l[1]);
      const uint32_t u0 = pack2(o0[0] * r0, o0[1] * r1), u1 = pack2(o0[2] * r0, o0[3] * r1), u2 = pack2(o1[0] * r0, o1[1] * r1), u3 = pack2(o1[2] * r0, o1[3] * r1);
      constexpr uint32_t OB = M_BAR + 8 * B_OM;
      const uint32_t a0 = rba + ooff, a1 = rbc + ooff;
      st_async32(a0, u0, rba + OB); st_async32(a1, u0, rbc + OB);
      st_async32(a0 + 128, u1, rba + OB); st_async32(a1 + 128, u1, rbc + OB);
      st_async32(a0 + 768, u2, rba + OB); st_async32(a1 + 768, u2, rbc + OB);
      st_async32(a0 + 896, u3, rba + OB); st_async32(a1 + 896, u3, rbc + OB);
      bar_arrive(N_GO2, 384);
      sts32(sb + ooff, u0); sts32(sb + ooff + 128, u1); sts32(sb + ooff + 768, u2); sts32(sb + ooff + 896, u3);
      ASTAMP(2);
      uint32_t fb[8][4];
      const uint32_t wa = sb + M_WO + 16384 + w * 256 + (ln >> 4) * 1024 + (ln & 15) * 16 + zz;
      ldmatrix4_t(fb[0], wa);
      SCHED(3);
#pragma unroll
      for (int ks = 1; ks < 8; ks++) {
        ldmatrix4_t(fb[ks], wa + ks * 2048);
        if (ks == 7) { __syncwarp(); if (ln == 0) mbar_arrive(BAR(B_OM) + (fb[0][0] & zz)); }
      }
      if (blk % 3 == 2) cnext = (int)uni(lds32(sb + M_CAND + ((T + 1) & 3) * 4));
      {
        float d[12], e[12];
        constexpr uint64_t ob = mkdesc(M_OM, 128, 256, 0);
        uint8_t* q[3][3];
        auto addr = [&](int i) {
          asm volatile("ld.shared.v2.u64 {%0,%1}, [%2];" : "=l"(q[i][0]), "=l"(q[i][1]) : "r"(pt0 + i * 4096) : "memory");
          if (i < 2) asm volatile("ld.shared.u64 %0, [%1];" : "=l"(q[i][2]) : "r"(pt0 + i * 4096 + 2048) : "memory");
          else asm volatile("ld.shared.v2.u64 {%0,%1}, [%2];" : "=l"(q[i][2]), "=l"(in) : "r"(pt0 + i * 4096 + 2048) : "memory");
        };
        auto put = [&](const float* d, int i) {
          st_rlx64(q[i][0], (pack2(d[0], d[1]) & ~1u) | tag, pack2(d[2], d[3]));
          st_rlx64(q[i][1], (pack2(d[4], d[5]) & ~1u) | tag, pack2(d[6], d[7]));
          st_rlx64(q[i][2], (pack2(d[8], d[9]) & ~1u) | tag, pack2(d[10], d[11]));
        };
        addr(0); addr(1);
        SCHED(6);
        tok_max();
        ASTAMP(3);
        mbar_wait(BAR(B_OM), ph);
        ASTAMP(4);
        constexpr uint64_t w0 = mkdesc(M_WO, 1024, 128, 0);
        float (&f)[12] = d;
        wg_fence();
        wgmma_ss24<0, 1, 1>(d, w0, ob);
#pragma unroll
        for (int ks = 1; ks < 8; ks++) wgmma_ss24<1, 1, 1>(d, w0 + ks * 128, ob + ks * 48);
        wg_commit();
        wgmma_rs24<0, 1>(e, fb[0], ob);
#pragma unroll
        for (int ks = 1; ks < HAND_; ks++) wgmma_rs24<1, 1>(e, fb[ks], ob + ks * 48);
        wg_commit();
        wg_wait<1>(); reg_fence(d);
        put(d, 0);
        addr(2);
        SCHED(4);
        ASTAMP(5);
        wg_fence();
#pragma unroll
        for (int ks = HAND_; ks < 8; ks++) wgmma_rs24<1, 1>(e, fb[ks], ob + ks * 48);
        wg_commit();
        wgmma_rs24<0, 1, 1>(f, fa[0], ob);
#pragma unroll
        for (int ks = 1; ks < HAND_; ks++) wgmma_rs24<1, 1>(f, fa[ks], ob + ks * 48);
        wg_commit();
        wg_wait<1>(); reg_fence(e);
        put(e, 1);
        SCHED(5);
        if (C < 2) {
          wg_fence();
#pragma unroll
          for (int ks = HAND_; ks < 8; ks++) wgmma_rs24<1, 1>(f, fa[ks], ob + ks * 48);
          wg_commit();
        }
        synced = __all_sync(~0u, mbar_test(BAR(B_SYNC), ph));
        tx = uni(lds32(sb + M_BASE + ph * 4)) + xd;
        wg_wait<0>(); reg_fence(f);
        if (C < 2) put(f, 2);
        bar_arrive(N_GO3, 384);
        ASTAMP(6);
        if (T == 0 && w == 0) TSTAMP(14, cta, 1);
      }
    } else {
      mbar_wait(BAR(B_V), ph);
      wg_wait<0>(); reg_fence(s);
      tok_max();
    }
    uint2 v[8];
    auto poll = [&](uint2* v) {
      v[0] = ld_rlx64<0>(in); v[1] = ld_rlx64<512>(in); v[2] = ld_rlx64<1024>(in); v[3] = ld_rlx64<1536>(in);
      v[4] = ld_rlx64<2048>(in); v[5] = ld_rlx64<2560>(in); v[6] = ld_rlx64<3072>(in); v[7] = ld_rlx64<3584>(in);
    };
    uint8_t* outp;
    asm volatile("ld.shared.u64 %0, [%1];" : "=l"(outp) : "r"(pt0 + 2048 + 8) : "memory");
    const uint32_t itag = gentag((E - 1) * (uint32_t)(NSTEP - 1) + T + 1);
    const bool sum = more && cnext < 0;
    if (more) {
      if (!synced) { mbar_wait(BAR(B_SYNC), ph); tx = uni(lds32(sb + M_BASE + ph * 4)) + xd; }
      ASTAMP(7);
      if (__builtin_expect(cnext >= 0, 0)) {
        const unsigned long long* hp = (const unsigned long long*)&G.hc[T + 1 - LAG][0] + ((blk / 3) * 8 + 2 * w + ((ln >> 2) & 1));
        unsigned long long v0; int guard = 0;
        while (v0 = ld_rlxu64(hp), !__all_sync(~0u, (uint32_t)(v0 >> 32) == E)) { if (++guard > (1 << 22)) TRAP(); }
        st_rlx((uint32_t*)outp, (ln & 3) == 1 ? ((uint32_t)v0 >> ((ln & 8) * 2)) & 0xffffu : (ln & 1) ? 0u : itag);
      } else {
        spin_until(tx);
        ASTAMP(8);
      }
    }
    if (!more) in = part;
    poll(v);
    auto late = [&](const uint2* v) {
      return __any_sync(~0u, (or3(xo2(v[0].x, v[1].x, tag), xo2(v[2].x, v[3].x, tag), xo2(v[4].x, v[5].x, tag)) | xo2(v[6].x, v[7].x, tag)) & 1u);
    };
    tok_exp1(); tok_exp2();
    auto reduce = [&]() {
      if (sum) {
        ASTAMP(9);
        int guard = 0;
        while (late(v)) {
          if (++guard > (1 << 22)) TRAP();
          poll(v);
        }
#pragma unroll
        for (int i = 0; i < 4; i++) { v[i].x = add2(v[i].x, v[i + 4].x); v[i].y = add2(v[i].y, v[i + 4].y); }
        const bool hi = ln & 8;
        const uint32_t x0 = add2(v[0].x, v[1].x), x1 = add2(v[2].x, v[3].x), y0 = add2(v[0].y, v[1].y), y1 = add2(v[2].y, v[3].y);
        const uint32_t m0 = hi ? y0 : x0, m1 = hi ? y1 : x1;
        const uint32_t n0 = __shfl_xor_sync(~0u, hi ? x0 : y0, 8), n1 = __shfl_xor_sync(~0u, hi ? x1 : y1, 8);
        float k0 = (blo(m0) + blo(m1)) + (blo(n0) + blo(n1)), k1 = (bhi(m0) + bhi(m1)) + (bhi(n0) + bhi(n1));
        k0 += __shfl_xor_sync(~0u, k0, 16); k1 += __shfl_xor_sync(~0u, k1, 16);
        st_rlx((uint32_t*)outp, (ln & 1) ? pack2(k0, k1) : pack2_tag(k0, k1, itag));
        ASTAMP(10);
        if (T == 0 && w == 0) TSTAMP(14, cta, 2);
        CSTAMP(12 + w, (clk() & ~15u) | min(guard + 1, 15));
      }
      if (more) bar_arrive(N_GO4, 384);
    };
    reduce();
    {
      PIN(ln);
      const uint32_t oa = sb + M_OST + w * 128 + (ln >> 3) * 512 + (ln & 7) * 16;
      const uint32_t a[3][4] = {{0, pt[0], 0, pt[1]}, {0, pt[2], 0, pt[3]}, {0, pt[4], 0, 0}};
      constexpr uint64_t dv = mkdesc(M_V, 2048, 128, 0);
#pragma unroll 1
      for (int h = 0; h < 2; h++) {
        float o[32];
        const uint64_t dh = dv + (uint64_t)(h * 64);
        wg_fence();
        wgmma_rs64<0, 0>(o, a[0], dh); wgmma_rs64<1, 0>(o, a[1], dh + 256); wgmma_rs64<1, 0>(o, a[2], dh + 512);
        wg_commit();
        if (h == 0) {
          ts += __shfl_xor_sync(~0u, ts, 1);
          ts += __shfl_xor_sync(~0u, ts, 2);
          ts = rcp(ts);
          mbar_wait(BAR(B_OFREE), ph ^ 1);
        }
        wg_wait<0>(); reg_fence(o);
        if (h == 1 && ln < 3) mbar_arrive_remote(mapa(BAR(B_VFREE), ln));
#define OT(i) pack2(o[4 * (i) + 2] * ts, o[4 * (i) + 3] * ts)
        stmatrix4(oa + h * 4096, OT(0), OT(1), OT(2), OT(3));
        stmatrix4(oa + h * 4096 + 2048, OT(4), OT(5), OT(6), OT(7));
      }
      const uint32_t z5 = DRAIN(oa);
      __syncwarp();
      if (ln == 0) mbar_arrive(BAR(B_OST) + z5);
      ASTAMP(11);
    }
  }
}

__global__ void __cluster_dims__(3, 1, 1) __launch_bounds__(512, 1) main_kernel(Params p) {
  extern __shared__ __align__(1024) uint8_t sm[];
  const uint32_t sb = smem_u32(sm);
  if ((sb & 0xFFFFFFu) != SBASE) TRAP();
  asm volatile("griddepcontrol.launch_dependents;");
  const int warp = __shfl_sync(~0u, threadIdx.x >> 5, 0);
  const int cta = blockIdx.x, head = cta / 3, c = cta % 3;
  const uint32_t E = __shfl_sync(~0u, *(volatile uint32_t*)&g_epoch + 1, 0);
  uint8_t* const part = G.xch;
  uint8_t* const memg = part + 96 * 16384;

  if (threadIdx.x == 0 && cta == 0) GSTAMP(0, 0);
  if (threadIdx.x < B_NUM) {
    const int i = threadIdx.x;
    const uint32_t cnt = i == B_STG || i == B_STG1 ? 8 : i == B_OST ? 4 : i == B_HAE || i == B_HBE ? 6 : i == B_KFREE || i == B_VFREE ? 12 : i == B_SS ? 2 : i == B_OM ? 5 :
                         i == B_QK ? (c < 2 ? 9 : 1) : i == B_V ? (c < 2 ? 1 : 9) : 1;
    mbar_init(BAR(i), cnt);
    if (i == B_HA || i == B_HB || i == B_STG || i == B_HAE || i == B_HBE || i == B_TFREE)
      asm volatile("mbarrier.arrive.shared::cta.b64 _, [%0], %1;" :: "r"(BAR(i)), "r"(cnt) : "memory");
    asm volatile("fence.mbarrier_init.release.cluster;" ::: "memory");
  }
  if (warp < 8) {
    const int tid = threadIdx.x;
    uint4 wa[6], wb[6];
#pragma unroll
    for (int i = 0; i < 6; i++) {
      const int mi = i >> 1, e = (tid >> 2) + (i & 1) * 64;
      const uint4* src = (const uint4*)(p.wo + (size_t)(head * 128 + e) * 512 + min(3 * mi + c, 7) * 64 + (tid & 3) * 16);
      wa[i] = __ldg(src); wb[i] = __ldg(src + 1);
    }
    stage_weights(sb, (c == 0 ? p.wq : c == 1 ? p.wk : p.wv) + head * 128, 4096, tid, 256);
#pragma unroll
    for (int i = 0; i < 6; i++) {
      const int mi = i >> 1, e = (tid >> 2) + (i & 1) * 64;
      const uint4 a = wa[i], b = wb[i];
      const uint32_t dst = sb + M_WO + mi * 16384 + (e >> 3) * 1024 + (tid & 3) * 256 + (e & 7) * 16;
      sts128(dst, make_uint4(__byte_perm(a.x, a.y, 0x5410), __byte_perm(a.z, a.w, 0x5410), __byte_perm(b.x, b.y, 0x5410), __byte_perm(b.z, b.w, 0x5410)));
      sts128(dst + 128, make_uint4(__byte_perm(a.x, a.y, 0x7632), __byte_perm(a.z, a.w, 0x7632), __byte_perm(b.x, b.y, 0x7632), __byte_perm(b.z, b.w, 0x7632)));
    }
  } else {
    const int i0 = threadIdx.x - 256;
    const uint32_t tag0 = ((E - 1) * (uint32_t)(NSTEP - 1)) & 1;
    for (int i = i0; i < 1024; i += 256) *(uint4*)(part + block_of(head, c) * 16384 + i * 16) = make_uint4(tag0, 0, tag0, 0);
    if (i0 < 16) *(uint32_t*)(memg + i0 * 4096 + 3968) = 0;
    if (i0 < 2) st_rlx(&G.f_choice[block_of(head, c)][i0], 0);
    if (i0 < 8) st_rlx64(&G.sync[i0 >> 2][cta][i0 & 3], 0, 0);
    __threadfence();
    if (i0 < 12) sts32(sb + M_ZERO + i0 * 4, 0);
    if (i0 < 2) { sts32(sb + M_BASE + i0 * 4, clk32() - 65536); sts32(sb + M_BAS2 + i0 * 4, clk32() - 65536); sts32(sb + M_CAND + i0 * 4, (uint32_t)-1); }
  }

  if (warp < 8) {
    asm volatile("setmaxnreg.inc.sync.aligned.u32 176;");
    weight_role(p, sb, warp, cta, c, E, memg);
  } else if (warp < 12) {
    asm volatile("setmaxnreg.inc.sync.aligned.u32 136;");
    attn_role(p, sb, warp - 8, cta, head, c, E, part, memg);
    cluster_sync();
  } else {
    asm volatile("setmaxnreg.dec.sync.aligned.u32 24;");
    const int tid = fresh_tid(), lane = tid & 31;
    const int w = warp - 12;
    cluster_sync();
    if (w != 2) {
      const int tl = w == 0 ? c : w == 1 ? 2 + c : 5 + c;
      int near = 0;
      if (lane == 0) { const int t0 = probe(memg + tl * 8192, 3); near = probe(memg + tl * 8192 + 4096, 3) < t0; }
      near = uni(near);
      if (lane < 3) asm volatile("st.shared::cluster.u32 [%0], %1;" :: "r"(mapa(sb + M_NEAR + tl * 4, lane)), "r"(near) : "memory");
      __syncwarp();
    }
    if (w == 0) {
      int yadj = 0, dmin = 1 << 20; uint32_t prev = 0; bool cprev = false;
      uint32_t s1 = (2 + c) * 8192, s2 = (5 + c) * 8192;
#pragma unroll 1
      for (int T = 0; T < NSTEP - 1; T++) {
        const uint32_t ph = T & 1;
        mbar_wait(BAR(B_SS), ph);
        const uint32_t cq = clk();
        const uint32_t g0 = (uint32_t)gtime64(); uint32_t g1, ce;
        do { g1 = (uint32_t)gtime64(); ce = clk(); } while (g1 == g0);
        const uint32_t tn = g1 * 8 - (((ce - cq) * 37u) >> 3), id = E * 128u + T;
        if (lane < 4) st_rlx64(&G.sync[ph][cta][lane], tn, id);
        if (lane < 3) mbar_expect(BAR(B_LAND + lane), lane ? 9216 : 6144);
        if (T == 0) { s1 += uni(lds32(sb + M_NEAR + (2 + c) * 4)) * 4096; s2 += uni(lds32(sb + M_NEAR + (5 + c) * 4)) * 4096; }
        wait_until(cq + SDLY_);
        int guard = 0; unsigned long long v0, v1, v2;
        for (;;) {
          v0 = ld_rlxu64(G.sync[ph][lane]); v1 = ld_rlxu64(G.sync[ph][lane + 32]); v2 = ld_rlxu64(G.sync[ph][lane + 64]);
          if (__all_sync(~0u, (uint32_t)(v0 >> 32) == id && (uint32_t)(v1 >> 32) == id && (uint32_t)(v2 >> 32) == id)) break;
          if (++guard > (1 << 22)) TRAP();
        }
        const bool cnd = (int)uni(lds32(sb + M_CAND + (T & 3) * 4)) >= 0;
        const int dl = __reduce_max_sync(~0u, max(max((int)((uint32_t)v0 - tn), (int)((uint32_t)v1 - tn)), (int)((uint32_t)v2 - tn)));
        const uint32_t base = uni(cq + ((min(dl, 8 * 4096) * 7) >> 5)) + (T == 0 ? SLOW0_ : T == 1 ? SLOW1_ : 0) +
                              (cnd ? CDLY_ : 0) - (T + 2 < NSEG ? 0 : BOFF_);
        const int dur = (int)(base - prev);
        if (!cnd && !cprev) {
          yadj = T > 2 && dur > dmin + 700 ? min(yadj + YUP_, 400) : max(yadj - YDN_, 0);
          if (T > 1) dmin = min(dmin + 20, dur);
        }
        prev = base; cprev = cnd;
        if (lane == 0) { sts32(sb + M_BASE + ph * 4, base); sts32(sb + M_BAS2 + ph * 4, base + yadj); mbar_arrive(BAR(B_SYNC)); }
        CSTAMP(0, base); CSTAMP(1, clk());
        const uint32_t ts = base + YDLY_ + yadj - (T + 2 >= LAG && T + 2 < NSEG ? 0 : YOFF_);
        const uint8_t* const t0 = memg + uni(lds32(sb + M_NEAR)) * 4096, * const t1 = memg + 8192 + uni(lds32(sb + M_NEAR + 4)) * 4096;
        wait_until(ts);
        e_g2s(sb + M_MEM, t0, 3072, BAR(B_LAND)); e_g2s(sb + M_MEM + 3072, t1, 3072, BAR(B_LAND));
        CSTAMP(2, clk());
        spin_until(ts + Y1_);
        e_mc(sb + M_MEM + (2 + c) * 3072, memg + s1, 3072, BAR(B_LAND + 1), 7);
        CSTAMP(3, clk());
        spin_until(ts + Y2_);
        e_mc(sb + M_MEM + (5 + c) * 3072, memg + s2, 3072, BAR(B_LAND + 2), 7);
        CSTAMP(4, clk());
      }
    } else if (w == 1) {
#pragma unroll 1
      for (int T = 0; T < NSTEP; T++) {
        const uint32_t ph = T & 1;
        const int s = c == 0 ? T : T - LAG;
        const bool act = s >= 0 && s < NSEG;
        mbar_wait(BAR(B_OST), ph);
        if (cta == 0) TSTAMP(2, T, 0);
        fence_async_smem();
        if (T < NSTEP - 1) wait_until(uni(lds32(sb + M_BAS2 + ph * 4)) + ODLY_);
        STAMP(22);
        if (act) paced_st(o_slot(c, s, head), sb + M_OST, OGAP_);
        if (c == 2 && T < NSTEP - 1) {
          mbar_wait(BAR(B_STG1), ph ^ 1);
          mbar_wait(BAR(B_VFREE), ph);
          STAMP(23);
          e_mc(sb + M_V + 2048, G.mix[cta % 6].tok[cta / 6][ph ^ 1] + 8192, 8192, BAR(B_V), 6);
          e_mc(sb + M_V + 2048, G.mix[cta % 6].tok[cta / 6][ph ^ 1], 8192, BAR(B_V), 1);
        }
        bulk_wait();
        __syncwarp();
        e_arrive(BAR(B_OFREE));
        if (cta == 0) TSTAMP(2, T, 1);
        if (act && lane < 8) st_rel(&G.f_o[T][head >> 2][c * 4 + (head & 3)][lane], E);
        __syncwarp();
        if (cta == 0) TSTAMP(2, T, 2);
      }
    } else if (w == 2) {
      unsigned long long run = 0;
      static_assert(LAG >= 2, "config");
      constexpr uint32_t NA = EA / 4 * 4096;
      e_expect(BAR(B_QK), c < 2 ? 2048 : 4096); e_expect(BAR(B_V), c == 0 ? 10240 : c == 1 ? 2048 : 0);
      e_expect(BAR(B_TOK), c == 0 ? 16384 : 0); e_expect(BAR(B_OM), 4096);
      e_expect(BAR(B_HA), NA); e_expect(BAR(B_HB), 65536 - NA);
      wait_eq(&G.f_h1[c == 1 ? 0 : 1], E); fence_async_glob();
      {
        const uint32_t o0 = c == 0 ? NA : 0, o1 = c == 2 ? NA : 32768;
        e_mc(sb + M_H + (c == 1 ? 32768 : 0) + o0, G.seg[c == 1 ? 0 : 1].h[0] + o0, o1 - o0, BAR(c == 2 ? B_HA : B_HB), 7);
      }
      TSTAMP(14, cta, 3);
      if (c == 2) wait_eq(&G.f_h1[2], E);
      mbar_wait(BAR(B_HAE), 1);
      e_expect(BAR(B_HA), NA);
      if (c == 2) { fence_async_glob(); e_mc(sb + M_H, G.seg[2].h[0], NA, BAR(B_HA), 7); }
      int cprev = -1;
#pragma unroll 1
      for (int T = 0; T < NSTEP - 1; T++) {
        const int s1 = T + 2, s2 = T + 2 - LAG;
        const uint32_t ph = T & 1;
        const bool l1 = s1 < NSEG, l2 = s2 >= 0 && s2 < NSEG, la = s1 + 1 < NSEG;
        const bool mine = c == 0 ? l1 : c == 1 ? l2 : la;
        const uint32_t* fl = c != 1 ? &G.f_h1[min(s1 + (c >> 1), NSEG - 1)] : (const uint32_t*)G.f_h2[max(s2, 0)][lane & 3] + 1;
        const uint32_t want = E & 0x1FFFFFu, sh = c != 1 ? 0 : 11;
        mbar_wait(BAR(B_HBE), ph ^ 1);
        const bool early = __all_sync(~0u, ((ld_acq(fl) >> sh) & 0x1FFFFFu) == want);
        mbar_wait(BAR(B_LAND + 2), ph);
        STAMP(16);
        e_expect(BAR(B_HB), (l1 ? 32768 - NA : 0) + (l2 ? 32768 : 0));
        if (mine) {
          if (!early) {
            int guard = 0;
            while (!__all_sync(~0u, ((ld_acq(fl) >> sh) & 0x1FFFFFu) == want)) { __nanosleep(32); if (++guard > (1 << 22)) TRAP(); }
          }
          fence_async_glob();
          if (c == 1) { mbar_wait(BAR(B_QK), ph); spin_until(clk32() + HDLY_); }
          if (c < 2) paced_h(sb + M_H + c * 32768, G.seg[c ? s2 : s1].h[c], c ? 0 : NA, 32768, 4096, BAR(B_HB), HGAP_);
        }
        int cd = -1;
        if (l2) { cd = route_step(s2, E, lane, run); if (cta == 0) TSTAMP(5, s2, 0); }
        if (lane == 0) sts32(sb + M_CAND + ((T + 2) & 3) * 4, (uint32_t)cd);
        __syncwarp();
        STAMP(17);
        mbar_wait(BAR(B_HAE), ph);
        e_expect(BAR(B_HA), la ? NA : 0);
        if (c == 2 && la) {
          spin_until(clk32() + ADLY_);
          STAMP(18);
          paced_h(sb + M_H, G.seg[s1 + 1].h[0], 0, NA, 4096, BAR(B_HA), AGAP_);
        }
        mbar_wait(BAR(B_OST), ph);
        e_expect(BAR(B_QK), c < 2 ? 2048 : cprev >= 0 ? 8192 : 4096);
        e_expect(BAR(B_V), c < 2 ? 10240 : 8192);
        e_expect(BAR(B_TOK), c == 0 ? 8192 : 16384);
        e_expect(BAR(B_OM), 4096);
        cprev = cd;
      }
    } else {
      const uint32_t mytok = sb + M_Q + c * 12288 + 2048, tb = BAR(c < 2 ? B_TOK : B_V);
      mbar_wait(BAR(B_STG1), 0);
      fence_async_smem();
      if (c) e_s2g(G.mix[cta % 6].tok[cta / 6][1], sb + M_TST, 8192);
#pragma unroll 1
      for (int T = 0; T < NSTEP - 1; T++) {
        const uint32_t ph = T & 1;
        uint8_t* const tok = G.mix[cta % 6].tok[cta / 6][ph ^ 1];
        mbar_wait(BAR(B_STG), ph ^ 1);
        fence_async_smem();
        if (cta == 0 && (T == 0 || T == NSEG || T == NSTEP - 2)) GSTAMP(0, T == 0 ? 2 : T == NSEG ? 3 : 4);
        if (T > 0) mbar_wait(BAR(B_QK), ph);
        STAMP(20);
        paced_st(tok + 8192, sb + M_TST + 8192, TGAP_);
        bulk_wait();
        __syncwarp();
        e_arrive(BAR(B_TFREE));
        if (T == 0) e_mc(mytok, tok + 8192, 8192, tb, 1);
        STAMP(21);
        if (c < 2) {
          mbar_wait(BAR(B_KFREE), ph);
          spin_until(clk32() + KDLY_);
          STAMP(23);
          if (c) e_mc(mytok, tok, 8192, tb, 1);
          e_mc(mytok, tok + 8192, 8192, tb, 6);
        }
        mbar_wait(BAR(B_STG1), ph ^ 1);
        fence_async_smem();
        wait_until(uni(lds32(sb + M_BAS2 + ph * 4)) + TDLY_);
        if (c) paced_st(G.mix[cta % 6].tok[cta / 6][ph], sb + M_TST, T1GAP_);
        STAMP(24);
      }
      bulk_wait();
    }
    __syncwarp();
    cluster_sync();
  }
}

constexpr uint32_t A_RING = 0;
constexpr int A_NST = 6;
constexpr uint32_t A_STG = A_RING + A_NST * 8192;
constexpr uint32_t A_WD = A_STG + 8192;
constexpr uint32_t A_WG = A_WD + 57344;
constexpr uint32_t A_WU = A_WG + 57344;
constexpr uint32_t A_XN = A_WU + 57344;
constexpr uint32_t A_BAR = A_XN + 2048;
constexpr uint32_t A_TOTAL = A_BAR + 256;
static_assert(A_TOTAL <= 232448, "aux smem");

__device__ __forceinline__ uint32_t ptag(int s) { return ((s / PRING) & 1) ^ 1; }
static_assert((NSEG / PRING) % 2 == 0, "tags");
__device__ __forceinline__ void load_row(uint32_t* v, const void* row, int lane) {
  const uint4 a = __ldcg((const uint4*)row + lane), b = __ldcg((const uint4*)row + 32 + lane);
  v[0] = a.x; v[1] = a.y; v[2] = a.z; v[3] = a.w; v[4] = b.x; v[5] = b.y; v[6] = b.z; v[7] = b.w;
}
__device__ __forceinline__ void store_row(void* row, const uint32_t* v, int lane) {
  ((uint4*)row)[lane] = make_uint4(v[0], v[1], v[2], v[3]); ((uint4*)row)[32 + lane] = make_uint4(v[4], v[5], v[6], v[7]);
}
__device__ __forceinline__ void store_img(uint8_t* img, int r, const uint32_t* v, int lane) {
  uint8_t* b = img + (lane >> 3) * 4096 + (r >> 3) * 1024 + (r & 7) * 128 + (((lane ^ r) & 7) << 4);
  *(uint4*)b = make_uint4(v[0], v[1], v[2], v[3]);
  *(uint4*)(b + 16384) = make_uint4(v[4], v[5], v[6], v[7]);
}
template <int NT> __device__ __forceinline__ void ln_rows(const uint32_t (*v)[8], uint32_t (*y)[8]) {
  float c[NT], sm[NT], sq[NT];
#pragma unroll
  for (int k = 0; k < NT; k++) {
    c[k] = blo(__shfl_sync(~0u, v[k][0], 0));
    float s0 = 0.f, s1 = 0.f, q0 = 0.f, q1 = 0.f;
#pragma unroll
    for (int i = 0; i < 8; i++) { const float a = blo(v[k][i]) - c[k], b = bhi(v[k][i]) - c[k]; s0 += a; s1 += b; q0 = fmaf(a, a, q0); q1 = fmaf(b, b, q1); }
    sm[k] = s0 + s1; sq[k] = q0 + q1;
  }
#pragma unroll
  for (int o = 16; o > 0; o >>= 1)
#pragma unroll
    for (int k = 0; k < NT; k++) {
      sm[k] += __shfl_xor_sync(~0u, sm[k], o); sq[k] += __shfl_xor_sync(~0u, sq[k], o);
    }
#pragma unroll
  for (int k = 0; k < NT; k++) {
    const float dm = sm[k] * (1.f / 512.f), var = fmaxf(fmaf(-dm, dm, sq[k] * (1.f / 512.f)), 0.f);
    const float mb = rbf(c[k] + dm), inv = rcp(rbf(sqrt_fast(rbf(rbf(var) + 1e-5f))));
#pragma unroll
    for (int i = 0; i < 8; i++) { const uint32_t a = pack2(blo(v[k][i]) - mb, bhi(v[k][i]) - mb); y[k][i] = pack2(blo(a) * inv, bhi(a) * inv); }
  }
}
__device__ __forceinline__ void input_ln_pair(const bf16* x, int s, int pr, int lane) {
  uint32_t v[2][8], y[2][8];
  load_row(v[0], x + (size_t)(s * 32 + 2 * pr) * 512, lane); load_row(v[1], x + (size_t)(s * 32 + 2 * pr + 1) * 512, lane);
  ln_rows<2>(v, y);
  store_img(G.seg[s].h[0], 2 * pr, y[0], lane); store_img(G.seg[s].h[0], 2 * pr + 1, y[1], lane);
}
__device__ __forceinline__ float load_wr(uint32_t* wv, const bf16* wr, int lane) {
  load_row(wv, wr, lane);
  float wsum = 0.f;
#pragma unroll
  for (int i = 0; i < 8; i++) wsum += blo(wv[i]) + bhi(wv[i]);
#pragma unroll
  for (int o = 16; o > 0; o >>= 1) wsum += __shfl_xor_sync(~0u, wsum, o);
  return wsum;
}

template <bool FAST>
__device__ __forceinline__ unsigned long long token_post(int st, int tk, const bf16* res, bf16* dst, bf16* req, unsigned long long best,
                                                         const uint32_t* wv, float wsum, uint32_t E, int lane) {
  const int s = tk >> 5;
  uint32_t x[8];
  load_row(x, res, lane);
  {
    int guard = 0;
    while (__popc(__ballot_sync(~0u, ld_rlx(G.f_acc[st][s][lane]) == E)) < (FAST ? 24 : 32)) { __nanosleep(FAST ? 20 : 100); if (++guard > (1 << 22)) TRAP(); }
  }
  if (tk == s * 32 && st == 0 && lane == 0) TSTAMP(4, s, 0);
  {
    const uint8_t* pp = pp_slot(st, s) + (lane >> 4) * 8192 + (tk & 31) * 256 + (((lane & 15) ^ (tk & 7)) << 4);
    const uint32_t tag = ptag(s);
    uint4 q[8][2];
#define PLD(k, h) q[k][h] = ld_rlx128<(k) * 32768 + (h) * 16384>(pp)
#define PLD8(h) PLD(0, h); PLD(1, h); PLD(2, h); PLD(3, h); PLD(4, h); PLD(5, h); PLD(6, h); PLD(7, h)
#define PBAD(h) __any_sync(~0u, (or3(xo2(q[0][h].x, q[1][h].x, tag), xo2(q[2][h].x, q[3][h].x, tag), xo2(q[4][h].x, q[5][h].x, tag)) | xo2(q[6][h].x, q[7][h].x, tag)) & ~lane & 1u)
#define PSUM(f, h, m) (((f(q[0][h].m) + f(q[1][h].m)) + (f(q[2][h].m) + f(q[3][h].m))) + ((f(q[4][h].m) + f(q[5][h].m)) + (f(q[6][h].m) + f(q[7][h].m))))
    const uint32_t eye = (lane >> 2) == 2 * (lane & 3) ? 0x3f80u : (lane >> 2) == 2 * (lane & 3) + 1 ? 0x3f800000u : 0u;
    auto padd = [&](int h) {
      if (FAST) {
        float u[4] = {0.f, 0.f, 0.f, 0.f}, v[4] = {0.f, 0.f, 0.f, 0.f};
#pragma unroll
        for (int k = 0; k < 8; k++) { hmma8(u, q[k][h].x, q[k][h].y, eye); hmma8(v, q[k][h].z, q[k][h].w, eye); }
        x[4 * h] = add2(x[4 * h], pack2(u[0], u[1])); x[4 * h + 1] = add2(x[4 * h + 1], pack2(u[2], u[3]));
        x[4 * h + 2] = add2(x[4 * h + 2], pack2(v[0], v[1])); x[4 * h + 3] = add2(x[4 * h + 3], pack2(v[2], v[3]));
      } else {
        x[4 * h] = add2(x[4 * h], pack2(PSUM(blo, h, x), PSUM(bhi, h, x))); x[4 * h + 1] = add2(x[4 * h + 1], pack2(PSUM(blo, h, y), PSUM(bhi, h, y)));
        x[4 * h + 2] = add2(x[4 * h + 2], pack2(PSUM(blo, h, z), PSUM(bhi, h, z))); x[4 * h + 3] = add2(x[4 * h + 3], pack2(PSUM(blo, h, w), PSUM(bhi, h, w)));
      }
    };
    int guard = 0;
    PLD8(0);
    if (FAST) { PLD8(1); }
    while (PBAD(0)) { if (++guard > (1 << 20)) TRAP(); PLD8(0); }
    padd(0);
    if (!FAST) { PLD8(1); }
    while (PBAD(1)) { if (++guard > (1 << 20)) TRAP(); PLD8(1); }
    padd(1);
  }
  const float c = blo(__shfl_sync(~0u, x[0], 0));
  float s0 = 0.f, s1 = 0.f, q0 = 0.f, q1 = 0.f, r0 = 0.f, r1 = 0.f;
#pragma unroll
  for (int i = 0; i < 8; i++) {
    const float a = blo(x[i]) - c, b = bhi(x[i]) - c;
    s0 += a; s1 += b; q0 = fmaf(a, a, q0); q1 = fmaf(b, b, q1); r0 = fmaf(a, blo(wv[i]), r0); r1 = fmaf(b, bhi(wv[i]), r1);
  }
  s0 += s1; q0 += q1; r0 += r1;
#pragma unroll
  for (int o = 16; o > 0; o >>= 1) { s0 += __shfl_xor_sync(~0u, s0, o); q0 += __shfl_xor_sync(~0u, q0, o); r0 += __shfl_xor_sync(~0u, r0, o); }
  const float dm = s0 * (1.f / 512.f), m = c + dm, var = fmaxf(fmaf(-dm, dm, q0 * (1.f / 512.f)), 0.f);
  const float mb = rbf(m), inv = rcp(rbf(sqrt_fast(rbf(rbf(var) + 1e-5f))));
  const uint32_t nmb = pack2(-mb, -mb);
  const unsigned long long wd = rword(E, tk, fmaf(c - mb, wsum, r0) * inv);
  uint32_t xn[8], x2[8];
#pragma unroll
  for (int i = 0; i < 8; i++) { const uint32_t d = add2(x[i], nmb); xn[i] = pack2(blo(d) * inv, bhi(d) * inv); x2[i] = add2(x[i], xn[i]); }
  if (st == 0) {
    const float mb2 = rbf(fmaf(m - mb, inv, m)), inv2 = rcp(rbf(sqrt_fast(rbf(rbf(var * (1.f + inv) * (1.f + inv)) + 1e-5f))));
    const uint32_t nmb2 = pack2(-mb2, -mb2);
    uint32_t h[8];
#pragma unroll
    for (int i = 0; i < 8; i++) { const uint32_t d2 = add2(x2[i], nmb2); h[i] = pack2(blo(d2) * inv2, bhi(d2) * inv2); }
    store_img(G.seg[s].h[1], tk & 31, h, lane);
  }
  store_row(dst, x2, lane);
  if (wd > best) { store_row(req, xn, lane); store_row(req + 512, x, lane); }
  return wd;
}

__device__ __forceinline__ void ffn_slice(uint32_t sb, const bf16* xn, float* yacc, uint32_t* flag, uint32_t E, int t, bool urgent) {
  const int w = t >> 5, g = (t >> 2) & 7;
  if (t == 0 && urgent) sts32(sb + A_BAR + 160, 1);
  { const uint2 u = __ldcg((const uint2*)xn + t); asm volatile("st.shared.v2.u32 [%0], {%1,%2};" :: "r"(sb + A_XN + t * 8), "r"(u.x), "r"(u.y) : "memory"); }
  fence_async_smem();
  bar_sync(4, 128);
  float ga[4], ua[4];
  constexpr uint64_t da = mkdesc(A_WG, 896, 128, 0), db = mkdesc(A_XN, 16, 128, 0);
  wg_fence();
  wgmma_ss8<0, 1, 0>(ga, da, db); wgmma_ss8<0, 1, 0>(ua, da + (A_WU - A_WG) / 16, db);
#pragma unroll
  for (int ks = 1; ks < 32; ks++) { wgmma_ss8<1, 1, 0>(ga, da + ks * 112, db + ks * 2); wgmma_ss8<1, 1, 0>(ua, da + (A_WU - A_WG) / 16 + ks * 112, db + ks * 2); }
  wg_commit(); wg_wait<0>(); reg_fence(ga); reg_fence(ua);
  if ((t & 3) == 0) {
#pragma unroll
    for (int h = 0; h < 2; h++) {
      const float gs = rbf(ga[2 * h]), us = rbf(ua[2 * h]);
      const float v = 16 * w + 8 * h < 56 ? rbf(gs * rcp(1.f + __expf(-gs))) * us : 0.f;
      asm volatile("st.shared.u16 [%0], %1;" :: "r"(sb + A_XN + 1280 + (16 * w + 8 * h + g) * 2), "h"((unsigned short)pack2(v, 0.f)) : "memory");
    }
  }
  fence_async_smem();
  bar_sync(4, 128);
#pragma unroll 1
  for (int j = 0; j < 2; j++) {
    float y[4][4];
    const uint64_t dd = mkdesc(A_WD, 8192, 128, 0) + (uint64_t)(j * 256);
    wg_fence();
#pragma unroll
    for (int m = 0; m < 4; m++) {
      wgmma_ss8<0, 1, 0>(y[m], dd + m * 64, mkdesc(A_XN + 1280, 16, 128, 0));
#pragma unroll
      for (int ks = 1; ks < 4; ks++) wgmma_ss8<1, 1, 0>(y[m], dd + m * 64 + ks * 1024, mkdesc(A_XN + 1280 + ks * 32, 16, 128, 0));
    }
    wg_commit(); wg_wait<0>();
#pragma unroll
    for (int m = 0; m < 4; m++) {
      reg_fence(y[m]);
      if ((t & 3) == 0) { float* o = yacc + j * 256 + m * 64 + 16 * w + g; o[0] = y[m][0]; o[8] = y[m][2]; }
    }
  }
  bar_sync(4, 128);
  if (t < 8) { sts32(sb + A_BAR + 160, 0); st_rel(flag + t, E); }
  __syncwarp();
}

__device__ __forceinline__ void ffn_gather(uint32_t sb, int q, int j, uint32_t E, int lane) {
  wait_all(G.f_y[q][4 * j + (lane & 3)], E);
  float4 y[4][4];
#pragma unroll
  for (int k = 0; k < 4; k++)
#pragma unroll
    for (int i = 0; i < 4; i++) y[k][i] = __ldcg((const float4*)G.y[q & 7][4 * j + k] + i * 32 + lane);
#pragma unroll
  for (int i = 0; i < 4; i++)
    sts128f(sb + 1024 + j * 2048 + i * 512 + lane * 16, (y[0][i].x + y[1][i].x) + (y[2][i].x + y[3][i].x), (y[0][i].y + y[1][i].y) + (y[2][i].y + y[3][i].y),
            (y[0][i].z + y[1][i].z) + (y[2][i].z + y[3][i].z), (y[0][i].w + y[1][i].w) + (y[2][i].w + y[3][i].w));
  bar_sync(9, 256);
}
__device__ __forceinline__ void ffn_finish(uint32_t sb, int q, const bf16* req, float r, uint32_t E, int lane, uint32_t* v) {
  if (lane == 0) sts32(sb + 16, q);
  bar_sync(8, 256);
  uint32_t xn[8];
  load_row(xn, req, lane); load_row(v, req + 512, lane);
  const float rs = rbf(1.f / (1.f + __expf(-rbf(r))));
  ffn_gather(sb, q, 7, E, lane);
#pragma unroll
  for (int i = 0; i < 4; i++) {
    float y[4] = {0.f, 0.f, 0.f, 0.f};
#pragma unroll
    for (int j = 0; j < 8; j++) {
      const uint4 u = lds128(sb + 1024 + j * 2048 + (i >> 1) * 1024 + lane * 32 + (i & 1) * 16);
      y[0] += __uint_as_float(u.x); y[1] += __uint_as_float(u.y); y[2] += __uint_as_float(u.z); y[3] += __uint_as_float(u.w);
    }
    v[2 * i] = add2(v[2 * i], add2(xn[2 * i], pack2(rbf(y[0]) * rs, rbf(y[1]) * rs)));
    v[2 * i + 1] = add2(v[2 * i + 1], add2(xn[2 * i + 1], pack2(rbf(y[2]) * rs, rbf(y[3]) * rs)));
  }
}

__global__ void __launch_bounds__(512, 1) aux_kernel(Params p) {
  extern __shared__ __align__(1024) uint8_t sm[];
  const uint32_t sb = smem_u32(sm);
  if ((sb & 0xFFFFFFu) != SBASE) TRAP();
  const int warp = __shfl_sync(~0u, threadIdx.x >> 5, 0);
  const int cta = blockIdx.x;
  const uint32_t E = __shfl_sync(~0u, *(volatile uint32_t*)&g_epoch + 1, 0);
  const uint32_t bars = sb + A_BAR;

  if (cta < 32) {
    const int cg = cta & 3, kg = cta >> 2;
    if (threadIdx.x == 0) {
      for (int i = 0; i < A_NST; i++) { mbar_init(bars + 8 * i, 1); mbar_init(bars + 64 + 8 * i, 2); }
      mbar_init(bars + 128, 8); mbar_init(bars + 136, 8); mbar_init(bars + 144, 1);
      sts32(bars + 160, 0);
      asm volatile("fence.mbarrier_init.release.cluster;" ::: "memory");
    }
    if (warp < 8) {
      asm volatile("setmaxnreg.inc.sync.aligned.u32 176;");
      const int tid = fresh_tid(), lane = tid & 31;
      uint32_t W[32][4];
      bar_arrive(3, 384);
      stage_weights(sb + A_WD, p.wo + (size_t)kg * 512 * 512 + cg * 128, 512, tid, 256);
      cp_async_wait();
      bar_sync(1, 256);
      load_frags(W, sb + A_WD, warp >> 2, warp & 3, lane);
      PIN(W[31][3]);
      bar_sync(1, 256);
      bar_arrive(2, 384);
      const uint32_t so = sb + A_STG + ((lane >> 4) * 8 + (lane & 7)) * 256 + (((warp * 2 + ((lane >> 3) & 1)) ^ (lane & 7)) << 4);
      const uint32_t tm = lane < 4 ? 0x00010001u : 0u;
      int stage = 0; uint32_t ph = 0, job = 0;
#pragma unroll 1
      for (int T = 0; T < NSTEP; T++) {
#pragma unroll 1
        for (int k = 0; k < 3; k++) {
          const int st = k == 0 ? 0 : 3 - k, s = st == 0 ? T : T - LAG;
          if (s < 0 || s >= NSEG) continue;
          float d[16];
#pragma unroll
          for (int hh = 0; hh < 4; hh++) {
            mbar_wait(bars + 8 * stage, ph);
            while (uni(lds32(bars + 160))) __nanosleep(100);
            const uint64_t db = mkdesc(A_RING, 512, 128, 0) + (uint64_t)(stage * 512);
            wg_fence();
            if (hh == 0) wgmma_rs32<0, 0>(d, W[0], db); else wgmma_rs32<1, 0>(d, W[hh * 8], db);
#pragma unroll
            for (int ks = 1; ks < 8; ks++) wgmma_rs32<1, 0>(d, W[hh * 8 + ks], db + ks * 64);
            wg_commit();
            if (hh > 0) { wg_wait<1>(); if ((tid & 127) == 0) mbar_arrive(bars + 64 + 8 * (stage == 0 ? A_NST - 1 : stage - 1)); }
            if (++stage == A_NST) { stage = 0; ph ^= 1; }
          }
          mbar_wait(bars + 144, (job & 1) ^ 1);
          wg_wait<0>(); reg_fence(d);
          if ((tid & 127) == 0) mbar_arrive(bars + 64 + 8 * (stage == 0 ? A_NST - 1 : stage - 1));
          if (cta == 0 && tid == 0) TSTAMP(6, T, k);
          const uint32_t tv = tm * ptag(s);
#define TG(i) ((pack2(d[2 * (i)], d[2 * (i) + 1]) & ~tm) | tv)
          stmatrix4_t(so, TG(0), pack2(d[2], d[3]), TG(2), pack2(d[6], d[7]));
          stmatrix4_t(so + 4096, TG(4), pack2(d[10], d[11]), TG(6), pack2(d[14], d[15]));
          fence_async_smem();
          __syncwarp();
          if (lane == 0) mbar_arrive(bars + 128 + 8 * (job & 1));
          job++;
        }
      }
    } else if (warp < 12) {
      asm volatile("setmaxnreg.dec.sync.aligned.u32 120;");
      const int tid = fresh_tid(), lane = tid & 31;
      const int w = warp - 8, t = tid - 256;
      uint32_t wv[8];
      const float wsum = load_wr(wv, p.wr, lane);
#pragma unroll 1
      for (int s = cta + 4; s < NSEG; s += 32) {
#pragma unroll 1
        for (int pr = w; pr < 16; pr += 4) input_ln_pair(p.x, s, pr, lane);
        bar_sync(4, 128);
        if (t == 0) st_rel(&G.f_h1[s], E);
      }
      bar_sync(2, 384);
      { int guard = 0; while (ld_rlx(&G.f_loaded[cta]) != E) { __nanosleep(200); if (++guard > (1 << 22)) TRAP(); } }
#pragma unroll 1
      for (int i = t; i < 512 * 7; i += 128) {
        const int k = i / 7, pc = i % 7;
        cp_async16(sb + A_WG + (k >> 3) * 896 + pc * 128 + (k & 7) * 16, p.wg + (size_t)k * 1792 + cta * 56 + pc * 8);
        cp_async16(sb + A_WU + (k >> 3) * 896 + pc * 128 + (k & 7) * 16, p.wu + (size_t)k * 1792 + cta * 56 + pc * 8);
        cp_async16(sb + A_WD + (i >> 9) * 8192 + (i & 63) * 128 + ((i >> 6) & 7) * 16, p.wd + (size_t)cta * 56 * 512 + i * 8);
        if ((i >> 7) % 4 == 3) cp_async_wait();
      }
      cp_async_wait();
      fence_async_smem();
      bar_sync(4, 128);
      const int tj = (cta * 4 + w) & 31, st = 1 + ((cta >> 3) & 1), sq = cta >> 4;
      unsigned long long run = 0, run2 = 0, best = 0, hist = 0;
      uint32_t open = 0;
#pragma unroll 1
      for (int i = 0; i <= NSTEP; i++) {
        int tok = -1; const bf16* req = nullptr;
        if (i < NSEG) {
          const int cd = (int)uni(route_step(i, E, lane, run));
          run = __shfl_sync(~0u, run, 0);
          hist = hist << 8 | (uint32_t)(cd + 1);
          if (cd >= 0) { tok = rtok(run); req = G.seg[tok >> 5].req1[tok & 31][0]; }
        } else {
          const unsigned long long m = wait_words(G.f_l2[i - NSEG], E);
          const unsigned long long n = ld_rlxu64(G.f_l2[min(i - NSEG + 1 + (lane & 7), LAG)]);
          const bool over = bar_or(4, 128, rfresh(n, E) && n != m);
          if (m != run2 && !over) { run2 = m; tok = rtok(m); req = G.req2[(tok >> 5) < (rtok(run) >> 5) ? 0 : 1][tok][0]; }
        }
        tok = __shfl_sync(~0u, tok, 0);
        if (tok >= 0) {
          if (cta == 0 && t == 0) TSTAMP(8, i & 127, 0);
          ffn_slice(sb, req, G.y[i & 7][cta], G.f_y[i][cta], E, t, i < NSEG);
          if (cta == 0 && t == 0) TSTAMP(8, i & 127, 1);
        }
        const int s = i - LAG;
        if (s < 0 || i >= NSEG) continue;
        const int cd = (int)((hist >> (8 * LAG)) & 255) - 1;
        if (cd >= 0 && st == 2) best = 0;
        const int ts = rtok(run) >> 5;
        if ((s & 1) == sq) {
          const int tk = s * 32 + tj;
          unsigned long long wd = (unsigned long long)E << 43;
          if (st == 1 ? s < ts || i < NSEG - 1 : s >= ts) {
            if (st == 2 && cd == tj) wait_eq(&G.f_hc[s], E);
            wd = token_post<false>(st, tk, st == 2 && cd == tj ? G.x2c[s] : G.seg[tk >> 5].x2[tk & 31],
                                   st == 2 || s < ts ? p.out + (size_t)tk * 512 : G.seg[s].n[tj], G.req2[st - 1][tk][0], best, wv, wsum, E, lane);
            best = max(best, wd);
            if (st == 1 && s >= ts) open |= 1u << (s >> 1);
          }
          __syncwarp();
          if (lane < 4) st_rel64(&G.f_w2[st - 1][s][tj][lane], wd);
          __syncwarp();
        }
        if (st == 1) {
          if (i == NSEG - 1 && t == 0 && cta == 0) GSTAMP(1, 0);
#pragma unroll 1
          for (int n = i == NSEG - 1 ? 32 : 2; n > 0 && open; n--) {
            const int s0 = 2 * (__ffs(open) - 1) + sq;
            if (s0 >= ts) break;
            open &= open - 1;
            uint32_t v[8];
            load_row(v, G.seg[s0].n[tj], lane);
            wait_words(G.f_w2[1][s0][tj], E);
            store_row(p.out + (size_t)(s0 * 32 + tj) * 512, v, lane);
          }
          if (i == NSEG - 1) {
            __syncwarp();
            if (lane == 0) st_rel(&G.f_cp[sq * 32 + tj], E);
            if (t == 0 && cta == 0) GSTAMP(1, 3);
          }
        }
      }
    } else {
      asm volatile("setmaxnreg.dec.sync.aligned.u32 40;");
      const int tid = fresh_tid(), lane = tid & 31;
      const int w = warp - 12;
      bar_sync(3, 384);
      if (w == 0) {
        int stage = 0; uint32_t ph = 1;
#pragma unroll 1
        for (int T = 0; T < NSTEP; T++) {
#pragma unroll 1
          for (int k = 0; k < 3; k++) {
            const int st = k == 0 ? 0 : 3 - k, s = st == 0 ? T : T - LAG;
            if (s < 0 || s >= NSEG) continue;
            const uint32_t* fl = G.f_o[T][kg][st * 4 + (lane & 3)];
            uint32_t ready = 0; int guard = 0;
#pragma unroll 1
            for (int hh = 0; hh < 4; hh++) {
              while (!((ready >> hh) & 1)) {
                ready = __ballot_sync(~0u, ld_rlx(fl) == E);
                if (++guard > (1 << 23)) TRAP();
              }
              fence_async_glob();
              mbar_wait(bars + 64 + 8 * stage, ph);
              e_expect(bars + 8 * stage, 8192);
              e_g2s(sb + A_RING + stage * 8192, o_slot(st, s, kg * 4 + hh), 8192, bars + 8 * stage);
              if (++stage == A_NST) { stage = 0; ph ^= 1; }
            }
          }
          if (cta == 0 && lane == 0) TSTAMP(3, T, 0);
        }
      } else if (w < 3) {
        uint32_t job = 0;
#pragma unroll 1
        for (int T = 0; T < NSTEP; T++) {
#pragma unroll 1
          for (int k = 0; k < 3; k++) {
            const int st = k == 0 ? 0 : 3 - k, s = st == 0 ? T : T - LAG;
            if (s < 0 || s >= NSEG) continue;
            if ((job++ & 1) != w - 1) continue;
            if (s >= PRING) wait_words(st == 0 ? G.f_h2[s - PRING][lane & 3] : G.f_w2[st - 1][s - PRING][lane], E);
            mbar_wait(bars + 128 + 8 * (w - 1), ((job - 1) >> 1) & 1);
            if (cta == 0 && st == 0) TSTAMP(7, s, 0);
            e_s2g(pp_slot(st, s) + cta * 8192, sb + A_STG, 8192);
            if (lane < 8) st_rlx(&G.f_acc[st][s][cta][lane], E);
            asm volatile("cp.async.bulk.commit_group;\n cp.async.bulk.wait_group.read 0;" ::: "memory");
            __syncwarp();
            e_arrive(bars + 144);
            __syncwarp();
            if (cta == 0 && st == 0) TSTAMP(7, s, 1);
          }
        }
        bulk_wait();
      }
    }
  } else {
    const int tid = fresh_tid(), lane = tid & 31;
    const int qd = cta - 32;
    input_ln_pair(p.x, qd, warp, lane);
    bar_sync(6, 512);
    if (tid == 0) st_rel(&G.f_h1[qd], E);
    volatile int* bc = (volatile int*)sm;
    if (warp == 15) {
      unsigned long long run = 0;
      unsigned long long b2[2][2] = {{0, 0}, {0, 0}};
      auto track = [&](int s) {
#pragma unroll
        for (int k = 0; k < 2; k++) {
          const unsigned long long m = warp_max<16>(wait_words(G.f_w2[k][s][lane], E));
          if (lane == (s & 31)) { if (s < 32) b2[k][0] = m; else b2[k][1] = m; }
        }
      };
#pragma unroll 1
      for (int s = 0; s < NSEG; s++) {
        const int cd = route_step(s, E, lane, run);
        if (cd >= 0 && qd == (s & 1)) {
          uint32_t v[1][8], h[1][8];
          ffn_finish(sb, s, G.seg[s].req1[cd][0], rscore(run), E, lane, v[0]);
          if (lane == 0) TSTAMP(8, s, 2);
          ln_rows<1>(v, h);
#pragma unroll
          for (int i = 0; i < 8; i++) st_rlx64(&G.hc[s][(i >> 2) * 128 + 4 * lane + (i & 3)], h[0][i], E);
          if (lane == 0) TSTAMP(8, s, 3);
          store_row(G.x2c[s], v[0], lane);
          __syncwarp();
          if (lane == 0) st_rel(&G.f_hc[s], E);
        }
        if (qd == 2 && s > LAG) track(s - LAG - 1);
      }
      wait_eq(&G.f_hc[rtok(run) >> 5], E);
      if (lane == 0) *bc = rtok(run);
      bar_sync(7, 288);
      if (qd == 2) {
        uint32_t v[8];
        const int ts = rtok(run) >> 5;
        track(NSEG - LAG - 1);
        run = 0;
        int kl = 0;
#pragma unroll 1
        for (int k = 0; k <= LAG; k++) {
          const int s = NSEG - LAG - 1 + k;
          const unsigned long long m = warp_max<16>(k == 0 ? max(lane < ts ? b2[0][0] : b2[1][0], lane + 32 < ts ? b2[0][1] : b2[1][1])
                                                           : wait_words(G.f_w2[s < ts ? 0 : 1][s][lane], E));
          const bool lead = m > run;
          if (lead) { run = m; __threadfence(); }
          if (lane < 4) st_rlx64(&G.f_l2[k][lane], (uint32_t)run, (uint32_t)(run >> 32));
          if (lead) kl = k;
          if (k == LAG - 1) { wait_all(&G.f_cp[lane], E); wait_all(&G.f_cp[32 + lane], E); }
          if (k == LAG - 1 || (k == LAG && lead)) ffn_finish(sb, NSEG + kl, G.req2[(rtok(run) >> 5) < ts ? 0 : 1][rtok(run)][0], rscore(run), E, lane, v);
        }
        if (lane == 0) GSTAMP(1, 1);
        store_row(p.out + (size_t)rtok(run) * 512, v, lane);
        if (lane == 0) GSTAMP(1, 2);
      }
      if (lane == 0) sts32(sb + 16, (uint32_t)-1);
      bar_sync(8, 256);
      if (qd == 2) {
        asm volatile("griddepcontrol.wait;" ::: "memory");
        if (lane == 0) *(volatile uint32_t*)&g_epoch = E;
      }
    } else if (warp >= 8) {
#pragma unroll 1
      for (;;) {
        bar_sync(8, 256);
        const int q = (int)uni(lds32(sb + 16));
        if (q < 0) break;
        ffn_gather(sb, q, warp - 8, E, lane);
      }
    } else {
      uint32_t wv[8];
      const float wsum = load_wr(wv, p.wr, lane);
      unsigned long long best = 0;
      int ttok = 0;
#pragma unroll 1
      for (int i = 0; i < NSTEP; i++) {
        const bool last = i >= NSEG;
        if (i == NSEG) { bar_sync(7, 288); ttok = *bc; best = 0; }
        const int s = last ? i - LAG : i, st = !last ? 0 : s < (ttok >> 5) ? 1 : 2;
        const int tk = s * 32 + qd * 8 + warp;
        const unsigned long long wd = token_post<true>(st, tk, !last ? p.x + (size_t)tk * 512 : tk == ttok ? G.x2c[s] : G.seg[tk >> 5].x2[tk & 31],
                                                 last ? p.out + (size_t)tk * 512 : G.seg[s].x2[tk & 31], last ? G.req2[st - 1][tk][0] : G.seg[s].req1[tk & 31][0], best, wv, wsum, E, lane);
        best = max(best, wd);
        volatile unsigned long long* ws = (volatile unsigned long long*)(sm + 64) + (i & 1) * 8;
        if (lane == 0) ws[warp] = wd;
        const unsigned long long lead = i == NSTEP - 1 ? ld_rlxu64(G.f_l2[LAG - 1]) : 0;
        bar_sync(5, 256);
        if (warp == 0) {
          if (qd == 0 && lane == 0) TSTAMP(4, i, 1);
          if (!last) { const unsigned long long m = warp_max<4>(ws[lane & 7]); if (lane < 4) st_rel64(&G.f_h2[s][qd][lane], m); }
          else {
            const unsigned long long v = ws[lane >> 2];
            if (!__all_sync(~0u, rfresh(lead, E) && v < lead)) __threadfence();
            st_rlx64(&G.f_w2[st - 1][s][qd * 8 + (lane >> 2)][lane & 3], (uint32_t)v, (uint32_t)(v >> 32));
            asm volatile("st.relaxed.gpu.global.u64 [%0], %1;" :: "l"(&G.f_w2[2 - st][s][qd * 8 + (lane >> 2)][lane & 3]), "l"((unsigned long long)E << 43) : "memory");
          }
          if (qd == 0 && lane == 0) TSTAMP(4, i, 2);
        }
        __syncwarp();
      }
    }
  }
}

}

extern "C" void kernel_launch(void* const* d_in, const int* in_sizes, int n_in, void* d_out, int out_size) {
  (void)in_sizes; (void)n_in; (void)out_size;
  static bool init = false;
  if (!init) {
    cudaFuncSetAttribute(main_kernel, cudaFuncAttributeMaxDynamicSharedMemorySize, M_TOTAL);
    cudaFuncSetAttribute(aux_kernel, cudaFuncAttributeMaxDynamicSharedMemorySize, A_TOTAL);
    init = true;
  }
  Params p;
  p.x = (const bf16*)d_in[0]; p.mem0 = (const bf16*)d_in[1]; p.wq = (const bf16*)d_in[2]; p.wk = (const bf16*)d_in[3];
  p.wv = (const bf16*)d_in[4]; p.wo = (const bf16*)d_in[5]; p.wr = (const bf16*)d_in[8]; p.wg = (const bf16*)d_in[9];
  p.wu = (const bf16*)d_in[10]; p.wd = (const bf16*)d_in[11]; p.out = (bf16*)d_out; p.zero = 0; p.zero2 = 0;
  cudaStream_t st = cudaStreamPerThread;
  main_kernel<<<96, 512, M_TOTAL, st>>>(p);
  cudaLaunchConfig_t cfg = {};
  cfg.gridDim = dim3(36); cfg.blockDim = dim3(512); cfg.dynamicSmemBytes = A_TOTAL; cfg.stream = st;
  cudaLaunchAttribute at[1];
  at[0].id = cudaLaunchAttributeProgrammaticStreamSerialization; at[0].val.programmaticStreamSerializationAllowed = 1;
  cfg.attrs = at; cfg.numAttrs = 1;
  cudaLaunchKernelEx(&cfg, aux_kernel, p);
}
```

```cpp
#include <cuda_runtime.h>
#include <cuda_bf16.h>
#include <stdint.h>
#include <stddef.h>

namespace {

typedef __nv_bfloat16 bf16;

constexpr int NSEG = 64;
#define LAG_ 5
constexpr int LAG = LAG_;
constexpr int NSTEP = NSEG + LAG;
constexpr int ORING = 8, PRING = 4;
static_assert(LAG < 8, "rings");

#define E1_ 10
#define E3_ 10
constexpr int E1 = E1_, EA = E1_ + E3_;
static_assert(EA % 4 == 0 && EA < 32, "early part: whole 64-column chunks");
#define PAUSE_ 13
#define PAUS2_ 29
#define PST2_ 2
#define HAND_ 4
#define SALT_ 0
#define TP(i, v) (v)
#define XDLY_ TP(0, 2075)
#define YDLY_ TP(1, 3400)
#define X1_ TP(2, 100)
#define X2_ TP(3, 350)
#define Y1_ TP(4, 200)
#define Y2_ TP(5, 450)
#define HGAP_ TP(6, 50)
#define TGAP_ TP(7, 100)
#define ADLY_ TP(8, 600)
#define ODLY_ TP(9, 2800)
#define HDLY_ TP(11, 0)
#define TDLY_ TP(15, 4150)
#define SDLY_ TP(12, 800)
#define AGAP_ 100
#define BOFF_ TP(13, 200)
#define YOFF_ TP(16, 150)
#define YUP_ TP(20, 40)
#define YDN_ TP(21, 4)
#define T1GAP_ TP(22, 0)
#define OGAP_ TP(23, 0)
#define CDLY_ TP(17, 300)
#define SLOW0_ TP(18, 400)
#define SLOW1_ TP(19, 300)
#define KDLY_ TP(14, 300)
__device__ uint32_t g_epoch;
struct Seg {
  uint8_t h[2][32768];
  bf16 x2[32][512], n[32][512];
  bf16 req1[32][2][512];
};
struct Mix {
  uint8_t tok[16][2][16384];
  uint8_t o[4][32][8192];
  uint8_t pp[2][8 * 32768];
};
struct Scratch {
  uint8_t xch[96 * 16384 + 65536];
  unsigned long long f_h2[NSEG][4][4];
  unsigned long long f_l2[8][4];
  unsigned long long sync[2][96][4];
  uint32_t f_o[NSTEP][8][12][8];
  uint32_t f_y[NSTEP + 1][32][8], f_cp[64];
  uint32_t f_choice[96][2], f_loaded[32], f_h1[NSEG], f_hc[NSEG];
  uint8_t pad0[2097152 - (96 * 16384 + 65536 + NSEG * 128 + 256 + 6144 + NSTEP * 3072 + (NSTEP + 1) * 1024 + 256 + 768 + 128 + NSEG * 8)];
  Mix mix[6];
  uint32_t f_acc[3][NSEG][32][8];
  unsigned long long f_w2[2][NSEG][32][4];
  uint2 hc[NSEG][256];
  bf16 x2c[NSEG][512];
  float y[8][32][512];
  Seg seg[NSEG];
  bf16 req2[2][2048][2][512];
};
static_assert(sizeof(Mix) == 2097152 && offsetof(Scratch, mix) == 2097152 && offsetof(Scratch, seg) % 1024 == 0 && ORING == 8 && PRING == 4, "layout");
__device__ uint8_t g_raw[sizeof(Scratch) + 2097152];
__device__ __forceinline__ Scratch& scr() { return *(Scratch*)(((uintptr_t)g_raw + 2097151) & ~(uintptr_t)2097151); }
#define G scr()
__device__ __forceinline__ uint8_t* o_slot(int st, int s, int head) { const int j = st * 8 + (s & 7); return G.mix[j % 6].o[j / 6][head]; }
__device__ __forceinline__ uint8_t* pp_slot(int st, int s) { const int j = st * 4 + (s & 3); return G.mix[j % 6].pp[j / 6]; }

#define TRAP() __trap()
__device__ __forceinline__ uint32_t smem_u32(const void* p) { return (uint32_t)__cvta_generic_to_shared(p); }
__device__ __forceinline__ int fresh_tid() { const int t = threadIdx.x; return __shfl_sync(~0u, t, t & 31); }
__device__ __forceinline__ unsigned long long gtime64() { unsigned long long t; asm volatile("mov.u64 %0, %%globaltimer;" : "=l"(t) :: "memory"); return t; }
__device__ __forceinline__ uint32_t clk() { unsigned long long c; asm volatile("mov.u64 %0, %%clock64;" : "=l"(c) :: "memory"); return (uint32_t)c; }
__device__ __forceinline__ void wait_until(uint32_t t) {
  while ((int)(t - clk()) > 450) __nanosleep(32);
  uint32_t c;
  do { asm volatile("mov.u32 %0, %%clock;" : "=r"(c) :: "memory"); } while ((int)(c - t) < 0);
}
__device__ __forceinline__ void mbar_init(uint32_t bar, uint32_t cnt) { asm volatile("mbarrier.init.shared::cta.b64 [%0], %1;" :: "r"(bar), "r"(cnt) : "memory"); }
__device__ __forceinline__ void mbar_arrive(uint32_t bar) { asm volatile("mbarrier.arrive.shared::cta.b64 _, [%0];" :: "r"(bar) : "memory"); }
__device__ __forceinline__ void mbar_arrive_remote(uint32_t bar) { asm volatile("mbarrier.arrive.relaxed.cluster.shared::cluster.b64 _, [%0];" :: "r"(bar) : "memory"); }
__device__ __forceinline__ void mbar_expect(uint32_t bar, uint32_t bytes) { asm volatile("mbarrier.arrive.expect_tx.shared::cta.b64 _, [%0], %1;" :: "r"(bar), "r"(bytes) : "memory"); }
__device__ __forceinline__ bool mbar_try(uint32_t bar, uint32_t parity) {
  uint32_t ok;
  asm volatile("{.reg .pred p; mbarrier.try_wait.parity.shared::cta.b64 p, [%1], %2; selp.u32 %0, 1, 0, p;}" : "=r"(ok) : "r"(bar), "r"(parity) : "memory");
  return ok;
}
__device__ __forceinline__ bool mbar_test(uint32_t bar, uint32_t parity) {
  uint32_t ok;
  asm volatile("{.reg .pred p; mbarrier.test_wait.parity.shared::cta.b64 p, [%1], %2; selp.u32 %0, 1, 0, p;}" : "=r"(ok) : "r"(bar), "r"(parity) : "memory");
  return ok;
}
__device__ __forceinline__ void mbar_wait(uint32_t bar, uint32_t parity) {
  asm volatile("{\n.reg .pred p;\nWAIT:\nmbarrier.try_wait.parity.shared::cta.b64 p, [%0], %1;\n@!p bra WAIT;\n}" :: "r"(bar), "r"(parity) : "memory");
}
__device__ __forceinline__ uint32_t ld_acq(const uint32_t* p) { uint32_t v; asm volatile("ld.acquire.gpu.global.u32 %0, [%1];" : "=r"(v) : "l"(p) : "memory"); return v; }
__device__ __forceinline__ void st_rel(uint32_t* p, uint32_t v) { asm volatile("st.release.gpu.global.u32 [%0], %1;" :: "l"(p), "r"(v) : "memory"); }
__device__ __forceinline__ void st_rel64(unsigned long long* p, unsigned long long v) { asm volatile("st.release.gpu.global.u64 [%0], %1;" :: "l"(p), "l"(v) : "memory"); }
__device__ __forceinline__ uint32_t ld_rlx(const uint32_t* p) { uint32_t v; asm volatile("ld.relaxed.gpu.global.u32 %0, [%1];" : "=r"(v) : "l"(p) : "memory"); return v; }
__device__ __forceinline__ unsigned long long ld_rlxu64(const unsigned long long* p) { unsigned long long v; asm volatile("ld.relaxed.gpu.global.u64 %0, [%1];" : "=l"(v) : "l"(p) : "memory"); return v; }
__device__ __forceinline__ void st_rlx(uint32_t* p, uint32_t v) { asm volatile("st.relaxed.gpu.global.u32 [%0], %1;" :: "l"(p), "r"(v) : "memory"); }
__device__ __forceinline__ void bulk_wait() { asm volatile("cp.async.bulk.commit_group;\n cp.async.bulk.wait_group 0;" ::: "memory"); }
__device__ __forceinline__ void fence_acq() { asm volatile("fence.acquire.gpu;" ::: "memory"); }
__device__ __forceinline__ void wait_all(const uint32_t* p, uint32_t v, bool acquire = true) {
  int guard = 0;
  while (!__all_sync(~0u, ld_rlx(p) == v)) { __nanosleep(32); if (++guard > (1 << 22)) TRAP(); }
  if (acquire) fence_acq();
}
__device__ __forceinline__ void wait_eq(const uint32_t* p, uint32_t v) {
  int guard = 0;
  while (ld_rlx(p) != v) { __nanosleep(64); if (++guard > (1 << 22)) TRAP(); }
  fence_acq();
}
__device__ __forceinline__ unsigned long long rword(uint32_t E, int tok, float r) {
  uint32_t u = __float_as_uint(r + 0.f);
  u = r != r ? 0u : (u >> 31) ? ~u : u | 0x80000000u;
  return (unsigned long long)(E & 0x1FFFFFu) << 43 | (unsigned long long)u << 11 | (uint32_t)(2047 - tok);
}
__device__ __forceinline__ int rtok(unsigned long long v) { return 2047 - (int)(v & 2047u); }
__device__ __forceinline__ float rscore(unsigned long long v) { const uint32_t u = (uint32_t)(v >> 11); return __uint_as_float((u >> 31) ? u & 0x7fffffffu : ~u); }
__device__ __forceinline__ bool rfresh(unsigned long long v, uint32_t E) { return (uint32_t)(v >> 43) == (E & 0x1FFFFFu); }
template <int TOP> __device__ __forceinline__ unsigned long long warp_max(unsigned long long v) {
#pragma unroll
  for (int o = TOP; o > 0; o >>= 1) { const unsigned long long ov = __shfl_xor_sync(~0u, v, o); v = ov > v ? ov : v; }
  return v;
}
template <int off> __device__ __forceinline__ uint2 ld_rlx64(const void* p) { unsigned long long v; asm volatile("ld.relaxed.gpu.global.b64 %0, [%1+%2];" : "=l"(v) : "l"(p), "n"(off) : "memory"); return make_uint2((uint32_t)v, (uint32_t)(v >> 32)); }
template <int off> __device__ __forceinline__ uint4 ld_rlx128(const void* p) {
  unsigned long long a, b; asm volatile("ld.relaxed.gpu.global.v2.b64 {%0,%1}, [%2+%3];" : "=l"(a), "=l"(b) : "l"(p), "n"(off) : "memory");
  return make_uint4((uint32_t)a, (uint32_t)(a >> 32), (uint32_t)b, (uint32_t)(b >> 32));
}
__device__ __forceinline__ void st_rlx64(void* p, uint32_t lo, uint32_t hi) { asm volatile("{.reg .b64 t; mov.b64 t, {%1,%2}; st.relaxed.gpu.global.b64 [%0], t;}" :: "l"(p), "r"(lo), "r"(hi) : "memory"); }
__device__ __forceinline__ void cp_async16(uint32_t dst, const void* src) { asm volatile("cp.async.cg.shared.global [%0], [%1], 16;" :: "r"(dst), "l"(src) : "memory"); }
__device__ __forceinline__ void cp_async_wait() { asm volatile("cp.async.wait_all;" ::: "memory"); }
__device__ __forceinline__ void fence_async_smem() { asm volatile("fence.proxy.async.shared::cta;" ::: "memory"); }
__device__ __forceinline__ void fence_async_glob() { asm volatile("fence.proxy.async.global;" ::: "memory"); }
__device__ __forceinline__ float ex2(float x) { float y; asm("ex2.approx.ftz.f32 %0, %1;" : "=f"(y) : "f"(x)); return y; }
__device__ __forceinline__ float sqrt_fast(float x) { float y; asm("sqrt.approx.ftz.f32 %0, %1;" : "=f"(y) : "f"(x)); return y; }
__device__ __forceinline__ float rcp(float x) { float y; asm("rcp.approx.ftz.f32 %0, %1;" : "=f"(y) : "f"(x)); return y; }
__device__ __forceinline__ void bar_sync(int id, int n) { asm volatile("bar.sync %0, %1;" :: "r"(id), "r"(n) : "memory"); }
__device__ __forceinline__ bool bar_or(int id, int n, bool v) {
  uint32_t r;
  asm volatile("{.reg .pred p, q; setp.ne.u32 p, %3, 0; barrier.cta.red.or.aligned.pred q, %1, %2, p; selp.u32 %0, 1, 0, q;}" : "=r"(r) : "r"(id), "r"(n), "r"((uint32_t)v) : "memory");
  return r;
}
__device__ __forceinline__ uint32_t mapa(uint32_t a, uint32_t rank) { uint32_t r; asm volatile("mapa.shared::cluster.u32 %0, %1, %2;" : "=r"(r) : "r"(a), "r"(rank)); return r; }
__device__ __forceinline__ void cluster_sync() { asm volatile("barrier.cluster.arrive.release.aligned; barrier.cluster.wait.acquire.aligned;" ::: "memory"); }
__device__ __forceinline__ void st_async32(uint32_t dst, uint32_t v, uint32_t bar) { asm volatile("st.async.shared::cluster.mbarrier::complete_tx::bytes.b32 [%0], %1, [%2];" :: "r"(dst), "r"(v), "r"(bar) : "memory"); }
#define ELECT(op) "{.reg .pred p; elect.sync _|p, 0xffffffff; @p " op "}"
__device__ __forceinline__ void e_arrive(uint32_t bar) { asm volatile(ELECT("mbarrier.arrive.shared::cta.b64 _, [%0];") :: "r"(bar) : "memory"); }
__device__ __forceinline__ void e_expect(uint32_t bar, uint32_t bytes) { asm volatile(ELECT("mbarrier.arrive.expect_tx.shared::cta.b64 _, [%0], %1;") :: "r"(bar), "r"(bytes) : "memory"); }
__device__ __forceinline__ void e_g2s(uint32_t dst, const void* src, uint32_t bytes, uint32_t bar) {
  asm volatile(ELECT("cp.async.bulk.shared::cluster.global.mbarrier::complete_tx::bytes [%0], [%1], %2, [%3];") :: "r"(dst), "l"(src), "r"(bytes), "r"(bar) : "memory");
}
__device__ __forceinline__ void e_mc(uint32_t dst, const void* src, uint32_t bytes, uint32_t bar, uint16_t mask) {
  asm volatile(ELECT("cp.async.bulk.shared::cluster.global.mbarrier::complete_tx::bytes.multicast::cluster [%0], [%1], %2, [%3], %4;")
               :: "r"(dst), "l"(src), "r"(bytes), "r"(bar), "h"(mask) : "memory");
}
__device__ __forceinline__ void e_s2g(void* dst, uint32_t src, uint32_t bytes) {
  asm volatile(ELECT("cp.async.bulk.global.shared::cta.bulk_group [%0], [%1], %2;") :: "l"(dst), "r"(src), "r"(bytes) : "memory");
}
__device__ __forceinline__ uint32_t clk32() { uint32_t c; asm volatile("mov.u32 %0, %%clock;" : "=r"(c) :: "memory"); return c; }
__device__ __forceinline__ void spin_until(uint32_t t) { while ((int)(clk32() - t) < 0) {} }
__device__ __forceinline__ uint32_t uni(uint32_t v) { return __shfl_sync(~0u, v, 0); }
__device__ __forceinline__ uint32_t pack2(float lo, float hi) { uint32_t r; asm("cvt.rn.bf16x2.f32 %0, %1, %2;" : "=r"(r) : "f"(hi), "f"(lo)); return r; }
__device__ __forceinline__ uint32_t add2(uint32_t a, uint32_t b) { uint32_t r; asm("add.rn.bf16x2 %0, %1, %2;" : "=r"(r) : "r"(a), "r"(b)); return r; }
__device__ __forceinline__ float rbf(float x) { return __bfloat162float(__float2bfloat16_rn(x)); }
__device__ __forceinline__ float blo(uint32_t u) { return __uint_as_float(u << 16); }
__device__ __forceinline__ float bhi(uint32_t u) { return __uint_as_float(u & 0xffff0000u); }
__device__ __forceinline__ uint32_t gentag(uint32_t g) { return (g & 1u) | (g & 2u) << 15; }
__device__ __forceinline__ uint32_t pack2_tag(float lo, float hi, uint32_t tag) {
  const uint32_t u = __byte_perm(__float_as_uint(lo), __float_as_uint(hi), 0x7632);
  return u + ((u ^ tag) & 0x10001u);
}
__device__ __forceinline__ uint32_t xo2(uint32_t a, uint32_t b, uint32_t t) { uint32_t r; asm("lop3.b32 %0, %1, %2, %3, 0x7e;" : "=r"(r) : "r"(a), "r"(b), "r"(t)); return r; }
__device__ __forceinline__ uint32_t or3(uint32_t a, uint32_t b, uint32_t c) { uint32_t r; asm("lop3.b32 %0, %1, %2, %3, 0xfe;" : "=r"(r) : "r"(a), "r"(b), "r"(c)); return r; }
__device__ __forceinline__ void stmatrix4(uint32_t a, uint32_t r0, uint32_t r1, uint32_t r2, uint32_t r3) {
  asm volatile("stmatrix.sync.aligned.m8n8.x4.shared.b16 [%0], {%1,%2,%3,%4};" :: "r"(a), "r"(r0), "r"(r1), "r"(r2), "r"(r3) : "memory");
}
__device__ __forceinline__ void stmatrix4_t(uint32_t a, uint32_t r0, uint32_t r1, uint32_t r2, uint32_t r3) {
  asm volatile("stmatrix.sync.aligned.m8n8.x4.trans.shared.b16 [%0], {%1,%2,%3,%4};" :: "r"(a), "r"(r0), "r"(r1), "r"(r2), "r"(r3) : "memory");
}
__device__ __forceinline__ void ldmatrix4_t(uint32_t* r, uint32_t a) {
  asm volatile("ldmatrix.sync.aligned.m8n8.x4.trans.shared.b16 {%0,%1,%2,%3}, [%4];" : "=r"(r[0]), "=r"(r[1]), "=r"(r[2]), "=r"(r[3]) : "r"(a) : "memory");
}
__device__ __forceinline__ void ldmatrix4(uint32_t* r, uint32_t a) {
  asm volatile("ldmatrix.sync.aligned.m8n8.x4.shared.b16 {%0,%1,%2,%3}, [%4];" : "=r"(r[0]), "=r"(r[1]), "=r"(r[2]), "=r"(r[3]) : "r"(a) : "memory");
}
__device__ __forceinline__ void hmma16(float* c, const uint32_t* a, uint32_t b0, uint32_t b1) {
  asm volatile("mma.sync.aligned.m16n8k16.row.col.f32.bf16.bf16.f32 {%0,%1,%2,%3}, {%4,%5,%6,%7}, {%8,%9}, {%0,%1,%2,%3};"
               : "+f"(c[0]), "+f"(c[1]), "+f"(c[2]), "+f"(c[3]) : "r"(a[0]), "r"(a[1]), "r"(a[2]), "r"(a[3]), "r"(b0), "r"(b1));
}
__device__ __forceinline__ void hmma8(float* c, uint32_t a0, uint32_t a1, uint32_t b0) {
  asm volatile("mma.sync.aligned.m16n8k8.row.col.f32.bf16.bf16.f32 {%0,%1,%2,%3}, {%4,%5}, {%6}, {%0,%1,%2,%3};"
               : "+f"(c[0]), "+f"(c[1]), "+f"(c[2]), "+f"(c[3]) : "r"(a0), "r"(a1), "r"(b0));
}
__device__ __forceinline__ uint4 lds128(uint32_t a) { uint4 v; asm volatile("ld.shared.v4.u32 {%0,%1,%2,%3}, [%4];" : "=r"(v.x), "=r"(v.y), "=r"(v.z), "=r"(v.w) : "r"(a) : "memory"); return v; }
__device__ __forceinline__ void sts128(uint32_t a, uint4 v) { asm volatile("st.shared.v4.u32 [%0], {%1,%2,%3,%4};" :: "r"(a), "r"(v.x), "r"(v.y), "r"(v.z), "r"(v.w) : "memory"); }
__device__ __forceinline__ void sts128f(uint32_t a, float x, float y, float z, float w) { asm volatile("st.shared.v4.f32 [%0], {%1,%2,%3,%4};" :: "r"(a), "f"(x), "f"(y), "f"(z), "f"(w) : "memory"); }
__device__ __forceinline__ uint32_t lds32(uint32_t a) { uint32_t v; asm volatile("ld.shared.u32 %0, [%1];" : "=r"(v) : "r"(a) : "memory"); return v; }
__device__ __forceinline__ void sts32(uint32_t a, uint32_t v) { asm volatile("st.shared.u32 [%0], %1;" :: "r"(a), "r"(v) : "memory"); }

constexpr uint32_t SBASE = 1024;
__host__ __device__ constexpr uint64_t mkdesc(uint32_t off, uint32_t lbo, uint32_t sbo, uint32_t swz) {
  return (uint64_t)(((SBASE + off) & 0x3FFFF) >> 4) | ((uint64_t)(lbo >> 4) << 16) | ((uint64_t)(sbo >> 4) << 32) | ((uint64_t)swz << 62);
}
__device__ __forceinline__ void wg_fence() { asm volatile("wgmma.fence.sync.aligned;" ::: "memory"); }
__device__ __forceinline__ void wg_commit() { asm volatile("wgmma.commit_group.sync.aligned;" ::: "memory"); }
template <int N> __device__ __forceinline__ void wg_wait() { asm volatile("wgmma.wait_group.sync.aligned %0;" :: "n"(N) : "memory"); }

template <int N> __device__ __forceinline__ void reg_fence(float (&d)[N], int n = N) {
#pragma unroll
  for (int i = 0; i < N; i++) if (i < n) asm volatile("" : "+f"(d[i]) :: "memory");
}
#define F4(b) "+f"(d[b]), "+f"(d[b + 1]), "+f"(d[b + 2]), "+f"(d[b + 3])
#define F8(b) F4(b), F4(b + 4)
#define F16(b) F8(b), F8(b + 8)
#define G4(b) "=f"(d[b]), "=f"(d[b + 1]), "=f"(d[b + 2]), "=f"(d[b + 3])
#define G8(b) G4(b), G4(b + 4)
#define G16(b) G8(b), G8(b + 8)
#define RS_IN "r"(a[0]), "r"(a[1]), "r"(a[2]), "r"(a[3]), "l"(db), "n"(SD), "n"(TB)
#define SS_IN "l"(da), "l"(db), "n"(SD), "n"(TA), "n"(TB)
#define WG_OP(str, out0, out1, in) do { if (SD || KEEP) asm volatile(str : out1 : in); else asm volatile(str : out0 : in); } while (0)
#define O12(X) X##8(0), X##4(8)
#define O20(X) X##16(0), X##4(16)
#define O32(X) X##16(0), X##16(16)
template <int SD, int TB, int KEEP = 0> __device__ __forceinline__ void wgmma_rs24(float* d, const uint32_t* a, uint64_t db) {
  WG_OP("wgmma.mma_async.sync.aligned.m64n24k16.f32.bf16.bf16 {%0,%1,%2,%3,%4,%5,%6,%7,%8,%9,%10,%11}, {%12,%13,%14,%15}, %16, %17, 1, 1, %18;", O12(G), O12(F), RS_IN);
}
template <int SD, int TB, int KEEP = 0> __device__ __forceinline__ void wgmma_rs32(float* d, const uint32_t* a, uint64_t db) {
  WG_OP("wgmma.mma_async.sync.aligned.m64n32k16.f32.bf16.bf16 {%0,%1,%2,%3,%4,%5,%6,%7,%8,%9,%10,%11,%12,%13,%14,%15}, {%16,%17,%18,%19}, %20, %21, 1, 1, %22;", G16(0), F16(0), RS_IN);
}
template <int SD, int TB, int KEEP = 0> __device__ __forceinline__ void wgmma_rs40(float* d, const uint32_t* a, uint64_t db) {
  WG_OP("wgmma.mma_async.sync.aligned.m64n40k16.f32.bf16.bf16 {%0,%1,%2,%3,%4,%5,%6,%7,%8,%9,%10,%11,%12,%13,%14,%15,"
        "%16,%17,%18,%19}, {%20,%21,%22,%23}, %24, %25, 1, 1, %26;", O20(G), O20(F), RS_IN);
}
template <int SD, int TB, int KEEP = 0> __device__ __forceinline__ void wgmma_rs64(float* d, const uint32_t* a, uint64_t db) {
  WG_OP("wgmma.mma_async.sync.aligned.m64n64k16.f32.bf16.bf16 {%0,%1,%2,%3,%4,%5,%6,%7,%8,%9,%10,%11,%12,%13,%14,%15,"
        "%16,%17,%18,%19,%20,%21,%22,%23,%24,%25,%26,%27,%28,%29,%30,%31}, {%32,%33,%34,%35}, %36, %37, 1, 1, %38;", O32(G), O32(F), RS_IN);
}
template <int SD, int TA, int TB, int KEEP = 0> __device__ __forceinline__ void wgmma_ss24(float* d, uint64_t da, uint64_t db) {
  WG_OP("wgmma.mma_async.sync.aligned.m64n24k16.f32.bf16.bf16 {%0,%1,%2,%3,%4,%5,%6,%7,%8,%9,%10,%11}, %12, %13, %14, 1, 1, %15, %16;", O12(G), O12(F), SS_IN);
}
template <int SD, int TA, int TB, int KEEP = 0> __device__ __forceinline__ void wgmma_ss8(float* d, uint64_t da, uint64_t db) {
  WG_OP("wgmma.mma_async.sync.aligned.m64n8k16.f32.bf16.bf16 {%0,%1,%2,%3}, %4, %5, %6, 1, 1, %7, %8;", G4(0), F4(0), SS_IN);
}
__device__ __forceinline__ void bar_arrive(int id, int n) { asm volatile("bar.arrive %0, %1;" :: "r"(id), "r"(n) : "memory"); }
__device__ __forceinline__ uint32_t vis_bits(int pos, int t) {
  uint32_t m = 0;
#pragma unroll
  for (int i = 0; i < 8; i++) m |= (8 * (i / 2 + 1) + 2 * t + (i & 1) <= pos) ? 1u << i : 0u;
  return m;
}

__device__ __forceinline__ unsigned long long wait_words(const unsigned long long* p, uint32_t E) {
  int guard = 0; unsigned long long m;
  while (m = ld_rlxu64(p), !__all_sync(~0u, rfresh(m, E))) { __nanosleep(20); if (++guard > (1 << 22)) TRAP(); }
  fence_acq();
  return m;
}
__device__ __forceinline__ int route_step(int s, uint32_t E, int lane, unsigned long long& run) {
  const unsigned long long m = warp_max<2>(wait_words(G.f_h2[s][lane & 3], E));
  if (s == 0 || m > run) { run = m; return rtok(m) & 31; }
  return -1;
}

struct Params {
  const bf16 *x, *mem0, *wq, *wk, *wv, *wo, *wr, *wg, *wu, *wd;
  bf16* out;
  uint32_t zero2;
  unsigned long long zero;
};

constexpr uint32_t WSTG_STRIDE = 272;
__device__ __forceinline__ void stage_weights(uint32_t stg, const bf16* src, int ld, int tid, int nthr) {
  for (int i = tid; i < 512 * 16; i += nthr) {
    int k = i >> 4, c = i & 15;
    cp_async16(stg + k * WSTG_STRIDE + c * 16, src + (size_t)k * ld + c * 8);
  }
}
__device__ __forceinline__ void load_frags(uint32_t (*W)[4], uint32_t stg, int wg, int w, int lane) {
  uint32_t a = stg + ((lane >> 4) * 8 + (lane & 7)) * WSTG_STRIDE + (64 * wg + 16 * w + ((lane >> 3) & 1) * 8) * 2;
#pragma unroll
  for (int ks = 0; ks < 32; ks++) ldmatrix4_t(W[ks], a + ks * 16 * WSTG_STRIDE);
}

constexpr uint32_t M_H = 0;
constexpr uint32_t M_MEM = 65536;
constexpr uint32_t M_Q = M_MEM + 24576;
constexpr uint32_t M_K = M_Q + 12288;
constexpr uint32_t M_V = M_K + 12288;
constexpr uint32_t M_OM = M_V + 12288;
constexpr uint32_t M_OST = M_OM + 6144;
constexpr uint32_t M_TST = M_OST + 8192;
constexpr uint32_t M_WO = M_TST + 16384;
constexpr uint32_t M_M0 = M_WO + 49152;
constexpr uint32_t M_PT = M_M0 + 2048;
constexpr uint32_t M_BAR = M_PT + 12288;
constexpr uint32_t M_TOTAL = M_BAR + 384;
static_assert(M_TOTAL <= 232448, "main smem");
static_assert(M_WO >= 512 * WSTG_STRIDE, "staging overlaps Wo");
enum { B_LAND = 0  , B_QK = 3, B_V, B_TOK, B_OM, B_HA, B_HB, B_HAE, B_HBE, B_OST, B_OFREE, B_SYNC,
       B_STG, B_STG1, B_SS, B_TFREE, B_KFREE, B_VFREE, B_FIX  , B_NUM = B_FIX + 8 };
static_assert(B_NUM * 8 <= 256, "barriers");
constexpr uint32_t M_CAND = M_BAR + 256;
constexpr uint32_t M_BASE = M_BAR + 272;
constexpr uint32_t M_ZERO = M_BAR + 280;
constexpr uint32_t M_BAS2 = M_BAR + 328;
constexpr uint32_t M_NEAR = M_BAR + 288;
enum { N_GO2 = 3, N_GO3, N_GO4, N_AG, N_W };

#define GSTAMP(slot, i)
#define TSTAMP(slot, i, k)
#define STAMP(i)
#define ASTAMP(i)
#define WSTAMP(i)
#define CSTAMP(i, v)
#define PIN(x) asm volatile("" : "+r"(x))
#define SCHED(k) asm volatile("{\n.reg .pred p;\nsetp.ne.u32 p, %0, 0;\n@p trap;\n}" :: "r"(zz & (1u << (k))) : "memory")
#define HOLD(k, v) asm volatile("{\n.reg .pred p;\nsetp.ne.u32 p, %0, 0;\n@p st.shared.u32 [%0], %1;\n}" :: "r"(zz & (1u << (k))), "r"(v) : "memory")
#define DRAIN(a) (lds32((a) + zz) & zz)
#define BAR(i) (sb + M_BAR + 8 * (i))

__device__ __forceinline__ int probe(const uint8_t* p, int n) {
  int best = 1 << 30; uint32_t v = 0;
#pragma unroll 1
  for (int r = 0; r < n; r++) {
    uint32_t t0 = clk();
    asm volatile("atom.relaxed.gpu.global.or.b32 %0, [%1], %2;" : "=r"(v) : "l"(p + 3968), "r"(v & 0u) : "memory");
    if (v == 0x7fffffffu) t0++;
    best = min(best, (int)(clk() - t0));
  }
  return best;
}
__device__ __forceinline__ void load_mem0(uint4* u, int k0, int lane, const bf16* mem0) {
#pragma unroll
  for (int i = 0; i < 2; i++) {
    const unsigned short* m = (const unsigned short*)mem0 + k0 + lane + 32 * i;
    u[i] = make_uint4(m[0] | (uint32_t)m[512] << 16, m[1024] | (uint32_t)m[1536] << 16, m[2048] | (uint32_t)m[2560] << 16, m[3072] | (uint32_t)m[3584] << 16);
  }
}

__device__ __forceinline__ void paced_h(uint32_t dst, const uint8_t* src, uint32_t o0, uint32_t o1, uint32_t piece, uint32_t bar, int gap) {
  uint32_t t = clk32();
#pragma unroll 1
  for (uint32_t o = o0; o < o1; o += piece) {
    e_mc(dst + o, src + o, piece, bar, 7);
    spin_until(t += gap);
  }
}

__device__ __forceinline__ void paced_st(uint8_t* dst, uint32_t src, int gap) {
  uint32_t t = clk32();
#pragma unroll 1
  for (uint32_t o = 0; o < 8192; o += 4096) {
    e_s2g(dst + o, src + o, 4096);
    if (o + 4096 < 8192) spin_until(t += gap);
  }
}
__device__ __forceinline__ int block_of(int head, int c) { return c == 2 ? head : 32 + 2 * head + c; }

__device__ __forceinline__ void weight_role(const Params& p, const uint32_t sb, const int warp, const int cta, const int C, const uint32_t E,
                                            const uint8_t* const memg) {
  const int tid = fresh_tid(), lane = tid & 31;
  const int wg = warp >> 2, w = warp & 3;
  uint32_t W[32][4];
  cp_async_wait();
  bar_sync(1, 256);
  load_frags(W, sb, wg, w, lane);
  bar_sync(1, 256);
  if (tid < 128) sts128(sb + M_V + 5 * 2048 + tid * 16, make_uint4(0, 0, 0, 0));
  fence_async_smem();
  cluster_sync();
  if (tid == 0 && cta == 0) GSTAMP(0, 1);
  if (tid == 0) TSTAMP(13, cta, 0);

  const uint32_t rba = mapa(sb, C == 2 ? 0 : 2), rbc = mapa(sb, C == 1 ? 0 : 1);
  const uint32_t MYBAR = M_BAR + 8 * (C < 2 ? B_QK : B_V);
  uint32_t qoff = M_Q + C * 12288 + warp * 256 + lane * 4;
  uint32_t toff = sb + warp * 256 + (lane >> 4) * 2048 + (lane & 15) * 16;
  uint32_t rbar = mapa(sb + M_BAR, min(lane, 2));
  uint32_t sv = sb + M_MEM + lane * 32 + ((lane >> 2) & 3) * 8;
  PIN(qoff); PIN(toff); PIN(rbar); PIN(sv);
  const uint32_t gen0 = (E - 1) * (uint32_t)(NSTEP - 1);
  uint32_t fix = 0;
  const bool sig = w == 0 && lane < 3;
  const int blk = block_of(cta / 3, C);
  const int pk = (blk < 24 ? PAUSE_ : PAUS2_) + (wg ? -PST2_ : PST2_);
  int cand = -1;
  float d[16];
#pragma unroll
  for (int i = 0; i < 16; i++) d[i] = 0.f;
  uint32_t tp[8];
#pragma unroll 1
  for (int T = -1; T < NSTEP; T++) {
    const uint32_t ph = T & 1;
    const uint64_t Z = p.zero << ph;
    const uint32_t zz = p.zero2;
    if (T >= 0) {
      WSTAMP(0);
      if (T == 1 && tid == 0) TSTAMP(16, cta, 0);
      const uint64_t db = mkdesc(M_MEM, 128, 256, 0) + Z;
      stmatrix4(toff + M_TST + 8192, tp[0], tp[1], tp[2], tp[3]); stmatrix4(toff + M_TST + 12288, tp[4], tp[5], tp[6], tp[7]);
      if (sig) mbar_arrive_remote(rbar + 8 * B_HBE);
      mbar_wait(BAR(B_LAND), ph);
      WSTAMP(1);
      if (T == 1 && tid == 0) TSTAMP(16, cta, 1);
      const uint32_t gt = gentag(gen0 + T);
      auto old = [&](uint32_t a) { return lds32(a) ^ gt; };
      uint32_t bad = 0;
      bool redo = false, ready = false;
      wg_fence();
      wgmma_rs24<0, 1, 1>(d, W[0], db);
#pragma unroll
      for (int ks = 1; ks < 32; ks++) {
        if (ks == 2) bad |= old(sv + min(warp, 5) * 1024);
        if (ks == 10 || ks == 22) bad |= xo2(lds32(sv + (ks == 10 ? 6 : 15) * 1024 + warp * 1024), lds32(sv + (ks == 10 ? 14 : 23) * 1024), gt);
        if (ks == 6) {
          const uint32_t z5 = DRAIN(toff + M_TST);
          __syncwarp();
          if (lane == 0) mbar_arrive(BAR(B_STG) + z5);
        }
        if (ks == 27) ready = mbar_test(BAR(C < 2 ? B_KFREE : B_VFREE), ph ^ 1) & mbar_test(BAR(B_HA), ph);
        if (ks == 30) redo = bar_or(N_W, 256, T > 0 && (bad & 0x10001u));
        if (ks == 8 || ks == 20) { mbar_wait(BAR(B_LAND + (ks + 4) / 12), ph); WSTAMP(6 + (ks + 4) / 12); wg_fence(); }
        wgmma_rs24<1, 1>(d, W[ks], db + ks * 48);
      }
      wg_commit();
      uint32_t a0 = rba + qoff, a1 = a0 + 128, a2 = rbc + qoff, a3 = a2 + 128, ba = rba + MYBAR, bc = rbc + MYBAR;
      PIN(a0); PIN(a1); PIN(a2); PIN(a3); PIN(ba); PIN(bc);
      if (!ready) {
        mbar_wait(BAR(C < 2 ? B_KFREE : B_VFREE), ph ^ 1);
        if (T < NSTEP - 1) mbar_wait(BAR(B_HA), ph);
      }
      wg_wait<0>(); reg_fence(d);
      if (__builtin_expect(redo, 0)) {
        auto stale = [&]() { return __any_sync(~0u, (old(sv + warp * 3072) | old(sv + warp * 3072 + 1024) | old(sv + warp * 3072 + 2048)) & 0x10001u); };
        auto fetch = [&](int r) {
          e_expect(BAR(B_FIX + warp), 3072);
          e_g2s(sb + M_MEM + warp * 3072, memg + warp * 8192 + ((uni(lds32(sb + M_NEAR + warp * 4)) ^ r) & 1) * 4096, 3072, BAR(B_FIX + warp));
        };
        bool late = stale();
        if (late) fetch(0);
        constexpr uint64_t dc = mkdesc(M_MEM, 128, 256, 0);
#pragma unroll
        for (int ks = 0; ks < 32; ks++) {
          if (ks % 12 == 0) {
            if (ks) { wg_commit(); wg_wait<0>(); reg_fence(d); }
            if (warp / 3 == ks / 12) {
              for (int guard = 0; late; guard++) {
                mbar_wait(BAR(B_FIX + warp), fix); fix ^= 1;
                late = stale();
                if (late) fetch(guard + 1);
                if (guard > (1 << 20)) TRAP();
              }
            }
            bar_sync(N_W, 256);
            wg_fence();
          }
          if (ks == 0) wgmma_rs24<0, 1, 1>(d, W[0], dc); else wgmma_rs24<1, 1>(d, W[ks], dc + ks * 48);
        }
        wg_commit();
        wg_wait<0>(); reg_fence(d);
      }
      WSTAMP(2);
      if (T == 0 && tid == 0) TSTAMP(13, cta, 2);
      if (T == 1 && tid == 0) TSTAMP(16, cta, 2);
      uint32_t lo[3], hi[3];
#pragma unroll
      for (int j = 0; j < 3; j++) { lo[j] = pack2(d[4 * j], d[4 * j + 1]); hi[j] = pack2(d[4 * j + 2], d[4 * j + 3]); }
      if (__builtin_expect(T == 0, 0)) { sts32(sb + M_M0 + tid * 8, lo[0]); sts32(sb + M_M0 + tid * 8 + 4, hi[0]); }
      if (__builtin_expect(cand >= 0, 0)) {
        if (T == LAG) { lo[1] = lds32(sb + M_M0 + tid * 8); hi[1] = lds32(sb + M_M0 + tid * 8 + 4); }
        if (C < 2) { st_async32(a0 + 5 * 2048, lo[2], ba); st_async32(a1 + 5 * 2048, hi[2], ba); }
        else { sts32(sb + qoff + 5 * 2048, lo[2]); sts32(sb + qoff + 5 * 2048 + 128, hi[2]); }
        lo[2] = lo[1]; hi[2] = hi[1];
      }
      uint32_t z5;
      if (C == 0) {
        sts32(sb + qoff, lo[0]); sts32(sb + qoff + 128, hi[0]); z5 = DRAIN(sb + qoff);
        st_async32(a0, lo[2], ba); st_async32(a1, hi[2], ba); st_async32(a2, lo[1], bc); st_async32(a3, hi[1], bc);
      } else if (C == 1) {
        sts32(sb + qoff, lo[1]); sts32(sb + qoff + 128, hi[1]); z5 = DRAIN(sb + qoff);
        st_async32(a0, lo[2], ba); st_async32(a1, hi[2], ba); st_async32(a2, lo[0], bc); st_async32(a3, hi[0], bc);
      } else {
        sts32(sb + qoff, lo[2]); sts32(sb + qoff + 128, hi[2]); z5 = DRAIN(sb + qoff);
        st_async32(a0, lo[0], ba); st_async32(a1, hi[0], ba); st_async32(a2, lo[1], bc); st_async32(a3, hi[1], bc);
      }
      __syncwarp();
      if (lane == 0) { mbar_arrive(sb + MYBAR + z5); if (w == 3) mbar_arrive(BAR(B_SS)); }
      if (T == NSTEP - 1) break;
    }
    {
      const uint64_t dh = mkdesc(M_H, 16, 1024, 1) + Z;
      if (T + 2 < NSEG) {
        if (T < 0) mbar_wait(BAR(B_HA), ph);
        WSTAMP(3);
        wg_fence();
        wgmma_rs32<0, 0, 1>(d, W[0], dh);
#pragma unroll
        for (int ks = 1; ks < EA; ks++) {
          if (ks == E1) { wg_commit(); if (T >= 0) bar_sync(N_GO2, 384); wg_fence(); }
          wgmma_rs32<1, 0>(d, W[ks], dh + (ks >> 2) * 256 + (ks & 3) * 2);
        }
        wg_commit();
        mbar_wait(BAR(B_HB), ph);
        wg_wait<0>();
        if (sig) mbar_arrive_remote(rbar + 8 * B_HAE);
        WSTAMP(4);
        if (T == 0 && tid == 0) TSTAMP(17, cta, 0);
        if (T >= 0) bar_sync(N_GO3, 384);
        if (wg == 1) bar_sync(N_W, 256);
        wg_fence();
#pragma unroll
        for (int ks = EA; ks < 32; ks++) wgmma_rs32<1, 0>(d, W[ks], dh + (ks >> 2) * 256 + (ks & 3) * 2);
        wg_commit();
        if (wg == 0) bar_arrive(N_W, 256);
        mbar_wait(BAR(B_TFREE), ph ^ 1);
        wg_wait<0>(); reg_fence(d);
      } else {
        bar_sync(N_GO2, 384);
        mbar_wait(BAR(B_HB), ph);
        if (sig) mbar_arrive_remote(rbar + 8 * B_HAE);
        bar_sync(N_GO3, 384);
        mbar_wait(BAR(B_TFREE), ph ^ 1);
      }
#pragma unroll
      for (int i = 0; i < 8; i++) { tp[i] = pack2(d[2 * i], d[2 * i + 1]); PIN(tp[i]); }
      const uint32_t t1 = toff + (C == 0 && !ph ? M_Q + 2048 : M_TST);
      auto staged = [&]() {
        const uint32_t z5 = DRAIN(t1);
        __syncwarp();
        if (lane == 0) mbar_arrive(BAR(B_STG1) + z5);
      };
      if (T < 0 || (T + 2 >= LAG && T + 2 < NSTEP)) {
        wg_fence();
        wgmma_rs32<0, 0, 1>(d, W[0], dh + 2048);
        stmatrix4(t1, tp[0], tp[1], tp[2], tp[3]); stmatrix4(t1 + 4096, tp[4], tp[5], tp[6], tp[7]);
#pragma unroll
        for (int ks = 1; ks < 32; ks++) {
          if (ks == 5) staged();
          if (ks == PAUSE_ - PST2_ || ks == PAUSE_ + PST2_ || ks == PAUS2_ - PST2_ || ks == PAUS2_ + PST2_) {
            wg_commit();
            if (T >= 0 && ks == pk) bar_sync(N_GO4, 384);
            wg_fence();
          }
          wgmma_rs32<1, 0>(d, W[ks], dh + 2048 + (ks >> 2) * 256 + (ks & 3) * 2);
        }
        wg_commit();
      } else {
        stmatrix4(t1, tp[0], tp[1], tp[2], tp[3]); stmatrix4(t1 + 4096, tp[4], tp[5], tp[6], tp[7]);
        staged();
        bar_sync(N_GO4, 384);
      }
      if (T >= 0) cand = __shfl_sync(~0u, (int)lds32(sb + M_CAND + ((T + 1) & 3) * 4), 0);
      wg_wait<0>(); reg_fence(d);
      if (T >= 0) WSTAMP(6);
      if (T < 0 && tid == 0) TSTAMP(13, cta, 1);
#pragma unroll
      for (int i = 0; i < 8; i++) tp[i] = pack2(d[2 * i], d[2 * i + 1]);
    }
  }
  cluster_sync();
  if (tid == 0 && cta == 0) GSTAMP(0, 5);
}

__device__ __forceinline__ void attn_role(const Params& p, const uint32_t sb, const int w, const int cta, const int head, const int C, const uint32_t E,
                                          uint8_t* const part, uint8_t* const memg) {
  const int tid = fresh_tid(), lane = tid & 31;
  const int g = lane >> 2, t = lane & 3, blk = block_of(head, C);
  uint32_t tag = ((E - 1) * (uint32_t)(NSTEP - 1)) & 1;
  uint4 m0[2][2];
  load_mem0(m0[0], w * 64, lane, p.mem0); load_mem0(m0[1], w * 64 + 256, lane, p.mem0);
  cluster_sync();
#pragma unroll
  for (int k = 0; k < 2; k++) {
#pragma unroll 1
    for (int i = 0; i < 6; i++) sts128(sb + M_MEM + (w + 4 * k) * 3072 + lane * 16 + i * 512, make_uint4(0, 0, 0, 0));
    __syncwarp();
#pragma unroll
    for (int i = 0; i < 2; i++) sts128(sb + M_MEM + ((w + 4 * k) * 4 + (lane >> 4) + 2 * i) * 768 + (lane & 15) * 16, m0[k][i]);
  }
  fence_async_smem();
  bar_sync(N_AG, 128);
  if (w == 3 && lane < 3) mbar_arrive(BAR(B_LAND + lane));
  if (lane == 0) {
    if (w == 0) TSTAMP(15, cta, 0);
    sts32(sb + M_PT + w * 4, probe(part + blk * 16384 + w * 4096, 3));
    if (w == 0) TSTAMP(15, cta, 1);
  }
  bar_sync(N_AG, 128);
  const uint32_t inear = lds32(sb + M_PT + (w >> 1) * 8 + 4) < lds32(sb + M_PT + (w >> 1) * 8);
  if (lane == 0 && !(w & 1)) st_rlx(&G.f_choice[blk][w >> 1], (E << 1) | inear);
  if (w == 0) TSTAMP(15, cta, 2);
  uint32_t nb;
  {
    const int i = min(lane >> 1, C < 2 ? 8 : 5);
    const int r = ((i / 3 * 3 + C) * 4 + w) * 3 + i % 3;
    int guard = 0; uint32_t cw;
    while (__any_sync(~0u, ((cw = ld_rlx(&G.f_choice[r][lane & 1])) >> 1) != (E & 0x7FFFFFFFu))) { if (++guard > (1 << 22)) TRAP(); }
    nb = __ballot_sync(~0u, cw & 1) >> (lane >> 4);
    if (w == 0) TSTAMP(15, cta, 3);
  }
  bar_sync(N_AG, 128);
  const uint32_t pt0 = sb + M_PT + (tid & 127) * 16;
  {
    const uint32_t po = (C * 4 + w) * 49152 + (lane >> 4) * 8192 + head * 128 + (lane & 15) * 8;
    const uint8_t* in = part + (blk * 16384 + (w >> 1) * 8192 + inear * 4096 + (w & 1) * 64 + (lane >> 3) * 128 + (lane & 7) * 8);
    const uint8_t* outp = memg + ((blk / 12) * 8192 + (blk % 12) * 256 + w * 64 + (lane >> 4) * 4096 + (lane & 4) * 8 + (lane & 8) * 2 + (lane & 3) * 4);
#pragma unroll
    for (int i = 0; i < 12; i++) {
      const int j = i / 4 * 3 + (i & 3);
      const uint8_t* a = (i & 3) < 3 ? part + (po + i / 4 * 589824 + (i & 3) * 16384 + ((nb >> (2 * j)) & 1) * 4096) : i == 11 ? in : outp;
      asm volatile("st.shared.u64 [%0], %1;" :: "r"(pt0 + (i >> 1) * 2048 + (i & 1) * 8), "l"(a) : "memory");
    }
  }
  const int xd = __shfl_sync(~0u, XDLY_ + (blk < 24 ? 0 : blk < 60 ? X1_ : X2_), 0);
  const uint32_t rba = mapa(sb, C == 2 ? 0 : 2), rbc = mapa(sb, C == 1 ? 0 : 1);
  uint32_t vis = vis_bits(8 + 8 * w + g, t);
  uint32_t ln = lane;
#pragma unroll
  for (int i = 0; i < SALT_; i++) ln += lds32(sb + M_ZERO);
  PIN(vis); PIN(ln);
  if (tid == 256 && C == 0) st_rlx(&G.f_loaded[head], E);
  uint32_t fa[8][4];
#pragma unroll
  for (int ks = 0; ks < 8; ks++) ldmatrix4_t(fa[ks], sb + M_WO + 32768 + w * 256 + (lane >> 4) * 1024 + (lane & 15) * 16 + ks * 2048);
  if (w == 0) TSTAMP(14, cta, 0);
#pragma unroll 1
  for (int T = 0; T < NSTEP; T++) {
    const uint32_t ph = T & 1;
    const uint32_t zz = uni(lds32(sb + M_ZERO));
    const bool more = T < NSTEP - 1;
    const float sc = 0.08838834764831845f * 1.4426950408889634f;
    tag ^= 1;
    float s[20];
    const uint8_t* in; int cnext = -1; uint32_t tx; bool synced;
    float x[10], tm, ts;
    uint32_t pt[5];
    auto tok_max = [&]() {
      PIN(vis);
      x[0] = s[2]; x[1] = s[3];
#pragma unroll
      for (int i = 0; i < 8; i++) x[2 + i] = (vis >> i & 1) ? s[4 * (i / 2 + 1) + 2 + (i & 1)] : -INFINITY;
      tm = fmaxf(fmaxf(fmaxf(fmaxf(x[0], x[1]), fmaxf(x[2], x[3])), fmaxf(fmaxf(x[4], x[5]), fmaxf(x[6], x[7]))), fmaxf(x[8], x[9]));
      HOLD(7, __float_as_uint(tm));
    };
    auto tok_exp1 = [&]() {
      tm = fmaxf(tm, __shfl_xor_sync(~0u, tm, 1));
      tm = fmaxf(tm, __shfl_xor_sync(~0u, tm, 2));
      const float b = -tm * sc;
#pragma unroll
      for (int i = 0; i < 10; i++) x[i] = fmaf(x[i], sc, b);
      HOLD(10, __float_as_uint(x[9]));
    };
    auto tok_exp2 = [&]() {
#pragma unroll
      for (int i = 0; i < 10; i++) x[i] = ex2(x[i]);
      ts = (((x[0] + x[1]) + (x[2] + x[3])) + ((x[4] + x[5]) + (x[6] + x[7]))) + (x[8] + x[9]);
#pragma unroll
      for (int k = 0; k < 5; k++) pt[k] = pack2(x[2 * k], x[2 * k + 1]);
      HOLD(8, __float_as_uint(ts));
    };
    {
      uint32_t q[8][4];
      auto load_q = [&](uint32_t a, int h) {
#pragma unroll
        for (int k2 = 0; k2 < 4; k2++) {
          uint32_t r[4];
          ldmatrix4_t(r, a + k2 * 512);
          q[2 * k2][h] = r[0]; q[2 * k2][h + 2] = r[1]; q[2 * k2 + 1][h] = r[2]; q[2 * k2 + 1][h + 2] = r[3];
        }
      };
      PIN(ln);
      const uint32_t qa = sb + M_Q + ln * 16, qt = qa + w * 2048 + (C == 0 && ph ? M_TST - M_Q : 2048);
      const int cand = C == 2 ? (int)uni(lds32(sb + M_CAND + (T & 3) * 4)) : -1;
      mbar_wait(BAR(B_TOK), ph);
      load_q(qt, 1);
      mbar_wait(BAR(B_QK), ph);
      ASTAMP(0);
      if (T == 0 && w == 0) TSTAMP(13, cta, 3);
      if (__builtin_expect(cand >= 0, 0)) {
        mbar_wait(BAR(B_V), ph);
        PIN(ln);
        const int e = w * 32 + ln;
#pragma unroll
        for (int i = 0; i < 3; i++) {
          const uint32_t v = lds32(sb + M_Q + i * 12288 + 5 * 2048 + e * 16 + 4);
          asm volatile("st.shared.u16 [%0], %1;" :: "r"(sb + M_Q + i * 12288 + (1 + (cand >> 3)) * 2048 + e * 16 + (cand & 7) * 2), "h"((unsigned short)v) : "memory");
        }
        fence_async_smem();
        bar_sync(N_AG, 128);
        load_q(qt, 1);
      }
      constexpr uint64_t dk = mkdesc(M_K, 128, 2048, 0);
      fence_async_smem();
      uint32_t r[4][4];
#pragma unroll
      for (int k2 = 0; k2 < 4; k2++) ldmatrix4_t(r[k2], qa + k2 * 512);
#pragma unroll
      for (int k2 = 0; k2 < 4; k2++) {
        q[2 * k2][0] = r[k2][0]; q[2 * k2][2] = r[k2][1]; q[2 * k2 + 1][0] = r[k2][2]; q[2 * k2 + 1][2] = r[k2][3];
        if (k2 & 1) {
          wg_fence();
#pragma unroll
          for (int ks = 2 * k2 - 2; ks < 2 * k2 + 2; ks++) { if (ks == 0) wgmma_rs40<0, 1>(s, q[0], dk); else wgmma_rs40<1, 1>(s, q[ks], dk + ks * 16); }
        }
      }
      wg_commit();
    }
    if (more) {
      uint32_t v[5][4];
      PIN(ln);
      const uint32_t va = sb + M_V + w * 512 + ((ln >> 3) & 1) * 128 + (ln >> 4) * 2048 + (ln & 7) * 16;
      const uint32_t ooff = M_OM + w * 1536 + C * 256 + ln * 4;
      mbar_wait(BAR(B_V), ph);
      wg_wait<0>(); reg_fence(s);
      if (ln < 3) mbar_arrive_remote(mapa(BAR(B_KFREE), ln));
      ldmatrix4(v[0], va); ldmatrix4(v[1], va + 256); ldmatrix4(v[2], va + 4096); ldmatrix4(v[3], va + 4096 + 256);
      ldmatrix4(v[4], sb + M_V + 8192 + w * 512 + ln * 16);
      ASTAMP(1);
      float m = fmaxf(fmaxf(fmaxf(fmaxf(s[0], s[1]), fmaxf(s[4], s[5])), fmaxf(fmaxf(s[8], s[9]), fmaxf(s[12], s[13]))), fmaxf(s[16], s[17]));
      m = fmaxf(m, __shfl_xor_sync(~0u, m, 1));
      m = fmaxf(m, __shfl_xor_sync(~0u, m, 2));
      const float b = -m * sc;
      uint32_t pm[5];
#pragma unroll
      for (int j = 0; j < 5; j++) pm[j] = pack2(ex2(fmaf(s[4 * j], sc, b)), ex2(fmaf(s[4 * j + 1], sc, b)));
      float o0[4] = {0.f, 0.f, 0.f, 0.f}, o1[4] = {0.f, 0.f, 0.f, 0.f}, l[4] = {0.f, 0.f, 0.f, 0.f};
      const uint32_t one[4] = {0x3f803f80u, 0x3f803f80u, 0x3f803f80u, 0x3f803f80u};
      hmma16(l, one, pm[0], pm[1]); hmma16(o0, v[0], pm[0], pm[1]); hmma16(o1, v[1], pm[0], pm[1]);
      hmma16(l, one, pm[2], pm[3]); hmma16(o0, v[2], pm[2], pm[3]); hmma16(o1, v[3], pm[2], pm[3]);
      hmma8(l, one[0], one[1], pm[4]); hmma8(o0, v[4][0], v[4][1], pm[4]); hmma8(o1, v[4][2], v[4][3], pm[4]);
      const float r0 = rcp(l[0]), r1 = rcp(l[1]);
      const uint32_t u0 = pack2(o0[0] * r0, o0[1] * r1), u1 = pack2(o0[2] * r0, o0[3] * r1), u2 = pack2(o1[0] * r0, o1[1] * r1), u3 = pack2(o1[2] * r0, o1[3] * r1);
      constexpr uint32_t OB = M_BAR + 8 * B_OM;
      const uint32_t a0 = rba + ooff, a1 = rbc + ooff;
      st_async32(a0, u0, rba + OB); st_async32(a1, u0, rbc + OB);
      st_async32(a0 + 128, u1, rba + OB); st_async32(a1 + 128, u1, rbc + OB);
      st_async32(a0 + 768, u2, rba + OB); st_async32(a1 + 768, u2, rbc + OB);
      st_async32(a0 + 896, u3, rba + OB); st_async32(a1 + 896, u3, rbc + OB);
      bar_arrive(N_GO2, 384);
      sts32(sb + ooff, u0); sts32(sb + ooff + 128, u1); sts32(sb + ooff + 768, u2); sts32(sb + ooff + 896, u3);
      ASTAMP(2);
      uint32_t fb[8][4];
      const uint32_t wa = sb + M_WO + 16384 + w * 256 + (ln >> 4) * 1024 + (ln & 15) * 16 + zz;
      ldmatrix4_t(fb[0], wa);
      SCHED(3);
#pragma unroll
      for (int ks = 1; ks < 8; ks++) {
        ldmatrix4_t(fb[ks], wa + ks * 2048);
        if (ks == 7) { __syncwarp(); if (ln == 0) mbar_arrive(BAR(B_OM) + (fb[0][0] & zz)); }
      }
      if (blk % 3 == 2) cnext = (int)uni(lds32(sb + M_CAND + ((T + 1) & 3) * 4));
      {
        float d[12], e[12];
        constexpr uint64_t ob = mkdesc(M_OM, 128, 256, 0);
        uint8_t* q[3][3];
        auto addr = [&](int i) {
          asm volatile("ld.shared.v2.u64 {%0,%1}, [%2];" : "=l"(q[i][0]), "=l"(q[i][1]) : "r"(pt0 + i * 4096) : "memory");
          if (i < 2) asm volatile("ld.shared.u64 %0, [%1];" : "=l"(q[i][2]) : "r"(pt0 + i * 4096 + 2048) : "memory");
          else asm volatile("ld.shared.v2.u64 {%0,%1}, [%2];" : "=l"(q[i][2]), "=l"(in) : "r"(pt0 + i * 4096 + 2048) : "memory");
        };
        auto put = [&](const float* d, int i) {
          st_rlx64(q[i][0], (pack2(d[0], d[1]) & ~1u) | tag, pack2(d[2], d[3]));
          st_rlx64(q[i][1], (pack2(d[4], d[5]) & ~1u) | tag, pack2(d[6], d[7]));
          st_rlx64(q[i][2], (pack2(d[8], d[9]) & ~1u) | tag, pack2(d[10], d[11]));
        };
        addr(0); addr(1);
        SCHED(6);
        tok_max();
        ASTAMP(3);
        mbar_wait(BAR(B_OM), ph);
        ASTAMP(4);
        constexpr uint64_t w0 = mkdesc(M_WO, 1024, 128, 0);
        float (&f)[12] = d;
        wg_fence();
        wgmma_ss24<0, 1, 1>(d, w0, ob);
#pragma unroll
        for (int ks = 1; ks < 8; ks++) wgmma_ss24<1, 1, 1>(d, w0 + ks * 128, ob + ks * 48);
        wg_commit();
        wgmma_rs24<0, 1>(e, fb[0], ob);
#pragma unroll
        for (int ks = 1; ks < HAND_; ks++) wgmma_rs24<1, 1>(e, fb[ks], ob + ks * 48);
        wg_commit();
        wg_wait<1>(); reg_fence(d);
        put(d, 0);
        addr(2);
        SCHED(4);
        ASTAMP(5);
        wg_fence();
#pragma unroll
        for (int ks = HAND_; ks < 8; ks++) wgmma_rs24<1, 1>(e, fb[ks], ob + ks * 48);
        wg_commit();
        wgmma_rs24<0, 1, 1>(f, fa[0], ob);
#pragma unroll
        for (int ks = 1; ks < HAND_; ks++) wgmma_rs24<1, 1>(f, fa[ks], ob + ks * 48);
        wg_commit();
        wg_wait<1>(); reg_fence(e);
        put(e, 1);
        SCHED(5);
        if (C < 2) {
          wg_fence();
#pragma unroll
          for (int ks = HAND_; ks < 8; ks++) wgmma_rs24<1, 1>(f, fa[ks], ob + ks * 48);
          wg_commit();
        }
        synced = __all_sync(~0u, mbar_test(BAR(B_SYNC), ph));
        tx = uni(lds32(sb + M_BASE + ph * 4)) + xd;
        wg_wait<0>(); reg_fence(f);
        if (C < 2) put(f, 2);
        bar_arrive(N_GO3, 384);
        ASTAMP(6);
        if (T == 0 && w == 0) TSTAMP(14, cta, 1);
      }
    } else {
      mbar_wait(BAR(B_V), ph);
      wg_wait<0>(); reg_fence(s);
      tok_max();
    }
    uint2 v[8];
    auto poll = [&](uint2* v) {
      v[0] = ld_rlx64<0>(in); v[1] = ld_rlx64<512>(in); v[2] = ld_rlx64<1024>(in); v[3] = ld_rlx64<1536>(in);
      v[4] = ld_rlx64<2048>(in); v[5] = ld_rlx64<2560>(in); v[6] = ld_rlx64<3072>(in); v[7] = ld_rlx64<3584>(in);
    };
    uint8_t* outp;
    asm volatile("ld.shared.u64 %0, [%1];" : "=l"(outp) : "r"(pt0 + 2048 + 8) : "memory");
    const uint32_t itag = gentag((E - 1) * (uint32_t)(NSTEP - 1) + T + 1);
    const bool sum = more && cnext < 0;
    if (more) {
      if (!synced) { mbar_wait(BAR(B_SYNC), ph); tx = uni(lds32(sb + M_BASE + ph * 4)) + xd; }
      ASTAMP(7);
      if (__builtin_expect(cnext >= 0, 0)) {
        const unsigned long long* hp = (const unsigned long long*)&G.hc[T + 1 - LAG][0] + ((blk / 3) * 8 + 2 * w + ((ln >> 2) & 1));
        unsigned long long v0; int guard = 0;
        while (v0 = ld_rlxu64(hp), !__all_sync(~0u, (uint32_t)(v0 >> 32) == E)) { if (++guard > (1 << 22)) TRAP(); }
        st_rlx((uint32_t*)outp, (ln & 3) == 1 ? ((uint32_t)v0 >> ((ln & 8) * 2)) & 0xffffu : (ln & 1) ? 0u : itag);
      } else {
        spin_until(tx);
        ASTAMP(8);
      }
    }
    if (!more) in = part;
    poll(v);
    auto late = [&](const uint2* v) {
      return __any_sync(~0u, (or3(xo2(v[0].x, v[1].x, tag), xo2(v[2].x, v[3].x, tag), xo2(v[4].x, v[5].x, tag)) | xo2(v[6].x, v[7].x, tag)) & 1u);
    };
    tok_exp1(); tok_exp2();
    auto reduce = [&]() {
      if (sum) {
        ASTAMP(9);
        int guard = 0;
        while (late(v)) {
          if (++guard > (1 << 22)) TRAP();
          poll(v);
        }
#pragma unroll
        for (int i = 0; i < 4; i++) { v[i].x = add2(v[i].x, v[i + 4].x); v[i].y = add2(v[i].y, v[i + 4].y); }
        const bool hi = ln & 8;
        const uint32_t x0 = add2(v[0].x, v[1].x), x1 = add2(v[2].x, v[3].x), y0 = add2(v[0].y, v[1].y), y1 = add2(v[2].y, v[3].y);
        const uint32_t m0 = hi ? y0 : x0, m1 = hi ? y1 : x1;
        const uint32_t n0 = __shfl_xor_sync(~0u, hi ? x0 : y0, 8), n1 = __shfl_xor_sync(~0u, hi ? x1 : y1, 8);
        float k0 = (blo(m0) + blo(m1)) + (blo(n0) + blo(n1)), k1 = (bhi(m0) + bhi(m1)) + (bhi(n0) + bhi(n1));
        k0 += __shfl_xor_sync(~0u, k0, 16); k1 += __shfl_xor_sync(~0u, k1, 16);
        st_rlx((uint32_t*)outp, (ln & 1) ? pack2(k0, k1) : pack2_tag(k0, k1, itag));
        ASTAMP(10);
        if (T == 0 && w == 0) TSTAMP(14, cta, 2);
        CSTAMP(12 + w, (clk() & ~15u) | min(guard + 1, 15));
      }
      if (more) bar_arrive(N_GO4, 384);
    };
    reduce();
    {
      PIN(ln);
      const uint32_t oa = sb + M_OST + w * 128 + (ln >> 3) * 512 + (ln & 7) * 16;
      const uint32_t a[3][4] = {{0, pt[0], 0, pt[1]}, {0, pt[2], 0, pt[3]}, {0, pt[4], 0, 0}};
      constexpr uint64_t dv = mkdesc(M_V, 2048, 128, 0);
#pragma unroll 1
      for (int h = 0; h < 2; h++) {
        float o[32];
        const uint64_t dh = dv + (uint64_t)(h * 64);
        wg_fence();
        wgmma_rs64<0, 0>(o, a[0], dh); wgmma_rs64<1, 0>(o, a[1], dh + 256); wgmma_rs64<1, 0>(o, a[2], dh + 512);
        wg_commit();
        if (h == 0) {
          ts += __shfl_xor_sync(~0u, ts, 1);
          ts += __shfl_xor_sync(~0u, ts, 2);
          ts = rcp(ts);
          mbar_wait(BAR(B_OFREE), ph ^ 1);
        }
        wg_wait<0>(); reg_fence(o);
        if (h == 1 && ln < 3) mbar_arrive_remote(mapa(BAR(B_VFREE), ln));
#define OT(i) pack2(o[4 * (i) + 2] * ts, o[4 * (i) + 3] * ts)
        stmatrix4(oa + h * 4096, OT(0), OT(1), OT(2), OT(3));
        stmatrix4(oa + h * 4096 + 2048, OT(4), OT(5), OT(6), OT(7));
      }
      const uint32_t z5 = DRAIN(oa);
      __syncwarp();
      if (ln == 0) mbar_arrive(BAR(B_OST) + z5);
      ASTAMP(11);
    }
  }
}

__global__ void __cluster_dims__(3, 1, 1) __launch_bounds__(512, 1) main_kernel(Params p) {
  extern __shared__ __align__(1024) uint8_t sm[];
  const uint32_t sb = smem_u32(sm);
  if ((sb & 0xFFFFFFu) != SBASE) TRAP();
  asm volatile("griddepcontrol.launch_dependents;");
  const int warp = __shfl_sync(~0u, threadIdx.x >> 5, 0);
  const int cta = blockIdx.x, head = cta / 3, c = cta % 3;
  const uint32_t E = __shfl_sync(~0u, *(volatile uint32_t*)&g_epoch + 1, 0);
  uint8_t* const part = G.xch;
  uint8_t* const memg = part + 96 * 16384;

  if (threadIdx.x == 0 && cta == 0) GSTAMP(0, 0);
  if (threadIdx.x < B_NUM) {
    const int i = threadIdx.x;
    const uint32_t cnt = i == B_STG || i == B_STG1 ? 8 : i == B_OST ? 4 : i == B_HAE || i == B_HBE ? 6 : i == B_KFREE || i == B_VFREE ? 12 : i == B_SS ? 2 : i == B_OM ? 5 :
                         i == B_QK ? (c < 2 ? 9 : 1) : i == B_V ? (c < 2 ? 1 : 9) : 1;
    mbar_init(BAR(i), cnt);
    if (i == B_HA || i == B_HB || i == B_STG || i == B_HAE || i == B_HBE || i == B_TFREE)
      asm volatile("mbarrier.arrive.shared::cta.b64 _, [%0], %1;" :: "r"(BAR(i)), "r"(cnt) : "memory");
    asm volatile("fence.mbarrier_init.release.cluster;" ::: "memory");
  }
  if (warp < 8) {
    const int tid = threadIdx.x;
    uint4 wa[6], wb[6];
#pragma unroll
    for (int i = 0; i < 6; i++) {
      const int mi = i >> 1, e = (tid >> 2) + (i & 1) * 64;
      const uint4* src = (const uint4*)(p.wo + (size_t)(head * 128 + e) * 512 + min(3 * mi + c, 7) * 64 + (tid & 3) * 16);
      wa[i] = __ldg(src); wb[i] = __ldg(src + 1);
    }
    stage_weights(sb, (c == 0 ? p.wq : c == 1 ? p.wk : p.wv) + head * 128, 4096, tid, 256);
#pragma unroll
    for (int i = 0; i < 6; i++) {
      const int mi = i >> 1, e = (tid >> 2) + (i & 1) * 64;
      const uint4 a = wa[i], b = wb[i];
      const uint32_t dst = sb + M_WO + mi * 16384 + (e >> 3) * 1024 + (tid & 3) * 256 + (e & 7) * 16;
      sts128(dst, make_uint4(__byte_perm(a.x, a.y, 0x5410), __byte_perm(a.z, a.w, 0x5410), __byte_perm(b.x, b.y, 0x5410), __byte_perm(b.z, b.w, 0x5410)));
      sts128(dst + 128, make_uint4(__byte_perm(a.x, a.y, 0x7632), __byte_perm(a.z, a.w, 0x7632), __byte_perm(b.x, b.y, 0x7632), __byte_perm(b.z, b.w, 0x7632)));
    }
  } else {
    const int i0 = threadIdx.x - 256;
    const uint32_t tag0 = ((E - 1) * (uint32_t)(NSTEP - 1)) & 1;
    for (int i = i0; i < 1024; i += 256) *(uint4*)(part + block_of(head, c) * 16384 + i * 16) = make_uint4(tag0, 0, tag0, 0);
    if (i0 < 16) *(uint32_t*)(memg + i0 * 4096 + 3968) = 0;
    if (i0 < 2) st_rlx(&G.f_choice[block_of(head, c)][i0], 0);
    if (i0 < 8) st_rlx64(&G.sync[i0 >> 2][cta][i0 & 3], 0, 0);
    __threadfence();
    if (i0 < 12) sts32(sb + M_ZERO + i0 * 4, 0);
    if (i0 < 2) { sts32(sb + M_BASE + i0 * 4, clk32() - 65536); sts32(sb + M_BAS2 + i0 * 4, clk32() - 65536); sts32(sb + M_CAND + i0 * 4, (uint32_t)-1); }
  }

  if (warp < 8) {
    asm volatile("setmaxnreg.inc.sync.aligned.u32 176;");
    weight_role(p, sb, warp, cta, c, E, memg);
  } else if (warp < 12) {
    asm volatile("setmaxnreg.inc.sync.aligned.u32 136;");
    attn_role(p, sb, warp - 8, cta, head, c, E, part, memg);
    cluster_sync();
  } else {
    asm volatile("setmaxnreg.dec.sync.aligned.u32 24;");
    const int tid = fresh_tid(), lane = tid & 31;
    const int w = warp - 12;
    cluster_sync();
    if (w != 2) {
      const int tl = w == 0 ? c : w == 1 ? 2 + c : 5 + c;
      int near = 0;
      if (lane == 0) { const int t0 = probe(memg + tl * 8192, 3); near = probe(memg + tl * 8192 + 4096, 3) < t0; }
      near = uni(near);
      if (lane < 3) asm volatile("st.shared::cluster.u32 [%0], %1;" :: "r"(mapa(sb + M_NEAR + tl * 4, lane)), "r"(near) : "memory");
      __syncwarp();
    }
    if (w == 0) {
      int yadj = 0, dmin = 1 << 20; uint32_t prev = 0; bool cprev = false;
      uint32_t s1 = (2 + c) * 8192, s2 = (5 + c) * 8192;
#pragma unroll 1
      for (int T = 0; T < NSTEP - 1; T++) {
        const uint32_t ph = T & 1;
        mbar_wait(BAR(B_SS), ph);
        const uint32_t cq = clk();
        const uint32_t g0 = (uint32_t)gtime64(); uint32_t g1, ce;
        do { g1 = (uint32_t)gtime64(); ce = clk(); } while (g1 == g0);
        const uint32_t tn = g1 * 8 - (((ce - cq) * 37u) >> 3), id = E * 128u + T;
        if (lane < 4) st_rlx64(&G.sync[ph][cta][lane], tn, id);
        if (lane < 3) mbar_expect(BAR(B_LAND + lane), lane ? 9216 : 6144);
        if (T == 0) { s1 += uni(lds32(sb + M_NEAR + (2 + c) * 4)) * 4096; s2 += uni(lds32(sb + M_NEAR + (5 + c) * 4)) * 4096; }
        wait_until(cq + SDLY_);
        int guard = 0; unsigned long long v0, v1, v2;
        for (;;) {
          v0 = ld_rlxu64(G.sync[ph][lane]); v1 = ld_rlxu64(G.sync[ph][lane + 32]); v2 = ld_rlxu64(G.sync[ph][lane + 64]);
          if (__all_sync(~0u, (uint32_t)(v0 >> 32) == id && (uint32_t)(v1 >> 32) == id && (uint32_t)(v2 >> 32) == id)) break;
          if (++guard > (1 << 22)) TRAP();
        }
        const bool cnd = (int)uni(lds32(sb + M_CAND + (T & 3) * 4)) >= 0;
        const int dl = __reduce_max_sync(~0u, max(max((int)((uint32_t)v0 - tn), (int)((uint32_t)v1 - tn)), (int)((uint32_t)v2 - tn)));
        const uint32_t base = uni(cq + ((min(dl, 8 * 4096) * 7) >> 5)) + (T == 0 ? SLOW0_ : T == 1 ? SLOW1_ : 0) +
                              (cnd ? CDLY_ : 0) - (T + 2 < NSEG ? 0 : BOFF_);
        const int dur = (int)(base - prev);
        if (!cnd && !cprev) {
          yadj = T > 2 && dur > dmin + 700 ? min(yadj + YUP_, 400) : max(yadj - YDN_, 0);
          if (T > 1) dmin = min(dmin + 20, dur);
        }
        prev = base; cprev = cnd;
        if (lane == 0) { sts32(sb + M_BASE + ph * 4, base); sts32(sb + M_BAS2 + ph * 4, base + yadj); mbar_arrive(BAR(B_SYNC)); }
        CSTAMP(0, base); CSTAMP(1, clk());
        if (T == 0) TSTAMP(16, cta, 3);
        const uint32_t ts = base + YDLY_ + yadj - (T + 2 >= LAG && T + 2 < NSEG ? 0 : YOFF_);
        const uint8_t* const t0 = memg + uni(lds32(sb + M_NEAR)) * 4096, * const t1 = memg + 8192 + uni(lds32(sb + M_NEAR + 4)) * 4096;
        if (T == 0) {
          const uint32_t gt = gentag((E - 1) * (uint32_t)(NSTEP - 1) + 1);
#pragma unroll 1
          for (int k = 0; k < 4; k++) {
            const uint32_t* a = (const uint32_t*)((k == 0 ? t0 : k == 1 ? t1 : memg + (k == 2 ? s1 : s2)) + lane * 32);
            int g2 = 0;
            while (__any_sync(~0u, (xo2(ld_rlx(a), ld_rlx(a + 256), gt) | (ld_rlx(a + 512) ^ gt)) & 0x10001u)) { if (++g2 > (1 << 22)) TRAP(); }
          }
        } else wait_until(ts);
        e_g2s(sb + M_MEM, t0, 3072, BAR(B_LAND)); e_g2s(sb + M_MEM + 3072, t1, 3072, BAR(B_LAND));
        CSTAMP(2, clk());
        if (T == 0) TSTAMP(17, cta, 1);
        spin_until(ts + Y1_);
        e_mc(sb + M_MEM + (2 + c) * 3072, memg + s1, 3072, BAR(B_LAND + 1), 7);
        CSTAMP(3, clk());
        spin_until(ts + Y2_);
        e_mc(sb + M_MEM + (5 + c) * 3072, memg + s2, 3072, BAR(B_LAND + 2), 7);
        CSTAMP(4, clk());
      }
    } else if (w == 1) {
#pragma unroll 1
      for (int T = 0; T < NSTEP; T++) {
        const uint32_t ph = T & 1;
        const int s = c == 0 ? T : T - LAG;
        const bool act = s >= 0 && s < NSEG;
        mbar_wait(BAR(B_OST), ph);
        if (cta == 0) TSTAMP(2, T, 0);
        fence_async_smem();
        if (T < NSTEP - 1) wait_until(uni(lds32(sb + M_BAS2 + ph * 4)) + ODLY_);
        STAMP(22);
        if (act) paced_st(o_slot(c, s, head), sb + M_OST, OGAP_);
        if (c == 2 && T < NSTEP - 1) {
          mbar_wait(BAR(B_STG1), ph ^ 1);
          mbar_wait(BAR(B_VFREE), ph);
          STAMP(23);
          e_mc(sb + M_V + 2048, G.mix[cta % 6].tok[cta / 6][ph ^ 1] + 8192, 8192, BAR(B_V), 6);
          e_mc(sb + M_V + 2048, G.mix[cta % 6].tok[cta / 6][ph ^ 1], 8192, BAR(B_V), 1);
        }
        bulk_wait();
        __syncwarp();
        e_arrive(BAR(B_OFREE));
        if (cta == 0) TSTAMP(2, T, 1);
        if (act && lane < 8) st_rel(&G.f_o[T][head >> 2][c * 4 + (head & 3)][lane], E);
        __syncwarp();
        if (cta == 0) TSTAMP(2, T, 2);
      }
    } else if (w == 2) {
      unsigned long long run = 0;
      static_assert(LAG >= 2, "config");
      constexpr uint32_t NA = EA / 4 * 4096;
      e_expect(BAR(B_QK), c < 2 ? 2048 : 4096); e_expect(BAR(B_V), c == 0 ? 10240 : c == 1 ? 2048 : 0);
      e_expect(BAR(B_TOK), c == 0 ? 16384 : 0); e_expect(BAR(B_OM), 4096);
      e_expect(BAR(B_HA), NA); e_expect(BAR(B_HB), 65536 - NA);
      wait_eq(&G.f_h1[c == 1 ? 0 : 1], E); fence_async_glob();
      {
        const uint32_t o0 = c == 0 ? NA : 0, o1 = c == 2 ? NA : 32768;
        e_mc(sb + M_H + (c == 1 ? 32768 : 0) + o0, G.seg[c == 1 ? 0 : 1].h[0] + o0, o1 - o0, BAR(c == 2 ? B_HA : B_HB), 7);
      }
      TSTAMP(14, cta, 3);
      if (c == 2) wait_eq(&G.f_h1[2], E);
      mbar_wait(BAR(B_HAE), 1);
      e_expect(BAR(B_HA), NA);
      if (c == 2) { fence_async_glob(); e_mc(sb + M_H, G.seg[2].h[0], NA, BAR(B_HA), 7); }
      int cprev = -1;
#pragma unroll 1
      for (int T = 0; T < NSTEP - 1; T++) {
        const int s1 = T + 2, s2 = T + 2 - LAG;
        const uint32_t ph = T & 1;
        const bool l1 = s1 < NSEG, l2 = s2 >= 0 && s2 < NSEG, la = s1 + 1 < NSEG;
        const bool mine = c == 0 ? l1 : c == 1 ? l2 : la;
        const uint32_t* fl = c != 1 ? &G.f_h1[min(s1 + (c >> 1), NSEG - 1)] : (const uint32_t*)G.f_h2[max(s2, 0)][lane & 3] + 1;
        const uint32_t want = E & 0x1FFFFFu, sh = c != 1 ? 0 : 11;
        mbar_wait(BAR(B_HBE), ph ^ 1);
        const bool early = __all_sync(~0u, ((ld_acq(fl) >> sh) & 0x1FFFFFu) == want);
        mbar_wait(BAR(B_LAND + 2), ph);
        STAMP(16);
        e_expect(BAR(B_HB), (l1 ? 32768 - NA : 0) + (l2 ? 32768 : 0));
        if (mine) {
          if (!early) {
            int guard = 0;
            while (!__all_sync(~0u, ((ld_acq(fl) >> sh) & 0x1FFFFFu) == want)) { __nanosleep(32); if (++guard > (1 << 22)) TRAP(); }
          }
          fence_async_glob();
          if (c == 1) { mbar_wait(BAR(B_QK), ph); spin_until(clk32() + HDLY_); }
          if (c < 2) paced_h(sb + M_H + c * 32768, G.seg[c ? s2 : s1].h[c], c ? 0 : NA, 32768, 4096, BAR(B_HB), HGAP_);
        }
        int cd = -1;
        if (l2) { cd = route_step(s2, E, lane, run); if (cta == 0) TSTAMP(5, s2, 0); }
        if (lane == 0) sts32(sb + M_CAND + ((T + 2) & 3) * 4, (uint32_t)cd);
        __syncwarp();
        STAMP(17);
        mbar_wait(BAR(B_HAE), ph);
        e_expect(BAR(B_HA), la ? NA : 0);
        if (c == 2 && la) {
          spin_until(clk32() + ADLY_);
          STAMP(18);
          paced_h(sb + M_H, G.seg[s1 + 1].h[0], 0, NA, 4096, BAR(B_HA), AGAP_);
        }
        mbar_wait(BAR(B_OST), ph);
        e_expect(BAR(B_QK), c < 2 ? 2048 : cprev >= 0 ? 8192 : 4096);
        e_expect(BAR(B_V), c < 2 ? 10240 : 8192);
        e_expect(BAR(B_TOK), c == 0 ? 8192 : 16384);
        e_expect(BAR(B_OM), 4096);
        cprev = cd;
      }
    } else {
      const uint32_t mytok = sb + M_Q + c * 12288 + 2048, tb = BAR(c < 2 ? B_TOK : B_V);
      mbar_wait(BAR(B_STG1), 0);
      fence_async_smem();
      if (c) e_s2g(G.mix[cta % 6].tok[cta / 6][1], sb + M_TST, 8192);
#pragma unroll 1
      for (int T = 0; T < NSTEP - 1; T++) {
        const uint32_t ph = T & 1;
        uint8_t* const tok = G.mix[cta % 6].tok[cta / 6][ph ^ 1];
        mbar_wait(BAR(B_STG), ph ^ 1);
        fence_async_smem();
        if (cta == 0 && (T == 0 || T == NSEG || T == NSTEP - 2)) GSTAMP(0, T == 0 ? 2 : T == NSEG ? 3 : 4);
        if (T > 0) mbar_wait(BAR(B_QK), ph);
        STAMP(20);
        paced_st(tok + 8192, sb + M_TST + 8192, TGAP_);
        bulk_wait();
        __syncwarp();
        e_arrive(BAR(B_TFREE));
        if (T == 0) e_mc(mytok, tok + 8192, 8192, tb, 1);
        STAMP(21);
        if (c < 2) {
          mbar_wait(BAR(B_KFREE), ph);
          spin_until(clk32() + KDLY_);
          STAMP(23);
          if (c) e_mc(mytok, tok, 8192, tb, 1);
          e_mc(mytok, tok + 8192, 8192, tb, 6);
        }
        mbar_wait(BAR(B_STG1), ph ^ 1);
        fence_async_smem();
        wait_until(uni(lds32(sb + M_BAS2 + ph * 4)) + TDLY_);
        if (c) paced_st(G.mix[cta % 6].tok[cta / 6][ph], sb + M_TST, T1GAP_);
        STAMP(24);
      }
      bulk_wait();
    }
    __syncwarp();
    cluster_sync();
  }
}

constexpr uint32_t A_RING = 0;
constexpr int A_NST = 6;
constexpr uint32_t A_STG = A_RING + A_NST * 8192;
constexpr uint32_t A_WD = A_STG + 8192;
constexpr uint32_t A_WG = A_WD + 57344;
constexpr uint32_t A_WU = A_WG + 57344;
constexpr uint32_t A_XN = A_WU + 57344;
constexpr uint32_t A_BAR = A_XN + 2048;
constexpr uint32_t A_TOTAL = A_BAR + 256;
static_assert(A_TOTAL <= 232448, "aux smem");

__device__ __forceinline__ uint32_t ptag(int s) { return ((s / PRING) & 1) ^ 1; }
static_assert((NSEG / PRING) % 2 == 0, "tags");
__device__ __forceinline__ void load_row(uint32_t* v, const void* row, int lane) {
  const uint4 a = __ldcg((const uint4*)row + lane), b = __ldcg((const uint4*)row + 32 + lane);
  v[0] = a.x; v[1] = a.y; v[2] = a.z; v[3] = a.w; v[4] = b.x; v[5] = b.y; v[6] = b.z; v[7] = b.w;
}
__device__ __forceinline__ void store_row(void* row, const uint32_t* v, int lane) {
  ((uint4*)row)[lane] = make_uint4(v[0], v[1], v[2], v[3]); ((uint4*)row)[32 + lane] = make_uint4(v[4], v[5], v[6], v[7]);
}
__device__ __forceinline__ void store_img(uint8_t* img, int r, const uint32_t* v, int lane) {
  uint8_t* b = img + (lane >> 3) * 4096 + (r >> 3) * 1024 + (r & 7) * 128 + (((lane ^ r) & 7) << 4);
  *(uint4*)b = make_uint4(v[0], v[1], v[2], v[3]);
  *(uint4*)(b + 16384) = make_uint4(v[4], v[5], v[6], v[7]);
}
template <int NT> __device__ __forceinline__ void ln_rows(const uint32_t (*v)[8], uint32_t (*y)[8]) {
  float c[NT], sm[NT], sq[NT];
#pragma unroll
  for (int k = 0; k < NT; k++) {
    c[k] = blo(__shfl_sync(~0u, v[k][0], 0));
    float s0 = 0.f, s1 = 0.f, q0 = 0.f, q1 = 0.f;
#pragma unroll
    for (int i = 0; i < 8; i++) { const float a = blo(v[k][i]) - c[k], b = bhi(v[k][i]) - c[k]; s0 += a; s1 += b; q0 = fmaf(a, a, q0); q1 = fmaf(b, b, q1); }
    sm[k] = s0 + s1; sq[k] = q0 + q1;
  }
#pragma unroll
  for (int o = 16; o > 0; o >>= 1)
#pragma unroll
    for (int k = 0; k < NT; k++) {
      sm[k] += __shfl_xor_sync(~0u, sm[k], o); sq[k] += __shfl_xor_sync(~0u, sq[k], o);
    }
#pragma unroll
  for (int k = 0; k < NT; k++) {
    const float dm = sm[k] * (1.f / 512.f), var = fmaxf(fmaf(-dm, dm, sq[k] * (1.f / 512.f)), 0.f);
    const float mb = rbf(c[k] + dm), inv = rcp(rbf(sqrt_fast(rbf(rbf(var) + 1e-5f))));
#pragma unroll
    for (int i = 0; i < 8; i++) { const uint32_t a = pack2(blo(v[k][i]) - mb, bhi(v[k][i]) - mb); y[k][i] = pack2(blo(a) * inv, bhi(a) * inv); }
  }
}
__device__ __forceinline__ void input_ln_pair(const bf16* x, int s, int pr, int lane) {
  uint32_t v[2][8], y[2][8];
  load_row(v[0], x + (size_t)(s * 32 + 2 * pr) * 512, lane); load_row(v[1], x + (size_t)(s * 32 + 2 * pr + 1) * 512, lane);
  ln_rows<2>(v, y);
  store_img(G.seg[s].h[0], 2 * pr, y[0], lane); store_img(G.seg[s].h[0], 2 * pr + 1, y[1], lane);
}
__device__ __forceinline__ float load_wr(uint32_t* wv, const bf16* wr, int lane) {
  load_row(wv, wr, lane);
  float wsum = 0.f;
#pragma unroll
  for (int i = 0; i < 8; i++) wsum += blo(wv[i]) + bhi(wv[i]);
#pragma unroll
  for (int o = 16; o > 0; o >>= 1) wsum += __shfl_xor_sync(~0u, wsum, o);
  return wsum;
}

template <bool FAST>
__device__ __forceinline__ unsigned long long token_post(int st, int tk, const bf16* res, bf16* dst, bf16* req, unsigned long long best,
                                                         const uint32_t* wv, float wsum, uint32_t E, int lane) {
  const int s = tk >> 5;
  uint32_t x[8];
  load_row(x, res, lane);
  {
    int guard = 0;
    while (__popc(__ballot_sync(~0u, ld_rlx(G.f_acc[st][s][lane]) == E)) < (FAST ? 24 : 32)) { __nanosleep(FAST ? 20 : 100); if (++guard > (1 << 22)) TRAP(); }
  }
  if (tk == s * 32 && st == 0 && lane == 0) TSTAMP(4, s, 0);
  {
    const uint8_t* pp = pp_slot(st, s) + (lane >> 4) * 8192 + (tk & 31) * 256 + (((lane & 15) ^ (tk & 7)) << 4);
    const uint32_t tag = ptag(s);
    uint4 q[8][2];
#define PLD(k, h) q[k][h] = ld_rlx128<(k) * 32768 + (h) * 16384>(pp)
#define PLD8(h) PLD(0, h); PLD(1, h); PLD(2, h); PLD(3, h); PLD(4, h); PLD(5, h); PLD(6, h); PLD(7, h)
#define PBAD(h) __any_sync(~0u, (or3(xo2(q[0][h].x, q[1][h].x, tag), xo2(q[2][h].x, q[3][h].x, tag), xo2(q[4][h].x, q[5][h].x, tag)) | xo2(q[6][h].x, q[7][h].x, tag)) & ~lane & 1u)
#define PSUM(f, h, m) (((f(q[0][h].m) + f(q[1][h].m)) + (f(q[2][h].m) + f(q[3][h].m))) + ((f(q[4][h].m) + f(q[5][h].m)) + (f(q[6][h].m) + f(q[7][h].m))))
    const uint32_t eye = (lane >> 2) == 2 * (lane & 3) ? 0x3f80u : (lane >> 2) == 2 * (lane & 3) + 1 ? 0x3f800000u : 0u;
    auto padd = [&](int h) {
      if (FAST) {
        float u[4] = {0.f, 0.f, 0.f, 0.f}, v[4] = {0.f, 0.f, 0.f, 0.f};
#pragma unroll
        for (int k = 0; k < 8; k++) { hmma8(u, q[k][h].x, q[k][h].y, eye); hmma8(v, q[k][h].z, q[k][h].w, eye); }
        x[4 * h] = add2(x[4 * h], pack2(u[0], u[1])); x[4 * h + 1] = add2(x[4 * h + 1], pack2(u[2], u[3]));
        x[4 * h + 2] = add2(x[4 * h + 2], pack2(v[0], v[1])); x[4 * h + 3] = add2(x[4 * h + 3], pack2(v[2], v[3]));
      } else {
        x[4 * h] = add2(x[4 * h], pack2(PSUM(blo, h, x), PSUM(bhi, h, x))); x[4 * h + 1] = add2(x[4 * h + 1], pack2(PSUM(blo, h, y), PSUM(bhi, h, y)));
        x[4 * h + 2] = add2(x[4 * h + 2], pack2(PSUM(blo, h, z), PSUM(bhi, h, z))); x[4 * h + 3] = add2(x[4 * h + 3], pack2(PSUM(blo, h, w), PSUM(bhi, h, w)));
      }
    };
    int guard = 0;
    PLD8(0);
    if (FAST) { PLD8(1); }
    while (PBAD(0)) { if (++guard > (1 << 20)) TRAP(); PLD8(0); }
    padd(0);
    if (!FAST) { PLD8(1); }
    while (PBAD(1)) { if (++guard > (1 << 20)) TRAP(); PLD8(1); }
    padd(1);
  }
  const float c = blo(__shfl_sync(~0u, x[0], 0));
  float s0 = 0.f, s1 = 0.f, q0 = 0.f, q1 = 0.f, r0 = 0.f, r1 = 0.f;
#pragma unroll
  for (int i = 0; i < 8; i++) {
    const float a = blo(x[i]) - c, b = bhi(x[i]) - c;
    s0 += a; s1 += b; q0 = fmaf(a, a, q0); q1 = fmaf(b, b, q1); r0 = fmaf(a, blo(wv[i]), r0); r1 = fmaf(b, bhi(wv[i]), r1);
  }
  s0 += s1; q0 += q1; r0 += r1;
#pragma unroll
  for (int o = 16; o > 0; o >>= 1) { s0 += __shfl_xor_sync(~0u, s0, o); q0 += __shfl_xor_sync(~0u, q0, o); r0 += __shfl_xor_sync(~0u, r0, o); }
  const float dm = s0 * (1.f / 512.f), m = c + dm, var = fmaxf(fmaf(-dm, dm, q0 * (1.f / 512.f)), 0.f);
  const float mb = rbf(m), inv = rcp(rbf(sqrt_fast(rbf(rbf(var) + 1e-5f))));
  const uint32_t nmb = pack2(-mb, -mb);
  const unsigned long long wd = rword(E, tk, fmaf(c - mb, wsum, r0) * inv);
  uint32_t xn[8], x2[8];
#pragma unroll
  for (int i = 0; i < 8; i++) { const uint32_t d = add2(x[i], nmb); xn[i] = pack2(blo(d) * inv, bhi(d) * inv); x2[i] = add2(x[i], xn[i]); }
  if (st == 0) {
    const float mb2 = rbf(fmaf(m - mb, inv, m)), inv2 = rcp(rbf(sqrt_fast(rbf(rbf(var * (1.f + inv) * (1.f + inv)) + 1e-5f))));
    const uint32_t nmb2 = pack2(-mb2, -mb2);
    uint32_t h[8];
#pragma unroll
    for (int i = 0; i < 8; i++) { const uint32_t d2 = add2(x2[i], nmb2); h[i] = pack2(blo(d2) * inv2, bhi(d2) * inv2); }
    store_img(G.seg[s].h[1], tk & 31, h, lane);
  }
  store_row(dst, x2, lane);
  if (wd > best) { store_row(req, xn, lane); store_row(req + 512, x, lane); }
  return wd;
}

__device__ __forceinline__ void ffn_slice(uint32_t sb, const bf16* xn, float* yacc, uint32_t* flag, uint32_t E, int t, bool urgent) {
  const int w = t >> 5, g = (t >> 2) & 7;
  if (t == 0 && urgent) sts32(sb + A_BAR + 160, 1);
  { const uint2 u = __ldcg((const uint2*)xn + t); asm volatile("st.shared.v2.u32 [%0], {%1,%2};" :: "r"(sb + A_XN + t * 8), "r"(u.x), "r"(u.y) : "memory"); }
  fence_async_smem();
  bar_sync(4, 128);
  float ga[4], ua[4];
  constexpr uint64_t da = mkdesc(A_WG, 896, 128, 0), db = mkdesc(A_XN, 16, 128, 0);
  wg_fence();
  wgmma_ss8<0, 1, 0>(ga, da, db); wgmma_ss8<0, 1, 0>(ua, da + (A_WU - A_WG) / 16, db);
#pragma unroll
  for (int ks = 1; ks < 32; ks++) { wgmma_ss8<1, 1, 0>(ga, da + ks * 112, db + ks * 2); wgmma_ss8<1, 1, 0>(ua, da + (A_WU - A_WG) / 16 + ks * 112, db + ks * 2); }
  wg_commit(); wg_wait<0>(); reg_fence(ga); reg_fence(ua);
  if ((t & 3) == 0) {
#pragma unroll
    for (int h = 0; h < 2; h++) {
      const float gs = rbf(ga[2 * h]), us = rbf(ua[2 * h]);
      const float v = 16 * w + 8 * h < 56 ? rbf(gs * rcp(1.f + __expf(-gs))) * us : 0.f;
      asm volatile("st.shared.u16 [%0], %1;" :: "r"(sb + A_XN + 1280 + (16 * w + 8 * h + g) * 2), "h"((unsigned short)pack2(v, 0.f)) : "memory");
    }
  }
  fence_async_smem();
  bar_sync(4, 128);
#pragma unroll 1
  for (int j = 0; j < 2; j++) {
    float y[4][4];
    const uint64_t dd = mkdesc(A_WD, 8192, 128, 0) + (uint64_t)(j * 256);
    wg_fence();
#pragma unroll
    for (int m = 0; m < 4; m++) {
      wgmma_ss8<0, 1, 0>(y[m], dd + m * 64, mkdesc(A_XN + 1280, 16, 128, 0));
#pragma unroll
      for (int ks = 1; ks < 4; ks++) wgmma_ss8<1, 1, 0>(y[m], dd + m * 64 + ks * 1024, mkdesc(A_XN + 1280 + ks * 32, 16, 128, 0));
    }
    wg_commit(); wg_wait<0>();
#pragma unroll
    for (int m = 0; m < 4; m++) {
      reg_fence(y[m]);
      if ((t & 3) == 0) { float* o = yacc + j * 256 + m * 64 + 16 * w + g; o[0] = y[m][0]; o[8] = y[m][2]; }
    }
  }
  bar_sync(4, 128);
  if (t < 8) { sts32(sb + A_BAR + 160, 0); st_rel(flag + t, E); }
  __syncwarp();
}

__device__ __forceinline__ void ffn_gather(uint32_t sb, int q, int j, uint32_t E, int lane) {
  wait_all(G.f_y[q][4 * j + (lane & 3)], E);
  float4 y[4][4];
#pragma unroll
  for (int k = 0; k < 4; k++)
#pragma unroll
    for (int i = 0; i < 4; i++) y[k][i] = __ldcg((const float4*)G.y[q & 7][4 * j + k] + i * 32 + lane);
#pragma unroll
  for (int i = 0; i < 4; i++)
    sts128f(sb + 1024 + j * 2048 + i * 512 + lane * 16, (y[0][i].x + y[1][i].x) + (y[2][i].x + y[3][i].x), (y[0][i].y + y[1][i].y) + (y[2][i].y + y[3][i].y),
            (y[0][i].z + y[1][i].z) + (y[2][i].z + y[3][i].z), (y[0][i].w + y[1][i].w) + (y[2][i].w + y[3][i].w));
  bar_sync(9, 256);
}
__device__ __forceinline__ void ffn_finish(uint32_t sb, int q, const bf16* req, float r, uint32_t E, int lane, uint32_t* v) {
  if (lane == 0) sts32(sb + 16, q);
  bar_sync(8, 256);
  uint32_t xn[8];
  load_row(xn, req, lane); load_row(v, req + 512, lane);
  const float rs = rbf(1.f / (1.f + __expf(-rbf(r))));
  ffn_gather(sb, q, 7, E, lane);
#pragma unroll
  for (int i = 0; i < 4; i++) {
    float y[4] = {0.f, 0.f, 0.f, 0.f};
#pragma unroll
    for (int j = 0; j < 8; j++) {
      const uint4 u = lds128(sb + 1024 + j * 2048 + (i >> 1) * 1024 + lane * 32 + (i & 1) * 16);
      y[0] += __uint_as_float(u.x); y[1] += __uint_as_float(u.y); y[2] += __uint_as_float(u.z); y[3] += __uint_as_float(u.w);
    }
    v[2 * i] = add2(v[2 * i], add2(xn[2 * i], pack2(rbf(y[0]) * rs, rbf(y[1]) * rs)));
    v[2 * i + 1] = add2(v[2 * i + 1], add2(xn[2 * i + 1], pack2(rbf(y[2]) * rs, rbf(y[3]) * rs)));
  }
}

__global__ void __launch_bounds__(512, 1) aux_kernel(Params p) {
  extern __shared__ __align__(1024) uint8_t sm[];
  const uint32_t sb = smem_u32(sm);
  if ((sb & 0xFFFFFFu) != SBASE) TRAP();
  const int warp = __shfl_sync(~0u, threadIdx.x >> 5, 0);
  const int cta = blockIdx.x;
  const uint32_t E = __shfl_sync(~0u, *(volatile uint32_t*)&g_epoch + 1, 0);
  const uint32_t bars = sb + A_BAR;

  if (cta < 32) {
    const int cg = cta & 3, kg = cta >> 2;
    if (threadIdx.x == 0) {
      for (int i = 0; i < A_NST; i++) { mbar_init(bars + 8 * i, 1); mbar_init(bars + 64 + 8 * i, 2); }
      mbar_init(bars + 128, 8); mbar_init(bars + 136, 8); mbar_init(bars + 144, 1);
      sts32(bars + 160, 0);
      asm volatile("fence.mbarrier_init.release.cluster;" ::: "memory");
    }
    if (warp < 8) {
      asm volatile("setmaxnreg.inc.sync.aligned.u32 176;");
      const int tid = fresh_tid(), lane = tid & 31;
      uint32_t W[32][4];
      bar_arrive(3, 384);
      stage_weights(sb + A_WD, p.wo + (size_t)kg * 512 * 512 + cg * 128, 512, tid, 256);
      cp_async_wait();
      bar_sync(1, 256);
      load_frags(W, sb + A_WD, warp >> 2, warp & 3, lane);
      PIN(W[31][3]);
      bar_sync(1, 256);
      bar_arrive(2, 384);
      const uint32_t so = sb + A_STG + ((lane >> 4) * 8 + (lane & 7)) * 256 + (((warp * 2 + ((lane >> 3) & 1)) ^ (lane & 7)) << 4);
      const uint32_t tm = lane < 4 ? 0x00010001u : 0u;
      int stage = 0; uint32_t ph = 0, job = 0;
#pragma unroll 1
      for (int T = 0; T < NSTEP; T++) {
#pragma unroll 1
        for (int k = 0; k < 3; k++) {
          const int st = k == 0 ? 0 : 3 - k, s = st == 0 ? T : T - LAG;
          if (s < 0 || s >= NSEG) continue;
          float d[16];
#pragma unroll
          for (int hh = 0; hh < 4; hh++) {
            mbar_wait(bars + 8 * stage, ph);
            while (uni(lds32(bars + 160))) __nanosleep(100);
            const uint64_t db = mkdesc(A_RING, 512, 128, 0) + (uint64_t)(stage * 512);
            wg_fence();
            if (hh == 0) wgmma_rs32<0, 0>(d, W[0], db); else wgmma_rs32<1, 0>(d, W[hh * 8], db);
#pragma unroll
            for (int ks = 1; ks < 8; ks++) wgmma_rs32<1, 0>(d, W[hh * 8 + ks], db + ks * 64);
            wg_commit();
            if (hh > 0) { wg_wait<1>(); if ((tid & 127) == 0) mbar_arrive(bars + 64 + 8 * (stage == 0 ? A_NST - 1 : stage - 1)); }
            if (++stage == A_NST) { stage = 0; ph ^= 1; }
          }
          mbar_wait(bars + 144, (job & 1) ^ 1);
          wg_wait<0>(); reg_fence(d);
          if ((tid & 127) == 0) mbar_arrive(bars + 64 + 8 * (stage == 0 ? A_NST - 1 : stage - 1));
          if (cta == 0 && tid == 0) TSTAMP(6, T, k);
          const uint32_t tv = tm * ptag(s);
#define TG(i) ((pack2(d[2 * (i)], d[2 * (i) + 1]) & ~tm) | tv)
          stmatrix4_t(so, TG(0), pack2(d[2], d[3]), TG(2), pack2(d[6], d[7]));
          stmatrix4_t(so + 4096, TG(4), pack2(d[10], d[11]), TG(6), pack2(d[14], d[15]));
          fence_async_smem();
          __syncwarp();
          if (lane == 0) mbar_arrive(bars + 128 + 8 * (job & 1));
          job++;
        }
      }
    } else if (warp < 12) {
      asm volatile("setmaxnreg.dec.sync.aligned.u32 120;");
      const int tid = fresh_tid(), lane = tid & 31;
      const int w = warp - 8, t = tid - 256;
      uint32_t wv[8];
      const float wsum = load_wr(wv, p.wr, lane);
#pragma unroll 1
      for (int s = cta + 4; s < NSEG; s += 32) {
#pragma unroll 1
        for (int pr = w; pr < 16; pr += 4) input_ln_pair(p.x, s, pr, lane);
        bar_sync(4, 128);
        if (t == 0) st_rel(&G.f_h1[s], E);
      }
      bar_sync(2, 384);
      { int guard = 0; while (ld_rlx(&G.f_loaded[cta]) != E) { __nanosleep(200); if (++guard > (1 << 22)) TRAP(); } }
#pragma unroll 1
      for (int i = t; i < 512 * 7; i += 128) {
        const int k = i / 7, pc = i % 7;
        cp_async16(sb + A_WG + (k >> 3) * 896 + pc * 128 + (k & 7) * 16, p.wg + (size_t)k * 1792 + cta * 56 + pc * 8);
        cp_async16(sb + A_WU + (k >> 3) * 896 + pc * 128 + (k & 7) * 16, p.wu + (size_t)k * 1792 + cta * 56 + pc * 8);
        cp_async16(sb + A_WD + (i >> 9) * 8192 + (i & 63) * 128 + ((i >> 6) & 7) * 16, p.wd + (size_t)cta * 56 * 512 + i * 8);
        if ((i >> 7) % 4 == 3) cp_async_wait();
      }
      cp_async_wait();
      fence_async_smem();
      bar_sync(4, 128);
      const int tj = (cta * 4 + w) & 31, st = 1 + ((cta >> 3) & 1), sq = cta >> 4;
      unsigned long long run = 0, run2 = 0, best = 0, hist = 0;
      uint32_t open = 0;
#pragma unroll 1
      for (int i = 0; i <= NSTEP; i++) {
        int tok = -1; const bf16* req = nullptr;
        if (i < NSEG) {
          const int cd = (int)uni(route_step(i, E, lane, run));
          run = __shfl_sync(~0u, run, 0);
          hist = hist << 8 | (uint32_t)(cd + 1);
          if (cd >= 0) { tok = rtok(run); req = G.seg[tok >> 5].req1[tok & 31][0]; }
        } else {
          const unsigned long long m = wait_words(G.f_l2[i - NSEG], E);
          const unsigned long long n = ld_rlxu64(G.f_l2[min(i - NSEG + 1 + (lane & 7), LAG)]);
          const bool over = bar_or(4, 128, rfresh(n, E) && n != m);
          if (m != run2 && !over) { run2 = m; tok = rtok(m); req = G.req2[(tok >> 5) < (rtok(run) >> 5) ? 0 : 1][tok][0]; }
        }
        tok = __shfl_sync(~0u, tok, 0);
        if (tok >= 0) {
          if (cta == 0 && t == 0) TSTAMP(8, i & 127, 0);
          ffn_slice(sb, req, G.y[i & 7][cta], G.f_y[i][cta], E, t, i < NSEG);
          if (cta == 0 && t == 0) TSTAMP(8, i & 127, 1);
        }
        const int s = i - LAG;
        if (s < 0 || i >= NSEG) continue;
        const int cd = (int)((hist >> (8 * LAG)) & 255) - 1;
        if (cd >= 0 && st == 2) best = 0;
        const int ts = rtok(run) >> 5;
        if ((s & 1) == sq) {
          const int tk = s * 32 + tj;
          unsigned long long wd = (unsigned long long)E << 43;
          if (st == 1 ? s < ts || i < NSEG - 1 : s >= ts) {
            if (st == 2 && cd == tj) wait_eq(&G.f_hc[s], E);
            wd = token_post<false>(st, tk, st == 2 && cd == tj ? G.x2c[s] : G.seg[tk >> 5].x2[tk & 31],
                                   st == 2 || s < ts ? p.out + (size_t)tk * 512 : G.seg[s].n[tj], G.req2[st - 1][tk][0], best, wv, wsum, E, lane);
            best = max(best, wd);
            if (st == 1 && s >= ts) open |= 1u << (s >> 1);
          }
          __syncwarp();
          if (lane < 4) st_rel64(&G.f_w2[st - 1][s][tj][lane], wd);
          __syncwarp();
        }
        if (st == 1) {
          if (i == NSEG - 1 && t == 0 && cta == 0) GSTAMP(1, 0);
#pragma unroll 1
          for (int n = i == NSEG - 1 ? 32 : 2; n > 0 && open; n--) {
            const int s0 = 2 * (__ffs(open) - 1) + sq;
            if (s0 >= ts) break;
            open &= open - 1;
            uint32_t v[8];
            load_row(v, G.seg[s0].n[tj], lane);
            wait_words(G.f_w2[1][s0][tj], E);
            store_row(p.out + (size_t)(s0 * 32 + tj) * 512, v, lane);
          }
          if (i == NSEG - 1) {
            __syncwarp();
            if (lane == 0) st_rel(&G.f_cp[sq * 32 + tj], E);
            if (t == 0 && cta == 0) GSTAMP(1, 3);
          }
        }
      }
    } else {
      asm volatile("setmaxnreg.dec.sync.aligned.u32 40;");
      const int tid = fresh_tid(), lane = tid & 31;
      const int w = warp - 12;
      bar_sync(3, 384);
      if (w == 0) {
        int stage = 0; uint32_t ph = 1;
#pragma unroll 1
        for (int T = 0; T < NSTEP; T++) {
#pragma unroll 1
          for (int k = 0; k < 3; k++) {
            const int st = k == 0 ? 0 : 3 - k, s = st == 0 ? T : T - LAG;
            if (s < 0 || s >= NSEG) continue;
            const uint32_t* fl = G.f_o[T][kg][st * 4 + (lane & 3)];
            uint32_t ready = 0; int guard = 0;
#pragma unroll 1
            for (int hh = 0; hh < 4; hh++) {
              while (!((ready >> hh) & 1)) {
                ready = __ballot_sync(~0u, ld_rlx(fl) == E);
                if (++guard > (1 << 23)) TRAP();
              }
              fence_async_glob();
              mbar_wait(bars + 64 + 8 * stage, ph);
              e_expect(bars + 8 * stage, 8192);
              e_g2s(sb + A_RING + stage * 8192, o_slot(st, s, kg * 4 + hh), 8192, bars + 8 * stage);
              if (++stage == A_NST) { stage = 0; ph ^= 1; }
            }
          }
          if (cta == 0 && lane == 0) TSTAMP(3, T, 0);
        }
      } else if (w < 3) {
        uint32_t job = 0;
#pragma unroll 1
        for (int T = 0; T < NSTEP; T++) {
#pragma unroll 1
          for (int k = 0; k < 3; k++) {
            const int st = k == 0 ? 0 : 3 - k, s = st == 0 ? T : T - LAG;
            if (s < 0 || s >= NSEG) continue;
            if ((job++ & 1) != w - 1) continue;
            if (s >= PRING) wait_words(st == 0 ? G.f_h2[s - PRING][lane & 3] : G.f_w2[st - 1][s - PRING][lane], E);
            mbar_wait(bars + 128 + 8 * (w - 1), ((job - 1) >> 1) & 1);
            if (cta == 0 && st == 0) TSTAMP(7, s, 0);
            e_s2g(pp_slot(st, s) + cta * 8192, sb + A_STG, 8192);
            if (lane < 8) st_rlx(&G.f_acc[st][s][cta][lane], E);
            asm volatile("cp.async.bulk.commit_group;\n cp.async.bulk.wait_group.read 0;" ::: "memory");
            __syncwarp();
            e_arrive(bars + 144);
            __syncwarp();
            if (cta == 0 && st == 0) TSTAMP(7, s, 1);
          }
        }
        bulk_wait();
      }
    }
  } else {
    const int tid = fresh_tid(), lane = tid & 31;
    const int qd = cta - 32;
    input_ln_pair(p.x, qd, warp, lane);
    bar_sync(6, 512);
    if (tid == 0) st_rel(&G.f_h1[qd], E);
    volatile int* bc = (volatile int*)sm;
    if (warp == 15) {
      unsigned long long run = 0;
      unsigned long long b2[2][2] = {{0, 0}, {0, 0}};
      auto track = [&](int s) {
#pragma unroll
        for (int k = 0; k < 2; k++) {
          const unsigned long long m = warp_max<16>(wait_words(G.f_w2[k][s][lane], E));
          if (lane == (s & 31)) { if (s < 32) b2[k][0] = m; else b2[k][1] = m; }
        }
      };
#pragma unroll 1
      for (int s = 0; s < NSEG; s++) {
        const int cd = route_step(s, E, lane, run);
        if (cd >= 0 && qd == (s & 1)) {
          uint32_t v[1][8], h[1][8];
          ffn_finish(sb, s, G.seg[s].req1[cd][0], rscore(run), E, lane, v[0]);
          if (lane == 0) TSTAMP(8, s, 2);
          ln_rows<1>(v, h);
#pragma unroll
          for (int i = 0; i < 8; i++) st_rlx64(&G.hc[s][(i >> 2) * 128 + 4 * lane + (i & 3)], h[0][i], E);
          if (lane == 0) TSTAMP(8, s, 3);
          store_row(G.x2c[s], v[0], lane);
          __syncwarp();
          if (lane == 0) st_rel(&G.f_hc[s], E);
        }
        if (qd == 2 && s > LAG) track(s - LAG - 1);
      }
      wait_eq(&G.f_hc[rtok(run) >> 5], E);
      if (lane == 0) *bc = rtok(run);
      bar_sync(7, 288);
      if (qd == 2) {
        uint32_t v[8];
        const int ts = rtok(run) >> 5;
        track(NSEG - LAG - 1);
        run = 0;
        int kl = 0;
#pragma unroll 1
        for (int k = 0; k <= LAG; k++) {
          const int s = NSEG - LAG - 1 + k;
          const unsigned long long m = warp_max<16>(k == 0 ? max(lane < ts ? b2[0][0] : b2[1][0], lane + 32 < ts ? b2[0][1] : b2[1][1])
                                                           : wait_words(G.f_w2[s < ts ? 0 : 1][s][lane], E));
          const bool lead = m > run;
          if (lead) { run = m; __threadfence(); }
          if (lane < 4) st_rlx64(&G.f_l2[k][lane], (uint32_t)run, (uint32_t)(run >> 32));
          if (lead) kl = k;
          if (k == LAG - 1) { wait_all(&G.f_cp[lane], E); wait_all(&G.f_cp[32 + lane], E); }
          if (k == LAG - 1 || (k == LAG && lead)) ffn_finish(sb, NSEG + kl, G.req2[(rtok(run) >> 5) < ts ? 0 : 1][rtok(run)][0], rscore(run), E, lane, v);
        }
        if (lane == 0) GSTAMP(1, 1);
        store_row(p.out + (size_t)rtok(run) * 512, v, lane);
        if (lane == 0) GSTAMP(1, 2);
      }
      if (lane == 0) sts32(sb + 16, (uint32_t)-1);
      bar_sync(8, 256);
      if (qd == 2) {
        asm volatile("griddepcontrol.wait;" ::: "memory");
        if (lane == 0) *(volatile uint32_t*)&g_epoch = E;
      }
    } else if (warp >= 8) {
#pragma unroll 1
      for (;;) {
        bar_sync(8, 256);
        const int q = (int)uni(lds32(sb + 16));
        if (q < 0) break;
        ffn_gather(sb, q, warp - 8, E, lane);
      }
    } else {
      uint32_t wv[8];
      const float wsum = load_wr(wv, p.wr, lane);
      unsigned long long best = 0;
      int ttok = 0;
#pragma unroll 1
      for (int i = 0; i < NSTEP; i++) {
        const bool last = i >= NSEG;
        if (i == NSEG) { bar_sync(7, 288); ttok = *bc; best = 0; }
        const int s = last ? i - LAG : i, st = !last ? 0 : s < (ttok >> 5) ? 1 : 2;
        const int tk = s * 32 + qd * 8 + warp;
        const unsigned long long wd = token_post<true>(st, tk, !last ? p.x + (size_t)tk * 512 : tk == ttok ? G.x2c[s] : G.seg[tk >> 5].x2[tk & 31],
                                                 last ? p.out + (size_t)tk * 512 : G.seg[s].x2[tk & 31], last ? G.req2[st - 1][tk][0] : G.seg[s].req1[tk & 31][0], best, wv, wsum, E, lane);
        best = max(best, wd);
        volatile unsigned long long* ws = (volatile unsigned long long*)(sm + 64) + (i & 1) * 8;
        if (lane == 0) ws[warp] = wd;
        const unsigned long long lead = i == NSTEP - 1 ? ld_rlxu64(G.f_l2[LAG - 1]) : 0;
        bar_sync(5, 256);
        if (warp == 0) {
          if (qd == 0 && lane == 0) TSTAMP(4, i, 1);
          if (!last) { const unsigned long long m = warp_max<4>(ws[lane & 7]); if (lane < 4) st_rel64(&G.f_h2[s][qd][lane], m); }
          else {
            const unsigned long long v = ws[lane >> 2];
            if (!__all_sync(~0u, rfresh(lead, E) && v < lead)) __threadfence();
            st_rlx64(&G.f_w2[st - 1][s][qd * 8 + (lane >> 2)][lane & 3], (uint32_t)v, (uint32_t)(v >> 32));
            asm volatile("st.relaxed.gpu.global.u64 [%0], %1;" :: "l"(&G.f_w2[2 - st][s][qd * 8 + (lane >> 2)][lane & 3]), "l"((unsigned long long)E << 43) : "memory");
          }
          if (qd == 0 && lane == 0) TSTAMP(4, i, 2);
        }
        __syncwarp();
      }
    }
  }
}

}

extern "C" void kernel_launch(void* const* d_in, const int* in_sizes, int n_in, void* d_out, int out_size) {
  (void)in_sizes; (void)n_in; (void)out_size;
  static bool init = false;
  if (!init) {
    cudaFuncSetAttribute(main_kernel, cudaFuncAttributeMaxDynamicSharedMemorySize, M_TOTAL);
    cudaFuncSetAttribute(aux_kernel, cudaFuncAttributeMaxDynamicSharedMemorySize, A_TOTAL);
    init = true;
  }
  Params p;
  p.x = (const bf16*)d_in[0]; p.mem0 = (const bf16*)d_in[1]; p.wq = (const bf16*)d_in[2]; p.wk = (const bf16*)d_in[3];
  p.wv = (const bf16*)d_in[4]; p.wo = (const bf16*)d_in[5]; p.wr = (const bf16*)d_in[8]; p.wg = (const bf16*)d_in[9];
  p.wu = (const bf16*)d_in[10]; p.wd = (const bf16*)d_in[11]; p.out = (bf16*)d_out; p.zero = 0; p.zero2 = 0;
  cudaStream_t st = cudaStreamPerThread;
  main_kernel<<<96, 512, M_TOTAL, st>>>(p);
  cudaLaunchConfig_t cfg = {};
  cfg.gridDim = dim3(36); cfg.blockDim = dim3(512); cfg.dynamicSmemBytes = A_TOTAL; cfg.stream = st;
  cudaLaunchAttribute at[1];
  at[0].id = cudaLaunchAttributeProgrammaticStreamSerialization; at[0].val.programmaticStreamSerializationAllowed = 1;
  cfg.attrs = at; cfg.numAttrs = 1;
  cudaLaunchKernelEx(&cfg, aux_kernel, p);
}
```

```cpp
#include <cuda_runtime.h>
#include <cuda_bf16.h>
#include <stdint.h>
#include <stddef.h>

namespace {

typedef __nv_bfloat16 bf16;

constexpr int NSEG = 64;
#define LAG_ 5
constexpr int LAG = LAG_;
constexpr int NSTEP = NSEG + LAG;
constexpr int ORING = 8, PRING = 4;
static_assert(LAG < 8, "rings");

#define E1_ 10
#define E3_ 10
constexpr int E1 = E1_, EA = E1_ + E3_;
static_assert(EA % 4 == 0 && EA < 32, "early part: whole 64-column chunks");
#define PAUSE_ 13
#define PAUS2_ 29
#define PST2_ 2
#define HAND_ 4
#define SALT_ 0
#define TP(i, v) (v)
#define XDLY_ TP(0, 2075)
#define YDLY_ TP(1, 3400)
#define X1_ TP(2, 100)
#define X2_ TP(3, 350)
#define Y1_ TP(4, 200)
#define Y2_ TP(5, 450)
#define HGAP_ TP(6, 50)
#define TGAP_ TP(7, 100)
#define ADLY_ TP(8, 600)
#define ODLY_ TP(9, 2800)
#define HDLY_ TP(11, 0)
#define TDLY_ TP(15, 4150)
#define SDLY_ TP(12, 800)
#define AGAP_ 100
#define BOFF_ TP(13, 200)
#define YOFF_ TP(16, 150)
#define YUP_ TP(20, 40)
#define YDN_ TP(21, 4)
#define T1GAP_ TP(22, 0)
#define OGAP_ TP(23, 0)
#define CDLY_ TP(17, 300)
#define SLOW0_ TP(18, 400)
#define SLOW1_ TP(19, 300)
#define KDLY_ TP(14, 300)
#define XFR_ TP(10, 2)
__device__ uint32_t g_epoch;
struct Seg {
  uint8_t h[2][32768];
  bf16 x2[32][512], n[32][512];
  bf16 req1[32][2][512];
};
struct Mix {
  uint8_t tok[16][2][16384];
  uint8_t o[4][32][8192];
  uint8_t pp[2][8 * 32768];
};
struct Scratch {
  uint8_t xch[96 * 16384 + 65536];
  unsigned long long f_h2[NSEG][4][4];
  unsigned long long f_l2[8][4];
  unsigned long long sync[2][96][4];
  uint32_t f_o[NSTEP][8][12][8];
  uint32_t f_y[NSTEP + 1][32][8], f_cp[64];
  uint32_t f_choice[96][2], f_loaded[32], f_h1[NSEG], f_hc[NSEG];
  uint8_t pad0[2097152 - (96 * 16384 + 65536 + NSEG * 128 + 256 + 6144 + NSTEP * 3072 + (NSTEP + 1) * 1024 + 256 + 768 + 128 + NSEG * 8)];
  Mix mix[6];
  uint32_t f_acc[3][NSEG][32][8];
  unsigned long long f_w2[2][NSEG][32][4];
  uint2 hc[NSEG][256];
  bf16 x2c[NSEG][512];
  float y[8][32][512];
  Seg seg[NSEG];
  bf16 req2[2][2048][2][512];
};
static_assert(sizeof(Mix) == 2097152 && offsetof(Scratch, mix) == 2097152 && offsetof(Scratch, seg) % 1024 == 0 && ORING == 8 && PRING == 4, "layout");
__device__ uint8_t g_raw[sizeof(Scratch) + 2097152];
__device__ __forceinline__ Scratch& scr() { return *(Scratch*)(((uintptr_t)g_raw + 2097151) & ~(uintptr_t)2097151); }
#define G scr()
__device__ __forceinline__ uint8_t* o_slot(int st, int s, int head) { const int j = st * 8 + (s & 7); return G.mix[j % 6].o[j / 6][head]; }
__device__ __forceinline__ uint8_t* pp_slot(int st, int s) { const int j = st * 4 + (s & 3); return G.mix[j % 6].pp[j / 6]; }

#define TRAP() __trap()
__device__ __forceinline__ uint32_t smem_u32(const void* p) { return (uint32_t)__cvta_generic_to_shared(p); }
__device__ __forceinline__ int fresh_tid() { const int t = threadIdx.x; return __shfl_sync(~0u, t, t & 31); }
__device__ __forceinline__ unsigned long long gtime64() { unsigned long long t; asm volatile("mov.u64 %0, %%globaltimer;" : "=l"(t) :: "memory"); return t; }
__device__ __forceinline__ uint32_t clk() { unsigned long long c; asm volatile("mov.u64 %0, %%clock64;" : "=l"(c) :: "memory"); return (uint32_t)c; }
__device__ __forceinline__ void wait_until(uint32_t t) {
  while ((int)(t - clk()) > 450) __nanosleep(32);
  uint32_t c;
  do { asm volatile("mov.u32 %0, %%clock;" : "=r"(c) :: "memory"); } while ((int)(c - t) < 0);
}
__device__ __forceinline__ void mbar_init(uint32_t bar, uint32_t cnt) { asm volatile("mbarrier.init.shared::cta.b64 [%0], %1;" :: "r"(bar), "r"(cnt) : "memory"); }
__device__ __forceinline__ void mbar_arrive(uint32_t bar) { asm volatile("mbarrier.arrive.shared::cta.b64 _, [%0];" :: "r"(bar) : "memory"); }
__device__ __forceinline__ void mbar_arrive_remote(uint32_t bar) { asm volatile("mbarrier.arrive.relaxed.cluster.shared::cluster.b64 _, [%0];" :: "r"(bar) : "memory"); }
__device__ __forceinline__ void mbar_expect(uint32_t bar, uint32_t bytes) { asm volatile("mbarrier.arrive.expect_tx.shared::cta.b64 _, [%0], %1;" :: "r"(bar), "r"(bytes) : "memory"); }
__device__ __forceinline__ bool mbar_try(uint32_t bar, uint32_t parity) {
  uint32_t ok;
  asm volatile("{.reg .pred p; mbarrier.try_wait.parity.shared::cta.b64 p, [%1], %2; selp.u32 %0, 1, 0, p;}" : "=r"(ok) : "r"(bar), "r"(parity) : "memory");
  return ok;
}
__device__ __forceinline__ bool mbar_test(uint32_t bar, uint32_t parity) {
  uint32_t ok;
  asm volatile("{.reg .pred p; mbarrier.test_wait.parity.shared::cta.b64 p, [%1], %2; selp.u32 %0, 1, 0, p;}" : "=r"(ok) : "r"(bar), "r"(parity) : "memory");
  return ok;
}
__device__ __forceinline__ void mbar_wait(uint32_t bar, uint32_t parity) {
  asm volatile("{\n.reg .pred p;\nWAIT:\nmbarrier.try_wait.parity.shared::cta.b64 p, [%0], %1;\n@!p bra WAIT;\n}" :: "r"(bar), "r"(parity) : "memory");
}
__device__ __forceinline__ uint32_t ld_acq(const uint32_t* p) { uint32_t v; asm volatile("ld.acquire.gpu.global.u32 %0, [%1];" : "=r"(v) : "l"(p) : "memory"); return v; }
__device__ __forceinline__ void st_rel(uint32_t* p, uint32_t v) { asm volatile("st.release.gpu.global.u32 [%0], %1;" :: "l"(p), "r"(v) : "memory"); }
__device__ __forceinline__ void st_rel64(unsigned long long* p, unsigned long long v) { asm volatile("st.release.gpu.global.u64 [%0], %1;" :: "l"(p), "l"(v) : "memory"); }
__device__ __forceinline__ uint32_t ld_rlx(const uint32_t* p) { uint32_t v; asm volatile("ld.relaxed.gpu.global.u32 %0, [%1];" : "=r"(v) : "l"(p) : "memory"); return v; }
__device__ __forceinline__ unsigned long long ld_rlxu64(const unsigned long long* p) { unsigned long long v; asm volatile("ld.relaxed.gpu.global.u64 %0, [%1];" : "=l"(v) : "l"(p) : "memory"); return v; }
__device__ __forceinline__ void st_rlx(uint32_t* p, uint32_t v) { asm volatile("st.relaxed.gpu.global.u32 [%0], %1;" :: "l"(p), "r"(v) : "memory"); }
__device__ __forceinline__ void bulk_wait() { asm volatile("cp.async.bulk.commit_group;\n cp.async.bulk.wait_group 0;" ::: "memory"); }
__device__ __forceinline__ void fence_acq() { asm volatile("fence.acquire.gpu;" ::: "memory"); }
__device__ __forceinline__ void wait_all(const uint32_t* p, uint32_t v, bool acquire = true) {
  int guard = 0;
  while (!__all_sync(~0u, ld_rlx(p) == v)) { __nanosleep(32); if (++guard > (1 << 22)) TRAP(); }
  if (acquire) fence_acq();
}
__device__ __forceinline__ void wait_eq(const uint32_t* p, uint32_t v) {
  int guard = 0;
  while (ld_rlx(p) != v) { __nanosleep(64); if (++guard > (1 << 22)) TRAP(); }
  fence_acq();
}
__device__ __forceinline__ unsigned long long rword(uint32_t E, int tok, float r) {
  uint32_t u = __float_as_uint(r + 0.f);
  u = r != r ? 0u : (u >> 31) ? ~u : u | 0x80000000u;
  return (unsigned long long)(E & 0x1FFFFFu) << 43 | (unsigned long long)u << 11 | (uint32_t)(2047 - tok);
}
__device__ __forceinline__ int rtok(unsigned long long v) { return 2047 - (int)(v & 2047u); }
__device__ __forceinline__ float rscore(unsigned long long v) { const uint32_t u = (uint32_t)(v >> 11); return __uint_as_float((u >> 31) ? u & 0x7fffffffu : ~u); }
__device__ __forceinline__ bool rfresh(unsigned long long v, uint32_t E) { return (uint32_t)(v >> 43) == (E & 0x1FFFFFu); }
template <int TOP> __device__ __forceinline__ unsigned long long warp_max(unsigned long long v) {
#pragma unroll
  for (int o = TOP; o > 0; o >>= 1) { const unsigned long long ov = __shfl_xor_sync(~0u, v, o); v = ov > v ? ov : v; }
  return v;
}
template <int off> __device__ __forceinline__ uint2 ld_rlx64(const void* p) { unsigned long long v; asm volatile("ld.relaxed.gpu.global.b64 %0, [%1+%2];" : "=l"(v) : "l"(p), "n"(off) : "memory"); return make_uint2((uint32_t)v, (uint32_t)(v >> 32)); }
template <int off> __device__ __forceinline__ uint4 ld_rlx128(const void* p) {
  unsigned long long a, b; asm volatile("ld.relaxed.gpu.global.v2.b64 {%0,%1}, [%2+%3];" : "=l"(a), "=l"(b) : "l"(p), "n"(off) : "memory");
  return make_uint4((uint32_t)a, (uint32_t)(a >> 32), (uint32_t)b, (uint32_t)(b >> 32));
}
__device__ __forceinline__ void st_rlx64(void* p, uint32_t lo, uint32_t hi) { asm volatile("{.reg .b64 t; mov.b64 t, {%1,%2}; st.relaxed.gpu.global.b64 [%0], t;}" :: "l"(p), "r"(lo), "r"(hi) : "memory"); }
__device__ __forceinline__ void cp_async16(uint32_t dst, const void* src) { asm volatile("cp.async.cg.shared.global [%0], [%1], 16;" :: "r"(dst), "l"(src) : "memory"); }
__device__ __forceinline__ void cp_async_wait() { asm volatile("cp.async.wait_all;" ::: "memory"); }
__device__ __forceinline__ void fence_async_smem() { asm volatile("fence.proxy.async.shared::cta;" ::: "memory"); }
__device__ __forceinline__ void fence_async_glob() { asm volatile("fence.proxy.async.global;" ::: "memory"); }
__device__ __forceinline__ float ex2(float x) { float y; asm("ex2.approx.ftz.f32 %0, %1;" : "=f"(y) : "f"(x)); return y; }
__device__ __forceinline__ float sqrt_fast(float x) { float y; asm("sqrt.approx.ftz.f32 %0, %1;" : "=f"(y) : "f"(x)); return y; }
__device__ __forceinline__ float rcp(float x) { float y; asm("rcp.approx.ftz.f32 %0, %1;" : "=f"(y) : "f"(x)); return y; }
__device__ __forceinline__ void bar_sync(int id, int n) { asm volatile("bar.sync %0, %1;" :: "r"(id), "r"(n) : "memory"); }
__device__ __forceinline__ bool bar_or(int id, int n, bool v) {
  uint32_t r;
  asm volatile("{.reg .pred p, q; setp.ne.u32 p, %3, 0; barrier.cta.red.or.aligned.pred q, %1, %2, p; selp.u32 %0, 1, 0, q;}" : "=r"(r) : "r"(id), "r"(n), "r"((uint32_t)v) : "memory");
  return r;
}
__device__ __forceinline__ uint32_t mapa(uint32_t a, uint32_t rank) { uint32_t r; asm volatile("mapa.shared::cluster.u32 %0, %1, %2;" : "=r"(r) : "r"(a), "r"(rank)); return r; }
__device__ __forceinline__ void cluster_sync() { asm volatile("barrier.cluster.arrive.release.aligned; barrier.cluster.wait.acquire.aligned;" ::: "memory"); }
__device__ __forceinline__ void st_async32(uint32_t dst, uint32_t v, uint32_t bar) { asm volatile("st.async.shared::cluster.mbarrier::complete_tx::bytes.b32 [%0], %1, [%2];" :: "r"(dst), "r"(v), "r"(bar) : "memory"); }
#define ELECT(op) "{.reg .pred p; elect.sync _|p, 0xffffffff; @p " op "}"
__device__ __forceinline__ void e_arrive(uint32_t bar) { asm volatile(ELECT("mbarrier.arrive.shared::cta.b64 _, [%0];") :: "r"(bar) : "memory"); }
__device__ __forceinline__ void e_expect(uint32_t bar, uint32_t bytes) { asm volatile(ELECT("mbarrier.arrive.expect_tx.shared::cta.b64 _, [%0], %1;") :: "r"(bar), "r"(bytes) : "memory"); }
__device__ __forceinline__ void e_g2s(uint32_t dst, const void* src, uint32_t bytes, uint32_t bar) {
  asm volatile(ELECT("cp.async.bulk.shared::cluster.global.mbarrier::complete_tx::bytes [%0], [%1], %2, [%3];") :: "r"(dst), "l"(src), "r"(bytes), "r"(bar) : "memory");
}
__device__ __forceinline__ void e_mc(uint32_t dst, const void* src, uint32_t bytes, uint32_t bar, uint16_t mask) {
  asm volatile(ELECT("cp.async.bulk.shared::cluster.global.mbarrier::complete_tx::bytes.multicast::cluster [%0], [%1], %2, [%3], %4;")
               :: "r"(dst), "l"(src), "r"(bytes), "r"(bar), "h"(mask) : "memory");
}
__device__ __forceinline__ void e_s2g(void* dst, uint32_t src, uint32_t bytes) {
  asm volatile(ELECT("cp.async.bulk.global.shared::cta.bulk_group [%0], [%1], %2;") :: "l"(dst), "r"(src), "r"(bytes) : "memory");
}
__device__ __forceinline__ uint32_t clk32() { uint32_t c; asm volatile("mov.u32 %0, %%clock;" : "=r"(c) :: "memory"); return c; }
__device__ __forceinline__ void spin_until(uint32_t t) { while ((int)(clk32() - t) < 0) {} }
__device__ __forceinline__ uint32_t uni(uint32_t v) { return __shfl_sync(~0u, v, 0); }
__device__ __forceinline__ uint32_t pack2(float lo, float hi) { uint32_t r; asm("cvt.rn.bf16x2.f32 %0, %1, %2;" : "=r"(r) : "f"(hi), "f"(lo)); return r; }
__device__ __forceinline__ uint32_t add2(uint32_t a, uint32_t b) { uint32_t r; asm("add.rn.bf16x2 %0, %1, %2;" : "=r"(r) : "r"(a), "r"(b)); return r; }
__device__ __forceinline__ float rbf(float x) { return __bfloat162float(__float2bfloat16_rn(x)); }
__device__ __forceinline__ float blo(uint32_t u) { return __uint_as_float(u << 16); }
__device__ __forceinline__ float bhi(uint32_t u) { return __uint_as_float(u & 0xffff0000u); }
__device__ __forceinline__ uint32_t gentag(uint32_t g) { return (g & 1u) | (g & 2u) << 15; }
__device__ __forceinline__ uint32_t pack2_tag(float lo, float hi, uint32_t tag) {
  const uint32_t u = __byte_perm(__float_as_uint(lo), __float_as_uint(hi), 0x7632);
  return u + ((u ^ tag) & 0x10001u);
}
__device__ __forceinline__ uint32_t xo2(uint32_t a, uint32_t b, uint32_t t) { uint32_t r; asm("lop3.b32 %0, %1, %2, %3, 0x7e;" : "=r"(r) : "r"(a), "r"(b), "r"(t)); return r; }
__device__ __forceinline__ uint32_t or3(uint32_t a, uint32_t b, uint32_t c) { uint32_t r; asm("lop3.b32 %0, %1, %2, %3, 0xfe;" : "=r"(r) : "r"(a), "r"(b), "r"(c)); return r; }
__device__ __forceinline__ void stmatrix4(uint32_t a, uint32_t r0, uint32_t r1, uint32_t r2, uint32_t r3) {
  asm volatile("stmatrix.sync.aligned.m8n8.x4.shared.b16 [%0], {%1,%2,%3,%4};" :: "r"(a), "r"(r0), "r"(r1), "r"(r2), "r"(r3) : "memory");
}
__device__ __forceinline__ void stmatrix4_t(uint32_t a, uint32_t r0, uint32_t r1, uint32_t r2, uint32_t r3) {
  asm volatile("stmatrix.sync.aligned.m8n8.x4.trans.shared.b16 [%0], {%1,%2,%3,%4};" :: "r"(a), "r"(r0), "r"(r1), "r"(r2), "r"(r3) : "memory");
}
__device__ __forceinline__ void ldmatrix4_t(uint32_t* r, uint32_t a) {
  asm volatile("ldmatrix.sync.aligned.m8n8.x4.trans.shared.b16 {%0,%1,%2,%3}, [%4];" : "=r"(r[0]), "=r"(r[1]), "=r"(r[2]), "=r"(r[3]) : "r"(a) : "memory");
}
__device__ __forceinline__ void ldmatrix4(uint32_t* r, uint32_t a) {
  asm volatile("ldmatrix.sync.aligned.m8n8.x4.shared.b16 {%0,%1,%2,%3}, [%4];" : "=r"(r[0]), "=r"(r[1]), "=r"(r[2]), "=r"(r[3]) : "r"(a) : "memory");
}
__device__ __forceinline__ void hmma16(float* c, const uint32_t* a, uint32_t b0, uint32_t b1) {
  asm volatile("mma.sync.aligned.m16n8k16.row.col.f32.bf16.bf16.f32 {%0,%1,%2,%3}, {%4,%5,%6,%7}, {%8,%9}, {%0,%1,%2,%3};"
               : "+f"(c[0]), "+f"(c[1]), "+f"(c[2]), "+f"(c[3]) : "r"(a[0]), "r"(a[1]), "r"(a[2]), "r"(a[3]), "r"(b0), "r"(b1));
}
__device__ __forceinline__ void hmma8(float* c, uint32_t a0, uint32_t a1, uint32_t b0) {
  asm volatile("mma.sync.aligned.m16n8k8.row.col.f32.bf16.bf16.f32 {%0,%1,%2,%3}, {%4,%5}, {%6}, {%0,%1,%2,%3};"
               : "+f"(c[0]), "+f"(c[1]), "+f"(c[2]), "+f"(c[3]) : "r"(a0), "r"(a1), "r"(b0));
}
__device__ __forceinline__ uint4 lds128(uint32_t a) { uint4 v; asm volatile("ld.shared.v4.u32 {%0,%1,%2,%3}, [%4];" : "=r"(v.x), "=r"(v.y), "=r"(v.z), "=r"(v.w) : "r"(a) : "memory"); return v; }
__device__ __forceinline__ void sts128(uint32_t a, uint4 v) { asm volatile("st.shared.v4.u32 [%0], {%1,%2,%3,%4};" :: "r"(a), "r"(v.x), "r"(v.y), "r"(v.z), "r"(v.w) : "memory"); }
__device__ __forceinline__ void sts128f(uint32_t a, float x, float y, float z, float w) { asm volatile("st.shared.v4.f32 [%0], {%1,%2,%3,%4};" :: "r"(a), "f"(x), "f"(y), "f"(z), "f"(w) : "memory"); }
__device__ __forceinline__ uint32_t lds32(uint32_t a) { uint32_t v; asm volatile("ld.shared.u32 %0, [%1];" : "=r"(v) : "r"(a) : "memory"); return v; }
__device__ __forceinline__ void sts32(uint32_t a, uint32_t v) { asm volatile("st.shared.u32 [%0], %1;" :: "r"(a), "r"(v) : "memory"); }

constexpr uint32_t SBASE = 1024;
__host__ __device__ constexpr uint64_t mkdesc(uint32_t off, uint32_t lbo, uint32_t sbo, uint32_t swz) {
  return (uint64_t)(((SBASE + off) & 0x3FFFF) >> 4) | ((uint64_t)(lbo >> 4) << 16) | ((uint64_t)(sbo >> 4) << 32) | ((uint64_t)swz << 62);
}
__device__ __forceinline__ void wg_fence() { asm volatile("wgmma.fence.sync.aligned;" ::: "memory"); }
__device__ __forceinline__ void wg_commit() { asm volatile("wgmma.commit_group.sync.aligned;" ::: "memory"); }
template <int N> __device__ __forceinline__ void wg_wait() { asm volatile("wgmma.wait_group.sync.aligned %0;" :: "n"(N) : "memory"); }

template <int N> __device__ __forceinline__ void reg_fence(float (&d)[N], int n = N) {
#pragma unroll
  for (int i = 0; i < N; i++) if (i < n) asm volatile("" : "+f"(d[i]) :: "memory");
}
#define F4(b) "+f"(d[b]), "+f"(d[b + 1]), "+f"(d[b + 2]), "+f"(d[b + 3])
#define F8(b) F4(b), F4(b + 4)
#define F16(b) F8(b), F8(b + 8)
#define G4(b) "=f"(d[b]), "=f"(d[b + 1]), "=f"(d[b + 2]), "=f"(d[b + 3])
#define G8(b) G4(b), G4(b + 4)
#define G16(b) G8(b), G8(b + 8)
#define RS_IN "r"(a[0]), "r"(a[1]), "r"(a[2]), "r"(a[3]), "l"(db), "n"(SD), "n"(TB)
#define SS_IN "l"(da), "l"(db), "n"(SD), "n"(TA), "n"(TB)
#define WG_OP(str, out0, out1, in) do { if (SD || KEEP) asm volatile(str : out1 : in); else asm volatile(str : out0 : in); } while (0)
#define O12(X) X##8(0), X##4(8)
#define O20(X) X##16(0), X##4(16)
#define O32(X) X##16(0), X##16(16)
template <int SD, int TB, int KEEP = 0> __device__ __forceinline__ void wgmma_rs24(float* d, const uint32_t* a, uint64_t db) {
  WG_OP("wgmma.mma_async.sync.aligned.m64n24k16.f32.bf16.bf16 {%0,%1,%2,%3,%4,%5,%6,%7,%8,%9,%10,%11}, {%12,%13,%14,%15}, %16, %17, 1, 1, %18;", O12(G), O12(F), RS_IN);
}
template <int SD, int TB, int KEEP = 0> __device__ __forceinline__ void wgmma_rs32(float* d, const uint32_t* a, uint64_t db) {
  WG_OP("wgmma.mma_async.sync.aligned.m64n32k16.f32.bf16.bf16 {%0,%1,%2,%3,%4,%5,%6,%7,%8,%9,%10,%11,%12,%13,%14,%15}, {%16,%17,%18,%19}, %20, %21, 1, 1, %22;", G16(0), F16(0), RS_IN);
}
template <int SD, int TB, int KEEP = 0> __device__ __forceinline__ void wgmma_rs40(float* d, const uint32_t* a, uint64_t db) {
  WG_OP("wgmma.mma_async.sync.aligned.m64n40k16.f32.bf16.bf16 {%0,%1,%2,%3,%4,%5,%6,%7,%8,%9,%10,%11,%12,%13,%14,%15,"
        "%16,%17,%18,%19}, {%20,%21,%22,%23}, %24, %25, 1, 1, %26;", O20(G), O20(F), RS_IN);
}
template <int SD, int TB, int KEEP = 0> __device__ __forceinline__ void wgmma_rs64(float* d, const uint32_t* a, uint64_t db) {
  WG_OP("wgmma.mma_async.sync.aligned.m64n64k16.f32.bf16.bf16 {%0,%1,%2,%3,%4,%5,%6,%7,%8,%9,%10,%11,%12,%13,%14,%15,"
        "%16,%17,%18,%19,%20,%21,%22,%23,%24,%25,%26,%27,%28,%29,%30,%31}, {%32,%33,%34,%35}, %36, %37, 1, 1, %38;", O32(G), O32(F), RS_IN);
}
template <int SD, int TA, int TB, int KEEP = 0> __device__ __forceinline__ void wgmma_ss24(float* d, uint64_t da, uint64_t db) {
  WG_OP("wgmma.mma_async.sync.aligned.m64n24k16.f32.bf16.bf16 {%0,%1,%2,%3,%4,%5,%6,%7,%8,%9,%10,%11}, %12, %13, %14, 1, 1, %15, %16;", O12(G), O12(F), SS_IN);
}
template <int SD, int TA, int TB, int KEEP = 0> __device__ __forceinline__ void wgmma_ss8(float* d, uint64_t da, uint64_t db) {
  WG_OP("wgmma.mma_async.sync.aligned.m64n8k16.f32.bf16.bf16 {%0,%1,%2,%3}, %4, %5, %6, 1, 1, %7, %8;", G4(0), F4(0), SS_IN);
}
__device__ __forceinline__ void bar_arrive(int id, int n) { asm volatile("bar.arrive %0, %1;" :: "r"(id), "r"(n) : "memory"); }
__device__ __forceinline__ uint32_t vis_bits(int pos, int t) {
  uint32_t m = 0;
#pragma unroll
  for (int i = 0; i < 8; i++) m |= (8 * (i / 2 + 1) + 2 * t + (i & 1) <= pos) ? 1u << i : 0u;
  return m;
}

__device__ __forceinline__ unsigned long long wait_words(const unsigned long long* p, uint32_t E) {
  int guard = 0; unsigned long long m;
  while (m = ld_rlxu64(p), !__all_sync(~0u, rfresh(m, E))) { __nanosleep(20); if (++guard > (1 << 22)) TRAP(); }
  fence_acq();
  return m;
}
__device__ __forceinline__ int route_step(int s, uint32_t E, int lane, unsigned long long& run) {
  const unsigned long long m = warp_max<2>(wait_words(G.f_h2[s][lane & 3], E));
  if (s == 0 || m > run) { run = m; return rtok(m) & 31; }
  return -1;
}

struct Params {
  const bf16 *x, *mem0, *wq, *wk, *wv, *wo, *wr, *wg, *wu, *wd;
  bf16* out;
  uint32_t zero2;
  unsigned long long zero;
};

constexpr uint32_t WSTG_STRIDE = 272;
__device__ __forceinline__ void stage_weights(uint32_t stg, const bf16* src, int ld, int tid, int nthr) {
  for (int i = tid; i < 512 * 16; i += nthr) {
    int k = i >> 4, c = i & 15;
    cp_async16(stg + k * WSTG_STRIDE + c * 16, src + (size_t)k * ld + c * 8);
  }
}
__device__ __forceinline__ void load_frags(uint32_t (*W)[4], uint32_t stg, int wg, int w, int lane) {
  uint32_t a = stg + ((lane >> 4) * 8 + (lane & 7)) * WSTG_STRIDE + (64 * wg + 16 * w + ((lane >> 3) & 1) * 8) * 2;
#pragma unroll
  for (int ks = 0; ks < 32; ks++) ldmatrix4_t(W[ks], a + ks * 16 * WSTG_STRIDE);
}

constexpr uint32_t M_H = 0;
constexpr uint32_t M_MEM = 65536;
constexpr uint32_t M_Q = M_MEM + 24576;
constexpr uint32_t M_K = M_Q + 12288;
constexpr uint32_t M_V = M_K + 12288;
constexpr uint32_t M_OM = M_V + 12288;
constexpr uint32_t M_OST = M_OM + 6144;
constexpr uint32_t M_TST = M_OST + 8192;
constexpr uint32_t M_WO = M_TST + 16384;
constexpr uint32_t M_M0 = M_WO + 49152;
constexpr uint32_t M_PT = M_M0 + 2048;
constexpr uint32_t M_BAR = M_PT + 12288;
constexpr uint32_t M_TOTAL = M_BAR + 384;
static_assert(M_TOTAL <= 232448, "main smem");
static_assert(M_WO >= 512 * WSTG_STRIDE, "staging overlaps Wo");
enum { B_LAND = 0  , B_QK = 3, B_V, B_TOK, B_OM, B_HA, B_HB, B_HAE, B_HBE, B_OST, B_OFREE, B_SYNC,
       B_STG, B_STG1, B_SS, B_TFREE, B_KFREE, B_VFREE, B_FIX  , B_NUM = B_FIX + 8 };
static_assert(B_NUM * 8 <= 256, "barriers");
constexpr uint32_t M_CAND = M_BAR + 256;
constexpr uint32_t M_BASE = M_BAR + 272;
constexpr uint32_t M_ZERO = M_BAR + 280;
constexpr uint32_t M_BAS2 = M_BAR + 328;
constexpr uint32_t M_NEAR = M_BAR + 288;
enum { N_GO2 = 3, N_GO3, N_GO4, N_AG, N_W };

#define GSTAMP(slot, i)
#define TSTAMP(slot, i, k)
#define STAMP(i)
#define ASTAMP(i)
#define WSTAMP(i)
#define CSTAMP(i, v)
#define PIN(x) asm volatile("" : "+r"(x))
#define SCHED(k) asm volatile("{\n.reg .pred p;\nsetp.ne.u32 p, %0, 0;\n@p trap;\n}" :: "r"(zz & (1u << (k))) : "memory")
#define HOLD(k, v) asm volatile("{\n.reg .pred p;\nsetp.ne.u32 p, %0, 0;\n@p st.shared.u32 [%0], %1;\n}" :: "r"(zz & (1u << (k))), "r"(v) : "memory")
#define DRAIN(a) (lds32((a) + zz) & zz)
#define BAR(i) (sb + M_BAR + 8 * (i))

__device__ __forceinline__ int probe(const uint8_t* p, int n) {
  int best = 1 << 30; uint32_t v = 0;
#pragma unroll 1
  for (int r = 0; r < n; r++) {
    uint32_t t0 = clk();
    asm volatile("atom.relaxed.gpu.global.or.b32 %0, [%1], %2;" : "=r"(v) : "l"(p + 3968), "r"(v & 0u) : "memory");
    if (v == 0x7fffffffu) t0++;
    best = min(best, (int)(clk() - t0));
  }
  return best;
}
__device__ __forceinline__ void load_mem0(uint4* u, int k0, int lane, const bf16* mem0) {
#pragma unroll
  for (int i = 0; i < 2; i++) {
    const unsigned short* m = (const unsigned short*)mem0 + k0 + lane + 32 * i;
    u[i] = make_uint4(m[0] | (uint32_t)m[512] << 16, m[1024] | (uint32_t)m[1536] << 16, m[2048] | (uint32_t)m[2560] << 16, m[3072] | (uint32_t)m[3584] << 16);
  }
}

__device__ __forceinline__ void paced_h(uint32_t dst, const uint8_t* src, uint32_t o0, uint32_t o1, uint32_t piece, uint32_t bar, int gap) {
  uint32_t t = clk32();
#pragma unroll 1
  for (uint32_t o = o0; o < o1; o += piece) {
    e_mc(dst + o, src + o, piece, bar, 7);
    spin_until(t += gap);
  }
}

__device__ __forceinline__ void paced_st(uint8_t* dst, uint32_t src, int gap) {
  uint32_t t = clk32();
#pragma unroll 1
  for (uint32_t o = 0; o < 8192; o += 4096) {
    e_s2g(dst + o, src + o, 4096);
    if (o + 4096 < 8192) spin_until(t += gap);
  }
}
__device__ __forceinline__ int block_of(int head, int c) { return c == 2 ? head : 32 + 2 * head + c; }

__device__ __forceinline__ void weight_role(const Params& p, const uint32_t sb, const int warp, const int cta, const int C, const uint32_t E,
                                            const uint8_t* const memg) {
  const int tid = fresh_tid(), lane = tid & 31;
  const int wg = warp >> 2, w = warp & 3;
  uint32_t W[32][4];
  cp_async_wait();
  bar_sync(1, 256);
  load_frags(W, sb, wg, w, lane);
  bar_sync(1, 256);
  if (tid < 128) sts128(sb + M_V + 5 * 2048 + tid * 16, make_uint4(0, 0, 0, 0));
  fence_async_smem();
  cluster_sync();
  if (tid == 0 && cta == 0) GSTAMP(0, 1);
  if (tid == 0) TSTAMP(13, cta, 0);

  const uint32_t rba = mapa(sb, C == 2 ? 0 : 2), rbc = mapa(sb, C == 1 ? 0 : 1);
  const uint32_t MYBAR = M_BAR + 8 * (C < 2 ? B_QK : B_V);
  uint32_t qoff = M_Q + C * 12288 + warp * 256 + lane * 4;
  uint32_t toff = sb + warp * 256 + (lane >> 4) * 2048 + (lane & 15) * 16;
  uint32_t rbar = mapa(sb + M_BAR, min(lane, 2));
  uint32_t sv = sb + M_MEM + lane * 32 + ((lane >> 2) & 3) * 8;
  PIN(qoff); PIN(toff); PIN(rbar); PIN(sv);
  const uint32_t gen0 = (E - 1) * (uint32_t)(NSTEP - 1);
  uint32_t fix = 0;
  const bool sig = w == 0 && lane < 3;
  const int blk = block_of(cta / 3, C);
  const int pk = (blk < 24 ? PAUSE_ : PAUS2_) + (wg ? -PST2_ : PST2_);
  int cand = -1;
  float d[16];
#pragma unroll
  for (int i = 0; i < 16; i++) d[i] = 0.f;
  uint32_t tp[8];
#pragma unroll 1
  for (int T = -1; T < NSTEP; T++) {
    const uint32_t ph = T & 1;
    const uint64_t Z = p.zero << ph;
    const uint32_t zz = p.zero2;
    if (T >= 0) {
      WSTAMP(0);
      if (T == 1 && tid == 0) TSTAMP(16, cta, 0);
      const uint64_t db = mkdesc(M_MEM, 128, 256, 0) + Z;
      stmatrix4(toff + M_TST + 8192, tp[0], tp[1], tp[2], tp[3]); stmatrix4(toff + M_TST + 12288, tp[4], tp[5], tp[6], tp[7]);
      if (sig) mbar_arrive_remote(rbar + 8 * B_HBE);
      mbar_wait(BAR(B_LAND), ph);
      WSTAMP(1);
      if (T == 1 && tid == 0) TSTAMP(16, cta, 1);
      const uint32_t gt = gentag(gen0 + T);
      auto old = [&](uint32_t a) { return lds32(a) ^ gt; };
      uint32_t bad = 0;
      bool redo = false, ready = false;
      wg_fence();
      wgmma_rs24<0, 1, 1>(d, W[0], db);
#pragma unroll
      for (int ks = 1; ks < 32; ks++) {
        if (ks == 2) bad |= old(sv + min(warp, 5) * 1024);
        if (ks == 10 || ks == 22) bad |= xo2(lds32(sv + (ks == 10 ? 6 : 15) * 1024 + warp * 1024), lds32(sv + (ks == 10 ? 14 : 23) * 1024), gt);
        if (ks == 6) {
          const uint32_t z5 = DRAIN(toff + M_TST);
          __syncwarp();
          if (lane == 0) mbar_arrive(BAR(B_STG) + z5);
        }
        if (ks == 27) ready = mbar_test(BAR(C < 2 ? B_KFREE : B_VFREE), ph ^ 1) & mbar_test(BAR(B_HA), ph);
        if (ks == 30) redo = bar_or(N_W, 256, T > 0 && (bad & 0x10001u));
        if (ks == 8 || ks == 20) { mbar_wait(BAR(B_LAND + (ks + 4) / 12), ph); WSTAMP(6 + (ks + 4) / 12); wg_fence(); }
        wgmma_rs24<1, 1>(d, W[ks], db + ks * 48);
      }
      wg_commit();
      uint32_t a0 = rba + qoff, a1 = a0 + 128, a2 = rbc + qoff, a3 = a2 + 128, ba = rba + MYBAR, bc = rbc + MYBAR;
      PIN(a0); PIN(a1); PIN(a2); PIN(a3); PIN(ba); PIN(bc);
      if (!ready) {
        mbar_wait(BAR(C < 2 ? B_KFREE : B_VFREE), ph ^ 1);
        if (T < NSTEP - 1) mbar_wait(BAR(B_HA), ph);
      }
      wg_wait<0>(); reg_fence(d);
      if (__builtin_expect(redo, 0)) {
        auto stale = [&]() { return __any_sync(~0u, (old(sv + warp * 3072) | old(sv + warp * 3072 + 1024) | old(sv + warp * 3072 + 2048)) & 0x10001u); };
        auto fetch = [&](int r) {
          e_expect(BAR(B_FIX + warp), 3072);
          e_g2s(sb + M_MEM + warp * 3072, memg + warp * 8192 + ((uni(lds32(sb + M_NEAR + warp * 4)) ^ r) & 1) * 4096, 3072, BAR(B_FIX + warp));
        };
        bool late = stale();
        if (late) fetch(0);
        constexpr uint64_t dc = mkdesc(M_MEM, 128, 256, 0);
#pragma unroll
        for (int ks = 0; ks < 32; ks++) {
          if (ks % 12 == 0) {
            if (ks) { wg_commit(); wg_wait<0>(); reg_fence(d); }
            if (warp / 3 == ks / 12) {
              for (int guard = 0; late; guard++) {
                mbar_wait(BAR(B_FIX + warp), fix); fix ^= 1;
                late = stale();
                if (late) fetch(guard + 1);
                if (guard > (1 << 20)) TRAP();
              }
            }
            bar_sync(N_W, 256);
            wg_fence();
          }
          if (ks == 0) wgmma_rs24<0, 1, 1>(d, W[0], dc); else wgmma_rs24<1, 1>(d, W[ks], dc + ks * 48);
        }
        wg_commit();
        wg_wait<0>(); reg_fence(d);
      }
      WSTAMP(2);
      if (T == 0 && tid == 0) TSTAMP(13, cta, 2);
      if (T == 1 && tid == 0) TSTAMP(16, cta, 2);
      uint32_t lo[3], hi[3];
#pragma unroll
      for (int j = 0; j < 3; j++) { lo[j] = pack2(d[4 * j], d[4 * j + 1]); hi[j] = pack2(d[4 * j + 2], d[4 * j + 3]); }
      if (__builtin_expect(T == 0, 0)) { sts32(sb + M_M0 + tid * 8, lo[0]); sts32(sb + M_M0 + tid * 8 + 4, hi[0]); }
      if (__builtin_expect(cand >= 0, 0)) {
        if (T == LAG) { lo[1] = lds32(sb + M_M0 + tid * 8); hi[1] = lds32(sb + M_M0 + tid * 8 + 4); }
        if (C < 2) { st_async32(a0 + 5 * 2048, lo[2], ba); st_async32(a1 + 5 * 2048, hi[2], ba); }
        else { sts32(sb + qoff + 5 * 2048, lo[2]); sts32(sb + qoff + 5 * 2048 + 128, hi[2]); }
        lo[2] = lo[1]; hi[2] = hi[1];
      }
      uint32_t z5;
      if (C == 0) {
        sts32(sb + qoff, lo[0]); sts32(sb + qoff + 128, hi[0]); z5 = DRAIN(sb + qoff);
        st_async32(a0, lo[2], ba); st_async32(a1, hi[2], ba); st_async32(a2, lo[1], bc); st_async32(a3, hi[1], bc);
      } else if (C == 1) {
        sts32(sb + qoff, lo[1]); sts32(sb + qoff + 128, hi[1]); z5 = DRAIN(sb + qoff);
        st_async32(a0, lo[2], ba); st_async32(a1, hi[2], ba); st_async32(a2, lo[0], bc); st_async32(a3, hi[0], bc);
      } else {
        sts32(sb + qoff, lo[2]); sts32(sb + qoff + 128, hi[2]); z5 = DRAIN(sb + qoff);
        st_async32(a0, lo[0], ba); st_async32(a1, hi[0], ba); st_async32(a2, lo[1], bc); st_async32(a3, hi[1], bc);
      }
      __syncwarp();
      if (lane == 0) { mbar_arrive(sb + MYBAR + z5); if (w == 3) mbar_arrive(BAR(B_SS)); }
      if (T == NSTEP - 1) break;
    }
    {
      const uint64_t dh = mkdesc(M_H, 16, 1024, 1) + Z;
      if (T + 2 < NSEG) {
        if (T < 0) mbar_wait(BAR(B_HA), ph);
        WSTAMP(3);
        wg_fence();
        wgmma_rs32<0, 0, 1>(d, W[0], dh);
#pragma unroll
        for (int ks = 1; ks < EA; ks++) {
          if (ks == E1) { wg_commit(); if (T >= 0) bar_sync(N_GO2, 384); wg_fence(); }
          wgmma_rs32<1, 0>(d, W[ks], dh + (ks >> 2) * 256 + (ks & 3) * 2);
        }
        wg_commit();
        mbar_wait(BAR(B_HB), ph);
        wg_wait<0>();
        if (sig) mbar_arrive_remote(rbar + 8 * B_HAE);
        WSTAMP(4);
        if (T == 0 && tid == 0) TSTAMP(17, cta, 0);
        if (T >= 0) bar_sync(N_GO3, 384);
        if (wg == 1) bar_sync(N_W, 256);
        wg_fence();
#pragma unroll
        for (int ks = EA; ks < 32; ks++) wgmma_rs32<1, 0>(d, W[ks], dh + (ks >> 2) * 256 + (ks & 3) * 2);
        wg_commit();
        if (wg == 0) bar_arrive(N_W, 256);
        mbar_wait(BAR(B_TFREE), ph ^ 1);
        wg_wait<0>(); reg_fence(d);
      } else {
        bar_sync(N_GO2, 384);
        mbar_wait(BAR(B_HB), ph);
        if (sig) mbar_arrive_remote(rbar + 8 * B_HAE);
        bar_sync(N_GO3, 384);
        mbar_wait(BAR(B_TFREE), ph ^ 1);
      }
#pragma unroll
      for (int i = 0; i < 8; i++) { tp[i] = pack2(d[2 * i], d[2 * i + 1]); PIN(tp[i]); }
      const uint32_t t1 = toff + (C == 0 && !ph ? M_Q + 2048 : M_TST);
      auto staged = [&]() {
        const uint32_t z5 = DRAIN(t1);
        __syncwarp();
        if (lane == 0) mbar_arrive(BAR(B_STG1) + z5);
      };
      if (T < 0 || (T + 2 >= LAG && T + 2 < NSTEP)) {
        wg_fence();
        wgmma_rs32<0, 0, 1>(d, W[0], dh + 2048);
        stmatrix4(t1, tp[0], tp[1], tp[2], tp[3]); stmatrix4(t1 + 4096, tp[4], tp[5], tp[6], tp[7]);
#pragma unroll
        for (int ks = 1; ks < 32; ks++) {
          if (ks == 5) staged();
          if (ks == PAUSE_ - PST2_ || ks == PAUSE_ + PST2_ || ks == PAUS2_ - PST2_ || ks == PAUS2_ + PST2_) {
            wg_commit();
            if (T >= 0 && ks == pk) bar_sync(N_GO4, 384);
            wg_fence();
          }
          wgmma_rs32<1, 0>(d, W[ks], dh + 2048 + (ks >> 2) * 256 + (ks & 3) * 2);
        }
        wg_commit();
      } else {
        stmatrix4(t1, tp[0], tp[1], tp[2], tp[3]); stmatrix4(t1 + 4096, tp[4], tp[5], tp[6], tp[7]);
        staged();
        bar_sync(N_GO4, 384);
      }
      if (T >= 0) cand = __shfl_sync(~0u, (int)lds32(sb + M_CAND + ((T + 1) & 3) * 4), 0);
      wg_wait<0>(); reg_fence(d);
      if (T >= 0) WSTAMP(6);
      if (T < 0 && tid == 0) TSTAMP(13, cta, 1);
#pragma unroll
      for (int i = 0; i < 8; i++) tp[i] = pack2(d[2 * i], d[2 * i + 1]);
    }
  }
  cluster_sync();
  if (tid == 0 && cta == 0) GSTAMP(0, 5);
}

__device__ __forceinline__ void attn_role(const Params& p, const uint32_t sb, const int w, const int cta, const int head, const int C, const uint32_t E,
                                          uint8_t* const part, uint8_t* const memg) {
  const int tid = fresh_tid(), lane = tid & 31;
  const int g = lane >> 2, t = lane & 3, blk = block_of(head, C);
  uint32_t tag = ((E - 1) * (uint32_t)(NSTEP - 1)) & 1;
  uint4 m0[2][2];
  load_mem0(m0[0], w * 64, lane, p.mem0); load_mem0(m0[1], w * 64 + 256, lane, p.mem0);
  cluster_sync();
#pragma unroll
  for (int k = 0; k < 2; k++) {
#pragma unroll 1
    for (int i = 0; i < 6; i++) sts128(sb + M_MEM + (w + 4 * k) * 3072 + lane * 16 + i * 512, make_uint4(0, 0, 0, 0));
    __syncwarp();
#pragma unroll
    for (int i = 0; i < 2; i++) sts128(sb + M_MEM + ((w + 4 * k) * 4 + (lane >> 4) + 2 * i) * 768 + (lane & 15) * 16, m0[k][i]);
  }
  fence_async_smem();
  bar_sync(N_AG, 128);
  if (w == 3 && lane < 3) mbar_arrive(BAR(B_LAND + lane));
  if (lane == 0) {
    if (w == 0) TSTAMP(15, cta, 0);
    sts32(sb + M_PT + w * 4, probe(part + blk * 16384 + w * 4096, 3));
    if (w == 0) TSTAMP(15, cta, 1);
  }
  bar_sync(N_AG, 128);
  const uint32_t inear = lds32(sb + M_PT + (w >> 1) * 8 + 4) < lds32(sb + M_PT + (w >> 1) * 8);
  if (lane == 0 && !(w & 1)) st_rlx(&G.f_choice[blk][w >> 1], (E << 1) | inear);
  if (w == 0) TSTAMP(15, cta, 2);
  uint32_t nb;
  {
    const int i = min(lane >> 1, C < 2 ? 8 : 5);
    const int r = ((i / 3 * 3 + C) * 4 + w) * 3 + i % 3;
    int guard = 0; uint32_t cw;
    while (__any_sync(~0u, ((cw = ld_rlx(&G.f_choice[r][lane & 1])) >> 1) != (E & 0x7FFFFFFFu))) { if (++guard > (1 << 22)) TRAP(); }
    nb = __ballot_sync(~0u, cw & 1) >> (lane >> 4);
    if (w == 0) TSTAMP(15, cta, 3);
  }
  bar_sync(N_AG, 128);
  const uint32_t pt0 = sb + M_PT + (tid & 127) * 16;
  {
    const uint32_t po = (C * 4 + w) * 49152 + (lane >> 4) * 8192 + head * 128 + (lane & 15) * 8;
    const uint8_t* in = part + (blk * 16384 + (w >> 1) * 8192 + inear * 4096 + (w & 1) * 64 + (lane >> 3) * 128 + (lane & 7) * 8);
    const uint8_t* outp = memg + ((blk / 12) * 8192 + (blk % 12) * 256 + w * 64 + (lane >> 4) * 4096 + (lane & 4) * 8 + (lane & 8) * 2 + (lane & 3) * 4);
#pragma unroll
    for (int i = 0; i < 12; i++) {
      const int j = i / 4 * 3 + (i & 3);
      const uint8_t* a = (i & 3) < 3 ? part + (po + i / 4 * 589824 + (i & 3) * 16384 + ((nb >> (2 * j)) & 1) * 4096) : i == 11 ? in : outp;
      asm volatile("st.shared.u64 [%0], %1;" :: "r"(pt0 + (i >> 1) * 2048 + (i & 1) * 8), "l"(a) : "memory");
    }
  }
  const int xd = __shfl_sync(~0u, XDLY_ + (blk < 24 ? 0 : blk < 60 ? X1_ : X2_), 0);
  const uint32_t rba = mapa(sb, C == 2 ? 0 : 2), rbc = mapa(sb, C == 1 ? 0 : 1);
  uint32_t vis = vis_bits(8 + 8 * w + g, t);
  uint32_t ln = lane;
#pragma unroll
  for (int i = 0; i < SALT_; i++) ln += lds32(sb + M_ZERO);
  PIN(vis); PIN(ln);
  if (tid == 256 && C == 0) st_rlx(&G.f_loaded[head], E);
  uint32_t fa[8][4];
#pragma unroll
  for (int ks = 0; ks < 8; ks++) ldmatrix4_t(fa[ks], sb + M_WO + 32768 + w * 256 + (lane >> 4) * 1024 + (lane & 15) * 16 + ks * 2048);
  if (w == 0) TSTAMP(14, cta, 0);
#pragma unroll 1
  for (int T = 0; T < NSTEP; T++) {
    const uint32_t ph = T & 1;
    const uint32_t zz = uni(lds32(sb + M_ZERO));
    const bool more = T < NSTEP - 1;
    const float sc = 0.08838834764831845f * 1.4426950408889634f;
    tag ^= 1;
    float s[20];
    const uint8_t* in; int cnext = -1; uint32_t tx; bool synced;
    float x[10], tm, ts;
    uint32_t pt[5];
    auto tok_max = [&]() {
      PIN(vis);
      x[0] = s[2]; x[1] = s[3];
#pragma unroll
      for (int i = 0; i < 8; i++) x[2 + i] = (vis >> i & 1) ? s[4 * (i / 2 + 1) + 2 + (i & 1)] : -INFINITY;
      tm = fmaxf(fmaxf(fmaxf(fmaxf(x[0], x[1]), fmaxf(x[2], x[3])), fmaxf(fmaxf(x[4], x[5]), fmaxf(x[6], x[7]))), fmaxf(x[8], x[9]));
      HOLD(7, __float_as_uint(tm));
    };
    auto tok_exp1 = [&]() {
      tm = fmaxf(tm, __shfl_xor_sync(~0u, tm, 1));
      tm = fmaxf(tm, __shfl_xor_sync(~0u, tm, 2));
      const float b = -tm * sc;
#pragma unroll
      for (int i = 0; i < 10; i++) x[i] = fmaf(x[i], sc, b);
      HOLD(10, __float_as_uint(x[9]));
    };
    auto tok_exp2 = [&]() {
#pragma unroll
      for (int i = 0; i < 10; i++) x[i] = ex2(x[i]);
      ts = (((x[0] + x[1]) + (x[2] + x[3])) + ((x[4] + x[5]) + (x[6] + x[7]))) + (x[8] + x[9]);
#pragma unroll
      for (int k = 0; k < 5; k++) pt[k] = pack2(x[2 * k], x[2 * k + 1]);
      HOLD(8, __float_as_uint(ts));
    };
    {
      uint32_t q[8][4];
      auto load_q = [&](uint32_t a, int h) {
#pragma unroll
        for (int k2 = 0; k2 < 4; k2++) {
          uint32_t r[4];
          ldmatrix4_t(r, a + k2 * 512);
          q[2 * k2][h] = r[0]; q[2 * k2][h + 2] = r[1]; q[2 * k2 + 1][h] = r[2]; q[2 * k2 + 1][h + 2] = r[3];
        }
      };
      PIN(ln);
      const uint32_t qa = sb + M_Q + ln * 16, qt = qa + w * 2048 + (C == 0 && ph ? M_TST - M_Q : 2048);
      const int cand = C == 2 ? (int)uni(lds32(sb + M_CAND + (T & 3) * 4)) : -1;
      mbar_wait(BAR(B_TOK), ph);
      load_q(qt, 1);
      mbar_wait(BAR(B_QK), ph);
      ASTAMP(0);
      if (T == 0 && w == 0) TSTAMP(13, cta, 3);
      if (__builtin_expect(cand >= 0, 0)) {
        mbar_wait(BAR(B_V), ph);
        PIN(ln);
        const int e = w * 32 + ln;
#pragma unroll
        for (int i = 0; i < 3; i++) {
          const uint32_t v = lds32(sb + M_Q + i * 12288 + 5 * 2048 + e * 16 + 4);
          asm volatile("st.shared.u16 [%0], %1;" :: "r"(sb + M_Q + i * 12288 + (1 + (cand >> 3)) * 2048 + e * 16 + (cand & 7) * 2), "h"((unsigned short)v) : "memory");
        }
        fence_async_smem();
        bar_sync(N_AG, 128);
        load_q(qt, 1);
      }
      constexpr uint64_t dk = mkdesc(M_K, 128, 2048, 0);
      fence_async_smem();
      uint32_t r[4][4];
#pragma unroll
      for (int k2 = 0; k2 < 4; k2++) ldmatrix4_t(r[k2], qa + k2 * 512);
#pragma unroll
      for (int k2 = 0; k2 < 4; k2++) {
        q[2 * k2][0] = r[k2][0]; q[2 * k2][2] = r[k2][1]; q[2 * k2 + 1][0] = r[k2][2]; q[2 * k2 + 1][2] = r[k2][3];
        if (k2 & 1) {
          wg_fence();
#pragma unroll
          for (int ks = 2 * k2 - 2; ks < 2 * k2 + 2; ks++) { if (ks == 0) wgmma_rs40<0, 1>(s, q[0], dk); else wgmma_rs40<1, 1>(s, q[ks], dk + ks * 16); }
        }
      }
      wg_commit();
    }
    if (more) {
      uint32_t v[5][4];
      PIN(ln);
      const uint32_t va = sb + M_V + w * 512 + ((ln >> 3) & 1) * 128 + (ln >> 4) * 2048 + (ln & 7) * 16;
      const uint32_t ooff = M_OM + w * 1536 + C * 256 + ln * 4;
      mbar_wait(BAR(B_V), ph);
      wg_wait<0>(); reg_fence(s);
      if (ln < 3) mbar_arrive_remote(mapa(BAR(B_KFREE), ln));
      ldmatrix4(v[0], va); ldmatrix4(v[1], va + 256); ldmatrix4(v[2], va + 4096); ldmatrix4(v[3], va + 4096 + 256);
      ldmatrix4(v[4], sb + M_V + 8192 + w * 512 + ln * 16);
      ASTAMP(1);
      float m = fmaxf(fmaxf(fmaxf(fmaxf(s[0], s[1]), fmaxf(s[4], s[5])), fmaxf(fmaxf(s[8], s[9]), fmaxf(s[12], s[13]))), fmaxf(s[16], s[17]));
      m = fmaxf(m, __shfl_xor_sync(~0u, m, 1));
      m = fmaxf(m, __shfl_xor_sync(~0u, m, 2));
      const float b = -m * sc;
      uint32_t pm[5];
#pragma unroll
      for (int j = 0; j < 5; j++) pm[j] = pack2(ex2(fmaf(s[4 * j], sc, b)), ex2(fmaf(s[4 * j + 1], sc, b)));
      float o0[4] = {0.f, 0.f, 0.f, 0.f}, o1[4] = {0.f, 0.f, 0.f, 0.f}, l[4] = {0.f, 0.f, 0.f, 0.f};
      const uint32_t one[4] = {0x3f803f80u, 0x3f803f80u, 0x3f803f80u, 0x3f803f80u};
      hmma16(l, one, pm[0], pm[1]); hmma16(o0, v[0], pm[0], pm[1]); hmma16(o1, v[1], pm[0], pm[1]);
      hmma16(l, one, pm[2], pm[3]); hmma16(o0, v[2], pm[2], pm[3]); hmma16(o1, v[3], pm[2], pm[3]);
      hmma8(l, one[0], one[1], pm[4]); hmma8(o0, v[4][0], v[4][1], pm[4]); hmma8(o1, v[4][2], v[4][3], pm[4]);
      const float r0 = rcp(l[0]), r1 = rcp(l[1]);
      const uint32_t u0 = pack2(o0[0] * r0, o0[1] * r1), u1 = pack2(o0[2] * r0, o0[3] * r1), u2 = pack2(o1[0] * r0, o1[1] * r1), u3 = pack2(o1[2] * r0, o1[3] * r1);
      constexpr uint32_t OB = M_BAR + 8 * B_OM;
      const uint32_t a0 = rba + ooff, a1 = rbc + ooff;
      st_async32(a0, u0, rba + OB); st_async32(a1, u0, rbc + OB);
      st_async32(a0 + 128, u1, rba + OB); st_async32(a1 + 128, u1, rbc + OB);
      st_async32(a0 + 768, u2, rba + OB); st_async32(a1 + 768, u2, rbc + OB);
      st_async32(a0 + 896, u3, rba + OB); st_async32(a1 + 896, u3, rbc + OB);
      bar_arrive(N_GO2, 384);
      sts32(sb + ooff, u0); sts32(sb + ooff + 128, u1); sts32(sb + ooff + 768, u2); sts32(sb + ooff + 896, u3);
      ASTAMP(2);
      uint32_t fb[8][4];
      const uint32_t wa = sb + M_WO + 16384 + w * 256 + (ln >> 4) * 1024 + (ln & 15) * 16 + zz;
      ldmatrix4_t(fb[0], wa);
      SCHED(3);
#pragma unroll
      for (int ks = 1; ks < 8; ks++) {
        ldmatrix4_t(fb[ks], wa + ks * 2048);
        if (ks == 7) { __syncwarp(); if (ln == 0) mbar_arrive(BAR(B_OM) + (fb[0][0] & zz)); }
      }
      if (blk % 3 == 2) cnext = (int)uni(lds32(sb + M_CAND + ((T + 1) & 3) * 4));
      {
        float d[12], e[12];
        constexpr uint64_t ob = mkdesc(M_OM, 128, 256, 0);
        uint8_t* q[3][3];
        auto addr = [&](int i) {
          asm volatile("ld.shared.v2.u64 {%0,%1}, [%2];" : "=l"(q[i][0]), "=l"(q[i][1]) : "r"(pt0 + i * 4096) : "memory");
          if (i < 2) asm volatile("ld.shared.u64 %0, [%1];" : "=l"(q[i][2]) : "r"(pt0 + i * 4096 + 2048) : "memory");
          else asm volatile("ld.shared.v2.u64 {%0,%1}, [%2];" : "=l"(q[i][2]), "=l"(in) : "r"(pt0 + i * 4096 + 2048) : "memory");
        };
        auto put = [&](const float* d, int i) {
          st_rlx64(q[i][0], (pack2(d[0], d[1]) & ~1u) | tag, pack2(d[2], d[3]));
          st_rlx64(q[i][1], (pack2(d[4], d[5]) & ~1u) | tag, pack2(d[6], d[7]));
          st_rlx64(q[i][2], (pack2(d[8], d[9]) & ~1u) | tag, pack2(d[10], d[11]));
        };
        addr(0); addr(1);
        SCHED(6);
        tok_max();
        ASTAMP(3);
        mbar_wait(BAR(B_OM), ph);
        ASTAMP(4);
        constexpr uint64_t w0 = mkdesc(M_WO, 1024, 128, 0);
        float (&f)[12] = d;
        wg_fence();
        wgmma_ss24<0, 1, 1>(d, w0, ob);
#pragma unroll
        for (int ks = 1; ks < 8; ks++) wgmma_ss24<1, 1, 1>(d, w0 + ks * 128, ob + ks * 48);
        wg_commit();
        wgmma_rs24<0, 1>(e, fb[0], ob);
#pragma unroll
        for (int ks = 1; ks < HAND_; ks++) wgmma_rs24<1, 1>(e, fb[ks], ob + ks * 48);
        wg_commit();
        wg_wait<1>(); reg_fence(d);
        put(d, 0);
        addr(2);
        SCHED(4);
        ASTAMP(5);
        wg_fence();
#pragma unroll
        for (int ks = HAND_; ks < 8; ks++) wgmma_rs24<1, 1>(e, fb[ks], ob + ks * 48);
        wg_commit();
        wgmma_rs24<0, 1, 1>(f, fa[0], ob);
#pragma unroll
        for (int ks = 1; ks < HAND_; ks++) wgmma_rs24<1, 1>(f, fa[ks], ob + ks * 48);
        wg_commit();
        wg_wait<1>(); reg_fence(e);
        put(e, 1);
        SCHED(5);
        if (C < 2) {
          wg_fence();
#pragma unroll
          for (int ks = HAND_; ks < 8; ks++) wgmma_rs24<1, 1>(f, fa[ks], ob + ks * 48);
          wg_commit();
        }
        synced = __all_sync(~0u, mbar_test(BAR(B_SYNC), ph));
        tx = uni(lds32(sb + M_BASE + ph * 4)) + xd;
        wg_wait<0>(); reg_fence(f);
        if (C < 2) put(f, 2);
        bar_arrive(N_GO3, 384);
        ASTAMP(6);
        if (T == 0 && w == 0) TSTAMP(14, cta, 1);
      }
    } else {
      mbar_wait(BAR(B_V), ph);
      wg_wait<0>(); reg_fence(s);
      tok_max();
    }
    uint2 v[8];
    auto poll = [&](uint2* v) {
      v[0] = ld_rlx64<0>(in); v[1] = ld_rlx64<512>(in); v[2] = ld_rlx64<1024>(in); v[3] = ld_rlx64<1536>(in);
      v[4] = ld_rlx64<2048>(in); v[5] = ld_rlx64<2560>(in); v[6] = ld_rlx64<3072>(in); v[7] = ld_rlx64<3584>(in);
    };
    uint8_t* outp;
    asm volatile("ld.shared.u64 %0, [%1];" : "=l"(outp) : "r"(pt0 + 2048 + 8) : "memory");
    const uint32_t itag = gentag((E - 1) * (uint32_t)(NSTEP - 1) + T + 1);
    const bool sum = more && cnext < 0;
    if (more) {
      if (!synced) { mbar_wait(BAR(B_SYNC), ph); tx = uni(lds32(sb + M_BASE + ph * 4)) + xd; }
      ASTAMP(7);
      if (__builtin_expect(cnext >= 0, 0)) {
        const unsigned long long* hp = (const unsigned long long*)&G.hc[T + 1 - LAG][0] + ((blk / 3) * 8 + 2 * w + ((ln >> 2) & 1));
        unsigned long long v0; int guard = 0;
        while (v0 = ld_rlxu64(hp), !__all_sync(~0u, (uint32_t)(v0 >> 32) == E)) { if (++guard > (1 << 22)) TRAP(); }
        st_rlx((uint32_t*)outp, (ln & 3) == 1 ? ((uint32_t)v0 >> ((ln & 8) * 2)) & 0xffffu : (ln & 1) ? 0u : itag);
      } else {
        spin_until(tx);
        ASTAMP(8);
      }
    }
    if (!more) in = part;
    poll(v);
    auto late = [&](const uint2* v) {
      return __any_sync(~0u, (or3(xo2(v[0].x, v[1].x, tag), xo2(v[2].x, v[3].x, tag), xo2(v[4].x, v[5].x, tag)) | xo2(v[6].x, v[7].x, tag)) & 1u);
    };
    tok_exp1(); tok_exp2();
    auto reduce = [&]() {
      if (sum) {
        ASTAMP(9);
        int guard = 0;
        while (late(v)) {
          if (++guard > (1 << 22)) TRAP();
          poll(v);
        }
#pragma unroll
        for (int i = 0; i < 4; i++) { v[i].x = add2(v[i].x, v[i + 4].x); v[i].y = add2(v[i].y, v[i + 4].y); }
        const bool hi = ln & 8;
        const uint32_t x0 = add2(v[0].x, v[1].x), x1 = add2(v[2].x, v[3].x), y0 = add2(v[0].y, v[1].y), y1 = add2(v[2].y, v[3].y);
        const uint32_t m0 = hi ? y0 : x0, m1 = hi ? y1 : x1;
        const uint32_t n0 = __shfl_xor_sync(~0u, hi ? x0 : y0, 8), n1 = __shfl_xor_sync(~0u, hi ? x1 : y1, 8);
        float k0 = (blo(m0) + blo(m1)) + (blo(n0) + blo(n1)), k1 = (bhi(m0) + bhi(m1)) + (bhi(n0) + bhi(n1));
        k0 += __shfl_xor_sync(~0u, k0, 16); k1 += __shfl_xor_sync(~0u, k1, 16);
        st_rlx((uint32_t*)outp, (ln & 1) ? pack2(k0, k1) : pack2_tag(k0, k1, itag));
        ASTAMP(10);
        if (T == 0 && w == 0) TSTAMP(14, cta, 2);
        CSTAMP(12 + w, (clk() & ~15u) | min(guard + 1, 15));
      }
      if (more) bar_arrive(N_GO4, 384);
    };
    reduce();
    {
      PIN(ln);
      const uint32_t oa = sb + M_OST + w * 128 + (ln >> 3) * 512 + (ln & 7) * 16;
      const uint32_t a[3][4] = {{0, pt[0], 0, pt[1]}, {0, pt[2], 0, pt[3]}, {0, pt[4], 0, 0}};
      constexpr uint64_t dv = mkdesc(M_V, 2048, 128, 0);
#pragma unroll 1
      for (int h = 0; h < 2; h++) {
        float o[32];
        const uint64_t dh = dv + (uint64_t)(h * 64);
        wg_fence();
        wgmma_rs64<0, 0>(o, a[0], dh); wgmma_rs64<1, 0>(o, a[1], dh + 256); wgmma_rs64<1, 0>(o, a[2], dh + 512);
        wg_commit();
        if (h == 0) {
          ts += __shfl_xor_sync(~0u, ts, 1);
          ts += __shfl_xor_sync(~0u, ts, 2);
          ts = rcp(ts);
          mbar_wait(BAR(B_OFREE), ph ^ 1);
        }
        wg_wait<0>(); reg_fence(o);
        if (h == 1 && ln < 3) mbar_arrive_remote(mapa(BAR(B_VFREE), ln));
#define OT(i) pack2(o[4 * (i) + 2] * ts, o[4 * (i) + 3] * ts)
        stmatrix4(oa + h * 4096, OT(0), OT(1), OT(2), OT(3));
        stmatrix4(oa + h * 4096 + 2048, OT(4), OT(5), OT(6), OT(7));
      }
      const uint32_t z5 = DRAIN(oa);
      __syncwarp();
      if (ln == 0) mbar_arrive(BAR(B_OST) + z5);
      ASTAMP(11);
    }
  }
}

__global__ void __cluster_dims__(3, 1, 1) __launch_bounds__(512, 1) main_kernel(Params p) {
  extern __shared__ __align__(1024) uint8_t sm[];
  const uint32_t sb = smem_u32(sm);
  if ((sb & 0xFFFFFFu) != SBASE) TRAP();
  asm volatile("griddepcontrol.launch_dependents;");
  const int warp = __shfl_sync(~0u, threadIdx.x >> 5, 0);
  const int cta = blockIdx.x, head = cta / 3, c = cta % 3;
  const uint32_t E = __shfl_sync(~0u, *(volatile uint32_t*)&g_epoch + 1, 0);
  uint8_t* const part = G.xch;
  uint8_t* const memg = part + 96 * 16384;

  if (threadIdx.x == 0 && cta == 0) GSTAMP(0, 0);
  if (threadIdx.x < B_NUM) {
    const int i = threadIdx.x;
    const uint32_t cnt = i == B_STG || i == B_STG1 ? 8 : i == B_OST ? 4 : i == B_HAE || i == B_HBE ? 6 : i == B_KFREE || i == B_VFREE ? 12 : i == B_SS ? 2 : i == B_OM ? 5 :
                         i == B_QK ? (c < 2 ? 9 : 1) : i == B_V ? (c < 2 ? 1 : 9) : 1;
    mbar_init(BAR(i), cnt);
    if (i == B_HA || i == B_HB || i == B_STG || i == B_HAE || i == B_HBE || i == B_TFREE)
      asm volatile("mbarrier.arrive.shared::cta.b64 _, [%0], %1;" :: "r"(BAR(i)), "r"(cnt) : "memory");
    asm volatile("fence.mbarrier_init.release.cluster;" ::: "memory");
  }
  if (warp < 8) {
    const int tid = threadIdx.x;
    uint4 wa[6], wb[6];
#pragma unroll
    for (int i = 0; i < 6; i++) {
      const int mi = i >> 1, e = (tid >> 2) + (i & 1) * 64;
      const uint4* src = (const uint4*)(p.wo + (size_t)(head * 128 + e) * 512 + min(3 * mi + c, 7) * 64 + (tid & 3) * 16);
      wa[i] = __ldg(src); wb[i] = __ldg(src + 1);
    }
    stage_weights(sb, (c == 0 ? p.wq : c == 1 ? p.wk : p.wv) + head * 128, 4096, tid, 256);
#pragma unroll
    for (int i = 0; i < 6; i++) {
      const int mi = i >> 1, e = (tid >> 2) + (i & 1) * 64;
      const uint4 a = wa[i], b = wb[i];
      const uint32_t dst = sb + M_WO + mi * 16384 + (e >> 3) * 1024 + (tid & 3) * 256 + (e & 7) * 16;
      sts128(dst, make_uint4(__byte_perm(a.x, a.y, 0x5410), __byte_perm(a.z, a.w, 0x5410), __byte_perm(b.x, b.y, 0x5410), __byte_perm(b.z, b.w, 0x5410)));
      sts128(dst + 128, make_uint4(__byte_perm(a.x, a.y, 0x7632), __byte_perm(a.z, a.w, 0x7632), __byte_perm(b.x, b.y, 0x7632), __byte_perm(b.z, b.w, 0x7632)));
    }
  } else {
    const int i0 = threadIdx.x - 256;
    const uint32_t tag0 = ((E - 1) * (uint32_t)(NSTEP - 1)) & 1;
    for (int i = i0; i < 1024; i += 256) *(uint4*)(part + block_of(head, c) * 16384 + i * 16) = make_uint4(tag0, 0, tag0, 0);
    if (i0 < 16) *(uint32_t*)(memg + i0 * 4096 + 3968) = 0;
    if (i0 < 2) st_rlx(&G.f_choice[block_of(head, c)][i0], 0);
    if (i0 < 8) st_rlx64(&G.sync[i0 >> 2][cta][i0 & 3], 0, 0);
    __threadfence();
    if (i0 < 12) sts32(sb + M_ZERO + i0 * 4, 0);
    if (i0 < 2) { sts32(sb + M_BASE + i0 * 4, clk32() - 65536); sts32(sb + M_BAS2 + i0 * 4, clk32() - 65536); sts32(sb + M_CAND + i0 * 4, (uint32_t)-1); }
  }

  if (warp < 8) {
    asm volatile("setmaxnreg.inc.sync.aligned.u32 176;");
    weight_role(p, sb, warp, cta, c, E, memg);
  } else if (warp < 12) {
    asm volatile("setmaxnreg.inc.sync.aligned.u32 136;");
    attn_role(p, sb, warp - 8, cta, head, c, E, part, memg);
    cluster_sync();
  } else {
    asm volatile("setmaxnreg.dec.sync.aligned.u32 24;");
    const int tid = fresh_tid(), lane = tid & 31;
    const int w = warp - 12;
    cluster_sync();
    if (w != 2) {
      const int tl = w == 0 ? c : w == 1 ? 2 + c : 5 + c;
      int near = 0;
      if (lane == 0) { const int t0 = probe(memg + tl * 8192, 3); near = probe(memg + tl * 8192 + 4096, 3) < t0; }
      near = uni(near);
      if (lane < 3) asm volatile("st.shared::cluster.u32 [%0], %1;" :: "r"(mapa(sb + M_NEAR + tl * 4, lane)), "r"(near) : "memory");
      __syncwarp();
    }
    if (w == 0) {
      int yadj = 0, dmin = 1 << 20; uint32_t prev = 0; bool cprev = false;
      uint32_t s1 = (2 + c) * 8192, s2 = (5 + c) * 8192;
#pragma unroll 1
      for (int T = 0; T < NSTEP - 1; T++) {
        const uint32_t ph = T & 1;
        mbar_wait(BAR(B_SS), ph);
        const uint32_t cq = clk();
        const uint32_t g0 = (uint32_t)gtime64(); uint32_t g1, ce;
        do { g1 = (uint32_t)gtime64(); ce = clk(); } while (g1 == g0);
        const uint32_t tn = g1 * 8 - (((ce - cq) * 37u) >> 3), id = E * 128u + T;
        if (lane < 4) st_rlx64(&G.sync[ph][cta][lane], tn, id);
        if (lane < 3) mbar_expect(BAR(B_LAND + lane), lane ? 9216 : 6144);
        if (T == 0) { s1 += uni(lds32(sb + M_NEAR + (2 + c) * 4)) * 4096; s2 += uni(lds32(sb + M_NEAR + (5 + c) * 4)) * 4096; }
        wait_until(cq + SDLY_);
        int guard = 0; unsigned long long v0, v1, v2;
        for (;;) {
          v0 = ld_rlxu64(G.sync[ph][lane]); v1 = ld_rlxu64(G.sync[ph][lane + 32]); v2 = ld_rlxu64(G.sync[ph][lane + 64]);
          if (__all_sync(~0u, (uint32_t)(v0 >> 32) == id && (uint32_t)(v1 >> 32) == id && (uint32_t)(v2 >> 32) == id)) break;
          if (++guard > (1 << 22)) TRAP();
        }
        const bool cnd = (int)uni(lds32(sb + M_CAND + (T & 3) * 4)) >= 0;
        const int dl = __reduce_max_sync(~0u, max(max((int)((uint32_t)v0 - tn), (int)((uint32_t)v1 - tn)), (int)((uint32_t)v2 - tn)));
        const uint32_t base = uni(cq + ((min(dl, 8 * 4096) * 7) >> 5)) + (T == 0 ? SLOW0_ : T == 1 ? SLOW1_ : 0) +
                              (cnd ? CDLY_ : 0) - (T + 2 < NSEG ? 0 : BOFF_);
        const int dur = (int)(base - prev);
        if (!cnd && !cprev) {
          yadj = T > 2 && dur > dmin + 700 ? min(yadj + YUP_, 400) : max(yadj - YDN_, 0);
          if (T > 1) dmin = min(dmin + 20, dur);
        }
        prev = base; cprev = cnd;
        if (lane == 0) { sts32(sb + M_BASE + ph * 4, base + ((yadj * XFR_) >> 2)); sts32(sb + M_BAS2 + ph * 4, base + yadj); mbar_arrive(BAR(B_SYNC)); }
        CSTAMP(0, base); CSTAMP(1, clk());
        if (T == 0) TSTAMP(16, cta, 3);
        const uint32_t ts = base + YDLY_ + yadj - (T + 2 >= LAG && T + 2 < NSEG ? 0 : YOFF_);
        const uint8_t* const t0 = memg + uni(lds32(sb + M_NEAR)) * 4096, * const t1 = memg + 8192 + uni(lds32(sb + M_NEAR + 4)) * 4096;
        if (T == 0) {
          const uint32_t gt = gentag((E - 1) * (uint32_t)(NSTEP - 1) + 1);
#pragma unroll 1
          for (int k = 0; k < 4; k++) {
            const uint32_t* a = (const uint32_t*)((k == 0 ? t0 : k == 1 ? t1 : memg + (k == 2 ? s1 : s2)) + lane * 32);
            int g2 = 0;
            while (__any_sync(~0u, (xo2(ld_rlx(a), ld_rlx(a + 256), gt) | (ld_rlx(a + 512) ^ gt)) & 0x10001u)) { if (++g2 > (1 << 22)) TRAP(); }
          }
        } else wait_until(ts);
        e_g2s(sb + M_MEM, t0, 3072, BAR(B_LAND)); e_g2s(sb + M_MEM + 3072, t1, 3072, BAR(B_LAND));
        CSTAMP(2, clk());
        if (T == 0) TSTAMP(17, cta, 1);
        spin_until(ts + Y1_);
        e_mc(sb + M_MEM + (2 + c) * 3072, memg + s1, 3072, BAR(B_LAND + 1), 7);
        CSTAMP(3, clk());
        spin_until(ts + Y2_);
        e_mc(sb + M_MEM + (5 + c) * 3072, memg + s2, 3072, BAR(B_LAND + 2), 7);
        CSTAMP(4, clk());
      }
    } else if (w == 1) {
#pragma unroll 1
      for (int T = 0; T < NSTEP; T++) {
        const uint32_t ph = T & 1;
        const int s = c == 0 ? T : T - LAG;
        const bool act = s >= 0 && s < NSEG;
        mbar_wait(BAR(B_OST), ph);
        if (cta == 0) TSTAMP(2, T, 0);
        fence_async_smem();
        if (T < NSTEP - 1) wait_until(uni(lds32(sb + M_BAS2 + ph * 4)) + ODLY_);
        STAMP(22);
        if (act) paced_st(o_slot(c, s, head), sb + M_OST, OGAP_);
        if (c == 2 && T < NSTEP - 1) {
          mbar_wait(BAR(B_STG1), ph ^ 1);
          mbar_wait(BAR(B_VFREE), ph);
          STAMP(23);
          e_mc(sb + M_V + 2048, G.mix[cta % 6].tok[cta / 6][ph ^ 1] + 8192, 8192, BAR(B_V), 6);
          e_mc(sb + M_V + 2048, G.mix[cta % 6].tok[cta / 6][ph ^ 1], 8192, BAR(B_V), 1);
        }
        bulk_wait();
        __syncwarp();
        e_arrive(BAR(B_OFREE));
        if (cta == 0) TSTAMP(2, T, 1);
        if (act && lane < 8) st_rel(&G.f_o[T][head >> 2][c * 4 + (head & 3)][lane], E);
        __syncwarp();
        if (cta == 0) TSTAMP(2, T, 2);
      }
    } else if (w == 2) {
      unsigned long long run = 0;
      static_assert(LAG >= 2, "config");
      constexpr uint32_t NA = EA / 4 * 4096;
      e_expect(BAR(B_QK), c < 2 ? 2048 : 4096); e_expect(BAR(B_V), c == 0 ? 10240 : c == 1 ? 2048 : 0);
      e_expect(BAR(B_TOK), c == 0 ? 16384 : 0); e_expect(BAR(B_OM), 4096);
      e_expect(BAR(B_HA), NA); e_expect(BAR(B_HB), 65536 - NA);
      wait_eq(&G.f_h1[c == 1 ? 0 : 1], E); fence_async_glob();
      {
        const uint32_t o0 = c == 0 ? NA : 0, o1 = c == 2 ? NA : 32768;
        e_mc(sb + M_H + (c == 1 ? 32768 : 0) + o0, G.seg[c == 1 ? 0 : 1].h[0] + o0, o1 - o0, BAR(c == 2 ? B_HA : B_HB), 7);
      }
      TSTAMP(14, cta, 3);
      if (c == 2) wait_eq(&G.f_h1[2], E);
      mbar_wait(BAR(B_HAE), 1);
      e_expect(BAR(B_HA), NA);
      if (c == 2) { fence_async_glob(); e_mc(sb + M_H, G.seg[2].h[0], NA, BAR(B_HA), 7); }
      int cprev = -1;
#pragma unroll 1
      for (int T = 0; T < NSTEP - 1; T++) {
        const int s1 = T + 2, s2 = T + 2 - LAG;
        const uint32_t ph = T & 1;
        const bool l1 = s1 < NSEG, l2 = s2 >= 0 && s2 < NSEG, la = s1 + 1 < NSEG;
        const bool mine = c == 0 ? l1 : c == 1 ? l2 : la;
        const uint32_t* fl = c != 1 ? &G.f_h1[min(s1 + (c >> 1), NSEG - 1)] : (const uint32_t*)G.f_h2[max(s2, 0)][lane & 3] + 1;
        const uint32_t want = E & 0x1FFFFFu, sh = c != 1 ? 0 : 11;
        mbar_wait(BAR(B_HBE), ph ^ 1);
        const bool early = __all_sync(~0u, ((ld_acq(fl) >> sh) & 0x1FFFFFu) == want);
        mbar_wait(BAR(B_LAND + 2), ph);
        STAMP(16);
        e_expect(BAR(B_HB), (l1 ? 32768 - NA : 0) + (l2 ? 32768 : 0));
        if (mine) {
          if (!early) {
            int guard = 0;
            while (!__all_sync(~0u, ((ld_acq(fl) >> sh) & 0x1FFFFFu) == want)) { __nanosleep(32); if (++guard > (1 << 22)) TRAP(); }
          }
          fence_async_glob();
          if (c == 1) { mbar_wait(BAR(B_QK), ph); spin_until(clk32() + HDLY_); }
          if (c < 2) paced_h(sb + M_H + c * 32768, G.seg[c ? s2 : s1].h[c], c ? 0 : NA, 32768, 4096, BAR(B_HB), HGAP_);
        }
        int cd = -1;
        if (l2) { cd = route_step(s2, E, lane, run); if (cta == 0) TSTAMP(5, s2, 0); }
        if (lane == 0) sts32(sb + M_CAND + ((T + 2) & 3) * 4, (uint32_t)cd);
        __syncwarp();
        STAMP(17);
        mbar_wait(BAR(B_HAE), ph);
        e_expect(BAR(B_HA), la ? NA : 0);
        if (c == 2 && la) {
          spin_until(clk32() + ADLY_);
          STAMP(18);
          paced_h(sb + M_H, G.seg[s1 + 1].h[0], 0, NA, 4096, BAR(B_HA), AGAP_);
        }
        mbar_wait(BAR(B_OST), ph);
        e_expect(BAR(B_QK), c < 2 ? 2048 : cprev >= 0 ? 8192 : 4096);
        e_expect(BAR(B_V), c < 2 ? 10240 : 8192);
        e_expect(BAR(B_TOK), c == 0 ? 8192 : 16384);
        e_expect(BAR(B_OM), 4096);
        cprev = cd;
      }
    } else {
      const uint32_t mytok = sb + M_Q + c * 12288 + 2048, tb = BAR(c < 2 ? B_TOK : B_V);
      mbar_wait(BAR(B_STG1), 0);
      fence_async_smem();
      if (c) e_s2g(G.mix[cta % 6].tok[cta / 6][1], sb + M_TST, 8192);
#pragma unroll 1
      for (int T = 0; T < NSTEP - 1; T++) {
        const uint32_t ph = T & 1;
        uint8_t* const tok = G.mix[cta % 6].tok[cta / 6][ph ^ 1];
        mbar_wait(BAR(B_STG), ph ^ 1);
        fence_async_smem();
        if (cta == 0 && (T == 0 || T == NSEG || T == NSTEP - 2)) GSTAMP(0, T == 0 ? 2 : T == NSEG ? 3 : 4);
        if (T > 0) mbar_wait(BAR(B_QK), ph);
        STAMP(20);
        paced_st(tok + 8192, sb + M_TST + 8192, TGAP_);
        bulk_wait();
        __syncwarp();
        e_arrive(BAR(B_TFREE));
        if (T == 0) e_mc(mytok, tok + 8192, 8192, tb, 1);
        STAMP(21);
        if (c < 2) {
          mbar_wait(BAR(B_KFREE), ph);
          spin_until(clk32() + KDLY_);
          STAMP(23);
          if (c) e_mc(mytok, tok, 8192, tb, 1);
          e_mc(mytok, tok + 8192, 8192, tb, 6);
        }
        mbar_wait(BAR(B_STG1), ph ^ 1);
        fence_async_smem();
        wait_until(uni(lds32(sb + M_BAS2 + ph * 4)) + TDLY_);
        if (c) paced_st(G.mix[cta % 6].tok[cta / 6][ph], sb + M_TST, T1GAP_);
        STAMP(24);
      }
      bulk_wait();
    }
    __syncwarp();
    cluster_sync();
  }
}

constexpr uint32_t A_RING = 0;
constexpr int A_NST = 6;
constexpr uint32_t A_STG = A_RING + A_NST * 8192;
constexpr uint32_t A_WD = A_STG + 8192;
constexpr uint32_t A_WG = A_WD + 57344;
constexpr uint32_t A_WU = A_WG + 57344;
constexpr uint32_t A_XN = A_WU + 57344;
constexpr uint32_t A_BAR = A_XN + 2048;
constexpr uint32_t A_TOTAL = A_BAR + 256;
static_assert(A_TOTAL <= 232448, "aux smem");

__device__ __forceinline__ void job_of(int T, int k, int& st, int& s) {
  st = k == 0 ? 0 : 3 - k; s = st == 0 ? T : T - LAG;
  if (T >= NSTEP - 2 && k) { st = T == NSTEP - 2 ? 2 : 1; s = NSEG - 3 + k; }
}
__device__ __forceinline__ uint32_t ptag(int s) { return ((s / PRING) & 1) ^ 1; }
static_assert((NSEG / PRING) % 2 == 0, "tags");
__device__ __forceinline__ void load_row(uint32_t* v, const void* row, int lane) {
  const uint4 a = __ldcg((const uint4*)row + lane), b = __ldcg((const uint4*)row + 32 + lane);
  v[0] = a.x; v[1] = a.y; v[2] = a.z; v[3] = a.w; v[4] = b.x; v[5] = b.y; v[6] = b.z; v[7] = b.w;
}
__device__ __forceinline__ void store_row(void* row, const uint32_t* v, int lane) {
  ((uint4*)row)[lane] = make_uint4(v[0], v[1], v[2], v[3]); ((uint4*)row)[32 + lane] = make_uint4(v[4], v[5], v[6], v[7]);
}
__device__ __forceinline__ void store_img(uint8_t* img, int r, const uint32_t* v, int lane) {
  uint8_t* b = img + (lane >> 3) * 4096 + (r >> 3) * 1024 + (r & 7) * 128 + (((lane ^ r) & 7) << 4);
  *(uint4*)b = make_uint4(v[0], v[1], v[2], v[3]);
  *(uint4*)(b + 16384) = make_uint4(v[4], v[5], v[6], v[7]);
}
template <int NT> __device__ __forceinline__ void ln_rows(const uint32_t (*v)[8], uint32_t (*y)[8]) {
  float c[NT], sm[NT], sq[NT];
#pragma unroll
  for (int k = 0; k < NT; k++) {
    c[k] = blo(__shfl_sync(~0u, v[k][0], 0));
    float s0 = 0.f, s1 = 0.f, q0 = 0.f, q1 = 0.f;
#pragma unroll
    for (int i = 0; i < 8; i++) { const float a = blo(v[k][i]) - c[k], b = bhi(v[k][i]) - c[k]; s0 += a; s1 += b; q0 = fmaf(a, a, q0); q1 = fmaf(b, b, q1); }
    sm[k] = s0 + s1; sq[k] = q0 + q1;
  }
#pragma unroll
  for (int o = 16; o > 0; o >>= 1)
#pragma unroll
    for (int k = 0; k < NT; k++) {
      sm[k] += __shfl_xor_sync(~0u, sm[k], o); sq[k] += __shfl_xor_sync(~0u, sq[k], o);
    }
#pragma unroll
  for (int k = 0; k < NT; k++) {
    const float dm = sm[k] * (1.f / 512.f), var = fmaxf(fmaf(-dm, dm, sq[k] * (1.f / 512.f)), 0.f);
    const float mb = rbf(c[k] + dm), inv = rcp(rbf(sqrt_fast(rbf(rbf(var) + 1e-5f))));
#pragma unroll
    for (int i = 0; i < 8; i++) { const uint32_t a = pack2(blo(v[k][i]) - mb, bhi(v[k][i]) - mb); y[k][i] = pack2(blo(a) * inv, bhi(a) * inv); }
  }
}
__device__ __forceinline__ void input_ln_pair(const bf16* x, int s, int pr, int lane) {
  uint32_t v[2][8], y[2][8];
  load_row(v[0], x + (size_t)(s * 32 + 2 * pr) * 512, lane); load_row(v[1], x + (size_t)(s * 32 + 2 * pr + 1) * 512, lane);
  ln_rows<2>(v, y);
  store_img(G.seg[s].h[0], 2 * pr, y[0], lane); store_img(G.seg[s].h[0], 2 * pr + 1, y[1], lane);
}
__device__ __forceinline__ float load_wr(uint32_t* wv, const bf16* wr, int lane) {
  load_row(wv, wr, lane);
  float wsum = 0.f;
#pragma unroll
  for (int i = 0; i < 8; i++) wsum += blo(wv[i]) + bhi(wv[i]);
#pragma unroll
  for (int o = 16; o > 0; o >>= 1) wsum += __shfl_xor_sync(~0u, wsum, o);
  return wsum;
}

template <bool FAST>
__device__ __forceinline__ unsigned long long token_post(int st, int tk, const bf16* res, bf16* dst, bf16* req, unsigned long long best,
                                                         const uint32_t* wv, float wsum, uint32_t E, int lane) {
  const int s = tk >> 5;
  uint32_t x[8];
  load_row(x, res, lane);
  {
    int guard = 0;
    while (__popc(__ballot_sync(~0u, ld_rlx(G.f_acc[st][s][lane]) == E)) < (FAST ? 24 : 32)) { __nanosleep(FAST ? 20 : 100); if (++guard > (1 << 22)) TRAP(); }
  }
  if (tk == s * 32 && st == 0 && lane == 0) TSTAMP(4, s, 0);
  {
    const uint8_t* pp = pp_slot(st, s) + (lane >> 4) * 8192 + (tk & 31) * 256 + (((lane & 15) ^ (tk & 7)) << 4);
    const uint32_t tag = ptag(s);
    uint4 q[8][2];
#define PLD(k, h) q[k][h] = ld_rlx128<(k) * 32768 + (h) * 16384>(pp)
#define PLD8(h) PLD(0, h); PLD(1, h); PLD(2, h); PLD(3, h); PLD(4, h); PLD(5, h); PLD(6, h); PLD(7, h)
#define PBAD(h) __any_sync(~0u, (or3(xo2(q[0][h].x, q[1][h].x, tag), xo2(q[2][h].x, q[3][h].x, tag), xo2(q[4][h].x, q[5][h].x, tag)) | xo2(q[6][h].x, q[7][h].x, tag)) & ~lane & 1u)
#define PSUM(f, h, m) (((f(q[0][h].m) + f(q[1][h].m)) + (f(q[2][h].m) + f(q[3][h].m))) + ((f(q[4][h].m) + f(q[5][h].m)) + (f(q[6][h].m) + f(q[7][h].m))))
    const uint32_t eye = (lane >> 2) == 2 * (lane & 3) ? 0x3f80u : (lane >> 2) == 2 * (lane & 3) + 1 ? 0x3f800000u : 0u;
    auto padd = [&](int h) {
      if (FAST) {
        float u[4] = {0.f, 0.f, 0.f, 0.f}, v[4] = {0.f, 0.f, 0.f, 0.f};
#pragma unroll
        for (int k = 0; k < 8; k++) { hmma8(u, q[k][h].x, q[k][h].y, eye); hmma8(v, q[k][h].z, q[k][h].w, eye); }
        x[4 * h] = add2(x[4 * h], pack2(u[0], u[1])); x[4 * h + 1] = add2(x[4 * h + 1], pack2(u[2], u[3]));
        x[4 * h + 2] = add2(x[4 * h + 2], pack2(v[0], v[1])); x[4 * h + 3] = add2(x[4 * h + 3], pack2(v[2], v[3]));
      } else {
        x[4 * h] = add2(x[4 * h], pack2(PSUM(blo, h, x), PSUM(bhi, h, x))); x[4 * h + 1] = add2(x[4 * h + 1], pack2(PSUM(blo, h, y), PSUM(bhi, h, y)));
        x[4 * h + 2] = add2(x[4 * h + 2], pack2(PSUM(blo, h, z), PSUM(bhi, h, z))); x[4 * h + 3] = add2(x[4 * h + 3], pack2(PSUM(blo, h, w), PSUM(bhi, h, w)));
      }
    };
    int guard = 0;
    PLD8(0);
    if (FAST) { PLD8(1); }
    while (PBAD(0)) { if (++guard > (1 << 20)) TRAP(); PLD8(0); }
    padd(0);
    if (!FAST) { PLD8(1); }
    while (PBAD(1)) { if (++guard > (1 << 20)) TRAP(); PLD8(1); }
    padd(1);
  }
  const float c = blo(__shfl_sync(~0u, x[0], 0));
  float s0 = 0.f, s1 = 0.f, q0 = 0.f, q1 = 0.f, r0 = 0.f, r1 = 0.f;
#pragma unroll
  for (int i = 0; i < 8; i++) {
    const float a = blo(x[i]) - c, b = bhi(x[i]) - c;
    s0 += a; s1 += b; q0 = fmaf(a, a, q0); q1 = fmaf(b, b, q1); r0 = fmaf(a, blo(wv[i]), r0); r1 = fmaf(b, bhi(wv[i]), r1);
  }
  s0 += s1; q0 += q1; r0 += r1;
#pragma unroll
  for (int o = 16; o > 0; o >>= 1) { s0 += __shfl_xor_sync(~0u, s0, o); q0 += __shfl_xor_sync(~0u, q0, o); r0 += __shfl_xor_sync(~0u, r0, o); }
  const float dm = s0 * (1.f / 512.f), m = c + dm, var = fmaxf(fmaf(-dm, dm, q0 * (1.f / 512.f)), 0.f);
  const float mb = rbf(m), inv = rcp(rbf(sqrt_fast(rbf(rbf(var) + 1e-5f))));
  const uint32_t nmb = pack2(-mb, -mb);
  const unsigned long long wd = rword(E, tk, fmaf(c - mb, wsum, r0) * inv);
  uint32_t xn[8], x2[8];
#pragma unroll
  for (int i = 0; i < 8; i++) { const uint32_t d = add2(x[i], nmb); xn[i] = pack2(blo(d) * inv, bhi(d) * inv); x2[i] = add2(x[i], xn[i]); }
  if (st == 0) {
    const float mb2 = rbf(fmaf(m - mb, inv, m)), inv2 = rcp(rbf(sqrt_fast(rbf(rbf(var * (1.f + inv) * (1.f + inv)) + 1e-5f))));
    const uint32_t nmb2 = pack2(-mb2, -mb2);
    uint32_t h[8];
#pragma unroll
    for (int i = 0; i < 8; i++) { const uint32_t d2 = add2(x2[i], nmb2); h[i] = pack2(blo(d2) * inv2, bhi(d2) * inv2); }
    store_img(G.seg[s].h[1], tk & 31, h, lane);
  }
  store_row(dst, x2, lane);
  if (wd > best) { store_row(req, xn, lane); store_row(req + 512, x, lane); }
  return wd;
}

__device__ __forceinline__ void ffn_slice(uint32_t sb, const bf16* xn, float* yacc, uint32_t* flag, uint32_t E, int t, bool urgent) {
  const int w = t >> 5, g = (t >> 2) & 7;
  if (t == 0 && urgent) sts32(sb + A_BAR + 160, 1);
  { const uint2 u = __ldcg((const uint2*)xn + t); asm volatile("st.shared.v2.u32 [%0], {%1,%2};" :: "r"(sb + A_XN + t * 8), "r"(u.x), "r"(u.y) : "memory"); }
  fence_async_smem();
  bar_sync(4, 128);
  float ga[4], ua[4];
  constexpr uint64_t da = mkdesc(A_WG, 896, 128, 0), db = mkdesc(A_XN, 16, 128, 0);
  wg_fence();
  wgmma_ss8<0, 1, 0>(ga, da, db); wgmma_ss8<0, 1, 0>(ua, da + (A_WU - A_WG) / 16, db);
#pragma unroll
  for (int ks = 1; ks < 32; ks++) { wgmma_ss8<1, 1, 0>(ga, da + ks * 112, db + ks * 2); wgmma_ss8<1, 1, 0>(ua, da + (A_WU - A_WG) / 16 + ks * 112, db + ks * 2); }
  wg_commit(); wg_wait<0>(); reg_fence(ga); reg_fence(ua);
  if ((t & 3) == 0) {
#pragma unroll
    for (int h = 0; h < 2; h++) {
      const float gs = rbf(ga[2 * h]), us = rbf(ua[2 * h]);
      const float v = 16 * w + 8 * h < 56 ? rbf(gs * rcp(1.f + __expf(-gs))) * us : 0.f;
      asm volatile("st.shared.u16 [%0], %1;" :: "r"(sb + A_XN + 1280 + (16 * w + 8 * h + g) * 2), "h"((unsigned short)pack2(v, 0.f)) : "memory");
    }
  }
  fence_async_smem();
  bar_sync(4, 128);
#pragma unroll 1
  for (int j = 0; j < 2; j++) {
    float y[4][4];
    const uint64_t dd = mkdesc(A_WD, 8192, 128, 0) + (uint64_t)(j * 256);
    wg_fence();
#pragma unroll
    for (int m = 0; m < 4; m++) {
      wgmma_ss8<0, 1, 0>(y[m], dd + m * 64, mkdesc(A_XN + 1280, 16, 128, 0));
#pragma unroll
      for (int ks = 1; ks < 4; ks++) wgmma_ss8<1, 1, 0>(y[m], dd + m * 64 + ks * 1024, mkdesc(A_XN + 1280 + ks * 32, 16, 128, 0));
    }
    wg_commit(); wg_wait<0>();
#pragma unroll
    for (int m = 0; m < 4; m++) {
      reg_fence(y[m]);
      if ((t & 3) == 0) { float* o = yacc + j * 256 + m * 64 + 16 * w + g; o[0] = y[m][0]; o[8] = y[m][2]; }
    }
  }
  bar_sync(4, 128);
  if (t < 8) { sts32(sb + A_BAR + 160, 0); st_rel(flag + t, E); }
  __syncwarp();
}

__device__ __forceinline__ void ffn_gather(uint32_t sb, int q, int j, uint32_t E, int lane) {
  wait_all(G.f_y[q][4 * j + (lane & 3)], E);
  float4 y[4][4];
#pragma unroll
  for (int k = 0; k < 4; k++)
#pragma unroll
    for (int i = 0; i < 4; i++) y[k][i] = __ldcg((const float4*)G.y[q & 7][4 * j + k] + i * 32 + lane);
#pragma unroll
  for (int i = 0; i < 4; i++)
    sts128f(sb + 1024 + j * 2048 + i * 512 + lane * 16, (y[0][i].x + y[1][i].x) + (y[2][i].x + y[3][i].x), (y[0][i].y + y[1][i].y) + (y[2][i].y + y[3][i].y),
            (y[0][i].z + y[1][i].z) + (y[2][i].z + y[3][i].z), (y[0][i].w + y[1][i].w) + (y[2][i].w + y[3][i].w));
  bar_sync(9, 256);
}
__device__ __forceinline__ void ffn_finish(uint32_t sb, int q, const bf16* req, float r, uint32_t E, int lane, uint32_t* v) {
  if (lane == 0) sts32(sb + 16, q);
  bar_sync(8, 256);
  uint32_t xn[8];
  load_row(xn, req, lane); load_row(v, req + 512, lane);
  const float rs = rbf(1.f / (1.f + __expf(-rbf(r))));
  ffn_gather(sb, q, 7, E, lane);
#pragma unroll
  for (int i = 0; i < 4; i++) {
    float y[4] = {0.f, 0.f, 0.f, 0.f};
#pragma unroll
    for (int j = 0; j < 8; j++) {
      const uint4 u = lds128(sb + 1024 + j * 2048 + (i >> 1) * 1024 + lane * 32 + (i & 1) * 16);
      y[0] += __uint_as_float(u.x); y[1] += __uint_as_float(u.y); y[2] += __uint_as_float(u.z); y[3] += __uint_as_float(u.w);
    }
    v[2 * i] = add2(v[2 * i], add2(xn[2 * i], pack2(rbf(y[0]) * rs, rbf(y[1]) * rs)));
    v[2 * i + 1] = add2(v[2 * i + 1], add2(xn[2 * i + 1], pack2(rbf(y[2]) * rs, rbf(y[3]) * rs)));
  }
}

__global__ void __launch_bounds__(512, 1) aux_kernel(Params p) {
  extern __shared__ __align__(1024) uint8_t sm[];
  const uint32_t sb = smem_u32(sm);
  if ((sb & 0xFFFFFFu) != SBASE) TRAP();
  const int warp = __shfl_sync(~0u, threadIdx.x >> 5, 0);
  const int cta = blockIdx.x;
  const uint32_t E = __shfl_sync(~0u, *(volatile uint32_t*)&g_epoch + 1, 0);
  const uint32_t bars = sb + A_BAR;

  if (cta < 32) {
    const int cg = cta & 3, kg = cta >> 2;
    if (threadIdx.x == 0) {
      for (int i = 0; i < A_NST; i++) { mbar_init(bars + 8 * i, 1); mbar_init(bars + 64 + 8 * i, 2); }
      mbar_init(bars + 128, 8); mbar_init(bars + 136, 8); mbar_init(bars + 144, 1);
      sts32(bars + 160, 0);
      asm volatile("fence.mbarrier_init.release.cluster;" ::: "memory");
    }
    if (warp < 8) {
      asm volatile("setmaxnreg.inc.sync.aligned.u32 176;");
      const int tid = fresh_tid(), lane = tid & 31;
      uint32_t W[32][4];
      bar_arrive(3, 384);
      stage_weights(sb + A_WD, p.wo + (size_t)kg * 512 * 512 + cg * 128, 512, tid, 256);
      cp_async_wait();
      bar_sync(1, 256);
      load_frags(W, sb + A_WD, warp >> 2, warp & 3, lane);
      PIN(W[31][3]);
      bar_sync(1, 256);
      bar_arrive(2, 384);
      const uint32_t so = sb + A_STG + ((lane >> 4) * 8 + (lane & 7)) * 256 + (((warp * 2 + ((lane >> 3) & 1)) ^ (lane & 7)) << 4);
      const uint32_t tm = lane < 4 ? 0x00010001u : 0u;
      int stage = 0; uint32_t ph = 0, job = 0;
#pragma unroll 1
      for (int T = 0; T < NSTEP; T++) {
#pragma unroll 1
        for (int k = 0; k < 3; k++) {
          int st, s; job_of(T, k, st, s);
          if (s < 0 || s >= NSEG) continue;
          float d[16];
#pragma unroll
          for (int hh = 0; hh < 4; hh++) {
            mbar_wait(bars + 8 * stage, ph);
            while (uni(lds32(bars + 160))) __nanosleep(100);
            const uint64_t db = mkdesc(A_RING, 512, 128, 0) + (uint64_t)(stage * 512);
            wg_fence();
            if (hh == 0) wgmma_rs32<0, 0>(d, W[0], db); else wgmma_rs32<1, 0>(d, W[hh * 8], db);
#pragma unroll
            for (int ks = 1; ks < 8; ks++) wgmma_rs32<1, 0>(d, W[hh * 8 + ks], db + ks * 64);
            wg_commit();
            if (hh > 0) { wg_wait<1>(); if ((tid & 127) == 0) mbar_arrive(bars + 64 + 8 * (stage == 0 ? A_NST - 1 : stage - 1)); }
            if (++stage == A_NST) { stage = 0; ph ^= 1; }
          }
          mbar_wait(bars + 144, (job & 1) ^ 1);
          wg_wait<0>(); reg_fence(d);
          if ((tid & 127) == 0) mbar_arrive(bars + 64 + 8 * (stage == 0 ? A_NST - 1 : stage - 1));
          if (cta == 0 && tid == 0) TSTAMP(6, T, k);
          const uint32_t tv = tm * ptag(s);
#define TG(i) ((pack2(d[2 * (i)], d[2 * (i) + 1]) & ~tm) | tv)
          stmatrix4_t(so, TG(0), pack2(d[2], d[3]), TG(2), pack2(d[6], d[7]));
          stmatrix4_t(so + 4096, TG(4), pack2(d[10], d[11]), TG(6), pack2(d[14], d[15]));
          fence_async_smem();
          __syncwarp();
          if (lane == 0) mbar_arrive(bars + 128 + 8 * (job & 1));
          job++;
        }
      }
    } else if (warp < 12) {
      asm volatile("setmaxnreg.dec.sync.aligned.u32 120;");
      const int tid = fresh_tid(), lane = tid & 31;
      const int w = warp - 8, t = tid - 256;
      uint32_t wv[8];
      const float wsum = load_wr(wv, p.wr, lane);
#pragma unroll 1
      for (int s = cta + 4; s < NSEG; s += 32) {
#pragma unroll 1
        for (int pr = w; pr < 16; pr += 4) input_ln_pair(p.x, s, pr, lane);
        bar_sync(4, 128);
        if (t == 0) st_rel(&G.f_h1[s], E);
      }
      bar_sync(2, 384);
      { int guard = 0; while (ld_rlx(&G.f_loaded[cta]) != E) { __nanosleep(200); if (++guard > (1 << 22)) TRAP(); } }
#pragma unroll 1
      for (int i = t; i < 512 * 7; i += 128) {
        const int k = i / 7, pc = i % 7;
        cp_async16(sb + A_WG + (k >> 3) * 896 + pc * 128 + (k & 7) * 16, p.wg + (size_t)k * 1792 + cta * 56 + pc * 8);
        cp_async16(sb + A_WU + (k >> 3) * 896 + pc * 128 + (k & 7) * 16, p.wu + (size_t)k * 1792 + cta * 56 + pc * 8);
        cp_async16(sb + A_WD + (i >> 9) * 8192 + (i & 63) * 128 + ((i >> 6) & 7) * 16, p.wd + (size_t)cta * 56 * 512 + i * 8);
        if ((i >> 7) % 4 == 3) cp_async_wait();
      }
      cp_async_wait();
      fence_async_smem();
      bar_sync(4, 128);
      const int tj = (cta * 4 + w) & 31, st = 1 + ((cta >> 3) & 1), sq = cta >> 4;
      unsigned long long run = 0, run2 = 0, best = 0, hist = 0;
      uint32_t open = 0;
#pragma unroll 1
      for (int i = 0; i <= NSTEP; i++) {
        int tok = -1; const bf16* req = nullptr;
        if (i < NSEG) {
          const int cd = (int)uni(route_step(i, E, lane, run));
          run = __shfl_sync(~0u, run, 0);
          hist = hist << 8 | (uint32_t)(cd + 1);
          if (cd >= 0) { tok = rtok(run); req = G.seg[tok >> 5].req1[tok & 31][0]; }
        } else {
          const unsigned long long m = wait_words(G.f_l2[i - NSEG], E);
          const unsigned long long n = ld_rlxu64(G.f_l2[min(i - NSEG + 1 + (lane & 7), LAG)]);
          const bool over = bar_or(4, 128, rfresh(n, E) && n != m);
          if (m != run2 && !over) { run2 = m; tok = rtok(m); req = G.req2[(tok >> 5) < (rtok(run) >> 5) ? 0 : 1][tok][0]; }
        }
        tok = __shfl_sync(~0u, tok, 0);
        if (tok >= 0) {
          if (cta == 0 && t == 0) TSTAMP(8, i & 127, 0);
          ffn_slice(sb, req, G.y[i & 7][cta], G.f_y[i][cta], E, t, i < NSEG);
          if (cta == 0 && t == 0) TSTAMP(8, i & 127, 1);
        }
        const int s = i - LAG;
        if (s < 0 || i >= NSEG) continue;
        const int cd = (int)((hist >> (8 * LAG)) & 255) - 1;
        if (cd >= 0 && st == 2) best = 0;
        const int ts = rtok(run) >> 5;
        if ((s & 1) == sq) {
          const int tk = s * 32 + tj;
          unsigned long long wd = (unsigned long long)E << 43;
          if (st == 1 ? s < ts || i < NSEG - 1 : s >= ts) {
            if (st == 2 && cd == tj) wait_eq(&G.f_hc[s], E);
            wd = token_post<false>(st, tk, st == 2 && cd == tj ? G.x2c[s] : G.seg[tk >> 5].x2[tk & 31],
                                   st == 2 || s < ts ? p.out + (size_t)tk * 512 : G.seg[s].n[tj], G.req2[st - 1][tk][0], best, wv, wsum, E, lane);
            best = max(best, wd);
            if (st == 1 && s >= ts) open |= 1u << (s >> 1);
          }
          __syncwarp();
          if (lane < 4) st_rel64(&G.f_w2[st - 1][s][tj][lane], wd);
          __syncwarp();
        }
        if (st == 1) {
          if (i == NSEG - 1 && t == 0 && cta == 0) GSTAMP(1, 0);
#pragma unroll 1
          for (int n = i == NSEG - 1 ? 32 : 2; n > 0 && open; n--) {
            const int s0 = 2 * (__ffs(open) - 1) + sq;
            if (s0 >= ts) break;
            open &= open - 1;
            uint32_t v[8];
            load_row(v, G.seg[s0].n[tj], lane);
            wait_words(G.f_w2[1][s0][tj], E);
            store_row(p.out + (size_t)(s0 * 32 + tj) * 512, v, lane);
          }
          if (i == NSEG - 1) {
            __syncwarp();
            if (lane == 0) st_rel(&G.f_cp[sq * 32 + tj], E);
            if (t == 0 && cta == 0) GSTAMP(1, 3);
          }
        }
      }
    } else {
      asm volatile("setmaxnreg.dec.sync.aligned.u32 40;");
      const int tid = fresh_tid(), lane = tid & 31;
      const int w = warp - 12;
      bar_sync(3, 384);
      if (w == 0) {
        int stage = 0; uint32_t ph = 1;
#pragma unroll 1
        for (int T = 0; T < NSTEP; T++) {
#pragma unroll 1
          for (int k = 0; k < 3; k++) {
            int st, s; job_of(T, k, st, s);
            if (s < 0 || s >= NSEG) continue;
            const uint32_t* fl = G.f_o[st ? s + LAG : s][kg][st * 4 + (lane & 3)];
            uint32_t ready = 0; int guard = 0;
#pragma unroll 1
            for (int hh = 0; hh < 4; hh++) {
              while (!((ready >> hh) & 1)) {
                ready = __ballot_sync(~0u, ld_rlx(fl) == E);
                if (++guard > (1 << 23)) TRAP();
              }
              fence_async_glob();
              mbar_wait(bars + 64 + 8 * stage, ph);
              e_expect(bars + 8 * stage, 8192);
              e_g2s(sb + A_RING + stage * 8192, o_slot(st, s, kg * 4 + hh), 8192, bars + 8 * stage);
              if (++stage == A_NST) { stage = 0; ph ^= 1; }
            }
          }
          if (cta == 0 && lane == 0) TSTAMP(3, T, 0);
        }
      } else if (w < 3) {
        uint32_t job = 0;
#pragma unroll 1
        for (int T = 0; T < NSTEP; T++) {
#pragma unroll 1
          for (int k = 0; k < 3; k++) {
            int st, s; job_of(T, k, st, s);
            if (s < 0 || s >= NSEG) continue;
            if ((job++ & 1) != w - 1) continue;
            if (s >= PRING) wait_words(st == 0 ? G.f_h2[s - PRING][lane & 3] : G.f_w2[st - 1][s - PRING][lane], E);
            mbar_wait(bars + 128 + 8 * (w - 1), ((job - 1) >> 1) & 1);
            if (cta == 0 && st == 0) TSTAMP(7, s, 0);
            e_s2g(pp_slot(st, s) + cta * 8192, sb + A_STG, 8192);
            if (lane < 8) st_rlx(&G.f_acc[st][s][cta][lane], E);
            asm volatile("cp.async.bulk.commit_group;\n cp.async.bulk.wait_group.read 0;" ::: "memory");
            __syncwarp();
            e_arrive(bars + 144);
            __syncwarp();
            if (cta == 0 && st == 0) TSTAMP(7, s, 1);
          }
        }
        bulk_wait();
      }
    }
  } else {
    const int tid = fresh_tid(), lane = tid & 31;
    const int qd = cta - 32;
    input_ln_pair(p.x, qd, warp, lane);
    bar_sync(6, 512);
    if (tid == 0) st_rel(&G.f_h1[qd], E);
    volatile int* bc = (volatile int*)sm;
    if (warp == 15) {
      unsigned long long run = 0;
      unsigned long long b2[2][2] = {{0, 0}, {0, 0}};
      auto track = [&](int s) {
#pragma unroll
        for (int k = 0; k < 2; k++) {
          const unsigned long long m = warp_max<16>(wait_words(G.f_w2[k][s][lane], E));
          if (lane == (s & 31)) { if (s < 32) b2[k][0] = m; else b2[k][1] = m; }
        }
      };
#pragma unroll 1
      for (int s = 0; s < NSEG; s++) {
        const int cd = route_step(s, E, lane, run);
        if (cd >= 0 && qd == (s & 1)) {
          uint32_t v[1][8], h[1][8];
          ffn_finish(sb, s, G.seg[s].req1[cd][0], rscore(run), E, lane, v[0]);
          if (lane == 0) TSTAMP(8, s, 2);
          ln_rows<1>(v, h);
#pragma unroll
          for (int i = 0; i < 8; i++) st_rlx64(&G.hc[s][(i >> 2) * 128 + 4 * lane + (i & 3)], h[0][i], E);
          if (lane == 0) TSTAMP(8, s, 3);
          store_row(G.x2c[s], v[0], lane);
          __syncwarp();
          if (lane == 0) st_rel(&G.f_hc[s], E);
        }
        if (qd == 2 && s > LAG) track(s - LAG - 1);
      }
      wait_eq(&G.f_hc[rtok(run) >> 5], E);
      if (lane == 0) *bc = rtok(run);
      bar_sync(7, 288);
      if (qd == 2) {
        uint32_t v[8];
        const int ts = rtok(run) >> 5;
        track(NSEG - LAG - 1);
        run = 0;
        int kl = 0; bool open = false;
#pragma unroll 1
        for (int k = 0; k <= LAG + 1; k++) {
          const int s = min(NSEG - LAG - 1 + k, NSEG - 1);
          unsigned long long m = max(lane < ts ? b2[0][0] : b2[1][0], lane + 32 < ts ? b2[0][1] : b2[1][1]);
          for (int guard = 0; k > 0; guard++) {
            m = ld_rlxu64(G.f_w2[s < ts ? 0 : 1][s][lane]);
            const bool done = open && __all_sync(~0u, ld_rlx(G.f_y[NSEG + kl][lane]) == E);
            if (k <= LAG ? __all_sync(~0u, rfresh(m, E)) : !open) break;
            if (done) { ffn_finish(sb, NSEG + kl, G.req2[(rtok(run) >> 5) < ts ? 0 : 1][rtok(run)][0], rscore(run), E, lane, v); open = false; }
            if (guard > (1 << 22)) TRAP();
          }
          if (k > LAG) break;
          fence_acq();
          m = warp_max<16>(m);
          if (m > run) { run = m; kl = k; open = true; __threadfence(); }
          if (lane < 4) st_rlx64(&G.f_l2[k][lane], (uint32_t)run, (uint32_t)(run >> 32));
          if (k == 0) { wait_all(&G.f_cp[lane], E); wait_all(&G.f_cp[32 + lane], E); }
        }
        if (lane == 0) GSTAMP(1, 1);
        store_row(p.out + (size_t)rtok(run) * 512, v, lane);
        if (lane == 0) GSTAMP(1, 2);
      }
      if (lane == 0) sts32(sb + 16, (uint32_t)-1);
      bar_sync(8, 256);
      if (qd == 2) {
        asm volatile("griddepcontrol.wait;" ::: "memory");
        if (lane == 0) *(volatile uint32_t*)&g_epoch = E;
      }
    } else if (warp >= 8) {
#pragma unroll 1
      for (;;) {
        bar_sync(8, 256);
        const int q = (int)uni(lds32(sb + 16));
        if (q < 0) break;
        ffn_gather(sb, q, warp - 8, E, lane);
      }
    } else {
      uint32_t wv[8];
      const float wsum = load_wr(wv, p.wr, lane);
      unsigned long long best = 0;
      int ttok = 0;
#pragma unroll 1
      for (int i = 0; i < NSTEP; i++) {
        const bool last = i >= NSEG;
        if (i == NSEG) { bar_sync(7, 288); ttok = *bc; best = 0; }
        const int s = last ? i - LAG : i, st = !last ? 0 : s < (ttok >> 5) ? 1 : 2;
        const int tk = s * 32 + qd * 8 + warp;
        const unsigned long long wd = token_post<true>(st, tk, !last ? p.x + (size_t)tk * 512 : tk == ttok ? G.x2c[s] : G.seg[tk >> 5].x2[tk & 31],
                                                 last ? p.out + (size_t)tk * 512 : G.seg[s].x2[tk & 31], last ? G.req2[st - 1][tk][0] : G.seg[s].req1[tk & 31][0], best, wv, wsum, E, lane);
        best = max(best, wd);
        volatile unsigned long long* ws = (volatile unsigned long long*)(sm + 64) + (i & 1) * 8;
        if (lane == 0) ws[warp] = wd;
        const unsigned long long lead = i == NSTEP - 1 ? ld_rlxu64(G.f_l2[LAG - 1]) : 0;
        bar_sync(5, 256);
        if (warp == 0) {
          if (qd == 0 && lane == 0) TSTAMP(4, i, 1);
          if (!last) { const unsigned long long m = warp_max<4>(ws[lane & 7]); if (lane < 4) st_rel64(&G.f_h2[s][qd][lane], m); }
          else {
            const unsigned long long v = ws[lane >> 2];
            if (!__all_sync(~0u, rfresh(lead, E) && v < lead)) __threadfence();
            st_rlx64(&G.f_w2[st - 1][s][qd * 8 + (lane >> 2)][lane & 3], (uint32_t)v, (uint32_t)(v >> 32));
            asm volatile("st.relaxed.gpu.global.u64 [%0], %1;" :: "l"(&G.f_w2[2 - st][s][qd * 8 + (lane >> 2)][lane & 3]), "l"((unsigned long long)E << 43) : "memory");
          }
          if (qd == 0 && lane == 0) TSTAMP(4, i, 2);
        }
        __syncwarp();
      }
    }
  }
}

}

extern "C" void kernel_launch(void* const* d_in, const int* in_sizes, int n_in, void* d_out, int out_size) {
  (void)in_sizes; (void)n_in; (void)out_size;
  static bool init = false;
  if (!init) {
    cudaFuncSetAttribute(main_kernel, cudaFuncAttributeMaxDynamicSharedMemorySize, M_TOTAL);
    cudaFuncSetAttribute(aux_kernel, cudaFuncAttributeMaxDynamicSharedMemorySize, A_TOTAL);
    init = true;
  }
  Params p;
  p.x = (const bf16*)d_in[0]; p.mem0 = (const bf16*)d_in[1]; p.wq = (const bf16*)d_in[2]; p.wk = (const bf16*)d_in[3];
  p.wv = (const bf16*)d_in[4]; p.wo = (const bf16*)d_in[5]; p.wr = (const bf16*)d_in[8]; p.wg = (const bf16*)d_in[9];
  p.wu = (const bf16*)d_in[10]; p.wd = (const bf16*)d_in[11]; p.out = (bf16*)d_out; p.zero = 0; p.zero2 = 0;
  cudaStream_t st = cudaStreamPerThread;
  main_kernel<<<96, 512, M_TOTAL, st>>>(p);
  cudaLaunchConfig_t cfg = {};
  cfg.gridDim = dim3(36); cfg.blockDim = dim3(512); cfg.dynamicSmemBytes = A_TOTAL; cfg.stream = st;
  cudaLaunchAttribute at[1];
  at[0].id = cudaLaunchAttributeProgrammaticStreamSerialization; at[0].val.programmaticStreamSerializationAllowed = 1;
  cfg.attrs = at; cfg.numAttrs = 1;
  cudaLaunchKernelEx(&cfg, aux_kernel, p);
}
```

```cpp
#include <cuda_runtime.h>
#include <cuda_bf16.h>
#include <stdint.h>
#include <stddef.h>

namespace {

typedef __nv_bfloat16 bf16;

constexpr int NSEG = 64;
#define LAG_ 5
constexpr int LAG = LAG_;
constexpr int NSTEP = NSEG + LAG;
constexpr int ORING = 8, PRING = 4;
static_assert(LAG < 8, "rings");

#define E1_ 10
#define E3_ 10
constexpr int E1 = E1_, EA = E1_ + E3_;
static_assert(EA % 4 == 0 && EA < 32, "early part: whole 64-column chunks");
#define PAUSE_ 13
#define PAUS2_ 29
#define PST2_ 2
#define HAND_ 4
#define SALT_ 0
#define TP(i, v) (v)
#define XDLY_ TP(0, 2075)
#define YDLY_ TP(1, 3400)
#define X1_ TP(2, 100)
#define X2_ TP(3, 350)
#define Y1_ TP(4, 200)
#define Y2_ TP(5, 450)
#define HGAP_ TP(6, 50)
#define TGAP_ TP(7, 100)
#define ADLY_ TP(8, 600)
#define ODLY_ TP(9, 2800)
#define HDLY_ TP(11, 0)
#define TDLY_ TP(15, 4150)
#define SDLY_ TP(12, 800)
#define AGAP_ 100
#define BOFF_ TP(13, 200)
#define YOFF_ TP(16, 150)
#define YUP_ TP(20, 40)
#define YDN_ TP(21, 4)
#define T1GAP_ 0
#define OGAP_ TP(23, 0)
#define CDLY_ TP(17, 300)
#define SLOW0_ TP(18, 400)
#define SLOW1_ TP(19, 300)
#define KDLY_ TP(14, 300)
#define XFR_ TP(10, 2)
__device__ uint32_t g_epoch;
struct Seg {
  uint8_t h[2][32768];
  bf16 x2[32][512], n[32][512];
  bf16 req1[32][2][512];
};
struct Mix {
  uint8_t tok[16][2][16384];
  uint8_t o[4][32][8192];
  uint8_t pp[2][8 * 32768];
};
struct Scratch {
  uint8_t xch[96 * 16384 + 65536];
  unsigned long long f_h2[NSEG][4][4];
  unsigned long long f_l2[8][4];
  unsigned long long sync[2][96][4];
  uint32_t f_o[NSTEP][8][12][8];
  uint32_t f_y[NSTEP + 1][32][8], f_cp[64];
  uint32_t f_choice[96][2], f_loaded[32], f_h1[NSEG], f_hc[NSEG];
  uint8_t pad0[2097152 - (96 * 16384 + 65536 + NSEG * 128 + 256 + 6144 + NSTEP * 3072 + (NSTEP + 1) * 1024 + 256 + 768 + 128 + NSEG * 8)];
  Mix mix[6];
  uint32_t f_acc[3][NSEG][32][8];
  unsigned long long f_w2[2][NSEG][32][4];
  uint2 hc[NSEG][256];
  bf16 x2c[NSEG][512];
  float y[8][32][512];
  Seg seg[NSEG];
  bf16 req2[2][2048][2][512];
};
static_assert(sizeof(Mix) == 2097152 && offsetof(Scratch, mix) == 2097152 && offsetof(Scratch, seg) % 1024 == 0 && ORING == 8 && PRING == 4, "layout");
__device__ uint8_t g_raw[sizeof(Scratch) + 2097152];
__device__ __forceinline__ Scratch& scr() { return *(Scratch*)(((uintptr_t)g_raw + 2097151) & ~(uintptr_t)2097151); }
#define G scr()
__device__ __forceinline__ uint8_t* o_slot(int st, int s, int head) { const int j = st * 8 + (s & 7); return G.mix[j % 6].o[j / 6][head]; }
__device__ __forceinline__ uint8_t* pp_slot(int st, int s) { const int j = st * 4 + (s & 3); return G.mix[j % 6].pp[j / 6]; }

#define TRAP() __trap()
__device__ __forceinline__ uint32_t smem_u32(const void* p) { return (uint32_t)__cvta_generic_to_shared(p); }
__device__ __forceinline__ int fresh_tid() { const int t = threadIdx.x; return __shfl_sync(~0u, t, t & 31); }
__device__ __forceinline__ unsigned long long gtime64() { unsigned long long t; asm volatile("mov.u64 %0, %%globaltimer;" : "=l"(t) :: "memory"); return t; }
__device__ __forceinline__ uint32_t clk() { unsigned long long c; asm volatile("mov.u64 %0, %%clock64;" : "=l"(c) :: "memory"); return (uint32_t)c; }
__device__ __forceinline__ void wait_until(uint32_t t) {
  while ((int)(t - clk()) > 450) __nanosleep(32);
  uint32_t c;
  do { asm volatile("mov.u32 %0, %%clock;" : "=r"(c) :: "memory"); } while ((int)(c - t) < 0);
}
__device__ __forceinline__ void mbar_init(uint32_t bar, uint32_t cnt) { asm volatile("mbarrier.init.shared::cta.b64 [%0], %1;" :: "r"(bar), "r"(cnt) : "memory"); }
__device__ __forceinline__ void mbar_arrive(uint32_t bar) { asm volatile("mbarrier.arrive.shared::cta.b64 _, [%0];" :: "r"(bar) : "memory"); }
__device__ __forceinline__ void mbar_arrive_remote(uint32_t bar) { asm volatile("mbarrier.arrive.relaxed.cluster.shared::cluster.b64 _, [%0];" :: "r"(bar) : "memory"); }
__device__ __forceinline__ void mbar_expect(uint32_t bar, uint32_t bytes) { asm volatile("mbarrier.arrive.expect_tx.shared::cta.b64 _, [%0], %1;" :: "r"(bar), "r"(bytes) : "memory"); }
__device__ __forceinline__ bool mbar_try(uint32_t bar, uint32_t parity) {
  uint32_t ok;
  asm volatile("{.reg .pred p; mbarrier.try_wait.parity.shared::cta.b64 p, [%1], %2; selp.u32 %0, 1, 0, p;}" : "=r"(ok) : "r"(bar), "r"(parity) : "memory");
  return ok;
}
__device__ __forceinline__ bool mbar_test(uint32_t bar, uint32_t parity) {
  uint32_t ok;
  asm volatile("{.reg .pred p; mbarrier.test_wait.parity.shared::cta.b64 p, [%1], %2; selp.u32 %0, 1, 0, p;}" : "=r"(ok) : "r"(bar), "r"(parity) : "memory");
  return ok;
}
__device__ __forceinline__ void mbar_wait(uint32_t bar, uint32_t parity) {
  asm volatile("{\n.reg .pred p;\nWAIT:\nmbarrier.try_wait.parity.shared::cta.b64 p, [%0], %1;\n@!p bra WAIT;\n}" :: "r"(bar), "r"(parity) : "memory");
}
__device__ __forceinline__ uint32_t ld_acq(const uint32_t* p) { uint32_t v; asm volatile("ld.acquire.gpu.global.u32 %0, [%1];" : "=r"(v) : "l"(p) : "memory"); return v; }
__device__ __forceinline__ void st_rel(uint32_t* p, uint32_t v) { asm volatile("st.release.gpu.global.u32 [%0], %1;" :: "l"(p), "r"(v) : "memory"); }
__device__ __forceinline__ void st_rel64(unsigned long long* p, unsigned long long v) { asm volatile("st.release.gpu.global.u64 [%0], %1;" :: "l"(p), "l"(v) : "memory"); }
__device__ __forceinline__ uint32_t ld_rlx(const uint32_t* p) { uint32_t v; asm volatile("ld.relaxed.gpu.global.u32 %0, [%1];" : "=r"(v) : "l"(p) : "memory"); return v; }
__device__ __forceinline__ unsigned long long ld_rlxu64(const unsigned long long* p) { unsigned long long v; asm volatile("ld.relaxed.gpu.global.u64 %0, [%1];" : "=l"(v) : "l"(p) : "memory"); return v; }
__device__ __forceinline__ void st_rlx(uint32_t* p, uint32_t v) { asm volatile("st.relaxed.gpu.global.u32 [%0], %1;" :: "l"(p), "r"(v) : "memory"); }
__device__ __forceinline__ void bulk_wait() { asm volatile("cp.async.bulk.commit_group;\n cp.async.bulk.wait_group 0;" ::: "memory"); }
__device__ __forceinline__ void fence_acq() { asm volatile("fence.acquire.gpu;" ::: "memory"); }
__device__ __forceinline__ void wait_all(const uint32_t* p, uint32_t v, bool acquire = true) {
  int guard = 0;
  while (!__all_sync(~0u, ld_rlx(p) == v)) { __nanosleep(32); if (++guard > (1 << 22)) TRAP(); }
  if (acquire) fence_acq();
}
__device__ __forceinline__ void wait_eq(const uint32_t* p, uint32_t v) {
  int guard = 0;
  while (ld_rlx(p) != v) { __nanosleep(64); if (++guard > (1 << 22)) TRAP(); }
  fence_acq();
}
__device__ __forceinline__ unsigned long long rword(uint32_t E, int tok, float r) {
  uint32_t u = __float_as_uint(r + 0.f);
  u = r != r ? 0u : (u >> 31) ? ~u : u | 0x80000000u;
  return (unsigned long long)(E & 0x1FFFFFu) << 43 | (unsigned long long)u << 11 | (uint32_t)(2047 - tok);
}
__device__ __forceinline__ int rtok(unsigned long long v) { return 2047 - (int)(v & 2047u); }
__device__ __forceinline__ float rscore(unsigned long long v) { const uint32_t u = (uint32_t)(v >> 11); return __uint_as_float((u >> 31) ? u & 0x7fffffffu : ~u); }
__device__ __forceinline__ bool rfresh(unsigned long long v, uint32_t E) { return (uint32_t)(v >> 43) == (E & 0x1FFFFFu); }
template <int TOP> __device__ __forceinline__ unsigned long long warp_max(unsigned long long v) {
#pragma unroll
  for (int o = TOP; o > 0; o >>= 1) { const unsigned long long ov = __shfl_xor_sync(~0u, v, o); v = ov > v ? ov : v; }
  return v;
}
template <int off> __device__ __forceinline__ uint2 ld_rlx64(const void* p) { unsigned long long v; asm volatile("ld.relaxed.gpu.global.b64 %0, [%1+%2];" : "=l"(v) : "l"(p), "n"(off) : "memory"); return make_uint2((uint32_t)v, (uint32_t)(v >> 32)); }
template <int off> __device__ __forceinline__ uint4 ld_rlx128(const void* p) {
  unsigned long long a, b; asm volatile("ld.relaxed.gpu.global.v2.b64 {%0,%1}, [%2+%3];" : "=l"(a), "=l"(b) : "l"(p), "n"(off) : "memory");
  return make_uint4((uint32_t)a, (uint32_t)(a >> 32), (uint32_t)b, (uint32_t)(b >> 32));
}
__device__ __forceinline__ void st_rlx64(void* p, uint32_t lo, uint32_t hi) { asm volatile("{.reg .b64 t; mov.b64 t, {%1,%2}; st.relaxed.gpu.global.b64 [%0], t;}" :: "l"(p), "r"(lo), "r"(hi) : "memory"); }
__device__ __forceinline__ void cp_async16(uint32_t dst, const void* src) { asm volatile("cp.async.cg.shared.global [%0], [%1], 16;" :: "r"(dst), "l"(src) : "memory"); }
__device__ __forceinline__ void cp_async_wait() { asm volatile("cp.async.wait_all;" ::: "memory"); }
__device__ __forceinline__ void fence_async_smem() { asm volatile("fence.proxy.async.shared::cta;" ::: "memory"); }
__device__ __forceinline__ void fence_async_glob() { asm volatile("fence.proxy.async.global;" ::: "memory"); }
__device__ __forceinline__ float ex2(float x) { float y; asm("ex2.approx.ftz.f32 %0, %1;" : "=f"(y) : "f"(x)); return y; }
__device__ __forceinline__ float sqrt_fast(float x) { float y; asm("sqrt.approx.ftz.f32 %0, %1;" : "=f"(y) : "f"(x)); return y; }
__device__ __forceinline__ float rcp(float x) { float y; asm("rcp.approx.ftz.f32 %0, %1;" : "=f"(y) : "f"(x)); return y; }
__device__ __forceinline__ void bar_sync(int id, int n) { asm volatile("bar.sync %0, %1;" :: "r"(id), "r"(n) : "memory"); }
__device__ __forceinline__ bool bar_or(int id, int n, bool v) {
  uint32_t r;
  asm volatile("{.reg .pred p, q; setp.ne.u32 p, %3, 0; barrier.cta.red.or.aligned.pred q, %1, %2, p; selp.u32 %0, 1, 0, q;}" : "=r"(r) : "r"(id), "r"(n), "r"((uint32_t)v) : "memory");
  return r;
}
__device__ __forceinline__ uint32_t mapa(uint32_t a, uint32_t rank) { uint32_t r; asm volatile("mapa.shared::cluster.u32 %0, %1, %2;" : "=r"(r) : "r"(a), "r"(rank)); return r; }
__device__ __forceinline__ void cluster_sync() { asm volatile("barrier.cluster.arrive.release.aligned; barrier.cluster.wait.acquire.aligned;" ::: "memory"); }
__device__ __forceinline__ void st_async32(uint32_t dst, uint32_t v, uint32_t bar) { asm volatile("st.async.shared::cluster.mbarrier::complete_tx::bytes.b32 [%0], %1, [%2];" :: "r"(dst), "r"(v), "r"(bar) : "memory"); }
#define ELECT(op) "{.reg .pred p; elect.sync _|p, 0xffffffff; @p " op "}"
__device__ __forceinline__ void e_arrive(uint32_t bar) { asm volatile(ELECT("mbarrier.arrive.shared::cta.b64 _, [%0];") :: "r"(bar) : "memory"); }
__device__ __forceinline__ void e_expect(uint32_t bar, uint32_t bytes) { asm volatile(ELECT("mbarrier.arrive.expect_tx.shared::cta.b64 _, [%0], %1;") :: "r"(bar), "r"(bytes) : "memory"); }
__device__ __forceinline__ void e_g2s(uint32_t dst, const void* src, uint32_t bytes, uint32_t bar) {
  asm volatile(ELECT("cp.async.bulk.shared::cluster.global.mbarrier::complete_tx::bytes [%0], [%1], %2, [%3];") :: "r"(dst), "l"(src), "r"(bytes), "r"(bar) : "memory");
}
__device__ __forceinline__ void e_mc(uint32_t dst, const void* src, uint32_t bytes, uint32_t bar, uint16_t mask) {
  asm volatile(ELECT("cp.async.bulk.shared::cluster.global.mbarrier::complete_tx::bytes.multicast::cluster [%0], [%1], %2, [%3], %4;")
               :: "r"(dst), "l"(src), "r"(bytes), "r"(bar), "h"(mask) : "memory");
}
__device__ __forceinline__ void e_s2g(void* dst, uint32_t src, uint32_t bytes) {
  asm volatile(ELECT("cp.async.bulk.global.shared::cta.bulk_group [%0], [%1], %2;") :: "l"(dst), "r"(src), "r"(bytes) : "memory");
}
__device__ __forceinline__ uint32_t clk32() { uint32_t c; asm volatile("mov.u32 %0, %%clock;" : "=r"(c) :: "memory"); return c; }
__device__ __forceinline__ void spin_until(uint32_t t) { while ((int)(clk32() - t) < 0) {} }
__device__ __forceinline__ uint32_t uni(uint32_t v) { return __shfl_sync(~0u, v, 0); }
__device__ __forceinline__ uint32_t pack2(float lo, float hi) { uint32_t r; asm("cvt.rn.bf16x2.f32 %0, %1, %2;" : "=r"(r) : "f"(hi), "f"(lo)); return r; }
__device__ __forceinline__ uint32_t add2(uint32_t a, uint32_t b) { uint32_t r; asm("add.rn.bf16x2 %0, %1, %2;" : "=r"(r) : "r"(a), "r"(b)); return r; }
__device__ __forceinline__ float rbf(float x) { return __bfloat162float(__float2bfloat16_rn(x)); }
__device__ __forceinline__ float blo(uint32_t u) { return __uint_as_float(u << 16); }
__device__ __forceinline__ float bhi(uint32_t u) { return __uint_as_float(u & 0xffff0000u); }
__device__ __forceinline__ uint32_t gentag(uint32_t g) { return (g & 1u) | (g & 2u) << 15; }
__device__ __forceinline__ uint32_t pack2_tag(float lo, float hi, uint32_t tag) {
  const uint32_t u = __byte_perm(__float_as_uint(lo), __float_as_uint(hi), 0x7632);
  return u + ((u ^ tag) & 0x10001u);
}
__device__ __forceinline__ uint32_t xo2(uint32_t a, uint32_t b, uint32_t t) { uint32_t r; asm("lop3.b32 %0, %1, %2, %3, 0x7e;" : "=r"(r) : "r"(a), "r"(b), "r"(t)); return r; }
__device__ __forceinline__ uint32_t or3(uint32_t a, uint32_t b, uint32_t c) { uint32_t r; asm("lop3.b32 %0, %1, %2, %3, 0xfe;" : "=r"(r) : "r"(a), "r"(b), "r"(c)); return r; }
__device__ __forceinline__ void stmatrix4(uint32_t a, uint32_t r0, uint32_t r1, uint32_t r2, uint32_t r3) {
  asm volatile("stmatrix.sync.aligned.m8n8.x4.shared.b16 [%0], {%1,%2,%3,%4};" :: "r"(a), "r"(r0), "r"(r1), "r"(r2), "r"(r3) : "memory");
}
__device__ __forceinline__ void stmatrix4_t(uint32_t a, uint32_t r0, uint32_t r1, uint32_t r2, uint32_t r3) {
  asm volatile("stmatrix.sync.aligned.m8n8.x4.trans.shared.b16 [%0], {%1,%2,%3,%4};" :: "r"(a), "r"(r0), "r"(r1), "r"(r2), "r"(r3) : "memory");
}
__device__ __forceinline__ void ldmatrix4_t(uint32_t* r, uint32_t a) {
  asm volatile("ldmatrix.sync.aligned.m8n8.x4.trans.shared.b16 {%0,%1,%2,%3}, [%4];" : "=r"(r[0]), "=r"(r[1]), "=r"(r[2]), "=r"(r[3]) : "r"(a) : "memory");
}
__device__ __forceinline__ void ldmatrix4(uint32_t* r, uint32_t a) {
  asm volatile("ldmatrix.sync.aligned.m8n8.x4.shared.b16 {%0,%1,%2,%3}, [%4];" : "=r"(r[0]), "=r"(r[1]), "=r"(r[2]), "=r"(r[3]) : "r"(a) : "memory");
}
__device__ __forceinline__ void hmma16(float* c, const uint32_t* a, uint32_t b0, uint32_t b1) {
  asm volatile("mma.sync.aligned.m16n8k16.row.col.f32.bf16.bf16.f32 {%0,%1,%2,%3}, {%4,%5,%6,%7}, {%8,%9}, {%0,%1,%2,%3};"
               : "+f"(c[0]), "+f"(c[1]), "+f"(c[2]), "+f"(c[3]) : "r"(a[0]), "r"(a[1]), "r"(a[2]), "r"(a[3]), "r"(b0), "r"(b1));
}
__device__ __forceinline__ void hmma8(float* c, uint32_t a0, uint32_t a1, uint32_t b0) {
  asm volatile("mma.sync.aligned.m16n8k8.row.col.f32.bf16.bf16.f32 {%0,%1,%2,%3}, {%4,%5}, {%6}, {%0,%1,%2,%3};"
               : "+f"(c[0]), "+f"(c[1]), "+f"(c[2]), "+f"(c[3]) : "r"(a0), "r"(a1), "r"(b0));
}
__device__ __forceinline__ uint4 lds128(uint32_t a) { uint4 v; asm volatile("ld.shared.v4.u32 {%0,%1,%2,%3}, [%4];" : "=r"(v.x), "=r"(v.y), "=r"(v.z), "=r"(v.w) : "r"(a) : "memory"); return v; }
__device__ __forceinline__ void sts128(uint32_t a, uint4 v) { asm volatile("st.shared.v4.u32 [%0], {%1,%2,%3,%4};" :: "r"(a), "r"(v.x), "r"(v.y), "r"(v.z), "r"(v.w) : "memory"); }
__device__ __forceinline__ void sts128f(uint32_t a, float x, float y, float z, float w) { asm volatile("st.shared.v4.f32 [%0], {%1,%2,%3,%4};" :: "r"(a), "f"(x), "f"(y), "f"(z), "f"(w) : "memory"); }
__device__ __forceinline__ uint32_t lds32(uint32_t a) { uint32_t v; asm volatile("ld.shared.u32 %0, [%1];" : "=r"(v) : "r"(a) : "memory"); return v; }
__device__ __forceinline__ void sts32(uint32_t a, uint32_t v) { asm volatile("st.shared.u32 [%0], %1;" :: "r"(a), "r"(v) : "memory"); }

constexpr uint32_t SBASE = 1024;
__host__ __device__ constexpr uint64_t mkdesc(uint32_t off, uint32_t lbo, uint32_t sbo, uint32_t swz) {
  return (uint64_t)(((SBASE + off) & 0x3FFFF) >> 4) | ((uint64_t)(lbo >> 4) << 16) | ((uint64_t)(sbo >> 4) << 32) | ((uint64_t)swz << 62);
}
__device__ __forceinline__ void wg_fence() { asm volatile("wgmma.fence.sync.aligned;" ::: "memory"); }
__device__ __forceinline__ void wg_commit() { asm volatile("wgmma.commit_group.sync.aligned;" ::: "memory"); }
template <int N> __device__ __forceinline__ void wg_wait() { asm volatile("wgmma.wait_group.sync.aligned %0;" :: "n"(N) : "memory"); }

template <int N> __device__ __forceinline__ void reg_fence(float (&d)[N], int n = N) {
#pragma unroll
  for (int i = 0; i < N; i++) if (i < n) asm volatile("" : "+f"(d[i]) :: "memory");
}
#define F4(b) "+f"(d[b]), "+f"(d[b + 1]), "+f"(d[b + 2]), "+f"(d[b + 3])
#define F8(b) F4(b), F4(b + 4)
#define F16(b) F8(b), F8(b + 8)
#define G4(b) "=f"(d[b]), "=f"(d[b + 1]), "=f"(d[b + 2]), "=f"(d[b + 3])
#define G8(b) G4(b), G4(b + 4)
#define G16(b) G8(b), G8(b + 8)
#define RS_IN "r"(a[0]), "r"(a[1]), "r"(a[2]), "r"(a[3]), "l"(db), "n"(SD), "n"(TB)
#define SS_IN "l"(da), "l"(db), "n"(SD), "n"(TA), "n"(TB)
#define WG_OP(str, out0, out1, in) do { if (SD || KEEP) asm volatile(str : out1 : in); else asm volatile(str : out0 : in); } while (0)
#define O12(X) X##8(0), X##4(8)
#define O20(X) X##16(0), X##4(16)
#define O32(X) X##16(0), X##16(16)
template <int SD, int TB, int KEEP = 0> __device__ __forceinline__ void wgmma_rs24(float* d, const uint32_t* a, uint64_t db) {
  WG_OP("wgmma.mma_async.sync.aligned.m64n24k16.f32.bf16.bf16 {%0,%1,%2,%3,%4,%5,%6,%7,%8,%9,%10,%11}, {%12,%13,%14,%15}, %16, %17, 1, 1, %18;", O12(G), O12(F), RS_IN);
}
template <int SD, int TB, int KEEP = 0> __device__ __forceinline__ void wgmma_rs32(float* d, const uint32_t* a, uint64_t db) {
  WG_OP("wgmma.mma_async.sync.aligned.m64n32k16.f32.bf16.bf16 {%0,%1,%2,%3,%4,%5,%6,%7,%8,%9,%10,%11,%12,%13,%14,%15}, {%16,%17,%18,%19}, %20, %21, 1, 1, %22;", G16(0), F16(0), RS_IN);
}
template <int SD, int TB, int KEEP = 0> __device__ __forceinline__ void wgmma_rs40(float* d, const uint32_t* a, uint64_t db) {
  WG_OP("wgmma.mma_async.sync.aligned.m64n40k16.f32.bf16.bf16 {%0,%1,%2,%3,%4,%5,%6,%7,%8,%9,%10,%11,%12,%13,%14,%15,"
        "%16,%17,%18,%19}, {%20,%21,%22,%23}, %24, %25, 1, 1, %26;", O20(G), O20(F), RS_IN);
}
template <int SD, int TB, int KEEP = 0> __device__ __forceinline__ void wgmma_rs64(float* d, const uint32_t* a, uint64_t db) {
  WG_OP("wgmma.mma_async.sync.aligned.m64n64k16.f32.bf16.bf16 {%0,%1,%2,%3,%4,%5,%6,%7,%8,%9,%10,%11,%12,%13,%14,%15,"
        "%16,%17,%18,%19,%20,%21,%22,%23,%24,%25,%26,%27,%28,%29,%30,%31}, {%32,%33,%34,%35}, %36, %37, 1, 1, %38;", O32(G), O32(F), RS_IN);
}
template <int SD, int TA, int TB, int KEEP = 0> __device__ __forceinline__ void wgmma_ss24(float* d, uint64_t da, uint64_t db) {
  WG_OP("wgmma.mma_async.sync.aligned.m64n24k16.f32.bf16.bf16 {%0,%1,%2,%3,%4,%5,%6,%7,%8,%9,%10,%11}, %12, %13, %14, 1, 1, %15, %16;", O12(G), O12(F), SS_IN);
}
template <int SD, int TA, int TB, int KEEP = 0> __device__ __forceinline__ void wgmma_ss8(float* d, uint64_t da, uint64_t db) {
  WG_OP("wgmma.mma_async.sync.aligned.m64n8k16.f32.bf16.bf16 {%0,%1,%2,%3}, %4, %5, %6, 1, 1, %7, %8;", G4(0), F4(0), SS_IN);
}
__device__ __forceinline__ void bar_arrive(int id, int n) { asm volatile("bar.arrive %0, %1;" :: "r"(id), "r"(n) : "memory"); }
__device__ __forceinline__ uint32_t vis_bits(int pos, int t) {
  uint32_t m = 0;
#pragma unroll
  for (int i = 0; i < 8; i++) m |= (8 * (i / 2 + 1) + 2 * t + (i & 1) <= pos) ? 1u << i : 0u;
  return m;
}

__device__ __forceinline__ unsigned long long wait_words(const unsigned long long* p, uint32_t E) {
  int guard = 0; unsigned long long m;
  while (m = ld_rlxu64(p), !__all_sync(~0u, rfresh(m, E))) { __nanosleep(20); if (++guard > (1 << 22)) TRAP(); }
  fence_acq();
  return m;
}
__device__ __forceinline__ int route_step(int s, uint32_t E, int lane, unsigned long long& run) {
  const unsigned long long m = warp_max<2>(wait_words(G.f_h2[s][lane & 3], E));
  if (s == 0 || m > run) { run = m; return rtok(m) & 31; }
  return -1;
}

struct Params {
  const bf16 *x, *mem0, *wq, *wk, *wv, *wo, *wr, *wg, *wu, *wd;
  bf16* out;
  uint32_t zero2;
  unsigned long long zero;
};

constexpr uint32_t WSTG_STRIDE = 272;
__device__ __forceinline__ void stage_weights(uint32_t stg, const bf16* src, int ld, int tid, int nthr) {
  for (int i = tid; i < 512 * 16; i += nthr) {
    int k = i >> 4, c = i & 15;
    cp_async16(stg + k * WSTG_STRIDE + c * 16, src + (size_t)k * ld + c * 8);
  }
}
__device__ __forceinline__ void load_frags(uint32_t (*W)[4], uint32_t stg, int wg, int w, int lane) {
  uint32_t a = stg + ((lane >> 4) * 8 + (lane & 7)) * WSTG_STRIDE + (64 * wg + 16 * w + ((lane >> 3) & 1) * 8) * 2;
#pragma unroll
  for (int ks = 0; ks < 32; ks++) ldmatrix4_t(W[ks], a + ks * 16 * WSTG_STRIDE);
}

constexpr uint32_t M_H = 0;
constexpr uint32_t M_MEM = 65536;
constexpr uint32_t M_Q = M_MEM + 24576;
constexpr uint32_t M_K = M_Q + 12288;
constexpr uint32_t M_V = M_K + 12288;
constexpr uint32_t M_OM = M_V + 12288;
constexpr uint32_t M_OST = M_OM + 6144;
constexpr uint32_t M_TST = M_OST + 8192;
constexpr uint32_t M_WO = M_TST + 16384;
constexpr uint32_t M_M0 = M_WO + 49152;
constexpr uint32_t M_PT = M_M0 + 2048;
constexpr uint32_t M_BAR = M_PT + 12288;
constexpr uint32_t M_TOTAL = M_BAR + 384;
static_assert(M_TOTAL <= 232448, "main smem");
static_assert(M_WO >= 512 * WSTG_STRIDE, "staging overlaps Wo");
enum { B_LAND = 0  , B_QK = 3, B_V, B_TOK, B_OM, B_HA, B_HB, B_HAE, B_HBE, B_OST, B_OFREE, B_SYNC,
       B_STG, B_STG1, B_SS, B_TFREE, B_KFREE, B_VFREE, B_FIX  , B_NUM = B_FIX + 8 };
static_assert(B_NUM * 8 <= 256, "barriers");
constexpr uint32_t M_CAND = M_BAR + 256;
constexpr uint32_t M_BASE = M_BAR + 272;
constexpr uint32_t M_ZERO = M_BAR + 280;
constexpr uint32_t M_BAS2 = M_BAR + 328;
constexpr uint32_t M_NEAR = M_BAR + 288;
enum { N_GO2 = 3, N_GO3, N_GO4, N_AG, N_W };

#define GSTAMP(slot, i)
#define TSTAMP(slot, i, k)
#define STAMP(i)
#define ASTAMP(i)
#define WSTAMP(i)
#define CSTAMP(i, v)
#define PIN(x) asm volatile("" : "+r"(x))
#define SCHED(k) asm volatile("{\n.reg .pred p;\nsetp.ne.u32 p, %0, 0;\n@p trap;\n}" :: "r"(zz & (1u << (k))) : "memory")
#define HOLD(k, v) asm volatile("{\n.reg .pred p;\nsetp.ne.u32 p, %0, 0;\n@p st.shared.u32 [%0], %1;\n}" :: "r"(zz & (1u << (k))), "r"(v) : "memory")
#define DRAIN(a) (lds32((a) + zz) & zz)
#define BAR(i) (sb + M_BAR + 8 * (i))
#define DLY(k)

__device__ __forceinline__ int probe(const uint8_t* p, int n) {
  int best = 1 << 30; uint32_t v = 0;
#pragma unroll 1
  for (int r = 0; r < n; r++) {
    uint32_t t0 = clk();
    asm volatile("atom.relaxed.gpu.global.or.b32 %0, [%1], %2;" : "=r"(v) : "l"(p + 3968), "r"(v & 0u) : "memory");
    if (v == 0x7fffffffu) t0++;
    best = min(best, (int)(clk() - t0));
  }
  return best;
}
__device__ __forceinline__ void load_mem0(uint4* u, int k0, int lane, const bf16* mem0) {
#pragma unroll
  for (int i = 0; i < 2; i++) {
    const unsigned short* m = (const unsigned short*)mem0 + k0 + lane + 32 * i;
    u[i] = make_uint4(m[0] | (uint32_t)m[512] << 16, m[1024] | (uint32_t)m[1536] << 16, m[2048] | (uint32_t)m[2560] << 16, m[3072] | (uint32_t)m[3584] << 16);
  }
}

__device__ __forceinline__ void paced_h(uint32_t dst, const uint8_t* src, uint32_t o0, uint32_t o1, uint32_t piece, uint32_t bar, int gap) {
  uint32_t t = clk32();
#pragma unroll 1
  for (uint32_t o = o0; o < o1; o += piece) {
    e_mc(dst + o, src + o, piece, bar, 7);
    spin_until(t += gap);
  }
}

__device__ __forceinline__ void paced_st(uint8_t* dst, uint32_t src, int gap) {
  uint32_t t = clk32();
#pragma unroll 1
  for (uint32_t o = 0; o < 8192; o += 4096) {
    e_s2g(dst + o, src + o, 4096);
    if (o + 4096 < 8192) spin_until(t += gap);
  }
}
__device__ __forceinline__ int block_of(int head, int c) { return c == 2 ? head : 32 + 2 * head + c; }

__device__ __forceinline__ void weight_role(const Params& p, const uint32_t sb, const int warp, const int cta, const int C, const uint32_t E,
                                            const uint8_t* const memg) {
  const int tid = fresh_tid(), lane = tid & 31;
  const int wg = warp >> 2, w = warp & 3;
  uint32_t W[32][4];
  cp_async_wait();
  bar_sync(1, 256);
  load_frags(W, sb, wg, w, lane);
  bar_sync(1, 256);
  if (tid < 128) sts128(sb + M_V + 5 * 2048 + tid * 16, make_uint4(0, 0, 0, 0));
  fence_async_smem();
  cluster_sync();
  if (tid == 0 && cta == 0) GSTAMP(0, 1);
  if (tid == 0) TSTAMP(13, cta, 0);

  const uint32_t rba = mapa(sb, C == 2 ? 0 : 2), rbc = mapa(sb, C == 1 ? 0 : 1);
  const uint32_t MYBAR = M_BAR + 8 * (C < 2 ? B_QK : B_V);
  uint32_t qoff = M_Q + C * 12288 + warp * 256 + lane * 4;
  uint32_t toff = sb + warp * 256 + (lane >> 4) * 2048 + (lane & 15) * 16;
  uint32_t rbar = mapa(sb + M_BAR, min(lane, 2));
  uint32_t sv = sb + M_MEM + lane * 32 + ((lane >> 2) & 3) * 8;
  PIN(qoff); PIN(toff); PIN(rbar); PIN(sv);
  const uint32_t gen0 = (E - 1) * (uint32_t)(NSTEP - 1);
  uint32_t fix = 0;
  const bool sig = w == 0 && lane < 3;
  const int blk = block_of(cta / 3, C);
  const int pk = (blk < 24 ? PAUSE_ : PAUS2_) + (wg ? -PST2_ : PST2_);
  int cand = -1;
  float d[16];
#pragma unroll
  for (int i = 0; i < 16; i++) d[i] = 0.f;
  uint32_t tp[8];
#pragma unroll 1
  for (int T = -1; T < NSTEP; T++) {
    const uint32_t ph = T & 1;
    const uint64_t Z = p.zero << ph;
    const uint32_t zz = p.zero2;
    if (T >= 0) {
      WSTAMP(0); if (C < 2) DLY(8); if (C == 2) DLY(9);
      if (T == 1 && tid == 0) TSTAMP(16, cta, 0);
      const uint64_t db = mkdesc(M_MEM, 128, 256, 0) + Z;
      stmatrix4(toff + M_TST + 8192, tp[0], tp[1], tp[2], tp[3]); stmatrix4(toff + M_TST + 12288, tp[4], tp[5], tp[6], tp[7]);
      if (sig) mbar_arrive_remote(rbar + 8 * B_HBE);
      mbar_wait(BAR(B_LAND), ph);
      WSTAMP(1);
      if (T == 1 && tid == 0) TSTAMP(16, cta, 1);
      const uint32_t gt = gentag(gen0 + T);
      auto old = [&](uint32_t a) { return lds32(a) ^ gt; };
      uint32_t bad = 0;
      bool redo = false, ready = false;
      wg_fence();
      wgmma_rs24<0, 1, 1>(d, W[0], db);
#pragma unroll
      for (int ks = 1; ks < 32; ks++) {
        if (ks == 2) bad |= old(sv + min(warp, 5) * 1024);
        if (ks == 10 || ks == 22) bad |= xo2(lds32(sv + (ks == 10 ? 6 : 15) * 1024 + warp * 1024), lds32(sv + (ks == 10 ? 14 : 23) * 1024), gt);
        if (ks == 6) {
          const uint32_t z5 = DRAIN(toff + M_TST);
          __syncwarp();
          if (lane == 0) mbar_arrive(BAR(B_STG) + z5);
        }
        if (ks == 27) ready = mbar_test(BAR(C < 2 ? B_KFREE : B_VFREE), ph ^ 1) & mbar_test(BAR(B_HA), ph);
        if (ks == 30) redo = bar_or(N_W, 256, T > 0 && (bad & 0x10001u));
        if (ks == 8 || ks == 20) { mbar_wait(BAR(B_LAND + (ks + 4) / 12), ph); WSTAMP(6 + (ks + 4) / 12); wg_fence(); }
        wgmma_rs24<1, 1>(d, W[ks], db + ks * 48);
      }
      wg_commit();
      uint32_t a0 = rba + qoff, a1 = a0 + 128, a2 = rbc + qoff, a3 = a2 + 128, ba = rba + MYBAR, bc = rbc + MYBAR;
      PIN(a0); PIN(a1); PIN(a2); PIN(a3); PIN(ba); PIN(bc);
      if (!ready) {
        mbar_wait(BAR(C < 2 ? B_KFREE : B_VFREE), ph ^ 1);
        if (T < NSTEP - 1) mbar_wait(BAR(B_HA), ph);
      }
      wg_wait<0>(); reg_fence(d);
      if (__builtin_expect(redo, 0)) {
        auto stale = [&]() { return __any_sync(~0u, (old(sv + warp * 3072) | old(sv + warp * 3072 + 1024) | old(sv + warp * 3072 + 2048)) & 0x10001u); };
        auto fetch = [&](int r) {
          e_expect(BAR(B_FIX + warp), 3072);
          e_g2s(sb + M_MEM + warp * 3072, memg + warp * 8192 + ((uni(lds32(sb + M_NEAR + warp * 4)) ^ r) & 1) * 4096, 3072, BAR(B_FIX + warp));
        };
        bool late = stale();
        if (late) fetch(0);
        constexpr uint64_t dc = mkdesc(M_MEM, 128, 256, 0);
#pragma unroll
        for (int ks = 0; ks < 32; ks++) {
          if (ks % 12 == 0) {
            if (ks) { wg_commit(); wg_wait<0>(); reg_fence(d); }
            if (warp / 3 == ks / 12) {
              for (int guard = 0; late; guard++) {
                mbar_wait(BAR(B_FIX + warp), fix); fix ^= 1;
                late = stale();
                if (late) fetch(guard + 1);
                if (guard > (1 << 20)) TRAP();
              }
            }
            bar_sync(N_W, 256);
            wg_fence();
          }
          if (ks == 0) wgmma_rs24<0, 1, 1>(d, W[0], dc); else wgmma_rs24<1, 1>(d, W[ks], dc + ks * 48);
        }
        wg_commit();
        wg_wait<0>(); reg_fence(d);
      }
      WSTAMP(2); DLY(1);
      if (T == 0 && tid == 0) TSTAMP(13, cta, 2);
      if (T == 1 && tid == 0) TSTAMP(16, cta, 2);
      uint32_t lo[3], hi[3];
#pragma unroll
      for (int j = 0; j < 3; j++) { lo[j] = pack2(d[4 * j], d[4 * j + 1]); hi[j] = pack2(d[4 * j + 2], d[4 * j + 3]); }
      if (__builtin_expect(T == 0, 0)) { sts32(sb + M_M0 + tid * 8, lo[0]); sts32(sb + M_M0 + tid * 8 + 4, hi[0]); }
      if (__builtin_expect(cand >= 0, 0)) {
        if (T == LAG) { lo[1] = lds32(sb + M_M0 + tid * 8); hi[1] = lds32(sb + M_M0 + tid * 8 + 4); }
        if (C < 2) { st_async32(a0 + 5 * 2048, lo[2], ba); st_async32(a1 + 5 * 2048, hi[2], ba); }
        else { sts32(sb + qoff + 5 * 2048, lo[2]); sts32(sb + qoff + 5 * 2048 + 128, hi[2]); }
        lo[2] = lo[1]; hi[2] = hi[1];
      }
      uint32_t z5;
      if (C == 0) {
        sts32(sb + qoff, lo[0]); sts32(sb + qoff + 128, hi[0]); z5 = DRAIN(sb + qoff);
        st_async32(a0, lo[2], ba); st_async32(a1, hi[2], ba); st_async32(a2, lo[1], bc); st_async32(a3, hi[1], bc);
      } else if (C == 1) {
        sts32(sb + qoff, lo[1]); sts32(sb + qoff + 128, hi[1]); z5 = DRAIN(sb + qoff);
        st_async32(a0, lo[2], ba); st_async32(a1, hi[2], ba); st_async32(a2, lo[0], bc); st_async32(a3, hi[0], bc);
      } else {
        sts32(sb + qoff, lo[2]); sts32(sb + qoff + 128, hi[2]); z5 = DRAIN(sb + qoff);
        st_async32(a0, lo[0], ba); st_async32(a1, hi[0], ba); st_async32(a2, lo[1], bc); st_async32(a3, hi[1], bc);
      }
      __syncwarp();
      if (lane == 0) { mbar_arrive(sb + MYBAR + z5); if (w == 3) mbar_arrive(BAR(B_SS)); }
      if (T == NSTEP - 1) break;
    }
    {
      const uint64_t dh = mkdesc(M_H, 16, 1024, 1) + Z;
      if (T + 2 < NSEG) {
        if (T < 0) mbar_wait(BAR(B_HA), ph);
        WSTAMP(3);
        wg_fence();
        wgmma_rs32<0, 0, 1>(d, W[0], dh);
#pragma unroll
        for (int ks = 1; ks < EA; ks++) {
          if (ks == E1) { wg_commit(); if (T >= 0) bar_sync(N_GO2, 384); wg_fence(); }
          wgmma_rs32<1, 0>(d, W[ks], dh + (ks >> 2) * 256 + (ks & 3) * 2);
        }
        wg_commit();
        mbar_wait(BAR(B_HB), ph);
        wg_wait<0>();
        if (sig) mbar_arrive_remote(rbar + 8 * B_HAE);
        WSTAMP(4);
        if (T == 0 && tid == 0) TSTAMP(17, cta, 0);
        if (T >= 0) bar_sync(N_GO3, 384);
        DLY(4);
        if (wg == 1) bar_sync(N_W, 256);
        wg_fence();
#pragma unroll
        for (int ks = EA; ks < 32; ks++) wgmma_rs32<1, 0>(d, W[ks], dh + (ks >> 2) * 256 + (ks & 3) * 2);
        wg_commit();
        if (wg == 0) bar_arrive(N_W, 256);
        mbar_wait(BAR(B_TFREE), ph ^ 1);
        wg_wait<0>(); reg_fence(d);
      } else {
        bar_sync(N_GO2, 384);
        mbar_wait(BAR(B_HB), ph);
        if (sig) mbar_arrive_remote(rbar + 8 * B_HAE);
        bar_sync(N_GO3, 384);
        mbar_wait(BAR(B_TFREE), ph ^ 1);
      }
#pragma unroll
      for (int i = 0; i < 8; i++) { tp[i] = pack2(d[2 * i], d[2 * i + 1]); PIN(tp[i]); }
      const uint32_t t1 = toff + (C == 0 && !ph ? M_Q + 2048 : M_TST);
      auto staged = [&]() {
        const uint32_t z5 = DRAIN(t1);
        __syncwarp();
        if (lane == 0) mbar_arrive(BAR(B_STG1) + z5);
      };
      if (T < 0 || (T + 2 >= LAG && T + 2 < NSTEP)) {
        wg_fence();
        wgmma_rs32<0, 0, 1>(d, W[0], dh + 2048);
        stmatrix4(t1, tp[0], tp[1], tp[2], tp[3]); stmatrix4(t1 + 4096, tp[4], tp[5], tp[6], tp[7]);
#pragma unroll
        for (int ks = 1; ks < 32; ks++) {
          if (ks == 5) staged();
          if (ks == PAUSE_ - PST2_ || ks == PAUSE_ + PST2_ || ks == PAUS2_ - PST2_ || ks == PAUS2_ + PST2_) {
            wg_commit();
            if (T >= 0 && ks == pk) bar_sync(N_GO4, 384);
            wg_fence();
          }
          wgmma_rs32<1, 0>(d, W[ks], dh + 2048 + (ks >> 2) * 256 + (ks & 3) * 2);
        }
        wg_commit();
      } else {
        stmatrix4(t1, tp[0], tp[1], tp[2], tp[3]); stmatrix4(t1 + 4096, tp[4], tp[5], tp[6], tp[7]);
        staged();
        bar_sync(N_GO4, 384);
      }
      if (T >= 0) cand = __shfl_sync(~0u, (int)lds32(sb + M_CAND + ((T + 1) & 3) * 4), 0);
      wg_wait<0>(); reg_fence(d);
      if (T >= 0) WSTAMP(6);
      if (T < 0 && tid == 0) TSTAMP(13, cta, 1);
#pragma unroll
      for (int i = 0; i < 8; i++) tp[i] = pack2(d[2 * i], d[2 * i + 1]);
    }
  }
  cluster_sync();
  if (tid == 0 && cta == 0) GSTAMP(0, 5);
}

__device__ __forceinline__ void attn_role(const Params& p, const uint32_t sb, const int w, const int cta, const int head, const int C, const uint32_t E,
                                          uint8_t* const part, uint8_t* const memg) {
  const int tid = fresh_tid(), lane = tid & 31;
  const int g = lane >> 2, t = lane & 3, blk = block_of(head, C);
  uint32_t tag = ((E - 1) * (uint32_t)(NSTEP - 1)) & 1;
  uint4 m0[2][2];
  load_mem0(m0[0], w * 64, lane, p.mem0); load_mem0(m0[1], w * 64 + 256, lane, p.mem0);
  cluster_sync();
#pragma unroll
  for (int k = 0; k < 2; k++) {
#pragma unroll 1
    for (int i = 0; i < 6; i++) sts128(sb + M_MEM + (w + 4 * k) * 3072 + lane * 16 + i * 512, make_uint4(0, 0, 0, 0));
    __syncwarp();
#pragma unroll
    for (int i = 0; i < 2; i++) sts128(sb + M_MEM + ((w + 4 * k) * 4 + (lane >> 4) + 2 * i) * 768 + (lane & 15) * 16, m0[k][i]);
  }
  fence_async_smem();
  bar_sync(N_AG, 128);
  if (w == 3 && lane < 3) mbar_arrive(BAR(B_LAND + lane));
  if (lane == 0) {
    if (w == 0) TSTAMP(15, cta, 0);
    sts32(sb + M_PT + w * 4, probe(part + blk * 16384 + w * 4096, 3));
    if (w == 0) TSTAMP(15, cta, 1);
  }
  bar_sync(N_AG, 128);
  const uint32_t inear = lds32(sb + M_PT + (w >> 1) * 8 + 4) < lds32(sb + M_PT + (w >> 1) * 8);
  if (lane == 0 && !(w & 1)) st_rlx(&G.f_choice[blk][w >> 1], (E << 1) | inear);
  if (w == 0) TSTAMP(15, cta, 2);
  uint32_t nb;
  {
    const int i = min(lane >> 1, C < 2 ? 8 : 5);
    const int r = ((i / 3 * 3 + C) * 4 + w) * 3 + i % 3;
    int guard = 0; uint32_t cw;
    while (__any_sync(~0u, ((cw = ld_rlx(&G.f_choice[r][lane & 1])) >> 1) != (E & 0x7FFFFFFFu))) { if (++guard > (1 << 22)) TRAP(); }
    nb = __ballot_sync(~0u, cw & 1) >> (lane >> 4);
    if (w == 0) TSTAMP(15, cta, 3);
  }
  bar_sync(N_AG, 128);
  const uint32_t pt0 = sb + M_PT + (tid & 127) * 16;
  {
    const uint32_t po = (C * 4 + w) * 49152 + (lane >> 4) * 8192 + head * 128 + (lane & 15) * 8;
    const uint8_t* in = part + (blk * 16384 + (w >> 1) * 8192 + inear * 4096 + (w & 1) * 64 + (lane >> 3) * 128 + (lane & 7) * 8);
    const uint8_t* outp = memg + ((blk / 12) * 8192 + (blk % 12) * 256 + w * 64 + (lane >> 4) * 4096 + (lane & 4) * 8 + (lane & 8) * 2 + (lane & 3) * 4);
#pragma unroll
    for (int i = 0; i < 12; i++) {
      const int j = i / 4 * 3 + (i & 3);
      const uint8_t* a = (i & 3) < 3 ? part + (po + i / 4 * 589824 + (i & 3) * 16384 + ((nb >> (2 * j)) & 1) * 4096) : i == 11 ? in : outp;
      asm volatile("st.shared.u64 [%0], %1;" :: "r"(pt0 + (i >> 1) * 2048 + (i & 1) * 8), "l"(a) : "memory");
    }
  }
  const int xd = __shfl_sync(~0u, XDLY_ + (blk < 24 ? 0 : blk < 60 ? X1_ : X2_), 0);
  const uint32_t rba = mapa(sb, C == 2 ? 0 : 2), rbc = mapa(sb, C == 1 ? 0 : 1);
  uint32_t vis = vis_bits(8 + 8 * w + g, t);
  uint32_t ln = lane;
#pragma unroll
  for (int i = 0; i < SALT_; i++) ln += lds32(sb + M_ZERO);
  PIN(vis); PIN(ln);
  if (tid == 256 && C == 0) st_rlx(&G.f_loaded[head], E);
  uint32_t fa[8][4];
#pragma unroll
  for (int ks = 0; ks < 8; ks++) ldmatrix4_t(fa[ks], sb + M_WO + 32768 + w * 256 + (lane >> 4) * 1024 + (lane & 15) * 16 + ks * 2048);
  if (w == 0) TSTAMP(14, cta, 0);
#pragma unroll 1
  for (int T = 0; T < NSTEP; T++) {
    const uint32_t ph = T & 1;
    const uint32_t zz = uni(lds32(sb + M_ZERO));
    const bool more = T < NSTEP - 1;
    const float sc = 0.08838834764831845f * 1.4426950408889634f;
    tag ^= 1;
    float s[20];
    const uint8_t* in; int cnext = -1; uint32_t tx; bool synced;
    float x[10], tm, ts;
    uint32_t pt[5];
    auto tok_max = [&]() {
      PIN(vis);
      x[0] = s[2]; x[1] = s[3];
#pragma unroll
      for (int i = 0; i < 8; i++) x[2 + i] = (vis >> i & 1) ? s[4 * (i / 2 + 1) + 2 + (i & 1)] : -INFINITY;
      tm = fmaxf(fmaxf(fmaxf(fmaxf(x[0], x[1]), fmaxf(x[2], x[3])), fmaxf(fmaxf(x[4], x[5]), fmaxf(x[6], x[7]))), fmaxf(x[8], x[9]));
      HOLD(7, __float_as_uint(tm));
    };
    auto tok_exp1 = [&]() {
      tm = fmaxf(tm, __shfl_xor_sync(~0u, tm, 1));
      tm = fmaxf(tm, __shfl_xor_sync(~0u, tm, 2));
      const float b = -tm * sc;
#pragma unroll
      for (int i = 0; i < 10; i++) x[i] = fmaf(x[i], sc, b);
      HOLD(10, __float_as_uint(x[9]));
    };
    auto tok_exp2 = [&]() {
#pragma unroll
      for (int i = 0; i < 10; i++) x[i] = ex2(x[i]);
      ts = (((x[0] + x[1]) + (x[2] + x[3])) + ((x[4] + x[5]) + (x[6] + x[7]))) + (x[8] + x[9]);
#pragma unroll
      for (int k = 0; k < 5; k++) pt[k] = pack2(x[2 * k], x[2 * k + 1]);
      HOLD(8, __float_as_uint(ts));
    };
    {
      uint32_t q[8][4];
      auto load_q = [&](uint32_t a, int h) {
#pragma unroll
        for (int k2 = 0; k2 < 4; k2++) {
          uint32_t r[4];
          ldmatrix4_t(r, a + k2 * 512);
          q[2 * k2][h] = r[0]; q[2 * k2][h + 2] = r[1]; q[2 * k2 + 1][h] = r[2]; q[2 * k2 + 1][h + 2] = r[3];
        }
      };
      PIN(ln);
      const uint32_t qa = sb + M_Q + ln * 16, qt = qa + w * 2048 + (C == 0 && ph ? M_TST - M_Q : 2048);
      const int cand = C == 2 ? (int)uni(lds32(sb + M_CAND + (T & 3) * 4)) : -1;
      mbar_wait(BAR(B_TOK), ph);
      load_q(qt, 1);
      mbar_wait(BAR(B_QK), ph);
      ASTAMP(0);
      if (T == 0 && w == 0) TSTAMP(13, cta, 3);
      if (__builtin_expect(cand >= 0, 0)) {
        mbar_wait(BAR(B_V), ph);
        PIN(ln);
        const int e = w * 32 + ln;
#pragma unroll
        for (int i = 0; i < 3; i++) {
          const uint32_t v = lds32(sb + M_Q + i * 12288 + 5 * 2048 + e * 16 + 4);
          asm volatile("st.shared.u16 [%0], %1;" :: "r"(sb + M_Q + i * 12288 + (1 + (cand >> 3)) * 2048 + e * 16 + (cand & 7) * 2), "h"((unsigned short)v) : "memory");
        }
        fence_async_smem();
        bar_sync(N_AG, 128);
        load_q(qt, 1);
      }
      constexpr uint64_t dk = mkdesc(M_K, 128, 2048, 0);
      fence_async_smem();
      uint32_t r[4][4];
#pragma unroll
      for (int k2 = 0; k2 < 4; k2++) ldmatrix4_t(r[k2], qa + k2 * 512);
#pragma unroll
      for (int k2 = 0; k2 < 4; k2++) {
        q[2 * k2][0] = r[k2][0]; q[2 * k2][2] = r[k2][1]; q[2 * k2 + 1][0] = r[k2][2]; q[2 * k2 + 1][2] = r[k2][3];
        if (k2 & 1) {
          wg_fence();
#pragma unroll
          for (int ks = 2 * k2 - 2; ks < 2 * k2 + 2; ks++) { if (ks == 0) wgmma_rs40<0, 1>(s, q[0], dk); else wgmma_rs40<1, 1>(s, q[ks], dk + ks * 16); }
        }
      }
      wg_commit();
    }
    if (more) {
      uint32_t v[5][4];
      PIN(ln);
      const uint32_t va = sb + M_V + w * 512 + ((ln >> 3) & 1) * 128 + (ln >> 4) * 2048 + (ln & 7) * 16;
      const uint32_t ooff = M_OM + w * 1536 + C * 256 + ln * 4;
      mbar_wait(BAR(B_V), ph);
      wg_wait<0>(); reg_fence(s);
      if (ln < 3) mbar_arrive_remote(mapa(BAR(B_KFREE), ln));
      ldmatrix4(v[0], va); ldmatrix4(v[1], va + 256); ldmatrix4(v[2], va + 4096); ldmatrix4(v[3], va + 4096 + 256);
      ldmatrix4(v[4], sb + M_V + 8192 + w * 512 + ln * 16);
      ASTAMP(1); DLY(2);
      float m = fmaxf(fmaxf(fmaxf(fmaxf(s[0], s[1]), fmaxf(s[4], s[5])), fmaxf(fmaxf(s[8], s[9]), fmaxf(s[12], s[13]))), fmaxf(s[16], s[17]));
      m = fmaxf(m, __shfl_xor_sync(~0u, m, 1));
      m = fmaxf(m, __shfl_xor_sync(~0u, m, 2));
      const float b = -m * sc;
      uint32_t pm[5];
#pragma unroll
      for (int j = 0; j < 5; j++) pm[j] = pack2(ex2(fmaf(s[4 * j], sc, b)), ex2(fmaf(s[4 * j + 1], sc, b)));
      float o0[4] = {0.f, 0.f, 0.f, 0.f}, o1[4] = {0.f, 0.f, 0.f, 0.f}, l[4] = {0.f, 0.f, 0.f, 0.f};
      const uint32_t one[4] = {0x3f803f80u, 0x3f803f80u, 0x3f803f80u, 0x3f803f80u};
      hmma16(l, one, pm[0], pm[1]); hmma16(o0, v[0], pm[0], pm[1]); hmma16(o1, v[1], pm[0], pm[1]);
      hmma16(l, one, pm[2], pm[3]); hmma16(o0, v[2], pm[2], pm[3]); hmma16(o1, v[3], pm[2], pm[3]);
      hmma8(l, one[0], one[1], pm[4]); hmma8(o0, v[4][0], v[4][1], pm[4]); hmma8(o1, v[4][2], v[4][3], pm[4]);
      const float r0 = rcp(l[0]), r1 = rcp(l[1]);
      const uint32_t u0 = pack2(o0[0] * r0, o0[1] * r1), u1 = pack2(o0[2] * r0, o0[3] * r1), u2 = pack2(o1[0] * r0, o1[1] * r1), u3 = pack2(o1[2] * r0, o1[3] * r1);
      constexpr uint32_t OB = M_BAR + 8 * B_OM;
      const uint32_t a0 = rba + ooff, a1 = rbc + ooff;
      st_async32(a0, u0, rba + OB); st_async32(a1, u0, rbc + OB);
      st_async32(a0 + 128, u1, rba + OB); st_async32(a1 + 128, u1, rbc + OB);
      st_async32(a0 + 768, u2, rba + OB); st_async32(a1 + 768, u2, rbc + OB);
      st_async32(a0 + 896, u3, rba + OB); st_async32(a1 + 896, u3, rbc + OB);
      bar_arrive(N_GO2, 384);
      sts32(sb + ooff, u0); sts32(sb + ooff + 128, u1); sts32(sb + ooff + 768, u2); sts32(sb + ooff + 896, u3);
      ASTAMP(2);
      uint32_t fb[8][4];
      const uint32_t wa = sb + M_WO + 16384 + w * 256 + (ln >> 4) * 1024 + (ln & 15) * 16 + zz;
      ldmatrix4_t(fb[0], wa);
      SCHED(3);
#pragma unroll
      for (int ks = 1; ks < 8; ks++) {
        ldmatrix4_t(fb[ks], wa + ks * 2048);
        if (ks == 7) { __syncwarp(); if (ln == 0) mbar_arrive(BAR(B_OM) + (fb[0][0] & zz)); }
      }
      if (blk % 3 == 2) cnext = (int)uni(lds32(sb + M_CAND + ((T + 1) & 3) * 4));
      {
        float d[12], e[12];
        constexpr uint64_t ob = mkdesc(M_OM, 128, 256, 0);
        uint8_t* q[3][3];
        auto addr = [&](int i) {
          asm volatile("ld.shared.v2.u64 {%0,%1}, [%2];" : "=l"(q[i][0]), "=l"(q[i][1]) : "r"(pt0 + i * 4096) : "memory");
          if (i < 2) asm volatile("ld.shared.u64 %0, [%1];" : "=l"(q[i][2]) : "r"(pt0 + i * 4096 + 2048) : "memory");
          else asm volatile("ld.shared.v2.u64 {%0,%1}, [%2];" : "=l"(q[i][2]), "=l"(in) : "r"(pt0 + i * 4096 + 2048) : "memory");
        };
        auto put = [&](const float* d, int i) {
          st_rlx64(q[i][0], (pack2(d[0], d[1]) & ~1u) | tag, pack2(d[2], d[3]));
          st_rlx64(q[i][1], (pack2(d[4], d[5]) & ~1u) | tag, pack2(d[6], d[7]));
          st_rlx64(q[i][2], (pack2(d[8], d[9]) & ~1u) | tag, pack2(d[10], d[11]));
        };
        addr(0); addr(1);
        SCHED(6);
        tok_max();
        ASTAMP(3);
        mbar_wait(BAR(B_OM), ph);
        ASTAMP(4); DLY(3);
        constexpr uint64_t w0 = mkdesc(M_WO, 1024, 128, 0);
        float (&f)[12] = d;
        wg_fence();
        wgmma_ss24<0, 1, 1>(d, w0, ob);
#pragma unroll
        for (int ks = 1; ks < 8; ks++) wgmma_ss24<1, 1, 1>(d, w0 + ks * 128, ob + ks * 48);
        wg_commit();
        wgmma_rs24<0, 1>(e, fb[0], ob);
#pragma unroll
        for (int ks = 1; ks < HAND_; ks++) wgmma_rs24<1, 1>(e, fb[ks], ob + ks * 48);
        wg_commit();
        wg_wait<1>(); reg_fence(d);
        put(d, 0);
        addr(2);
        SCHED(4);
        ASTAMP(5);
        wg_fence();
#pragma unroll
        for (int ks = HAND_; ks < 8; ks++) wgmma_rs24<1, 1>(e, fb[ks], ob + ks * 48);
        wg_commit();
        wgmma_rs24<0, 1, 1>(f, fa[0], ob);
#pragma unroll
        for (int ks = 1; ks < HAND_; ks++) wgmma_rs24<1, 1>(f, fa[ks], ob + ks * 48);
        wg_commit();
        wg_wait<1>(); reg_fence(e);
        put(e, 1);
        SCHED(5);
        if (C < 2) {
          wg_fence();
#pragma unroll
          for (int ks = HAND_; ks < 8; ks++) wgmma_rs24<1, 1>(f, fa[ks], ob + ks * 48);
          wg_commit();
        }
        synced = __all_sync(~0u, mbar_test(BAR(B_SYNC), ph));
        tx = uni(lds32(sb + M_BASE + ph * 4)) + xd;
        wg_wait<0>(); reg_fence(f);
        if (C < 2) put(f, 2);
        bar_arrive(N_GO3, 384);
        ASTAMP(6);
        if (T == 0 && w == 0) TSTAMP(14, cta, 1);
      }
    } else {
      mbar_wait(BAR(B_V), ph);
      wg_wait<0>(); reg_fence(s);
      tok_max();
    }
    uint2 v[8];
    auto poll = [&](uint2* v) {
      v[0] = ld_rlx64<0>(in); v[1] = ld_rlx64<512>(in); v[2] = ld_rlx64<1024>(in); v[3] = ld_rlx64<1536>(in);
      v[4] = ld_rlx64<2048>(in); v[5] = ld_rlx64<2560>(in); v[6] = ld_rlx64<3072>(in); v[7] = ld_rlx64<3584>(in);
    };
    uint8_t* outp;
    asm volatile("ld.shared.u64 %0, [%1];" : "=l"(outp) : "r"(pt0 + 2048 + 8) : "memory");
    const uint32_t itag = gentag((E - 1) * (uint32_t)(NSTEP - 1) + T + 1);
    const bool sum = more && cnext < 0;
    if (more) {
      if (!synced) { mbar_wait(BAR(B_SYNC), ph); tx = uni(lds32(sb + M_BASE + ph * 4)) + xd; }
      ASTAMP(7);
      if (__builtin_expect(cnext >= 0, 0)) {
        const unsigned long long* hp = (const unsigned long long*)&G.hc[T + 1 - LAG][0] + ((blk / 3) * 8 + 2 * w + ((ln >> 2) & 1));
        unsigned long long v0; int guard = 0;
        while (v0 = ld_rlxu64(hp), !__all_sync(~0u, (uint32_t)(v0 >> 32) == E)) { if (++guard > (1 << 22)) TRAP(); }
        st_rlx((uint32_t*)outp, (ln & 3) == 1 ? ((uint32_t)v0 >> ((ln & 8) * 2)) & 0xffffu : (ln & 1) ? 0u : itag);
      } else {
        spin_until(tx);
        ASTAMP(8);
      }
    }
    if (!more) in = part;
    poll(v);
    auto late = [&](const uint2* v) {
      return __any_sync(~0u, (or3(xo2(v[0].x, v[1].x, tag), xo2(v[2].x, v[3].x, tag), xo2(v[4].x, v[5].x, tag)) | xo2(v[6].x, v[7].x, tag)) & 1u);
    };
    tok_exp1(); tok_exp2();
    auto reduce = [&]() {
      if (sum) {
        ASTAMP(9); if (blk < 24) DLY(5); if (blk >= 24 && blk < 60) DLY(6); if (blk >= 60) DLY(7);
        int guard = 0;
        while (late(v)) {
          if (++guard > (1 << 22)) TRAP();
          poll(v);
        }
#pragma unroll
        for (int i = 0; i < 4; i++) { v[i].x = add2(v[i].x, v[i + 4].x); v[i].y = add2(v[i].y, v[i + 4].y); }
        const bool hi = ln & 8;
        const uint32_t x0 = add2(v[0].x, v[1].x), x1 = add2(v[2].x, v[3].x), y0 = add2(v[0].y, v[1].y), y1 = add2(v[2].y, v[3].y);
        const uint32_t m0 = hi ? y0 : x0, m1 = hi ? y1 : x1;
        const uint32_t n0 = __shfl_xor_sync(~0u, hi ? x0 : y0, 8), n1 = __shfl_xor_sync(~0u, hi ? x1 : y1, 8);
        float k0 = (blo(m0) + blo(m1)) + (blo(n0) + blo(n1)), k1 = (bhi(m0) + bhi(m1)) + (bhi(n0) + bhi(n1));
        k0 += __shfl_xor_sync(~0u, k0, 16); k1 += __shfl_xor_sync(~0u, k1, 16);
        st_rlx((uint32_t*)outp, (ln & 1) ? pack2(k0, k1) : pack2_tag(k0, k1, itag));
        ASTAMP(10);
        if (T == 0 && w == 0) TSTAMP(14, cta, 2);
        CSTAMP(12 + w, (clk() & ~15u) | min(guard + 1, 15));
      }
      if (more) bar_arrive(N_GO4, 384);
    };
    reduce(); DLY(10);
    {
      PIN(ln);
      const uint32_t oa = sb + M_OST + w * 128 + (ln >> 3) * 512 + (ln & 7) * 16;
      const uint32_t a[3][4] = {{0, pt[0], 0, pt[1]}, {0, pt[2], 0, pt[3]}, {0, pt[4], 0, 0}};
      constexpr uint64_t dv = mkdesc(M_V, 2048, 128, 0);
#pragma unroll 1
      for (int h = 0; h < 2; h++) {
        float o[32];
        const uint64_t dh = dv + (uint64_t)(h * 64);
        wg_fence();
        wgmma_rs64<0, 0>(o, a[0], dh); wgmma_rs64<1, 0>(o, a[1], dh + 256); wgmma_rs64<1, 0>(o, a[2], dh + 512);
        wg_commit();
        if (h == 0) {
          ts += __shfl_xor_sync(~0u, ts, 1);
          ts += __shfl_xor_sync(~0u, ts, 2);
          ts = rcp(ts);
          mbar_wait(BAR(B_OFREE), ph ^ 1);
        }
        wg_wait<0>(); reg_fence(o);
        if (h == 1 && ln < 3) mbar_arrive_remote(mapa(BAR(B_VFREE), ln));
#define OT(i) pack2(o[4 * (i) + 2] * ts, o[4 * (i) + 3] * ts)
        stmatrix4(oa + h * 4096, OT(0), OT(1), OT(2), OT(3));
        stmatrix4(oa + h * 4096 + 2048, OT(4), OT(5), OT(6), OT(7));
      }
      const uint32_t z5 = DRAIN(oa);
      __syncwarp();
      if (ln == 0) mbar_arrive(BAR(B_OST) + z5);
      ASTAMP(11);
    }
  }
}

__global__ void __cluster_dims__(3, 1, 1) __launch_bounds__(512, 1) main_kernel(Params p) {
  extern __shared__ __align__(1024) uint8_t sm[];
  const uint32_t sb = smem_u32(sm);
  if ((sb & 0xFFFFFFu) != SBASE) TRAP();
  asm volatile("griddepcontrol.launch_dependents;");
  const int warp = __shfl_sync(~0u, threadIdx.x >> 5, 0);
  const int cta = blockIdx.x, head = cta / 3, c = cta % 3;
  const uint32_t E = __shfl_sync(~0u, *(volatile uint32_t*)&g_epoch + 1, 0);
  uint8_t* const part = G.xch;
  uint8_t* const memg = part + 96 * 16384;

  if (threadIdx.x == 0 && cta == 0) GSTAMP(0, 0);
  if (threadIdx.x < B_NUM) {
    const int i = threadIdx.x;
    const uint32_t cnt = i == B_STG || i == B_STG1 ? 8 : i == B_OST ? 4 : i == B_HAE || i == B_HBE ? 6 : i == B_KFREE || i == B_VFREE ? 12 : i == B_SS ? 2 : i == B_OM ? 5 :
                         i == B_QK ? (c < 2 ? 9 : 1) : i == B_V ? (c < 2 ? 1 : 9) : 1;
    mbar_init(BAR(i), cnt);
    if (i == B_HA || i == B_HB || i == B_STG || i == B_HAE || i == B_HBE || i == B_TFREE)
      asm volatile("mbarrier.arrive.shared::cta.b64 _, [%0], %1;" :: "r"(BAR(i)), "r"(cnt) : "memory");
    asm volatile("fence.mbarrier_init.release.cluster;" ::: "memory");
  }
  if (warp < 8) {
    const int tid = threadIdx.x;
    uint4 wa[6], wb[6];
#pragma unroll
    for (int i = 0; i < 6; i++) {
      const int mi = i >> 1, e = (tid >> 2) + (i & 1) * 64;
      const uint4* src = (const uint4*)(p.wo + (size_t)(head * 128 + e) * 512 + min(3 * mi + c, 7) * 64 + (tid & 3) * 16);
      wa[i] = __ldg(src); wb[i] = __ldg(src + 1);
    }
    stage_weights(sb, (c == 0 ? p.wq : c == 1 ? p.wk : p.wv) + head * 128, 4096, tid, 256);
#pragma unroll
    for (int i = 0; i < 6; i++) {
      const int mi = i >> 1, e = (tid >> 2) + (i & 1) * 64;
      const uint4 a = wa[i], b = wb[i];
      const uint32_t dst = sb + M_WO + mi * 16384 + (e >> 3) * 1024 + (tid & 3) * 256 + (e & 7) * 16;
      sts128(dst, make_uint4(__byte_perm(a.x, a.y, 0x5410), __byte_perm(a.z, a.w, 0x5410), __byte_perm(b.x, b.y, 0x5410), __byte_perm(b.z, b.w, 0x5410)));
      sts128(dst + 128, make_uint4(__byte_perm(a.x, a.y, 0x7632), __byte_perm(a.z, a.w, 0x7632), __byte_perm(b.x, b.y, 0x7632), __byte_perm(b.z, b.w, 0x7632)));
    }
  } else {
    const int i0 = threadIdx.x - 256;
    const uint32_t tag0 = ((E - 1) * (uint32_t)(NSTEP - 1)) & 1;
    for (int i = i0; i < 1024; i += 256) *(uint4*)(part + block_of(head, c) * 16384 + i * 16) = make_uint4(tag0, 0, tag0, 0);
    if (i0 < 16) *(uint32_t*)(memg + i0 * 4096 + 3968) = 0;
    if (i0 < 2) st_rlx(&G.f_choice[block_of(head, c)][i0], 0);
    if (i0 < 8) st_rlx64(&G.sync[i0 >> 2][cta][i0 & 3], 0, 0);
    __threadfence();
    if (i0 < 12) sts32(sb + M_ZERO + i0 * 4, 0);
    if (i0 < 2) { sts32(sb + M_BASE + i0 * 4, clk32() - 65536); sts32(sb + M_BAS2 + i0 * 4, clk32() - 65536); sts32(sb + M_CAND + i0 * 4, (uint32_t)-1); }
  }

  if (warp < 8) {
    asm volatile("setmaxnreg.inc.sync.aligned.u32 176;");
    weight_role(p, sb, warp, cta, c, E, memg);
  } else if (warp < 12) {
    asm volatile("setmaxnreg.inc.sync.aligned.u32 136;");
    attn_role(p, sb, warp - 8, cta, head, c, E, part, memg);
    cluster_sync();
  } else {
    asm volatile("setmaxnreg.dec.sync.aligned.u32 24;");
    const int tid = fresh_tid(), lane = tid & 31;
    const int w = warp - 12;
    cluster_sync();
    if (w != 2) {
      const int tl = w == 0 ? c : w == 1 ? 2 + c : 5 + c;
      int near = 0;
      if (lane == 0) { const int t0 = probe(memg + tl * 8192, 3); near = probe(memg + tl * 8192 + 4096, 3) < t0; }
      near = uni(near);
      if (lane < 3) asm volatile("st.shared::cluster.u32 [%0], %1;" :: "r"(mapa(sb + M_NEAR + tl * 4, lane)), "r"(near) : "memory");
      __syncwarp();
    }
    if (w == 0) {
      int yadj = 0, dmin = 1 << 20; uint32_t prev = 0; bool cprev = false;
      uint32_t s1 = (2 + c) * 8192, s2 = (5 + c) * 8192;
#pragma unroll 1
      for (int T = 0; T < NSTEP - 1; T++) {
        const uint32_t ph = T & 1;
        mbar_wait(BAR(B_SS), ph);
        const uint32_t cq = clk();
        const uint32_t g0 = (uint32_t)gtime64(); uint32_t g1, ce;
        do { g1 = (uint32_t)gtime64(); ce = clk(); } while (g1 == g0);
        const uint32_t tn = g1 * 8 - (((ce - cq) * 37u) >> 3), id = E * 128u + T;
        if (lane < 4) st_rlx64(&G.sync[ph][cta][lane], tn, id);
        if (lane < 3) mbar_expect(BAR(B_LAND + lane), lane ? 9216 : 6144);
        if (T == 0) { s1 += uni(lds32(sb + M_NEAR + (2 + c) * 4)) * 4096; s2 += uni(lds32(sb + M_NEAR + (5 + c) * 4)) * 4096; }
        wait_until(cq + SDLY_);
        int guard = 0; unsigned long long v0, v1, v2;
        for (;;) {
          v0 = ld_rlxu64(G.sync[ph][lane]); v1 = ld_rlxu64(G.sync[ph][lane + 32]); v2 = ld_rlxu64(G.sync[ph][lane + 64]);
          if (__all_sync(~0u, (uint32_t)(v0 >> 32) == id && (uint32_t)(v1 >> 32) == id && (uint32_t)(v2 >> 32) == id)) break;
          if (++guard > (1 << 22)) TRAP();
        }
        const bool cnd = (int)uni(lds32(sb + M_CAND + (T & 3) * 4)) >= 0;
        const int dl = __reduce_max_sync(~0u, max(max((int)((uint32_t)v0 - tn), (int)((uint32_t)v1 - tn)), (int)((uint32_t)v2 - tn)));
        const uint32_t base = uni(cq + ((min(dl, 8 * 4096) * 7) >> 5)) + (T == 0 ? SLOW0_ : T == 1 ? SLOW1_ : 0) +
                              (cnd ? CDLY_ : 0) - (T + 2 < NSEG ? 0 : BOFF_);
        const int dur = (int)(base - prev);
        if (!cnd && !cprev) {
          yadj = T > 2 && dur > dmin + 700 ? min(yadj + YUP_, 400) : max(yadj - YDN_, 0);
          if (T > 1) dmin = min(dmin + 20, dur);
        }
        prev = base; cprev = cnd;
        if (lane == 0) { sts32(sb + M_BASE + ph * 4, base + ((yadj * XFR_) >> 2)); sts32(sb + M_BAS2 + ph * 4, base + yadj); mbar_arrive(BAR(B_SYNC)); }
        CSTAMP(0, base); CSTAMP(1, clk());
        if (T == 0) TSTAMP(16, cta, 3);
        const uint32_t ts = base + YDLY_ + yadj - (T + 2 >= LAG && T + 2 < NSEG ? 0 : YOFF_);
        const uint8_t* const t0 = memg + uni(lds32(sb + M_NEAR)) * 4096, * const t1 = memg + 8192 + uni(lds32(sb + M_NEAR + 4)) * 4096;
        if (T == 0) {
          const uint32_t gt = gentag((E - 1) * (uint32_t)(NSTEP - 1) + 1);
#pragma unroll 1
          for (int k = 0; k < 4; k++) {
            const uint32_t* a = (const uint32_t*)((k == 0 ? t0 : k == 1 ? t1 : memg + (k == 2 ? s1 : s2)) + lane * 32);
            int g2 = 0;
            while (__any_sync(~0u, (xo2(ld_rlx(a), ld_rlx(a + 256), gt) | (ld_rlx(a + 512) ^ gt)) & 0x10001u)) { if (++g2 > (1 << 22)) TRAP(); }
          }
        } else wait_until(ts);
        e_g2s(sb + M_MEM, t0, 3072, BAR(B_LAND)); e_g2s(sb + M_MEM + 3072, t1, 3072, BAR(B_LAND));
        CSTAMP(2, clk());
        if (T == 0) TSTAMP(17, cta, 1);
        spin_until(ts + Y1_);
        e_mc(sb + M_MEM + (2 + c) * 3072, memg + s1, 3072, BAR(B_LAND + 1), 7);
        CSTAMP(3, clk());
        spin_until(ts + Y2_);
        e_mc(sb + M_MEM + (5 + c) * 3072, memg + s2, 3072, BAR(B_LAND + 2), 7);
        CSTAMP(4, clk());
      }
    } else if (w == 1) {
#pragma unroll 1
      for (int T = 0; T < NSTEP; T++) {
        const uint32_t ph = T & 1;
        const int s = c == 0 ? T : T - LAG;
        const bool act = s >= 0 && s < NSEG;
        mbar_wait(BAR(B_OST), ph);
        if (cta == 0) TSTAMP(2, T, 0);
        fence_async_smem();
        if (T < NSTEP - 1) wait_until(uni(lds32(sb + M_BAS2 + ph * 4)) + ODLY_);
        STAMP(22);
        if (act) paced_st(o_slot(c, s, head), sb + M_OST, OGAP_);
        if (c == 2 && T < NSTEP - 1) {
          mbar_wait(BAR(B_STG1), ph ^ 1);
          mbar_wait(BAR(B_VFREE), ph);
          STAMP(23);
          e_mc(sb + M_V + 2048, G.mix[cta % 6].tok[cta / 6][ph ^ 1] + 8192, 8192, BAR(B_V), 6);
          e_mc(sb + M_V + 2048, G.mix[cta % 6].tok[cta / 6][ph ^ 1], 8192, BAR(B_V), 1);
        }
        bulk_wait();
        __syncwarp();
        e_arrive(BAR(B_OFREE));
        if (cta == 0) TSTAMP(2, T, 1);
        if (act && lane < 8) st_rel(&G.f_o[T][head >> 2][c * 4 + (head & 3)][lane], E);
        __syncwarp();
        if (cta == 0) TSTAMP(2, T, 2);
      }
    } else if (w == 2) {
      unsigned long long run = 0;
      static_assert(LAG >= 2, "config");
      constexpr uint32_t NA = EA / 4 * 4096;
      e_expect(BAR(B_QK), c < 2 ? 2048 : 4096); e_expect(BAR(B_V), c == 0 ? 10240 : c == 1 ? 2048 : 0);
      e_expect(BAR(B_TOK), c == 0 ? 16384 : 0); e_expect(BAR(B_OM), 4096);
      e_expect(BAR(B_HA), NA); e_expect(BAR(B_HB), 65536 - NA);
      wait_eq(&G.f_h1[c == 1 ? 0 : 1], E); fence_async_glob();
      {
        const uint32_t o0 = c == 0 ? NA : 0, o1 = c == 2 ? NA : 32768;
        e_mc(sb + M_H + (c == 1 ? 32768 : 0) + o0, G.seg[c == 1 ? 0 : 1].h[0] + o0, o1 - o0, BAR(c == 2 ? B_HA : B_HB), 7);
      }
      TSTAMP(14, cta, 3);
      if (c == 2) wait_eq(&G.f_h1[2], E);
      mbar_wait(BAR(B_HAE), 1);
      e_expect(BAR(B_HA), NA);
      if (c == 2) { fence_async_glob(); e_mc(sb + M_H, G.seg[2].h[0], NA, BAR(B_HA), 7); }
      int cprev = -1;
#pragma unroll 1
      for (int T = 0; T < NSTEP - 1; T++) {
        const int s1 = T + 2, s2 = T + 2 - LAG;
        const uint32_t ph = T & 1;
        const bool l1 = s1 < NSEG, l2 = s2 >= 0 && s2 < NSEG, la = s1 + 1 < NSEG;
        const bool mine = c == 0 ? l1 : c == 1 ? l2 : la;
        const uint32_t* fl = c != 1 ? &G.f_h1[min(s1 + (c >> 1), NSEG - 1)] : (const uint32_t*)G.f_h2[max(s2, 0)][lane & 3] + 1;
        const uint32_t want = E & 0x1FFFFFu, sh = c != 1 ? 0 : 11;
        mbar_wait(BAR(B_HBE), ph ^ 1);
        const bool early = __all_sync(~0u, ((ld_acq(fl) >> sh) & 0x1FFFFFu) == want);
        mbar_wait(BAR(B_LAND + 2), ph);
        STAMP(16);
        e_expect(BAR(B_HB), (l1 ? 32768 - NA : 0) + (l2 ? 32768 : 0));
        if (mine) {
          if (!early) {
            int guard = 0;
            while (!__all_sync(~0u, ((ld_acq(fl) >> sh) & 0x1FFFFFu) == want)) { __nanosleep(32); if (++guard > (1 << 22)) TRAP(); }
          }
          fence_async_glob();
          if (c == 1) { mbar_wait(BAR(B_QK), ph); spin_until(clk32() + HDLY_); }
          if (c < 2) paced_h(sb + M_H + c * 32768, G.seg[c ? s2 : s1].h[c], c ? 0 : NA, 32768, 4096, BAR(B_HB), HGAP_);
        }
        int cd = -1;
        if (l2) { cd = route_step(s2, E, lane, run); if (cta == 0) TSTAMP(5, s2, 0); }
        if (lane == 0) sts32(sb + M_CAND + ((T + 2) & 3) * 4, (uint32_t)cd);
        __syncwarp();
        STAMP(17);
        mbar_wait(BAR(B_HAE), ph);
        e_expect(BAR(B_HA), la ? NA : 0);
        if (c == 2 && la) {
          spin_until(clk32() + ADLY_);
          STAMP(18);
          paced_h(sb + M_H, G.seg[s1 + 1].h[0], 0, NA, 4096, BAR(B_HA), AGAP_);
        }
        mbar_wait(BAR(B_OST), ph);
        e_expect(BAR(B_QK), c < 2 ? 2048 : cprev >= 0 ? 8192 : 4096);
        e_expect(BAR(B_V), c < 2 ? 10240 : 8192);
        e_expect(BAR(B_TOK), c == 0 ? 8192 : 16384);
        e_expect(BAR(B_OM), 4096);
        cprev = cd;
      }
    } else {
      const uint32_t mytok = sb + M_Q + c * 12288 + 2048, tb = BAR(c < 2 ? B_TOK : B_V);
      mbar_wait(BAR(B_STG1), 0);
      fence_async_smem();
      if (c) e_s2g(G.mix[cta % 6].tok[cta / 6][1], sb + M_TST, 8192);
#pragma unroll 1
      for (int T = 0; T < NSTEP - 1; T++) {
        const uint32_t ph = T & 1;
        uint8_t* const tok = G.mix[cta % 6].tok[cta / 6][ph ^ 1];
        mbar_wait(BAR(B_STG), ph ^ 1);
        fence_async_smem();
        if (cta == 0 && (T == 0 || T == NSEG || T == NSTEP - 2)) GSTAMP(0, T == 0 ? 2 : T == NSEG ? 3 : 4);
        if (T > 0) mbar_wait(BAR(B_QK), ph);
        STAMP(20);
        paced_st(tok + 8192, sb + M_TST + 8192, TGAP_);
        bulk_wait();
        __syncwarp();
        e_arrive(BAR(B_TFREE));
        if (T == 0) e_mc(mytok, tok + 8192, 8192, tb, 1);
        STAMP(21);
        if (c < 2) {
          mbar_wait(BAR(B_KFREE), ph);
          spin_until(clk32() + KDLY_);
          STAMP(23);
          if (c) e_mc(mytok, tok, 8192, tb, 1);
          e_mc(mytok, tok + 8192, 8192, tb, 6);
        }
        mbar_wait(BAR(B_STG1), ph ^ 1);
        fence_async_smem();
        wait_until(uni(lds32(sb + M_BAS2 + ph * 4)) + TDLY_);
        if (c) paced_st(G.mix[cta % 6].tok[cta / 6][ph], sb + M_TST, T1GAP_);
        STAMP(24);
      }
      bulk_wait();
    }
    __syncwarp();
    cluster_sync();
  }
}

constexpr uint32_t A_RING = 0;
constexpr int A_NST = 6;
constexpr uint32_t A_STG = A_RING + A_NST * 8192;
constexpr uint32_t A_WD = A_STG + 8192;
constexpr uint32_t A_WG = A_WD + 57344;
constexpr uint32_t A_WU = A_WG + 57344;
constexpr uint32_t A_XN = A_WU + 57344;
constexpr uint32_t A_BAR = A_XN + 2048;
constexpr uint32_t A_TOTAL = A_BAR + 256;
static_assert(A_TOTAL <= 232448, "aux smem");

__device__ __forceinline__ void job_of(int T, int k, int& st, int& s) {
  st = k == 0 ? 0 : 3 - k; s = st == 0 ? T : T - LAG;
  if (T >= NSTEP - 2 && k) { st = T == NSTEP - 2 ? 2 : 1; s = NSEG - 3 + k; }
}
__device__ __forceinline__ uint32_t ptag(int s) { return ((s / PRING) & 1) ^ 1; }
static_assert((NSEG / PRING) % 2 == 0, "tags");
__device__ __forceinline__ void load_row(uint32_t* v, const void* row, int lane) {
  const uint4 a = __ldcg((const uint4*)row + lane), b = __ldcg((const uint4*)row + 32 + lane);
  v[0] = a.x; v[1] = a.y; v[2] = a.z; v[3] = a.w; v[4] = b.x; v[5] = b.y; v[6] = b.z; v[7] = b.w;
}
__device__ __forceinline__ void store_row(void* row, const uint32_t* v, int lane) {
  ((uint4*)row)[lane] = make_uint4(v[0], v[1], v[2], v[3]); ((uint4*)row)[32 + lane] = make_uint4(v[4], v[5], v[6], v[7]);
}
__device__ __forceinline__ void store_img(uint8_t* img, int r, const uint32_t* v, int lane) {
  uint8_t* b = img + (lane >> 3) * 4096 + (r >> 3) * 1024 + (r & 7) * 128 + (((lane ^ r) & 7) << 4);
  *(uint4*)b = make_uint4(v[0], v[1], v[2], v[3]);
  *(uint4*)(b + 16384) = make_uint4(v[4], v[5], v[6], v[7]);
}
template <int NT> __device__ __forceinline__ void ln_rows(const uint32_t (*v)[8], uint32_t (*y)[8]) {
  float c[NT], sm[NT], sq[NT];
#pragma unroll
  for (int k = 0; k < NT; k++) {
    c[k] = blo(__shfl_sync(~0u, v[k][0], 0));
    float s0 = 0.f, s1 = 0.f, q0 = 0.f, q1 = 0.f;
#pragma unroll
    for (int i = 0; i < 8; i++) { const float a = blo(v[k][i]) - c[k], b = bhi(v[k][i]) - c[k]; s0 += a; s1 += b; q0 = fmaf(a, a, q0); q1 = fmaf(b, b, q1); }
    sm[k] = s0 + s1; sq[k] = q0 + q1;
  }
#pragma unroll
  for (int o = 16; o > 0; o >>= 1)
#pragma unroll
    for (int k = 0; k < NT; k++) {
      sm[k] += __shfl_xor_sync(~0u, sm[k], o); sq[k] += __shfl_xor_sync(~0u, sq[k], o);
    }
#pragma unroll
  for (int k = 0; k < NT; k++) {
    const float dm = sm[k] * (1.f / 512.f), var = fmaxf(fmaf(-dm, dm, sq[k] * (1.f / 512.f)), 0.f);
    const float mb = rbf(c[k] + dm), inv = rcp(rbf(sqrt_fast(rbf(rbf(var) + 1e-5f))));
#pragma unroll
    for (int i = 0; i < 8; i++) { const uint32_t a = pack2(blo(v[k][i]) - mb, bhi(v[k][i]) - mb); y[k][i] = pack2(blo(a) * inv, bhi(a) * inv); }
  }
}
__device__ __forceinline__ void input_ln_pair(const bf16* x, int s, int pr, int lane) {
  uint32_t v[2][8], y[2][8];
  load_row(v[0], x + (size_t)(s * 32 + 2 * pr) * 512, lane); load_row(v[1], x + (size_t)(s * 32 + 2 * pr + 1) * 512, lane);
  ln_rows<2>(v, y);
  store_img(G.seg[s].h[0], 2 * pr, y[0], lane); store_img(G.seg[s].h[0], 2 * pr + 1, y[1], lane);
}
__device__ __forceinline__ float load_wr(uint32_t* wv, const bf16* wr, int lane) {
  load_row(wv, wr, lane);
  float wsum = 0.f;
#pragma unroll
  for (int i = 0; i < 8; i++) wsum += blo(wv[i]) + bhi(wv[i]);
#pragma unroll
  for (int o = 16; o > 0; o >>= 1) wsum += __shfl_xor_sync(~0u, wsum, o);
  return wsum;
}

template <bool FAST>
__device__ __forceinline__ unsigned long long token_post(int st, int tk, const bf16* res, bf16* dst, bf16* req, unsigned long long best,
                                                         const uint32_t* wv, float wsum, uint32_t E, int lane) {
  const int s = tk >> 5;
  uint32_t x[8];
  load_row(x, res, lane);
  {
    int guard = 0;
    while (__popc(__ballot_sync(~0u, ld_rlx(G.f_acc[st][s][lane]) == E)) < (FAST ? 24 : 32)) { __nanosleep(FAST ? 20 : 100); if (++guard > (1 << 22)) TRAP(); }
  }
  if (tk == s * 32 && st == 0 && lane == 0) TSTAMP(4, s, 0);
  {
    const uint8_t* pp = pp_slot(st, s) + (lane >> 4) * 8192 + (tk & 31) * 256 + (((lane & 15) ^ (tk & 7)) << 4);
    const uint32_t tag = ptag(s);
    uint4 q[8][2];
#define PLD(k, h) q[k][h] = ld_rlx128<(k) * 32768 + (h) * 16384>(pp)
#define PLD8(h) PLD(0, h); PLD(1, h); PLD(2, h); PLD(3, h); PLD(4, h); PLD(5, h); PLD(6, h); PLD(7, h)
#define PBAD(h) __any_sync(~0u, (or3(xo2(q[0][h].x, q[1][h].x, tag), xo2(q[2][h].x, q[3][h].x, tag), xo2(q[4][h].x, q[5][h].x, tag)) | xo2(q[6][h].x, q[7][h].x, tag)) & ~lane & 1u)
#define PSUM(f, h, m) (((f(q[0][h].m) + f(q[1][h].m)) + (f(q[2][h].m) + f(q[3][h].m))) + ((f(q[4][h].m) + f(q[5][h].m)) + (f(q[6][h].m) + f(q[7][h].m))))
    const uint32_t eye = (lane >> 2) == 2 * (lane & 3) ? 0x3f80u : (lane >> 2) == 2 * (lane & 3) + 1 ? 0x3f800000u : 0u;
    auto padd = [&](int h) {
      if (FAST) {
        float u[4] = {0.f, 0.f, 0.f, 0.f}, v[4] = {0.f, 0.f, 0.f, 0.f};
#pragma unroll
        for (int k = 0; k < 8; k++) { hmma8(u, q[k][h].x, q[k][h].y, eye); hmma8(v, q[k][h].z, q[k][h].w, eye); }
        x[4 * h] = add2(x[4 * h], pack2(u[0], u[1])); x[4 * h + 1] = add2(x[4 * h + 1], pack2(u[2], u[3]));
        x[4 * h + 2] = add2(x[4 * h + 2], pack2(v[0], v[1])); x[4 * h + 3] = add2(x[4 * h + 3], pack2(v[2], v[3]));
      } else {
        x[4 * h] = add2(x[4 * h], pack2(PSUM(blo, h, x), PSUM(bhi, h, x))); x[4 * h + 1] = add2(x[4 * h + 1], pack2(PSUM(blo, h, y), PSUM(bhi, h, y)));
        x[4 * h + 2] = add2(x[4 * h + 2], pack2(PSUM(blo, h, z), PSUM(bhi, h, z))); x[4 * h + 3] = add2(x[4 * h + 3], pack2(PSUM(blo, h, w), PSUM(bhi, h, w)));
      }
    };
    int guard = 0;
    PLD8(0);
    if (FAST) { PLD8(1); }
    while (PBAD(0)) { if (++guard > (1 << 20)) TRAP(); PLD8(0); }
    padd(0);
    if (!FAST) { PLD8(1); }
    while (PBAD(1)) { if (++guard > (1 << 20)) TRAP(); PLD8(1); }
    padd(1);
  }
  const float c = blo(__shfl_sync(~0u, x[0], 0));
  float s0 = 0.f, s1 = 0.f, q0 = 0.f, q1 = 0.f, r0 = 0.f, r1 = 0.f;
#pragma unroll
  for (int i = 0; i < 8; i++) {
    const float a = blo(x[i]) - c, b = bhi(x[i]) - c;
    s0 += a; s1 += b; q0 = fmaf(a, a, q0); q1 = fmaf(b, b, q1); r0 = fmaf(a, blo(wv[i]), r0); r1 = fmaf(b, bhi(wv[i]), r1);
  }
  s0 += s1; q0 += q1; r0 += r1;
#pragma unroll
  for (int o = 16; o > 0; o >>= 1) { s0 += __shfl_xor_sync(~0u, s0, o); q0 += __shfl_xor_sync(~0u, q0, o); r0 += __shfl_xor_sync(~0u, r0, o); }
  const float dm = s0 * (1.f / 512.f), m = c + dm, var = fmaxf(fmaf(-dm, dm, q0 * (1.f / 512.f)), 0.f);
  const float mb = rbf(m), inv = rcp(rbf(sqrt_fast(rbf(rbf(var) + 1e-5f))));
  const uint32_t nmb = pack2(-mb, -mb);
  const unsigned long long wd = rword(E, tk, fmaf(c - mb, wsum, r0) * inv);
  uint32_t xn[8], x2[8];
#pragma unroll
  for (int i = 0; i < 8; i++) { const uint32_t d = add2(x[i], nmb); xn[i] = pack2(blo(d) * inv, bhi(d) * inv); x2[i] = add2(x[i], xn[i]); }
  if (st == 0) {
    const float mb2 = rbf(fmaf(m - mb, inv, m)), inv2 = rcp(rbf(sqrt_fast(rbf(rbf(var * (1.f + inv) * (1.f + inv)) + 1e-5f))));
    const uint32_t nmb2 = pack2(-mb2, -mb2);
    uint32_t h[8];
#pragma unroll
    for (int i = 0; i < 8; i++) { const uint32_t d2 = add2(x2[i], nmb2); h[i] = pack2(blo(d2) * inv2, bhi(d2) * inv2); }
    store_img(G.seg[s].h[1], tk & 31, h, lane);
  }
  store_row(dst, x2, lane);
  if (wd > best) { store_row(req, xn, lane); store_row(req + 512, x, lane); }
  return wd;
}

__device__ __forceinline__ void ffn_slice(uint32_t sb, const bf16* xn, float* yacc, uint32_t* flag, uint32_t E, int t, bool urgent) {
  const int w = t >> 5, g = (t >> 2) & 7;
  if (t == 0 && urgent) sts32(sb + A_BAR + 160, 1);
  { const uint2 u = __ldcg((const uint2*)xn + t); asm volatile("st.shared.v2.u32 [%0], {%1,%2};" :: "r"(sb + A_XN + t * 8), "r"(u.x), "r"(u.y) : "memory"); }
  fence_async_smem();
  bar_sync(4, 128);
  float ga[4], ua[4];
  constexpr uint64_t da = mkdesc(A_WG, 896, 128, 0), db = mkdesc(A_XN, 16, 128, 0);
  wg_fence();
  wgmma_ss8<0, 1, 0>(ga, da, db); wgmma_ss8<0, 1, 0>(ua, da + (A_WU - A_WG) / 16, db);
#pragma unroll
  for (int ks = 1; ks < 32; ks++) { wgmma_ss8<1, 1, 0>(ga, da + ks * 112, db + ks * 2); wgmma_ss8<1, 1, 0>(ua, da + (A_WU - A_WG) / 16 + ks * 112, db + ks * 2); }
  wg_commit(); wg_wait<0>(); reg_fence(ga); reg_fence(ua);
  if ((t & 3) == 0) {
#pragma unroll
    for (int h = 0; h < 2; h++) {
      const float gs = rbf(ga[2 * h]), us = rbf(ua[2 * h]);
      const float v = 16 * w + 8 * h < 56 ? rbf(gs * rcp(1.f + __expf(-gs))) * us : 0.f;
      asm volatile("st.shared.u16 [%0], %1;" :: "r"(sb + A_XN + 1280 + (16 * w + 8 * h + g) * 2), "h"((unsigned short)pack2(v, 0.f)) : "memory");
    }
  }
  fence_async_smem();
  bar_sync(4, 128);
#pragma unroll 1
  for (int j = 0; j < 2; j++) {
    float y[4][4];
    const uint64_t dd = mkdesc(A_WD, 8192, 128, 0) + (uint64_t)(j * 256);
    wg_fence();
#pragma unroll
    for (int m = 0; m < 4; m++) {
      wgmma_ss8<0, 1, 0>(y[m], dd + m * 64, mkdesc(A_XN + 1280, 16, 128, 0));
#pragma unroll
      for (int ks = 1; ks < 4; ks++) wgmma_ss8<1, 1, 0>(y[m], dd + m * 64 + ks * 1024, mkdesc(A_XN + 1280 + ks * 32, 16, 128, 0));
    }
    wg_commit(); wg_wait<0>();
#pragma unroll
    for (int m = 0; m < 4; m++) {
      reg_fence(y[m]);
      if ((t & 3) == 0) { float* o = yacc + j * 256 + m * 64 + 16 * w + g; o[0] = y[m][0]; o[8] = y[m][2]; }
    }
  }
  bar_sync(4, 128);
  if (t < 8) { sts32(sb + A_BAR + 160, 0); st_rel(flag + t, E); }
  __syncwarp();
}

__device__ __forceinline__ void ffn_gather(uint32_t sb, int q, int j, uint32_t E, int lane) {
  wait_all(G.f_y[q][4 * j + (lane & 3)], E);
  float4 y[4][4];
#pragma unroll
  for (int k = 0; k < 4; k++)
#pragma unroll
    for (int i = 0; i < 4; i++) y[k][i] = __ldcg((const float4*)G.y[q & 7][4 * j + k] + i * 32 + lane);
#pragma unroll
  for (int i = 0; i < 4; i++)
    sts128f(sb + 1024 + j * 2048 + i * 512 + lane * 16, (y[0][i].x + y[1][i].x) + (y[2][i].x + y[3][i].x), (y[0][i].y + y[1][i].y) + (y[2][i].y + y[3][i].y),
            (y[0][i].z + y[1][i].z) + (y[2][i].z + y[3][i].z), (y[0][i].w + y[1][i].w) + (y[2][i].w + y[3][i].w));
  bar_sync(9, 256);
}
__device__ __forceinline__ void ffn_finish(uint32_t sb, int q, const bf16* req, float r, uint32_t E, int lane, uint32_t* v) {
  if (lane == 0) sts32(sb + 16, q);
  bar_sync(8, 256);
  uint32_t xn[8];
  load_row(xn, req, lane); load_row(v, req + 512, lane);
  const float rs = rbf(1.f / (1.f + __expf(-rbf(r))));
  ffn_gather(sb, q, 7, E, lane);
#pragma unroll
  for (int i = 0; i < 4; i++) {
    float y[4] = {0.f, 0.f, 0.f, 0.f};
#pragma unroll
    for (int j = 0; j < 8; j++) {
      const uint4 u = lds128(sb + 1024 + j * 2048 + (i >> 1) * 1024 + lane * 32 + (i & 1) * 16);
      y[0] += __uint_as_float(u.x); y[1] += __uint_as_float(u.y); y[2] += __uint_as_float(u.z); y[3] += __uint_as_float(u.w);
    }
    v[2 * i] = add2(v[2 * i], add2(xn[2 * i], pack2(rbf(y[0]) * rs, rbf(y[1]) * rs)));
    v[2 * i + 1] = add2(v[2 * i + 1], add2(xn[2 * i + 1], pack2(rbf(y[2]) * rs, rbf(y[3]) * rs)));
  }
}

__global__ void __launch_bounds__(512, 1) aux_kernel(Params p) {
  extern __shared__ __align__(1024) uint8_t sm[];
  const uint32_t sb = smem_u32(sm);
  if ((sb & 0xFFFFFFu) != SBASE) TRAP();
  const int warp = __shfl_sync(~0u, threadIdx.x >> 5, 0);
  const int cta = blockIdx.x;
  const uint32_t E = __shfl_sync(~0u, *(volatile uint32_t*)&g_epoch + 1, 0);
  const uint32_t bars = sb + A_BAR;

  if (cta < 32) {
    const int cg = cta & 3, kg = cta >> 2;
    if (threadIdx.x == 0) {
      for (int i = 0; i < A_NST; i++) { mbar_init(bars + 8 * i, 1); mbar_init(bars + 64 + 8 * i, 2); }
      mbar_init(bars + 128, 8); mbar_init(bars + 136, 8); mbar_init(bars + 144, 1);
      sts32(bars + 160, 0);
      asm volatile("fence.mbarrier_init.release.cluster;" ::: "memory");
    }
    if (warp < 8) {
      asm volatile("setmaxnreg.inc.sync.aligned.u32 176;");
      const int tid = fresh_tid(), lane = tid & 31;
      uint32_t W[32][4];
      bar_arrive(3, 384);
      stage_weights(sb + A_WD, p.wo + (size_t)kg * 512 * 512 + cg * 128, 512, tid, 256);
      cp_async_wait();
      bar_sync(1, 256);
      load_frags(W, sb + A_WD, warp >> 2, warp & 3, lane);
      PIN(W[31][3]);
      bar_sync(1, 256);
      bar_arrive(2, 384);
      const uint32_t so = sb + A_STG + ((lane >> 4) * 8 + (lane & 7)) * 256 + (((warp * 2 + ((lane >> 3) & 1)) ^ (lane & 7)) << 4);
      const uint32_t tm = lane < 4 ? 0x00010001u : 0u;
      int stage = 0; uint32_t ph = 0, job = 0;
#pragma unroll 1
      for (int T = 0; T < NSTEP; T++) {
#pragma unroll 1
        for (int k = 0; k < 3; k++) {
          int st, s; job_of(T, k, st, s);
          if (s < 0 || s >= NSEG) continue;
          float d[16];
#pragma unroll
          for (int hh = 0; hh < 4; hh++) {
            mbar_wait(bars + 8 * stage, ph);
            while (uni(lds32(bars + 160))) __nanosleep(100);
            const uint64_t db = mkdesc(A_RING, 512, 128, 0) + (uint64_t)(stage * 512);
            wg_fence();
            if (hh == 0) wgmma_rs32<0, 0>(d, W[0], db); else wgmma_rs32<1, 0>(d, W[hh * 8], db);
#pragma unroll
            for (int ks = 1; ks < 8; ks++) wgmma_rs32<1, 0>(d, W[hh * 8 + ks], db + ks * 64);
            wg_commit();
            if (hh > 0) { wg_wait<1>(); if ((tid & 127) == 0) mbar_arrive(bars + 64 + 8 * (stage == 0 ? A_NST - 1 : stage - 1)); }
            if (++stage == A_NST) { stage = 0; ph ^= 1; }
          }
          mbar_wait(bars + 144, (job & 1) ^ 1);
          wg_wait<0>(); reg_fence(d);
          if ((tid & 127) == 0) mbar_arrive(bars + 64 + 8 * (stage == 0 ? A_NST - 1 : stage - 1));
          if (cta == 0 && tid == 0) TSTAMP(6, T, k);
          const uint32_t tv = tm * ptag(s);
#define TG(i) ((pack2(d[2 * (i)], d[2 * (i) + 1]) & ~tm) | tv)
          stmatrix4_t(so, TG(0), pack2(d[2], d[3]), TG(2), pack2(d[6], d[7]));
          stmatrix4_t(so + 4096, TG(4), pack2(d[10], d[11]), TG(6), pack2(d[14], d[15]));
          fence_async_smem();
          __syncwarp();
          if (lane == 0) mbar_arrive(bars + 128 + 8 * (job & 1));
          job++;
        }
      }
    } else if (warp < 12) {
      asm volatile("setmaxnreg.dec.sync.aligned.u32 120;");
      const int tid = fresh_tid(), lane = tid & 31;
      const int w = warp - 8, t = tid - 256;
      uint32_t wv[8];
      const float wsum = load_wr(wv, p.wr, lane);
#pragma unroll 1
      for (int s = cta + 4; s < NSEG; s += 32) {
#pragma unroll 1
        for (int pr = w; pr < 16; pr += 4) input_ln_pair(p.x, s, pr, lane);
        bar_sync(4, 128);
        if (t == 0) st_rel(&G.f_h1[s], E);
      }
      bar_sync(2, 384);
      { int guard = 0; while (ld_rlx(&G.f_loaded[cta]) != E) { __nanosleep(200); if (++guard > (1 << 22)) TRAP(); } }
#pragma unroll 1
      for (int i = t; i < 512 * 7; i += 128) {
        const int k = i / 7, pc = i % 7;
        cp_async16(sb + A_WG + (k >> 3) * 896 + pc * 128 + (k & 7) * 16, p.wg + (size_t)k * 1792 + cta * 56 + pc * 8);
        cp_async16(sb + A_WU + (k >> 3) * 896 + pc * 128 + (k & 7) * 16, p.wu + (size_t)k * 1792 + cta * 56 + pc * 8);
        cp_async16(sb + A_WD + (i >> 9) * 8192 + (i & 63) * 128 + ((i >> 6) & 7) * 16, p.wd + (size_t)cta * 56 * 512 + i * 8);
        if ((i >> 7) % 4 == 3) cp_async_wait();
      }
      cp_async_wait();
      fence_async_smem();
      bar_sync(4, 128);
      const int tj = (cta * 4 + w) & 31, st = 1 + ((cta >> 3) & 1), sq = cta >> 4;
      unsigned long long run = 0, run2 = 0, best = 0, hist = 0;
      uint32_t open = 0;
#pragma unroll 1
      for (int i = 0; i <= NSTEP; i++) {
        int tok = -1; const bf16* req = nullptr;
        if (i < NSEG) {
          const int cd = (int)uni(route_step(i, E, lane, run));
          run = __shfl_sync(~0u, run, 0);
          hist = hist << 8 | (uint32_t)(cd + 1);
          if (cd >= 0) { tok = rtok(run); req = G.seg[tok >> 5].req1[tok & 31][0]; }
        } else {
          const unsigned long long m = wait_words(G.f_l2[i - NSEG], E);
          const unsigned long long n = ld_rlxu64(G.f_l2[min(i - NSEG + 1 + (lane & 7), LAG)]);
          const bool over = bar_or(4, 128, rfresh(n, E) && n != m);
          if (m != run2 && !over) { run2 = m; tok = rtok(m); req = G.req2[(tok >> 5) < (rtok(run) >> 5) ? 0 : 1][tok][0]; }
        }
        tok = __shfl_sync(~0u, tok, 0);
        if (tok >= 0) {
          if (cta == 0 && t == 0) TSTAMP(8, i & 127, 0);
          ffn_slice(sb, req, G.y[i & 7][cta], G.f_y[i][cta], E, t, i < NSEG);
          if (cta == 0 && t == 0) TSTAMP(8, i & 127, 1);
        }
        const int s = i - LAG;
        if (s < 0 || i >= NSEG) continue;
        const int cd = (int)((hist >> (8 * LAG)) & 255) - 1;
        if (cd >= 0 && st == 2) best = 0;
        const int ts = rtok(run) >> 5;
        if ((s & 1) == sq) {
          const int tk = s * 32 + tj;
          unsigned long long wd = (unsigned long long)E << 43;
          if (st == 1 ? s < ts || i < NSEG - 1 : s >= ts) {
            if (st == 2 && cd == tj) wait_eq(&G.f_hc[s], E);
            wd = token_post<false>(st, tk, st == 2 && cd == tj ? G.x2c[s] : G.seg[tk >> 5].x2[tk & 31],
                                   st == 2 || s < ts ? p.out + (size_t)tk * 512 : G.seg[s].n[tj], G.req2[st - 1][tk][0], best, wv, wsum, E, lane);
            best = max(best, wd);
            if (st == 1 && s >= ts) open |= 1u << (s >> 1);
          }
          __syncwarp();
          if (lane < 4) st_rel64(&G.f_w2[st - 1][s][tj][lane], wd);
          __syncwarp();
        }
        if (st == 1) {
          if (i == NSEG - 1 && t == 0 && cta == 0) GSTAMP(1, 0);
#pragma unroll 1
          for (int n = i == NSEG - 1 ? 32 : 2; n > 0 && open; n--) {
            const int s0 = 2 * (__ffs(open) - 1) + sq;
            if (s0 >= ts) break;
            open &= open - 1;
            uint32_t v[8];
            load_row(v, G.seg[s0].n[tj], lane);
            wait_words(G.f_w2[1][s0][tj], E);
            store_row(p.out + (size_t)(s0 * 32 + tj) * 512, v, lane);
          }
          if (i == NSEG - 1) {
            __syncwarp();
            if (lane == 0) st_rel(&G.f_cp[sq * 32 + tj], E);
            if (t == 0 && cta == 0) GSTAMP(1, 3);
          }
        }
      }
    } else {
      asm volatile("setmaxnreg.dec.sync.aligned.u32 40;");
      const int tid = fresh_tid(), lane = tid & 31;
      const int w = warp - 12;
      bar_sync(3, 384);
      if (w == 0) {
        int stage = 0; uint32_t ph = 1;
#pragma unroll 1
        for (int T = 0; T < NSTEP; T++) {
#pragma unroll 1
          for (int k = 0; k < 3; k++) {
            int st, s; job_of(T, k, st, s);
            if (s < 0 || s >= NSEG) continue;
            const uint32_t* fl = G.f_o[st ? s + LAG : s][kg][st * 4 + (lane & 3)];
            uint32_t ready = 0; int guard = 0;
#pragma unroll 1
            for (int hh = 0; hh < 4; hh++) {
              while (!((ready >> hh) & 1)) {
                ready = __ballot_sync(~0u, ld_rlx(fl) == E);
                if (++guard > (1 << 23)) TRAP();
              }
              fence_async_glob();
              mbar_wait(bars + 64 + 8 * stage, ph);
              e_expect(bars + 8 * stage, 8192);
              e_g2s(sb + A_RING + stage * 8192, o_slot(st, s, kg * 4 + hh), 8192, bars + 8 * stage);
              if (++stage == A_NST) { stage = 0; ph ^= 1; }
            }
          }
          if (cta == 0 && lane == 0) TSTAMP(3, T, 0);
        }
      } else if (w < 3) {
        uint32_t job = 0;
#pragma unroll 1
        for (int T = 0; T < NSTEP; T++) {
#pragma unroll 1
          for (int k = 0; k < 3; k++) {
            int st, s; job_of(T, k, st, s);
            if (s < 0 || s >= NSEG) continue;
            if ((job++ & 1) != w - 1) continue;
            if (s >= PRING) wait_words(st == 0 ? G.f_h2[s - PRING][lane & 3] : G.f_w2[st - 1][s - PRING][lane], E);
            mbar_wait(bars + 128 + 8 * (w - 1), ((job - 1) >> 1) & 1);
            if (cta == 0 && st == 0) TSTAMP(7, s, 0);
            e_s2g(pp_slot(st, s) + cta * 8192, sb + A_STG, 8192);
            if (lane < 8) st_rlx(&G.f_acc[st][s][cta][lane], E);
            asm volatile("cp.async.bulk.commit_group;\n cp.async.bulk.wait_group.read 0;" ::: "memory");
            __syncwarp();
            e_arrive(bars + 144);
            __syncwarp();
            if (cta == 0 && st == 0) TSTAMP(7, s, 1);
          }
        }
        bulk_wait();
      }
    }
  } else {
    const int tid = fresh_tid(), lane = tid & 31;
    const int qd = cta - 32;
    input_ln_pair(p.x, qd, warp, lane);
    bar_sync(6, 512);
    if (tid == 0) st_rel(&G.f_h1[qd], E);
    volatile int* bc = (volatile int*)sm;
    if (warp == 15) {
      unsigned long long run = 0;
      unsigned long long b2[2][2] = {{0, 0}, {0, 0}};
      auto track = [&](int s) {
#pragma unroll
        for (int k = 0; k < 2; k++) {
          const unsigned long long m = warp_max<16>(wait_words(G.f_w2[k][s][lane], E));
          if (lane == (s & 31)) { if (s < 32) b2[k][0] = m; else b2[k][1] = m; }
        }
      };
#pragma unroll 1
      for (int s = 0; s < NSEG; s++) {
        const int cd = route_step(s, E, lane, run);
        if (cd >= 0 && qd == (s & 1)) {
          uint32_t v[1][8], h[1][8];
          ffn_finish(sb, s, G.seg[s].req1[cd][0], rscore(run), E, lane, v[0]);
          if (lane == 0) TSTAMP(8, s, 2);
          ln_rows<1>(v, h);
#pragma unroll
          for (int i = 0; i < 8; i++) st_rlx64(&G.hc[s][(i >> 2) * 128 + 4 * lane + (i & 3)], h[0][i], E);
          if (lane == 0) TSTAMP(8, s, 3);
          store_row(G.x2c[s], v[0], lane);
          __syncwarp();
          if (lane == 0) st_rel(&G.f_hc[s], E);
        }
        if (qd == 2 && s > LAG) track(s - LAG - 1);
      }
      wait_eq(&G.f_hc[rtok(run) >> 5], E);
      if (lane == 0) *bc = rtok(run);
      bar_sync(7, 288);
      if (qd == 2) {
        uint32_t v[8];
        const int ts = rtok(run) >> 5;
        track(NSEG - LAG - 1);
        run = 0;
        int kl = 0; bool open = false;
#pragma unroll 1
        for (int k = 0; k <= LAG + 1; k++) {
          const int s = min(NSEG - LAG - 1 + k, NSEG - 1);
          unsigned long long m = max(lane < ts ? b2[0][0] : b2[1][0], lane + 32 < ts ? b2[0][1] : b2[1][1]);
          for (int guard = 0; k > 0; guard++) {
            m = ld_rlxu64(G.f_w2[s < ts ? 0 : 1][s][lane]);
            const bool done = open && __all_sync(~0u, ld_rlx(G.f_y[NSEG + kl][lane]) == E);
            if (k <= LAG ? __all_sync(~0u, rfresh(m, E)) : !open) break;
            if (done) { ffn_finish(sb, NSEG + kl, G.req2[(rtok(run) >> 5) < ts ? 0 : 1][rtok(run)][0], rscore(run), E, lane, v); open = false; }
            if (guard > (1 << 22)) TRAP();
          }
          if (k > LAG) break;
          fence_acq();
          m = warp_max<16>(m);
          if (m > run) { run = m; kl = k; open = true; __threadfence(); }
          if (lane < 4) st_rlx64(&G.f_l2[k][lane], (uint32_t)run, (uint32_t)(run >> 32));
          if (k == 0) { wait_all(&G.f_cp[lane], E); wait_all(&G.f_cp[32 + lane], E); }
        }
        if (lane == 0) GSTAMP(1, 1);
        store_row(p.out + (size_t)rtok(run) * 512, v, lane);
        if (lane == 0) GSTAMP(1, 2);
      }
      if (lane == 0) sts32(sb + 16, (uint32_t)-1);
      bar_sync(8, 256);
      if (qd == 2) {
        asm volatile("griddepcontrol.wait;" ::: "memory");
        if (lane == 0) *(volatile uint32_t*)&g_epoch = E;
      }
    } else if (warp >= 8) {
#pragma unroll 1
      for (;;) {
        bar_sync(8, 256);
        const int q = (int)uni(lds32(sb + 16));
        if (q < 0) break;
        ffn_gather(sb, q, warp - 8, E, lane);
      }
    } else {
      uint32_t wv[8];
      const float wsum = load_wr(wv, p.wr, lane);
      unsigned long long best = 0;
      int ttok = 0;
#pragma unroll 1
      for (int i = 0; i < NSTEP; i++) {
        const bool last = i >= NSEG;
        if (i == NSEG) { bar_sync(7, 288); ttok = *bc; best = 0; }
        const int s = last ? i - LAG : i, st = !last ? 0 : s < (ttok >> 5) ? 1 : 2;
        const int tk = s * 32 + qd * 8 + warp;
        const unsigned long long wd = token_post<true>(st, tk, !last ? p.x + (size_t)tk * 512 : tk == ttok ? G.x2c[s] : G.seg[tk >> 5].x2[tk & 31],
                                                 last ? p.out + (size_t)tk * 512 : G.seg[s].x2[tk & 31], last ? G.req2[st - 1][tk][0] : G.seg[s].req1[tk & 31][0], best, wv, wsum, E, lane);
        best = max(best, wd);
        volatile unsigned long long* ws = (volatile unsigned long long*)(sm + 64) + (i & 1) * 8;
        if (lane == 0) ws[warp] = wd;
        const unsigned long long lead = i == NSTEP - 1 ? ld_rlxu64(G.f_l2[LAG - 1]) : 0;
        bar_sync(5, 256);
        if (warp == 0) {
          if (qd == 0 && lane == 0) TSTAMP(4, i, 1);
          if (!last) { const unsigned long long m = warp_max<4>(ws[lane & 7]); if (lane < 4) st_rel64(&G.f_h2[s][qd][lane], m); }
          else {
            const unsigned long long v = ws[lane >> 2];
            if (!__all_sync(~0u, rfresh(lead, E) && v < lead)) __threadfence();
            st_rlx64(&G.f_w2[st - 1][s][qd * 8 + (lane >> 2)][lane & 3], (uint32_t)v, (uint32_t)(v >> 32));
            asm volatile("st.relaxed.gpu.global.u64 [%0], %1;" :: "l"(&G.f_w2[2 - st][s][qd * 8 + (lane >> 2)][lane & 3]), "l"((unsigned long long)E << 43) : "memory");
          }
          if (qd == 0 && lane == 0) TSTAMP(4, i, 2);
        }
        __syncwarp();
      }
    }
  }
}

}

extern "C" void kernel_launch(void* const* d_in, const int* in_sizes, int n_in, void* d_out, int out_size) {
  (void)in_sizes; (void)n_in; (void)out_size;
  static bool init = false;
  if (!init) {
    cudaFuncSetAttribute(main_kernel, cudaFuncAttributeMaxDynamicSharedMemorySize, M_TOTAL);
    cudaFuncSetAttribute(aux_kernel, cudaFuncAttributeMaxDynamicSharedMemorySize, A_TOTAL);
    init = true;
  }
  Params p;
  p.x = (const bf16*)d_in[0]; p.mem0 = (const bf16*)d_in[1]; p.wq = (const bf16*)d_in[2]; p.wk = (const bf16*)d_in[3];
  p.wv = (const bf16*)d_in[4]; p.wo = (const bf16*)d_in[5]; p.wr = (const bf16*)d_in[8]; p.wg = (const bf16*)d_in[9];
  p.wu = (const bf16*)d_in[10]; p.wd = (const bf16*)d_in[11]; p.out = (bf16*)d_out; p.zero = 0; p.zero2 = 0;
  cudaStream_t st = cudaStreamPerThread;
  main_kernel<<<96, 512, M_TOTAL, st>>>(p);
  cudaLaunchConfig_t cfg = {};
  cfg.gridDim = dim3(36); cfg.blockDim = dim3(512); cfg.dynamicSmemBytes = A_TOTAL; cfg.stream = st;
  cudaLaunchAttribute at[1];
  at[0].id = cudaLaunchAttributeProgrammaticStreamSerialization; at[0].val.programmaticStreamSerializationAllowed = 1;
  cfg.attrs = at; cfg.numAttrs = 1;
  cudaLaunchKernelEx(&cfg, aux_kernel, p);
}
```
